```python
import torch

def _softmax(x, axis=-1):
    return torch.softmax(x, dim=axis)

def _gelu(x):
    return torch.nn.functional.gelu(x, approximate='tanh')

def _silu(x):
    return torch.nn.functional.silu(x)

def _sigmoid(x):
    return torch.sigmoid(x)

def _layernorm(x, axis=-1, eps=1e-05):
    m = x.mean(dim=axis, keepdim=True)
    v = x.var(dim=axis, keepdim=True, unbiased=False)
    return (x - m) / torch.sqrt(v + eps)

def _scatter_add(tgt, idx, src, axis=0):
    return tgt.clone().index_add_(axis, idx, src)

def _segment_sum(src, seg, n):
    out = torch.zeros((n,) + src.shape[1:], dtype=src.dtype)
    return out.index_add_(0, seg, src)

def _pad(x, pw):
    flat = tuple((v for pair in reversed(pw) for v in pair))
    return torch.nn.functional.pad(x, flat)
kernel_name = 'adaLN_cond__ssm_conv_h3__mixer_s_mlp__prompt'

def setup_inputs():

    _w = lambda a: (lambda t: t.to(torch.bfloat16) if t.is_floating_point() else t)(torch.as_tensor(a))

    def _A_setup():
        B, S, D = (1, 2048, 640)
        ks = 4
        return {'q': _w((lambda *s: torch.randn(*s, dtype=torch.bfloat16) * 0.05)(B, S, D)), 'k': _w((lambda *s: torch.randn(*s, dtype=torch.bfloat16) * 0.8)(B, S, D)), 'v': _w((lambda *s: torch.randn(*s, dtype=torch.bfloat16) * 0.8)(B, S, D)), 'shift_k': _w((lambda *s: torch.randn(*s, dtype=torch.bfloat16) * 0.8)(D, ks) * 0.5), 'ssm_k': _w((lambda *s: torch.randn(*s, dtype=torch.bfloat16) * 0.8)(D, S) * (1.0 / S ** 0.5)), 'ssm_D': _w((lambda *s: torch.randn(*s, dtype=torch.bfloat16) * 0.8)(D))}
    _A_in = _A_setup()

    def _B_setup():
        B, S, D, F = (1, 2048, 640, 1728)
        return {'x': _w((lambda *s: torch.randn(*s, dtype=torch.bfloat16) * 0.05)(B, S, D)), 'w1': _w((lambda *s: torch.randn(*s, dtype=torch.bfloat16) * 3.2)(D, D) * D ** (-0.5)), 'w2': _w((lambda *s: torch.randn(*s, dtype=torch.bfloat16) * 3.2)(D, D) * D ** (-0.5)), 'w3': _w((lambda *s: torch.randn(*s, dtype=torch.bfloat16) * 3.2)(D, F) * D ** (-0.5)), 'w4': _w((lambda *s: torch.randn(*s, dtype=torch.bfloat16) * 3.2)(F, D) * F ** (-0.5))}
    _B_in = _B_setup()
    return {'A_q': _A_in['q'], 'A_k': _A_in['k'], 'A_v': _A_in['v'], 'A_shift_k': _A_in['shift_k'], 'A_ssm_k': _A_in['ssm_k'], 'A_ssm_D': _A_in['ssm_D'], 'B_x': _B_in['x'], 'B_w1': _B_in['w1'], 'B_w2': _B_in['w2'], 'B_w3': _B_in['w3'], 'B_w4': _B_in['w4'], 'c': _w((lambda *s: torch.randn(*s, dtype=torch.bfloat16) * 0.1)(1, 640) * 8.0), 'w_mod': _w((lambda *s: torch.randn(*s, dtype=torch.bfloat16) * 0.1)(640, 6 * 640) * 640 ** (-0.5) * 8.0)}

def reference(A_q, A_k, A_v, A_shift_k, A_ssm_k, A_ssm_D, B_x, B_w1, B_w2, B_w3, B_w4, c, w_mod):

    def _A_ref(q, k, v, shift_k, ssm_k, ssm_D):
        B, S, D = q.shape
        ks = shift_k.shape[-1]
        k_pad = _pad(k, ((0, 0), (ks - 1, 0), (0, 0)))
        k_shift = torch.zeros_like(k)
        for t in range(ks):
            k_shift = k_shift + k_pad[:, t:t + S, :] * shift_k[:, ks - 1 - t][None, None, :]
        kv = k_shift * v
        L = 2 * S
        kv_pad = _pad(kv, ((0, 0), (0, S), (0, 0)))
        kf_pad = _pad(ssm_k, ((0, 0), (0, S)))
        kv_f = (lambda x, axes=(-2, -1): torch.fft.rfft2(x.float(), dim=axes))(kv_pad[:, None, :, :], axes=(1, 2))
        kf_f = (lambda x, axes=(-2, -1): torch.fft.rfft2(x.float(), dim=axes))(kf_pad[:, None, :], axes=(1, 2))
        kf_f = (lambda x, *d: x.permute(*d))(kf_f, 1, 2, 0)
        y_f = kv_f * kf_f[None, :, :, :]
        y = (lambda x, s, axes=(-2, -1): torch.fft.irfft2(x, s=s, dim=axes).to(torch.bfloat16))(y_f, (1, L), axes=(1, 2))[:, 0, :S, :]
        y = y + kv * ssm_D[None, None, :]
        return q * y

    def _B_ref(x, w1, w2, w3, w4):
        B, S, D = x.shape
        h = _gelu(_layernorm(x, axis=-1) @ w1)
        c = D // 4
        g0 = _pad(h[:, :, 0 * c:1 * c], ((0, 0), (1, 0), (0, 0)))[:, :S, :]
        g1 = _pad(h[:, :, 1 * c:2 * c], ((0, 0), (0, 1), (0, 0)))[:, 1:, :]
        g2 = _pad(h[:, :, 2 * c:3 * c], ((0, 0), (2, 0), (0, 0)))[:, :S, :]
        g3 = _pad(h[:, :, 3 * c:], ((0, 0), (0, 2), (0, 0)))[:, 2:, :]
        hs = torch.concatenate([g0, g1, g2, g3], axis=-1) @ w2
        x1 = x + hs
        h2 = _gelu(_layernorm(x1, axis=-1) @ w3) @ w4
        return x1 + h2
    x = A_q
    mod = (_silu(c) @ w_mod).reshape(c.shape[0], 6, 1, -1)
    sa, ca, ga, sb, cb, gb = (mod[:, 0].clone(), mod[:, 1].clone(), mod[:, 2].clone(), mod[:, 3].clone(), mod[:, 4].clone(), mod[:, 5].clone())
    h = _layernorm(x, axis=-1) * (1 + ca) + sa
    x = x + ga * _A_ref(h, A_k, A_v, A_shift_k, A_ssm_k, A_ssm_D)
    h = _layernorm(x, axis=-1) * (1 + cb) + sb
    x = x + gb * _B_ref(h, B_w1, B_w2, B_w3, B_w4)
    return x
```

```cpp
#include <cuda_runtime.h>
#include <cuda_bf16.h>
#include <cuda.h>
#include <stdint.h>
#include <string.h>

namespace {

typedef __nv_bfloat16 bf16;
typedef __nv_bfloat162 bf162;

constexpr int S_ = 2048, D_ = 640, F_ = 1728;
constexpr int NTHREADS = 640;
constexpr int NSTAGE = 6;
constexpr int STAGE_BYTES = 32768;

constexpr int SM_RED = 0;
constexpr int SM_PK = 0;
constexpr int SM_PV = 24576;
constexpr int SM_K = 131072;
constexpr int K_STRIDE = 8320;
constexpr int SM_U = SM_K + 5 * K_STRIDE;
constexpr int U_PLANE = 2560, U_STRIDE = 5120;
constexpr int SM_Y = NSTAGE * STAGE_BYTES;
constexpr int SM_MOD = SM_Y + 20480;
constexpr int SM_GV = SM_MOD + 7680;
static_assert(SM_U + 5 * U_STRIDE <= SM_GV, "smem map");
constexpr int SM_BAR = SM_GV + 1024;
constexpr int SM_TOTAL = SM_BAR + 256;
constexpr int SMEM_BYTES = SM_TOTAL + 1024;
static_assert(SMEM_BYTES <= 232448, "smem");

constexpr int BAR_FULL = 0, BAR_EMPTY = 6, BAR_K = 12, BAR_U = 17, BAR_Y = 22;

__device__ __align__(1024) bf16 g_kvT[D_ * S_];
__device__ __align__(1024) uint32_t g_yv[128 * 5120];
__device__ __align__(1024) bf16 g_mod[6 * D_];
__device__ __align__(1024) bf16 g_hn[S_ * D_];
__device__ __align__(1024) bf16 g_hp[S_ * D_];
__device__ __align__(1024) bf16 g_x2[S_ * D_];
__device__ __align__(1024) bf16 g_h1[S_ * D_];
__device__ __align__(1024) bf16 g_x1[S_ * D_];
__device__ __align__(1024) bf16 g_g[S_ * F_];
__device__ __align__(1024) float2 g_st[S_ * 8];
__device__ __align__(1024) float g_cs[F_];
__device__ __align__(1024) unsigned g_flags[96 * 32];
__device__ __align__(1024) unsigned g_epoch[160];
constexpr int FL_P = 0, FL_C = 8, FL_CS = 9, FL_R = 16, FL_B1 = 32, FL_B2 = 48, FL_GA = 64, FL_GB = 80;

#define TS(i) do {} while (0)
#define TSW(i) do {} while (0)

struct Params {
    const bf16 *q, *k, *v, *shift, *ssmk, *ssmD, *w1, *w2, *w3, *w4, *c, *wmod;
    bf16* out;
};
struct Maps { CUtensorMap hn, w1a, w1b, w2a, w2b, w3a, w3b, w3c, w4a, w4b; };

template<int N> __device__ __forceinline__ void wg_rs(float* d,uint32_t a0,uint32_t a1,uint32_t a2,uint32_t a3,uint64_t db,int sc);
template<int N> __device__ __forceinline__ void wg_ss(float* d,uint64_t da,uint64_t db,int sc);
template<> __device__ __forceinline__ void wg_rs<32>(float* d,uint32_t a0,uint32_t a1,uint32_t a2,uint32_t a3,uint64_t db,int sc){
 asm volatile("{.reg .pred p; setp.ne.b32 p,%21,0; wgmma.mma_async.sync.aligned.m64n32k16.f32.bf16.bf16 {%0,%1,%2,%3,%4,%5,%6,%7,%8,%9,%10,%11,%12,%13,%14,%15},{%16,%17,%18,%19},%20,p,1,1,0;}"
 :"+f"(d[0]),"+f"(d[1]),"+f"(d[2]),"+f"(d[3]),"+f"(d[4]),"+f"(d[5]),"+f"(d[6]),"+f"(d[7]),"+f"(d[8]),"+f"(d[9]),"+f"(d[10]),"+f"(d[11]),"+f"(d[12]),"+f"(d[13]),"+f"(d[14]),"+f"(d[15])
 :"r"(a0),"r"(a1),"r"(a2),"r"(a3),"l"(db),"r"(sc)); }
template<> __device__ __forceinline__ void wg_rs<48>(float* d,uint32_t a0,uint32_t a1,uint32_t a2,uint32_t a3,uint64_t db,int sc){
 asm volatile("{.reg .pred p; setp.ne.b32 p,%29,0; wgmma.mma_async.sync.aligned.m64n48k16.f32.bf16.bf16 {%0,%1,%2,%3,%4,%5,%6,%7,%8,%9,%10,%11,%12,%13,%14,%15,%16,%17,%18,%19,%20,%21,%22,%23},{%24,%25,%26,%27},%28,p,1,1,0;}"
 :"+f"(d[0]),"+f"(d[1]),"+f"(d[2]),"+f"(d[3]),"+f"(d[4]),"+f"(d[5]),"+f"(d[6]),"+f"(d[7]),"+f"(d[8]),"+f"(d[9]),"+f"(d[10]),"+f"(d[11]),"+f"(d[12]),"+f"(d[13]),"+f"(d[14]),"+f"(d[15]),"+f"(d[16]),"+f"(d[17]),"+f"(d[18]),"+f"(d[19]),"+f"(d[20]),"+f"(d[21]),"+f"(d[22]),"+f"(d[23])
 :"r"(a0),"r"(a1),"r"(a2),"r"(a3),"l"(db),"r"(sc)); }
template<> __device__ __forceinline__ void wg_rs<64>(float* d,uint32_t a0,uint32_t a1,uint32_t a2,uint32_t a3,uint64_t db,int sc){
 asm volatile("{.reg .pred p; setp.ne.b32 p,%37,0; wgmma.mma_async.sync.aligned.m64n64k16.f32.bf16.bf16 {%0,%1,%2,%3,%4,%5,%6,%7,%8,%9,%10,%11,%12,%13,%14,%15,%16,%17,%18,%19,%20,%21,%22,%23,%24,%25,%26,%27,%28,%29,%30,%31},{%32,%33,%34,%35},%36,p,1,1,0;}"
 :"+f"(d[0]),"+f"(d[1]),"+f"(d[2]),"+f"(d[3]),"+f"(d[4]),"+f"(d[5]),"+f"(d[6]),"+f"(d[7]),"+f"(d[8]),"+f"(d[9]),"+f"(d[10]),"+f"(d[11]),"+f"(d[12]),"+f"(d[13]),"+f"(d[14]),"+f"(d[15]),"+f"(d[16]),"+f"(d[17]),"+f"(d[18]),"+f"(d[19]),"+f"(d[20]),"+f"(d[21]),"+f"(d[22]),"+f"(d[23]),"+f"(d[24]),"+f"(d[25]),"+f"(d[26]),"+f"(d[27]),"+f"(d[28]),"+f"(d[29]),"+f"(d[30]),"+f"(d[31])
 :"r"(a0),"r"(a1),"r"(a2),"r"(a3),"l"(db),"r"(sc)); }
template<> __device__ __forceinline__ void wg_rs<72>(float* d,uint32_t a0,uint32_t a1,uint32_t a2,uint32_t a3,uint64_t db,int sc){
 asm volatile("{.reg .pred p; setp.ne.b32 p,%41,0; wgmma.mma_async.sync.aligned.m64n72k16.f32.bf16.bf16 {%0,%1,%2,%3,%4,%5,%6,%7,%8,%9,%10,%11,%12,%13,%14,%15,%16,%17,%18,%19,%20,%21,%22,%23,%24,%25,%26,%27,%28,%29,%30,%31,%32,%33,%34,%35},{%36,%37,%38,%39},%40,p,1,1,0;}"
 :"+f"(d[0]),"+f"(d[1]),"+f"(d[2]),"+f"(d[3]),"+f"(d[4]),"+f"(d[5]),"+f"(d[6]),"+f"(d[7]),"+f"(d[8]),"+f"(d[9]),"+f"(d[10]),"+f"(d[11]),"+f"(d[12]),"+f"(d[13]),"+f"(d[14]),"+f"(d[15]),"+f"(d[16]),"+f"(d[17]),"+f"(d[18]),"+f"(d[19]),"+f"(d[20]),"+f"(d[21]),"+f"(d[22]),"+f"(d[23]),"+f"(d[24]),"+f"(d[25]),"+f"(d[26]),"+f"(d[27]),"+f"(d[28]),"+f"(d[29]),"+f"(d[30]),"+f"(d[31]),"+f"(d[32]),"+f"(d[33]),"+f"(d[34]),"+f"(d[35])
 :"r"(a0),"r"(a1),"r"(a2),"r"(a3),"l"(db),"r"(sc)); }
template<> __device__ __forceinline__ void wg_rs<80>(float* d,uint32_t a0,uint32_t a1,uint32_t a2,uint32_t a3,uint64_t db,int sc){
 asm volatile("{.reg .pred p; setp.ne.b32 p,%45,0; wgmma.mma_async.sync.aligned.m64n80k16.f32.bf16.bf16 {%0,%1,%2,%3,%4,%5,%6,%7,%8,%9,%10,%11,%12,%13,%14,%15,%16,%17,%18,%19,%20,%21,%22,%23,%24,%25,%26,%27,%28,%29,%30,%31,%32,%33,%34,%35,%36,%37,%38,%39},{%40,%41,%42,%43},%44,p,1,1,0;}"
 :"+f"(d[0]),"+f"(d[1]),"+f"(d[2]),"+f"(d[3]),"+f"(d[4]),"+f"(d[5]),"+f"(d[6]),"+f"(d[7]),"+f"(d[8]),"+f"(d[9]),"+f"(d[10]),"+f"(d[11]),"+f"(d[12]),"+f"(d[13]),"+f"(d[14]),"+f"(d[15]),"+f"(d[16]),"+f"(d[17]),"+f"(d[18]),"+f"(d[19]),"+f"(d[20]),"+f"(d[21]),"+f"(d[22]),"+f"(d[23]),"+f"(d[24]),"+f"(d[25]),"+f"(d[26]),"+f"(d[27]),"+f"(d[28]),"+f"(d[29]),"+f"(d[30]),"+f"(d[31]),"+f"(d[32]),"+f"(d[33]),"+f"(d[34]),"+f"(d[35]),"+f"(d[36]),"+f"(d[37]),"+f"(d[38]),"+f"(d[39])
 :"r"(a0),"r"(a1),"r"(a2),"r"(a3),"l"(db),"r"(sc)); }
template<> __device__ __forceinline__ void wg_rs<88>(float* d,uint32_t a0,uint32_t a1,uint32_t a2,uint32_t a3,uint64_t db,int sc){
 asm volatile("{.reg .pred p; setp.ne.b32 p,%49,0; wgmma.mma_async.sync.aligned.m64n88k16.f32.bf16.bf16 {%0,%1,%2,%3,%4,%5,%6,%7,%8,%9,%10,%11,%12,%13,%14,%15,%16,%17,%18,%19,%20,%21,%22,%23,%24,%25,%26,%27,%28,%29,%30,%31,%32,%33,%34,%35,%36,%37,%38,%39,%40,%41,%42,%43},{%44,%45,%46,%47},%48,p,1,1,0;}"
 :"+f"(d[0]),"+f"(d[1]),"+f"(d[2]),"+f"(d[3]),"+f"(d[4]),"+f"(d[5]),"+f"(d[6]),"+f"(d[7]),"+f"(d[8]),"+f"(d[9]),"+f"(d[10]),"+f"(d[11]),"+f"(d[12]),"+f"(d[13]),"+f"(d[14]),"+f"(d[15]),"+f"(d[16]),"+f"(d[17]),"+f"(d[18]),"+f"(d[19]),"+f"(d[20]),"+f"(d[21]),"+f"(d[22]),"+f"(d[23]),"+f"(d[24]),"+f"(d[25]),"+f"(d[26]),"+f"(d[27]),"+f"(d[28]),"+f"(d[29]),"+f"(d[30]),"+f"(d[31]),"+f"(d[32]),"+f"(d[33]),"+f"(d[34]),"+f"(d[35]),"+f"(d[36]),"+f"(d[37]),"+f"(d[38]),"+f"(d[39]),"+f"(d[40]),"+f"(d[41]),"+f"(d[42]),"+f"(d[43])
 :"r"(a0),"r"(a1),"r"(a2),"r"(a3),"l"(db),"r"(sc)); }
template<> __device__ __forceinline__ void wg_rs<96>(float* d,uint32_t a0,uint32_t a1,uint32_t a2,uint32_t a3,uint64_t db,int sc){
 asm volatile("{.reg .pred p; setp.ne.b32 p,%53,0; wgmma.mma_async.sync.aligned.m64n96k16.f32.bf16.bf16 {%0,%1,%2,%3,%4,%5,%6,%7,%8,%9,%10,%11,%12,%13,%14,%15,%16,%17,%18,%19,%20,%21,%22,%23,%24,%25,%26,%27,%28,%29,%30,%31,%32,%33,%34,%35,%36,%37,%38,%39,%40,%41,%42,%43,%44,%45,%46,%47},{%48,%49,%50,%51},%52,p,1,1,0;}"
 :"+f"(d[0]),"+f"(d[1]),"+f"(d[2]),"+f"(d[3]),"+f"(d[4]),"+f"(d[5]),"+f"(d[6]),"+f"(d[7]),"+f"(d[8]),"+f"(d[9]),"+f"(d[10]),"+f"(d[11]),"+f"(d[12]),"+f"(d[13]),"+f"(d[14]),"+f"(d[15]),"+f"(d[16]),"+f"(d[17]),"+f"(d[18]),"+f"(d[19]),"+f"(d[20]),"+f"(d[21]),"+f"(d[22]),"+f"(d[23]),"+f"(d[24]),"+f"(d[25]),"+f"(d[26]),"+f"(d[27]),"+f"(d[28]),"+f"(d[29]),"+f"(d[30]),"+f"(d[31]),"+f"(d[32]),"+f"(d[33]),"+f"(d[34]),"+f"(d[35]),"+f"(d[36]),"+f"(d[37]),"+f"(d[38]),"+f"(d[39]),"+f"(d[40]),"+f"(d[41]),"+f"(d[42]),"+f"(d[43]),"+f"(d[44]),"+f"(d[45]),"+f"(d[46]),"+f"(d[47])
 :"r"(a0),"r"(a1),"r"(a2),"r"(a3),"l"(db),"r"(sc)); }
template<> __device__ __forceinline__ void wg_rs<104>(float* d,uint32_t a0,uint32_t a1,uint32_t a2,uint32_t a3,uint64_t db,int sc){
 asm volatile("{.reg .pred p; setp.ne.b32 p,%57,0; wgmma.mma_async.sync.aligned.m64n104k16.f32.bf16.bf16 {%0,%1,%2,%3,%4,%5,%6,%7,%8,%9,%10,%11,%12,%13,%14,%15,%16,%17,%18,%19,%20,%21,%22,%23,%24,%25,%26,%27,%28,%29,%30,%31,%32,%33,%34,%35,%36,%37,%38,%39,%40,%41,%42,%43,%44,%45,%46,%47,%48,%49,%50,%51},{%52,%53,%54,%55},%56,p,1,1,0;}"
 :"+f"(d[0]),"+f"(d[1]),"+f"(d[2]),"+f"(d[3]),"+f"(d[4]),"+f"(d[5]),"+f"(d[6]),"+f"(d[7]),"+f"(d[8]),"+f"(d[9]),"+f"(d[10]),"+f"(d[11]),"+f"(d[12]),"+f"(d[13]),"+f"(d[14]),"+f"(d[15]),"+f"(d[16]),"+f"(d[17]),"+f"(d[18]),"+f"(d[19]),"+f"(d[20]),"+f"(d[21]),"+f"(d[22]),"+f"(d[23]),"+f"(d[24]),"+f"(d[25]),"+f"(d[26]),"+f"(d[27]),"+f"(d[28]),"+f"(d[29]),"+f"(d[30]),"+f"(d[31]),"+f"(d[32]),"+f"(d[33]),"+f"(d[34]),"+f"(d[35]),"+f"(d[36]),"+f"(d[37]),"+f"(d[38]),"+f"(d[39]),"+f"(d[40]),"+f"(d[41]),"+f"(d[42]),"+f"(d[43]),"+f"(d[44]),"+f"(d[45]),"+f"(d[46]),"+f"(d[47]),"+f"(d[48]),"+f"(d[49]),"+f"(d[50]),"+f"(d[51])
 :"r"(a0),"r"(a1),"r"(a2),"r"(a3),"l"(db),"r"(sc)); }
template<> __device__ __forceinline__ void wg_rs<112>(float* d,uint32_t a0,uint32_t a1,uint32_t a2,uint32_t a3,uint64_t db,int sc){
 asm volatile("{.reg .pred p; setp.ne.b32 p,%61,0; wgmma.mma_async.sync.aligned.m64n112k16.f32.bf16.bf16 {%0,%1,%2,%3,%4,%5,%6,%7,%8,%9,%10,%11,%12,%13,%14,%15,%16,%17,%18,%19,%20,%21,%22,%23,%24,%25,%26,%27,%28,%29,%30,%31,%32,%33,%34,%35,%36,%37,%38,%39,%40,%41,%42,%43,%44,%45,%46,%47,%48,%49,%50,%51,%52,%53,%54,%55},{%56,%57,%58,%59},%60,p,1,1,0;}"
 :"+f"(d[0]),"+f"(d[1]),"+f"(d[2]),"+f"(d[3]),"+f"(d[4]),"+f"(d[5]),"+f"(d[6]),"+f"(d[7]),"+f"(d[8]),"+f"(d[9]),"+f"(d[10]),"+f"(d[11]),"+f"(d[12]),"+f"(d[13]),"+f"(d[14]),"+f"(d[15]),"+f"(d[16]),"+f"(d[17]),"+f"(d[18]),"+f"(d[19]),"+f"(d[20]),"+f"(d[21]),"+f"(d[22]),"+f"(d[23]),"+f"(d[24]),"+f"(d[25]),"+f"(d[26]),"+f"(d[27]),"+f"(d[28]),"+f"(d[29]),"+f"(d[30]),"+f"(d[31]),"+f"(d[32]),"+f"(d[33]),"+f"(d[34]),"+f"(d[35]),"+f"(d[36]),"+f"(d[37]),"+f"(d[38]),"+f"(d[39]),"+f"(d[40]),"+f"(d[41]),"+f"(d[42]),"+f"(d[43]),"+f"(d[44]),"+f"(d[45]),"+f"(d[46]),"+f"(d[47]),"+f"(d[48]),"+f"(d[49]),"+f"(d[50]),"+f"(d[51]),"+f"(d[52]),"+f"(d[53]),"+f"(d[54]),"+f"(d[55])
 :"r"(a0),"r"(a1),"r"(a2),"r"(a3),"l"(db),"r"(sc)); }
template<> __device__ __forceinline__ void wg_rs<120>(float* d,uint32_t a0,uint32_t a1,uint32_t a2,uint32_t a3,uint64_t db,int sc){
 asm volatile("{.reg .pred p; setp.ne.b32 p,%65,0; wgmma.mma_async.sync.aligned.m64n120k16.f32.bf16.bf16 {%0,%1,%2,%3,%4,%5,%6,%7,%8,%9,%10,%11,%12,%13,%14,%15,%16,%17,%18,%19,%20,%21,%22,%23,%24,%25,%26,%27,%28,%29,%30,%31,%32,%33,%34,%35,%36,%37,%38,%39,%40,%41,%42,%43,%44,%45,%46,%47,%48,%49,%50,%51,%52,%53,%54,%55,%56,%57,%58,%59},{%60,%61,%62,%63},%64,p,1,1,0;}"
 :"+f"(d[0]),"+f"(d[1]),"+f"(d[2]),"+f"(d[3]),"+f"(d[4]),"+f"(d[5]),"+f"(d[6]),"+f"(d[7]),"+f"(d[8]),"+f"(d[9]),"+f"(d[10]),"+f"(d[11]),"+f"(d[12]),"+f"(d[13]),"+f"(d[14]),"+f"(d[15]),"+f"(d[16]),"+f"(d[17]),"+f"(d[18]),"+f"(d[19]),"+f"(d[20]),"+f"(d[21]),"+f"(d[22]),"+f"(d[23]),"+f"(d[24]),"+f"(d[25]),"+f"(d[26]),"+f"(d[27]),"+f"(d[28]),"+f"(d[29]),"+f"(d[30]),"+f"(d[31]),"+f"(d[32]),"+f"(d[33]),"+f"(d[34]),"+f"(d[35]),"+f"(d[36]),"+f"(d[37]),"+f"(d[38]),"+f"(d[39]),"+f"(d[40]),"+f"(d[41]),"+f"(d[42]),"+f"(d[43]),"+f"(d[44]),"+f"(d[45]),"+f"(d[46]),"+f"(d[47]),"+f"(d[48]),"+f"(d[49]),"+f"(d[50]),"+f"(d[51]),"+f"(d[52]),"+f"(d[53]),"+f"(d[54]),"+f"(d[55]),"+f"(d[56]),"+f"(d[57]),"+f"(d[58]),"+f"(d[59])
 :"r"(a0),"r"(a1),"r"(a2),"r"(a3),"l"(db),"r"(sc)); }
template<> __device__ __forceinline__ void wg_rs<128>(float* d,uint32_t a0,uint32_t a1,uint32_t a2,uint32_t a3,uint64_t db,int sc){
 asm volatile("{.reg .pred p; setp.ne.b32 p,%69,0; wgmma.mma_async.sync.aligned.m64n128k16.f32.bf16.bf16 {%0,%1,%2,%3,%4,%5,%6,%7,%8,%9,%10,%11,%12,%13,%14,%15,%16,%17,%18,%19,%20,%21,%22,%23,%24,%25,%26,%27,%28,%29,%30,%31,%32,%33,%34,%35,%36,%37,%38,%39,%40,%41,%42,%43,%44,%45,%46,%47,%48,%49,%50,%51,%52,%53,%54,%55,%56,%57,%58,%59,%60,%61,%62,%63},{%64,%65,%66,%67},%68,p,1,1,0;}"
 :"+f"(d[0]),"+f"(d[1]),"+f"(d[2]),"+f"(d[3]),"+f"(d[4]),"+f"(d[5]),"+f"(d[6]),"+f"(d[7]),"+f"(d[8]),"+f"(d[9]),"+f"(d[10]),"+f"(d[11]),"+f"(d[12]),"+f"(d[13]),"+f"(d[14]),"+f"(d[15]),"+f"(d[16]),"+f"(d[17]),"+f"(d[18]),"+f"(d[19]),"+f"(d[20]),"+f"(d[21]),"+f"(d[22]),"+f"(d[23]),"+f"(d[24]),"+f"(d[25]),"+f"(d[26]),"+f"(d[27]),"+f"(d[28]),"+f"(d[29]),"+f"(d[30]),"+f"(d[31]),"+f"(d[32]),"+f"(d[33]),"+f"(d[34]),"+f"(d[35]),"+f"(d[36]),"+f"(d[37]),"+f"(d[38]),"+f"(d[39]),"+f"(d[40]),"+f"(d[41]),"+f"(d[42]),"+f"(d[43]),"+f"(d[44]),"+f"(d[45]),"+f"(d[46]),"+f"(d[47]),"+f"(d[48]),"+f"(d[49]),"+f"(d[50]),"+f"(d[51]),"+f"(d[52]),"+f"(d[53]),"+f"(d[54]),"+f"(d[55]),"+f"(d[56]),"+f"(d[57]),"+f"(d[58]),"+f"(d[59]),"+f"(d[60]),"+f"(d[61]),"+f"(d[62]),"+f"(d[63])
 :"r"(a0),"r"(a1),"r"(a2),"r"(a3),"l"(db),"r"(sc)); }
template<> __device__ __forceinline__ void wg_ss<80>(float* d,uint64_t da,uint64_t db,int sc){
 asm volatile("{.reg .pred p; setp.ne.b32 p,%42,0; wgmma.mma_async.sync.aligned.m64n80k16.f32.bf16.bf16 {%0,%1,%2,%3,%4,%5,%6,%7,%8,%9,%10,%11,%12,%13,%14,%15,%16,%17,%18,%19,%20,%21,%22,%23,%24,%25,%26,%27,%28,%29,%30,%31,%32,%33,%34,%35,%36,%37,%38,%39},%40,%41,p,1,1,0,1;}"
 :"+f"(d[0]),"+f"(d[1]),"+f"(d[2]),"+f"(d[3]),"+f"(d[4]),"+f"(d[5]),"+f"(d[6]),"+f"(d[7]),"+f"(d[8]),"+f"(d[9]),"+f"(d[10]),"+f"(d[11]),"+f"(d[12]),"+f"(d[13]),"+f"(d[14]),"+f"(d[15]),"+f"(d[16]),"+f"(d[17]),"+f"(d[18]),"+f"(d[19]),"+f"(d[20]),"+f"(d[21]),"+f"(d[22]),"+f"(d[23]),"+f"(d[24]),"+f"(d[25]),"+f"(d[26]),"+f"(d[27]),"+f"(d[28]),"+f"(d[29]),"+f"(d[30]),"+f"(d[31]),"+f"(d[32]),"+f"(d[33]),"+f"(d[34]),"+f"(d[35]),"+f"(d[36]),"+f"(d[37]),"+f"(d[38]),"+f"(d[39])
 :"l"(da),"l"(db),"r"(sc)); }
template<> __device__ __forceinline__ void wg_ss<104>(float* d,uint64_t da,uint64_t db,int sc){
 asm volatile("{.reg .pred p; setp.ne.b32 p,%54,0; wgmma.mma_async.sync.aligned.m64n104k16.f32.bf16.bf16 {%0,%1,%2,%3,%4,%5,%6,%7,%8,%9,%10,%11,%12,%13,%14,%15,%16,%17,%18,%19,%20,%21,%22,%23,%24,%25,%26,%27,%28,%29,%30,%31,%32,%33,%34,%35,%36,%37,%38,%39,%40,%41,%42,%43,%44,%45,%46,%47,%48,%49,%50,%51},%52,%53,p,1,1,0,1;}"
 :"+f"(d[0]),"+f"(d[1]),"+f"(d[2]),"+f"(d[3]),"+f"(d[4]),"+f"(d[5]),"+f"(d[6]),"+f"(d[7]),"+f"(d[8]),"+f"(d[9]),"+f"(d[10]),"+f"(d[11]),"+f"(d[12]),"+f"(d[13]),"+f"(d[14]),"+f"(d[15]),"+f"(d[16]),"+f"(d[17]),"+f"(d[18]),"+f"(d[19]),"+f"(d[20]),"+f"(d[21]),"+f"(d[22]),"+f"(d[23]),"+f"(d[24]),"+f"(d[25]),"+f"(d[26]),"+f"(d[27]),"+f"(d[28]),"+f"(d[29]),"+f"(d[30]),"+f"(d[31]),"+f"(d[32]),"+f"(d[33]),"+f"(d[34]),"+f"(d[35]),"+f"(d[36]),"+f"(d[37]),"+f"(d[38]),"+f"(d[39]),"+f"(d[40]),"+f"(d[41]),"+f"(d[42]),"+f"(d[43]),"+f"(d[44]),"+f"(d[45]),"+f"(d[46]),"+f"(d[47]),"+f"(d[48]),"+f"(d[49]),"+f"(d[50]),"+f"(d[51])
 :"l"(da),"l"(db),"r"(sc)); }
template<> __device__ __forceinline__ void wg_ss<112>(float* d,uint64_t da,uint64_t db,int sc){
 asm volatile("{.reg .pred p; setp.ne.b32 p,%58,0; wgmma.mma_async.sync.aligned.m64n112k16.f32.bf16.bf16 {%0,%1,%2,%3,%4,%5,%6,%7,%8,%9,%10,%11,%12,%13,%14,%15,%16,%17,%18,%19,%20,%21,%22,%23,%24,%25,%26,%27,%28,%29,%30,%31,%32,%33,%34,%35,%36,%37,%38,%39,%40,%41,%42,%43,%44,%45,%46,%47,%48,%49,%50,%51,%52,%53,%54,%55},%56,%57,p,1,1,0,1;}"
 :"+f"(d[0]),"+f"(d[1]),"+f"(d[2]),"+f"(d[3]),"+f"(d[4]),"+f"(d[5]),"+f"(d[6]),"+f"(d[7]),"+f"(d[8]),"+f"(d[9]),"+f"(d[10]),"+f"(d[11]),"+f"(d[12]),"+f"(d[13]),"+f"(d[14]),"+f"(d[15]),"+f"(d[16]),"+f"(d[17]),"+f"(d[18]),"+f"(d[19]),"+f"(d[20]),"+f"(d[21]),"+f"(d[22]),"+f"(d[23]),"+f"(d[24]),"+f"(d[25]),"+f"(d[26]),"+f"(d[27]),"+f"(d[28]),"+f"(d[29]),"+f"(d[30]),"+f"(d[31]),"+f"(d[32]),"+f"(d[33]),"+f"(d[34]),"+f"(d[35]),"+f"(d[36]),"+f"(d[37]),"+f"(d[38]),"+f"(d[39]),"+f"(d[40]),"+f"(d[41]),"+f"(d[42]),"+f"(d[43]),"+f"(d[44]),"+f"(d[45]),"+f"(d[46]),"+f"(d[47]),"+f"(d[48]),"+f"(d[49]),"+f"(d[50]),"+f"(d[51]),"+f"(d[52]),"+f"(d[53]),"+f"(d[54]),"+f"(d[55])
 :"l"(da),"l"(db),"r"(sc)); }

__device__ __forceinline__ void wg_fence() { asm volatile("wgmma.fence.sync.aligned;" ::: "memory"); }
__device__ __forceinline__ void wg_commit() { asm volatile("wgmma.commit_group.sync.aligned;" ::: "memory"); }
template <int N> __device__ __forceinline__ void wg_wait() { asm volatile("wgmma.wait_group.sync.aligned %0;" ::"n"(N) : "memory"); }
template <int N> __device__ __forceinline__ void reg_fence(float* d) {
#pragma unroll
    for (int i = 0; i < N; i++) asm volatile("" : "+f"(d[i])::"memory");
}
__device__ __forceinline__ uint64_t mkdesc(uint32_t addr, uint32_t lbo, uint32_t sbo, uint32_t sw) {
    return (uint64_t)((addr & 0x3FFFF) >> 4) | ((uint64_t)(lbo >> 4) << 16) | ((uint64_t)(sbo >> 4) << 32) | ((uint64_t)sw << 62);
}
__device__ __forceinline__ uint32_t smem_u32(const void* p) { return (uint32_t)__cvta_generic_to_shared(p); }
__device__ __forceinline__ bool elect() {
    uint32_t p;
    asm volatile("{.reg .pred P; elect.sync _|P, 0xffffffff; selp.u32 %0,1,0,P;}" : "=r"(p));
    return p;
}
__device__ __forceinline__ void mbar_init(uint32_t bar, uint32_t cnt) { asm volatile("mbarrier.init.shared::cta.b64 [%0], %1;" ::"r"(bar), "r"(cnt) : "memory"); }
__device__ __forceinline__ void mbar_expect(uint32_t bar, uint32_t bytes) { asm volatile("mbarrier.arrive.expect_tx.shared::cta.b64 _, [%0], %1;" ::"r"(bar), "r"(bytes) : "memory"); }
__device__ __forceinline__ void mbar_arrive(uint32_t bar) { asm volatile("mbarrier.arrive.shared::cta.b64 _, [%0];" ::"r"(bar) : "memory"); }
__device__ __forceinline__ bool mbar_try(uint32_t bar, uint32_t par) {
    uint32_t ok;
    asm volatile("{.reg .pred p; mbarrier.try_wait.parity.shared::cta.b64 p, [%1], %2; selp.u32 %0,1,0,p;}" : "=r"(ok) : "r"(bar), "r"(par) : "memory");
    return ok;
}
constexpr int SPIN_LIMIT = 1 << 18;
__device__ __forceinline__ void mbar_wait(uint32_t bar, uint32_t par) {
    int n = 0;
    while (!mbar_try(bar, par) && ++n < SPIN_LIMIT) {}
}
__device__ __forceinline__ void bulk_g2s(uint32_t dst, const void* src, uint32_t bytes, uint32_t bar) {
    asm volatile("cp.async.bulk.shared::cluster.global.mbarrier::complete_tx::bytes [%0], [%1], %2, [%3];" ::"r"(dst), "l"(src), "r"(bytes), "r"(bar) : "memory");
}
__device__ __forceinline__ void bulk_prefetch(const void* src, uint32_t bytes) {
    asm volatile("cp.async.bulk.prefetch.L2.global [%0], %1;" ::"l"(src), "r"(bytes) : "memory");
}
__device__ __forceinline__ void tma2d(uint32_t dst, const CUtensorMap* m, int c0, int c1, uint32_t bar) {
    asm volatile("cp.async.bulk.tensor.2d.shared::cluster.global.mbarrier::complete_tx::bytes [%0], [%1, {%3, %4}], [%2];" ::"r"(dst), "l"(m), "r"(bar), "r"(c0), "r"(c1) : "memory");
}
__device__ __forceinline__ void prefetch_map(const CUtensorMap* m) { asm volatile("prefetch.tensormap [%0];" ::"l"(m) : "memory"); }
__device__ __forceinline__ void cpasync16(uint32_t dst, const void* src, uint32_t srcsz) {
    asm volatile("cp.async.cg.shared.global [%0], [%1], 16, %2;" ::"r"(dst), "l"(src), "r"(srcsz) : "memory");
}
__device__ __forceinline__ void bar_sync(int id, int n) { asm volatile("bar.sync %0, %1;" ::"r"(id), "r"(n) : "memory"); }
__device__ __forceinline__ void bar_arrive(int id, int n) { asm volatile("bar.arrive %0, %1;" ::"r"(id), "r"(n) : "memory"); }
__device__ __forceinline__ void fence_async_smem() { asm volatile("fence.proxy.async.shared::cta;" ::: "memory"); }
__device__ __forceinline__ void fence_async_global() { asm volatile("fence.proxy.async.global;" ::: "memory"); }
__device__ __forceinline__ void flag_release(int f) { asm volatile("red.release.gpu.global.add.u32 [%0], 1;" ::"l"(&g_flags[f * 32]) : "memory"); }
__device__ __forceinline__ void flag_wait(int f, unsigned target) {
    const unsigned* p = &g_flags[f * 32];
    unsigned v; int n = 0;
    do {
        asm volatile("ld.acquire.gpu.global.u32 %0, [%1];" : "=r"(v) : "l"(p) : "memory");
    } while ((int)(v - target) < 0 && ++n < SPIN_LIMIT);
}
__device__ __forceinline__ uint32_t lds32(uint32_t a) { uint32_t v; asm volatile("ld.shared.u32 %0, [%1];" : "=r"(v) : "r"(a)); return v; }
__device__ __forceinline__ uint32_t lds16(uint32_t a) { uint16_t v; asm volatile("ld.shared.u16 %0, [%1];" : "=h"(v) : "r"(a)); return v; }
__device__ __forceinline__ uint4 lds128(uint32_t a) { uint4 v; asm volatile("ld.shared.v4.u32 {%0,%1,%2,%3}, [%4];" : "=r"(v.x), "=r"(v.y), "=r"(v.z), "=r"(v.w) : "r"(a)); return v; }
__device__ __forceinline__ float4 lds128f(uint32_t a) { float4 v; asm volatile("ld.shared.v4.f32 {%0,%1,%2,%3}, [%4];" : "=f"(v.x), "=f"(v.y), "=f"(v.z), "=f"(v.w) : "r"(a)); return v; }
__device__ __forceinline__ void sts128(uint32_t a, uint4 v) { asm volatile("st.shared.v4.u32 [%0], {%1,%2,%3,%4};" ::"r"(a), "r"(v.x), "r"(v.y), "r"(v.z), "r"(v.w) : "memory"); }
__device__ __forceinline__ void sts128f(uint32_t a, float x, float y, float z, float w) { asm volatile("st.shared.v4.f32 [%0], {%1,%2,%3,%4};" ::"r"(a), "f"(x), "f"(y), "f"(z), "f"(w) : "memory"); }
__device__ __forceinline__ uint32_t prmt(uint32_t a, uint32_t b, uint32_t s) { uint32_t r; asm("prmt.b32 %0,%1,%2,%3;" : "=r"(r) : "r"(a), "r"(b), "r"(s)); return r; }
__device__ __forceinline__ uint32_t pack2(float lo, float hi) { uint32_t r; asm("cvt.rn.bf16x2.f32 %0, %1, %2;" : "=r"(r) : "f"(hi), "f"(lo)); return r; }
__device__ __forceinline__ float blo(uint32_t v) { return __uint_as_float(v << 16); }
__device__ __forceinline__ float bhi(uint32_t v) { return __uint_as_float(v & 0xffff0000u); }
__device__ __forceinline__ uint32_t bmul2(uint32_t a, uint32_t b) { uint32_t r; asm("mul.rn.bf16x2 %0,%1,%2;" : "=r"(r) : "r"(a), "r"(b)); return r; }
__device__ __forceinline__ uint32_t badd2(uint32_t a, uint32_t b) { uint32_t r; asm("add.rn.bf16x2 %0,%1,%2;" : "=r"(r) : "r"(a), "r"(b)); return r; }
__device__ __forceinline__ float rbf(float x) { return __bfloat162float(__float2bfloat16_rn(x)); }
__device__ __forceinline__ uint32_t ldcg32(const void* p) { uint32_t v; asm volatile("ld.global.cg.u32 %0, [%1];" : "=r"(v) : "l"(p) : "memory"); return v; }
__device__ __forceinline__ uint2 ldcg64(const void* p) { uint2 v; asm volatile("ld.global.cg.v2.u32 {%0,%1}, [%2];" : "=r"(v.x), "=r"(v.y) : "l"(p) : "memory"); return v; }
__device__ __forceinline__ float4 ldcg128f(const void* p) { float4 v; asm volatile("ld.global.cg.v4.f32 {%0,%1,%2,%3}, [%4];" : "=f"(v.x), "=f"(v.y), "=f"(v.z), "=f"(v.w) : "l"(p) : "memory"); return v; }
__device__ __forceinline__ float gelu(float x) {
    float t = x * x;
    float u = x * fmaf(t, 0.044715f * 0.7978845608028654f, 0.7978845608028654f);
    float th;
    asm("tanh.approx.f32 %0, %1;" : "=f"(th) : "f"(u));
    float hx = 0.5f * x;
    return fmaf(hx, th, hx);
}
__device__ __forceinline__ void ln_params(float sum, float sq, float& inv, float& nb) {
    float mean = sum * (1.0f / D_);
    float var = fmaxf(fmaf(-mean, mean, sq * (1.0f / D_)), 0.0f);
    float den = rbf(sqrtf(rbf(rbf(var) + 1e-5f)));
    inv = 1.0f / den;
    nb = -rbf(mean) * inv;
}
__device__ __forceinline__ void row_ln(const uint32_t* v, uint32_t* o) {
    float s = 0.f, q = 0.f;
#pragma unroll
    for (int i = 0; i < 10; i++) { float a = blo(v[i]), b = bhi(v[i]); s += a + b; q = fmaf(a, a, fmaf(b, b, q)); }
#pragma unroll
    for (int m = 16; m; m >>= 1) { s += __shfl_xor_sync(0xffffffffu, s, m); q += __shfl_xor_sync(0xffffffffu, q, m); }
    float inv, nb;
    ln_params(s, q, inv, nb);
#pragma unroll
    for (int i = 0; i < 10; i++) o[i] = pack2(fmaf(blo(v[i]), inv, nb), fmaf(bhi(v[i]), inv, nb));
}

struct AFrag { uint32_t m, a, b, c, d; };
__device__ __forceinline__ AFrag ldA(uint32_t a) { AFrag f; f.m = lds32(a - 16); f.a = lds32(a); f.b = lds32(a + 16); f.c = lds32(a + 32); f.d = lds32(a + 48); return f; }
template <int N, int M> __device__ __forceinline__ void conv_pair(float* d, const AFrag& f, uint64_t descU) {
    wg_rs<N>(d, f.a, f.b, f.m, f.a, descU + 8 * M, M > 0);
    if (M == 0) { wg_commit(); wg_wait<0>(); wg_fence(); }
    wg_rs<N>(d, f.c, f.d, f.b, f.c, descU + 8 * M + 1, 1);
}
template <int Q> __device__ __forceinline__ void conv_put(float* d, uint32_t r0, uint32_t r1) {
    sts128f(((Q & 1) ? r1 : r0) + (Q >> 1) * 128, d[4 * Q], d[4 * Q + 1], d[4 * Q + 2], d[4 * Q + 3]);
}
template <int M> __device__ __forceinline__ void conv_head(float* d, AFrag& f, uint32_t kaddr, uint64_t descU, uint32_t r0, uint32_t r1) {
    wg_fence();
    conv_pair<128 - 8 * M, M>(d, f, descU);
    wg_commit();
    if constexpr (M > 0) conv_put<16 - M>(d, r0, r1);
    AFrag n = ldA(kaddr + 256 * (M + 1));
    wg_wait<0>();
    f = n;
    if constexpr (M < 7) conv_head<M + 1>(d, f, kaddr, descU, r0, r1);
}
__device__ __forceinline__ void conv_main(float* d, AFrag f, uint32_t kaddr, uint64_t descU, uint32_t r0, uint32_t r1, int handoff) {
    conv_head<0>(d, f, kaddr, descU, r0, r1);
    AFrag f1 = ldA(kaddr + 256 * 9);
    wg_fence();
    conv_pair<64, 8>(d, f, descU); conv_pair<64, 9>(d, f1, descU);
    wg_commit();
    if (handoff) bar_arrive(handoff, 512);
    conv_put<8>(d, r0, r1);
    AFrag f2 = ldA(kaddr + 256 * 10), f3 = ldA(kaddr + 256 * 11);
    wg_wait<0>();
    wg_fence();
    conv_pair<48, 10>(d, f2, descU); conv_pair<48, 11>(d, f3, descU);
    wg_commit();
    conv_put<7>(d, r0, r1); conv_put<6>(d, r0, r1);
    AFrag f4 = ldA(kaddr + 256 * 12), f5 = ldA(kaddr + 256 * 13), f6 = ldA(kaddr + 256 * 14), f7 = ldA(kaddr + 256 * 15);
    wg_wait<0>();
    wg_fence();
    conv_pair<32, 12>(d, f4, descU); conv_pair<32, 13>(d, f5, descU); conv_pair<32, 14>(d, f6, descU); conv_pair<32, 15>(d, f7, descU);
    wg_commit();
    conv_put<5>(d, r0, r1); conv_put<4>(d, r0, r1);
    wg_wait<0>();
    conv_put<3>(d, r0, r1); conv_put<2>(d, r0, r1); conv_put<1>(d, r0, r1);
}

template <int N, bool ASWZ>
__device__ __forceinline__ void gemm_issue(float* acc, uint32_t sb, int st, int ph, int half, int sc0) {
    mbar_wait(sb + SM_BAR + (BAR_FULL + st) * 8, ph);
    uint32_t base = sb + st * STAGE_BYTES;
    uint64_t da = ASWZ ? mkdesc(base + half * 8192, 16, 1024, 1) : mkdesc(base + half * 1024, 2048, 128, 0);
    uint64_t db = mkdesc(base + 16384, 8192, 1024, 1);
    wg_fence();
#pragma unroll
    for (int k = 0; k < 4; k++) wg_ss<N>(acc, da + (ASWZ ? 2 : 256) * k, db + 128 * k, k == 0 ? sc0 : 1);
    wg_commit();
}
template <int N, bool ASWZ, int IT0, int NKB, bool ZERO, int ORDER_BAR, class HOOK>
__device__ __forceinline__ void gemm_loop(float* acc, uint32_t sb, int half, HOOK hook) {
    int st = IT0 % NSTAGE, ph = (IT0 / NSTAGE) & 1;
    const uint32_t ebar = sb + SM_BAR + BAR_EMPTY * 8;
    const bool signal = (threadIdx.x & 127) == 0;
    gemm_issue<N, ASWZ>(acc, sb, st, ph, half, ZERO ? 0 : 1);
    hook();
#pragma unroll 1
    for (int kb = 1; kb < NKB; kb++) {
        const int prev = st;
        if (++st == NSTAGE) { st = 0; ph ^= 1; }
        gemm_issue<N, ASWZ>(acc, sb, st, ph, half, 1);
        wg_wait<1>();
        if (signal) mbar_arrive(ebar + prev * 8);
    }
    if (ORDER_BAR) bar_arrive(ORDER_BAR, 512);
    wg_wait<0>();
    if (signal) mbar_arrive(ebar + st * 8);
    reg_fence<N / 2>(acc);
}

template <int N, int IT0, int ORDER_BAR>
__device__ __forceinline__ void gemm3(uint32_t sb, int rb, int col0, int half, int wq, int g, int c) {
    float acc[N / 2];
    const int row = 64 * half + 16 * wq + g;
    float4 s0, s1;
    gemm_loop<N, false, IT0, 10, true, ORDER_BAR>(acc, sb, half, [&]() {
        s0 = ldcg128f(&g_st[(rb * 128 + row) * 8 + 2 * c]);
        s1 = ldcg128f(&g_st[(rb * 128 + row + 8) * 8 + 2 * c]);
    });
    float a0 = s0.x + s0.z, b0 = s0.y + s0.w, a1 = s1.x + s1.z, b1 = s1.y + s1.w;
#pragma unroll
    for (int m = 1; m <= 2; m <<= 1) {
        a0 += __shfl_xor_sync(0xffffffffu, a0, m); b0 += __shfl_xor_sync(0xffffffffu, b0, m);
        a1 += __shfl_xor_sync(0xffffffffu, a1, m); b1 += __shfl_xor_sync(0xffffffffu, b1, m);
    }
    float inv0, nb0, inv1, nb1;
    ln_params(a0, b0, inv0, nb0);
    ln_params(a1, b1, inv1, nb1);
    uint32_t* dst = reinterpret_cast<uint32_t*>(g_g) + ((size_t)rb * 216 + (col0 >> 3)) * 512 + row * 4 + c;
    const float* cs = g_cs + col0 + 2 * c;
#pragma unroll
    for (int q = 0; q < N / 8; q++) {
        uint2 cr = ldcg64(cs + 8 * q);
        float c0 = __uint_as_float(cr.x), c1 = __uint_as_float(cr.y);
        dst[q * 512] = pack2(gelu(fmaf(acc[4 * q], inv0, nb0 * c0)), gelu(fmaf(acc[4 * q + 1], inv0, nb0 * c1)));
        dst[q * 512 + 32] = pack2(gelu(fmaf(acc[4 * q + 2], inv1, nb1 * c0)), gelu(fmaf(acc[4 * q + 3], inv1, nb1 * c1)));
    }
}

__global__ void __launch_bounds__(NTHREADS, 1) fused_kernel(const __grid_constant__ Maps maps, const Params p) {
    extern __shared__ __align__(1024) unsigned char smem_raw[];
    const uint32_t sb = (smem_u32(smem_raw) + 1023u) & ~1023u;
    const uint32_t bars = sb + SM_BAR;
    const int tid = threadIdx.x, lane = tid & 31;
    const int warp = __shfl_sync(0xffffffffu, tid >> 5, 0);
    const int wg = warp >> 2, wq = warp & 3;
    unsigned smid;
    asm volatile("mov.u32 %0, %%smid;" : "=r"(smid));
    int gpc, idx;
    if (smid < 64) { gpc = (smid & 15) >> 1; idx = (smid >> 4) * 2 + (smid & 1); }
    else if (smid < 120) { int t = smid - 64; gpc = 1 + (t % 14) / 2; idx = 8 + (t / 14) * 2 + (smid & 1); }
    else if (smid < 124) { gpc = 0; idx = 16 + (smid - 120); }
    else { gpc = 0; idx = 8 + (smid - 124); }
    const unsigned ep1 = *(volatile unsigned*)&g_epoch[smid] + 1;

    if (idx >= 16) {
        const int sp = idx - 16;
        if (warp == 0) { if (lane < 8) flag_wait(FL_P + lane, ep1 * 16); __syncwarp(); }
        __syncthreads();
        if (warp == 19 && elect()) {
            for (int i = 0; i < 10; i++) bulk_prefetch((const char*)p.w1 + sp * 204800 + i * 20480, 20480);
            for (int i = 0; i < 10; i++) bulk_prefetch((const char*)p.w2 + sp * 204800 + i * 20480, 20480);
            for (int i = 0; i < 27; i++) bulk_prefetch((const char*)p.w4 + sp * 552960 + i * 20480, 20480);
        }
        float* red = reinterpret_cast<float*>(smem_raw + (sb - smem_u32(smem_raw)));
        if (tid < 540) {
            const int cq = tid % 54, rg = tid / 54;
            const uint4* src = reinterpret_cast<const uint4*>(p.w3 + (size_t)rg * 64 * F_ + sp * 432) + cq;
            float a[8];
#pragma unroll
            for (int i = 0; i < 8; i++) a[i] = 0.f;
            for (int r0 = 0; r0 < 64; r0 += 8) {
                uint4 w[8];
#pragma unroll
                for (int i = 0; i < 8; i++) w[i] = __ldg(src + (size_t)(r0 + i) * (F_ / 8));
#pragma unroll
                for (int i = 0; i < 8; i++) {
                    a[0] += blo(w[i].x); a[1] += bhi(w[i].x); a[2] += blo(w[i].y); a[3] += bhi(w[i].y);
                    a[4] += blo(w[i].z); a[5] += bhi(w[i].z); a[6] += blo(w[i].w); a[7] += bhi(w[i].w);
                }
            }
#pragma unroll
            for (int i = 0; i < 8; i++) red[rg * 432 + cq * 8 + i] = a[i];
        }
        __syncthreads();
        if (tid < 432) {
            float s = 0.f;
#pragma unroll
            for (int i = 0; i < 10; i++) s += red[i * 432 + tid];
            g_cs[sp * 432 + tid] = s;
        }
        __syncthreads();
        if (tid == 0) { flag_release(FL_CS); g_epoch[smid] = ep1; TS(0); }
        return;
    }

    const int cta = gpc * 16 + idx;
    const int rb = 2 * gpc + (idx & 1), j = idx >> 1;
    const int g = lane >> 2, c = lane & 3;

    {
        const int r0 = 128 * idx;
        const char* kb = (const char*)(p.k + (size_t)r0 * D_ + 80 * gpc);
        const char* vb = (const char*)(p.v + (size_t)r0 * D_ + 80 * gpc);
#pragma unroll
        for (int i = 0; i < 2; i++) {
            int ch = tid + i * 640, row = ch / 10, cc = ch % 10;
            uint32_t so = (row >> 4) * 2576 + (row & 15) * 160 + cc * 16;
            cpasync16(sb + SM_PK + 2576 + so, kb + row * 1280 + cc * 16, 16);
            cpasync16(sb + SM_PV + so, vb + row * 1280 + cc * 16, 16);
        }
        if (tid < 30) {
            int row = tid / 10, cc = tid % 10;
            cpasync16(sb + SM_PK + (13 + row) * 160 + cc * 16, idx ? kb + (row - 3) * 1280 + cc * 16 : kb, idx ? 16 : 0);
        }
        asm volatile("cp.async.commit_group;" ::: "memory");
        const int h = warp / 10, pr = (warp % 10) * 4 + (lane >> 3), blk = lane & 7;
        const int ch = 80 * gpc + 2 * pr;
        const uint4 sw = __ldg(reinterpret_cast<const uint4*>(p.shift + ch * 4));
        if (tid == 0) {
            for (int i = 0; i < NSTAGE; i++) { mbar_init(bars + (BAR_FULL + i) * 8, 2); mbar_init(bars + (BAR_EMPTY + i) * 8, 2); }
            for (int i = BAR_K; i <= BAR_Y; i++) mbar_init(bars + i * 8, 1);
            asm volatile("fence.mbarrier_init.release.cluster;" ::: "memory");
        }
        if (warp == 1 && lane < 10) prefetch_map(&maps.hn + lane);
        if (warp == 2 && lane < 20)
            sts128(sb + SM_K + (lane >> 2) * K_STRIDE + ((lane >> 1) & 1) * 4160 + (lane & 1) * 16, make_uint4(0, 0, 0, 0));
        if (warp >= 10) {
            sts128(sb + SM_U + (warp - 10) * U_PLANE + 2048 + lane * 16, make_uint4(0, 0, 0, 0));
            fence_async_smem();
        }
        asm volatile("cp.async.wait_group 0;" ::: "memory");
        __syncthreads();
        if (warp == 0) TSW(1);
        if (warp == 4 && elect()) {
#pragma unroll
            for (int i = 0; i < 5; i++) {
                mbar_expect(bars + (BAR_K + i) * 8, 4096);
                bulk_g2s(sb + SM_K + i * K_STRIDE + 32, p.ssmk + (size_t)(cta * 5 + i) * S_, 4096, bars + (BAR_K + i) * 8);
            }
        }
        const uint32_t w0 = prmt(sw.x, sw.z, 0x5410), w1 = prmt(sw.x, sw.z, 0x7632), w2 = prmt(sw.y, sw.w, 0x5410), w3 = prmt(sw.y, sw.w, 0x7632);
        const uint32_t ka = sb + SM_PK + 2576 + blk * 2576 + h * 1280 + pr * 4;
        const uint32_t va = sb + SM_PV + blk * 2576 + h * 1280 + pr * 4;
        uint32_t kk[11], kv[8];
#pragma unroll
        for (int i = 0; i < 11; i++) kk[i] = lds32(ka + (i - 3) * 160 - ((i < 3 && h == 0) ? 16 : 0));
#pragma unroll
        for (int i = 0; i < 8; i++) {
            uint32_t t = badd2(badd2(badd2(bmul2(kk[i], w3), bmul2(kk[i + 1], w2)), bmul2(kk[i + 2], w1)), bmul2(kk[i + 3], w0));
            kv[i] = bmul2(t, lds32(va + i * 160));
        }
        uint4 o0, o1;
        o0.x = prmt(kv[1], kv[0], 0x5410); o0.y = prmt(kv[3], kv[2], 0x5410); o0.z = prmt(kv[5], kv[4], 0x5410); o0.w = prmt(kv[7], kv[6], 0x5410);
        o1.x = prmt(kv[1], kv[0], 0x7632); o1.y = prmt(kv[3], kv[2], 0x7632); o1.z = prmt(kv[5], kv[4], 0x7632); o1.w = prmt(kv[7], kv[6], 0x7632);
        uint4* dst = reinterpret_cast<uint4*>(g_kvT) + ch * 256 + h * 128 + (127 - (8 * idx + blk));
        dst[0] = o0;
        dst[256] = o1;
    }

    const int rho = 8 * rb + j;

    if (wg == 4) {
        asm volatile("setmaxnreg.dec.sync.aligned.u32 64;");
        const int t = tid - 512, cq = t & 3, rg = t >> 2;
        const uint4* src = reinterpret_cast<const uint4*>(p.wmod + (size_t)rg * 3840 + cta * 32) + cq;
        if (wq == 0) {
            bar_sync(13, 640);
            if (lane == 0) flag_release(FL_P + gpc);
            __syncwarp();
            TSW(2);
            flag_wait(FL_P + gpc, ep1 * 16);
            fence_async_global();
            TSW(3);
            if (elect()) {
#pragma unroll
                for (int i = 0; i < 5; i++) {
                    const char* us = (const char*)g_kvT + (size_t)(cta * 5 + i) * 4096;
                    mbar_expect(bars + (BAR_U + i) * 8, 4096);
                    bulk_g2s(sb + SM_U + i * U_STRIDE, us, 2048, bars + (BAR_U + i) * 8);
                    bulk_g2s(sb + SM_U + i * U_STRIDE + U_PLANE, us + 2048, 2048, bars + (BAR_U + i) * 8);
                }
            }
            __syncwarp();
        } else {
            bar_arrive(13, 640);
        }
        bar_sync(5, 128);
        if (cta < 120) {
            float a[8];
#pragma unroll
            for (int i = 0; i < 8; i++) a[i] = 0.f;
#pragma unroll 1
            for (int b = 0; b < 2; b++) {
                uint4 w[10];
#pragma unroll
                for (int i = 0; i < 10; i++) w[i] = __ldg(src + (size_t)(b * 10 + i) * 32 * 480);
#pragma unroll
                for (int i = 0; i < 10; i++) {
                    float cv = __bfloat162float(p.c[rg + 32 * (b * 10 + i)]);
                    float sv = rbf(__fdividef(cv, 1.0f + __expf(-cv)));
                    a[0] = fmaf(sv, blo(w[i].x), a[0]); a[1] = fmaf(sv, bhi(w[i].x), a[1]);
                    a[2] = fmaf(sv, blo(w[i].y), a[2]); a[3] = fmaf(sv, bhi(w[i].y), a[3]);
                    a[4] = fmaf(sv, blo(w[i].z), a[4]); a[5] = fmaf(sv, bhi(w[i].z), a[5]);
                    a[6] = fmaf(sv, blo(w[i].w), a[6]); a[7] = fmaf(sv, bhi(w[i].w), a[7]);
                }
            }
#pragma unroll
            for (int m = 4; m <= 16; m <<= 1)
#pragma unroll
                for (int i = 0; i < 8; i++) a[i] += __shfl_xor_sync(0xffffffffu, a[i], m);
            if (lane < 4) {
                uint32_t a0 = sb + SM_GV + wq * 128 + lane * 32;
                sts128f(a0, a[0], a[1], a[2], a[3]);
                sts128f(a0 + 16, a[4], a[5], a[6], a[7]);
            }
            bar_sync(5, 128);
            if (wq == 3) {
                float s = 0.f;
#pragma unroll
                for (int i = 0; i < 4; i++) s += __uint_as_float(lds32(sb + SM_GV + i * 128 + lane * 4));
                g_mod[cta * 32 + lane] = __float2bfloat16_rn(s);
                TSW(4);
            }
        }
        bar_sync(7, 640);
        if (wq == 3) {
            if (lane == 0) flag_release(FL_C);
            __syncwarp();
            TSW(20);
            flag_wait(FL_C, ep1 * 128);
            fence_async_global();
            TSW(21);
            if (elect()) {
                mbar_expect(bars + BAR_Y * 8, 20480 + 7680);
                bulk_g2s(sb + SM_Y, g_yv + rho * 5120, 20480, bars + BAR_Y * 8);
                bulk_g2s(sb + SM_MOD, g_mod, 7680, bars + BAR_Y * 8);
            }
        } else if (wq == 1) {
            int st = 0, ph = 1;
            for (int it = 0; it < 67; it++) {
                mbar_wait(bars + (BAR_EMPTY + st) * 8, ph);
                const CUtensorMap *ma, *mb;
                int col, kb, bytes;
                if (it < 10) { ma = &maps.w1a; mb = &maps.w1b; col = 80 * j; kb = it; bytes = 10240; }
                else if (it < 20) { ma = &maps.w2a; mb = &maps.w2b; col = 80 * j; kb = it - 10; bytes = 10240; }
                else if (it < 30) { ma = &maps.w3a; mb = &maps.w3b; col = 112 * j; kb = it - 20; bytes = 14336; }
                else if (it < 40) { ma = &maps.w3a; mb = &maps.w3c; col = 896 + 104 * j; kb = it - 30; bytes = 13312; }
                else { ma = &maps.w4a; mb = &maps.w4b; col = 80 * j; kb = it - 40; bytes = 10240; }
                if (elect()) {
                    uint32_t fb = bars + (BAR_FULL + st) * 8, dst = sb + st * STAGE_BYTES + 16384;
                    mbar_expect(fb, bytes);
                    tma2d(dst, ma, col, kb * 64, fb);
                    tma2d(dst + 8192, mb, col + 64, kb * 64, fb);
                }
                __syncwarp();
                if (++st == NSTAGE) { st = 0; ph ^= 1; }
            }
        } else if (wq == 0) {
            const int grp = j >> 1;
            const int delta = (grp & 1 ? 1 : -1) * (1 + (grp >> 1));
            int st = 0, ph = 1;
            for (int it = 0; it < 67; it++) {
                if (it == 0) {
                    int nb = rb + (delta > 0 ? 1 : -1);
                    if (lane == 0) flag_wait(FL_R + rb, ep1 * 8);
                    if (lane == 1 && nb >= 0 && nb < 16) flag_wait(FL_R + nb, ep1 * 8);
                    __syncwarp(); fence_async_global(); TSW(24);
                } else if (it == 10) { flag_wait(FL_B1 + rb, ep1 * 8); fence_async_global(); TSW(28); }
                else if (it == 20) { flag_wait(FL_CS, ep1 * 4); flag_wait(FL_B2 + rb, ep1 * 8); fence_async_global(); TSW(32); }
                else if (it == 40) { flag_wait(FL_GA + rb, ep1 * 8); fence_async_global(); TSW(40); }
                else if (it == 54) { flag_wait(FL_GB + rb, ep1 * 8); fence_async_global(); TSW(41); }
                mbar_wait(bars + (BAR_EMPTY + st) * 8, ph);
                if (elect()) {
                    uint32_t fb = bars + (BAR_FULL + st) * 8, dst = sb + st * STAGE_BYTES;
                    mbar_expect(fb, 16384);
                    if (it < 10) tma2d(dst, &maps.hn, it * 64, rb * 128 + delta, fb);
                    else {
                        const char* src;
                        if (it < 20) src = (const char*)g_h1 + (size_t)rb * 163840 + (it - 10) * 16384;
                        else if (it < 40) src = (const char*)g_x1 + (size_t)rb * 163840 + (it < 30 ? it - 20 : it - 30) * 16384;
                        else src = (const char*)g_g + (size_t)rb * 442368 + (it - 40) * 16384;
                        bulk_g2s(dst, src, 16384, fb);
                    }
                }
                __syncwarp();
                if (++st == NSTAGE) { st = 0; ph ^= 1; }
            }
        }
        return;
    }
    bar_arrive(13, 640);
    asm volatile("setmaxnreg.inc.sync.aligned.u32 104;");
    const int rrow = 32 * (rho >> 1) + 8 * (rho & 1) + (warp >> 1) + 16 * (warp & 1);

#pragma unroll 1
    for (int cc = wg; cc < 5; cc += 3) {
        if (cc == 3 && wg == 0) break;
        mbar_wait(bars + (BAR_K + cc) * 8, 0);
        uint32_t a = sb + SM_K + cc * K_STRIDE + 32 + (tid & 127) * 32;
        uint32_t pw = lds32(a - 4);
        uint4 x = lds128(a), y = lds128(a + 16), o;
        o.x = prmt(pw, x.x, 0x5432); o.y = prmt(x.x, x.y, 0x5432); o.z = prmt(x.y, x.z, 0x5432); o.w = prmt(x.z, x.w, 0x5432);
        sts128(a + 4160, o);
        o.x = prmt(x.w, y.x, 0x5432); o.y = prmt(y.x, y.y, 0x5432); o.z = prmt(y.y, y.z, 0x5432); o.w = prmt(y.z, y.w, 0x5432);
        sts128(a + 4176, o);
    }
    bar_sync(1 + wg, 128);
    if (wg >= 2) bar_sync(6, 512);
#pragma unroll 1
    for (int cc = wg; cc < 5; cc += 3) {
        if (cc == 3 && wg == 0) break;
        const int ch = cta * 5 + cc;
        const uint32_t sK = sb + SM_K + cc * K_STRIDE, sU = sb + SM_U + cc * U_STRIDE;
        uint32_t dD = (uint32_t)__bfloat16_as_ushort(p.ssmD[ch]);
        dD |= dD << 16;
        const uint32_t kaddr = sK + ((g & 1) ? 32 : 4192) + 4 * ((g >> 1) - c) + 64 * wq;
        AFrag f = ldA(kaddr);
        mbar_wait(bars + (BAR_U + cc) * 8, 0);
        if (wq == 0) TSW(5 + cc);
        const uint32_t red = sb + SM_RED + wg * 32768 + g * 1024;
        const int sx = (g & 1) << 2;
        const uint32_t r0 = red + wq * 8192 + (((c - wq + 8) ^ sx) - 8) * 16, r1 = red + wq * 8192 + ((c - wq + 4) ^ sx) * 16;
        float d[64];
        conv_main(d, f, kaddr, mkdesc(sU, U_PLANE, 128, 0), r0, r1, cc < 2 ? 6 : 0);
        if (wq == 0) TSW(10 + cc);
        if (c >= wq) sts128f(r0, d[0], d[1], d[2], d[3]);
        uint32_t u2[8];
#pragma unroll
        for (int q = 0; q < 4; q++) {
            uint32_t a = sU + (16 * wq + 4 * q + c) * 32 + (g ^ 1) * 2;
            u2[2 * q] = bmul2(lds16(a + 16) | (lds16(a) << 16), dD);
            u2[2 * q + 1] = bmul2(lds16(a + U_PLANE + 16) | (lds16(a + U_PLANE) << 16), dD);
        }
        bar_sync(1 + wg, 128);
        uint32_t* dst = g_yv + ch * 8 + ((g + (ch >> 2)) & 7);
#pragma unroll
        for (int q = 0; q < 4; q++) {
            int kap = 16 * wq + 4 * q + c;
            uint32_t a = red + ((kap ^ sx) << 4);
            float4 s = lds128f(a);
#pragma unroll
            for (int w = 1; w < 4; w++) {
                if (q < 3 || kap <= 63 - w) {
                    float4 x = lds128f(a + w * 8192);
                    s.x += x.x; s.y += x.y; s.z += x.z; s.w += x.w;
                }
            }
            uint32_t* o = dst + (size_t)(126 - 2 * kap) * 5120;
            o[0] = badd2(pack2(s.y, s.x), u2[2 * q]);
            o[5120] = badd2(pack2(s.w, s.z), u2[2 * q + 1]);
        }
        if (cc == 1) bar_sync(1 + wg, 128);
        if (wq == 0) TSW(15 + cc);
    }
    fence_async_smem();
    bar_arrive(7, 640);

    {
        uint32_t x[10], a[10], b[10];
        const uint32_t* xr = reinterpret_cast<const uint32_t*>(p.q + (size_t)rrow * D_) + lane;
#pragma unroll
        for (int i = 0; i < 10; i++) x[i] = __ldg(xr + 32 * i);
        row_ln(x, a);
        const int up = lane >> 4, gg = warp >> 1, e = warp & 1;
        const uint32_t ya = sb + SM_Y + lane * 64 + ((gg + (lane >> 1)) & 7) * 4;
        const uint32_t sel = (up ? 0x1054u : 0x5410u) + (e ? 0x2222u : 0u);
        const uint32_t ma = sb + SM_MOD + lane * 4;
        const uint32_t one2 = 0x3f803f80u;
        mbar_wait(bars + BAR_Y * 8, 0);
        if (warp == 0) TSW(22);
#pragma unroll
        for (int i = 0; i < 10; i++) {
            uint32_t y0 = lds32(ya + i * 2048 + up * 32), y1 = lds32(ya + i * 2048 + (up ^ 1) * 32);
            uint32_t yv = prmt(y0, y1, sel);
            uint32_t sa = lds32(ma + i * 128), ca = lds32(ma + 1280 + i * 128), ga = lds32(ma + 2560 + i * 128);
            uint32_t hh = badd2(bmul2(a[i], badd2(ca, one2)), sa);
            x[i] = badd2(x[i], bmul2(ga, bmul2(hh, yv)));
        }
        row_ln(x, a);
#pragma unroll
        for (int i = 0; i < 10; i++) {
            uint32_t sbv = lds32(ma + 3840 + i * 128), cb = lds32(ma + 5120 + i * 128);
            a[i] = badd2(bmul2(a[i], badd2(cb, one2)), sbv);
        }
        row_ln(a, b);
        uint32_t* o = reinterpret_cast<uint32_t*>(g_hn + (size_t)rrow * D_) + lane;
#pragma unroll
        for (int i = 0; i < 10; i++) o[32 * i] = b[i];
        bar_sync(8, 512);
        if (tid == 0) { flag_release(FL_R + rb); TS(23); }
        bar_sync(8, 512);
        uint32_t* o1 = reinterpret_cast<uint32_t*>(g_hp + (size_t)rrow * D_) + lane;
        uint32_t* o2 = reinterpret_cast<uint32_t*>(g_x2 + (size_t)rrow * D_) + lane;
#pragma unroll
        for (int i = 0; i < 10; i++) { o1[32 * i] = a[i]; o2[32 * i] = x[i]; }
    }

    const int half = wg & 1;
    const int row = 64 * half + 16 * wq + g;
    const size_t tile_w = ((size_t)rb * 80 + 10 * j) * 512 + row * 4 + c;
    if (wg >= 2) {
        {
            float acc[40];
            gemm_loop<80, true, 0, 10, true, 0>(acc, sb, half, [&]() { if (tid == 256) TS(25); });
            if (tid == 256) TS(26);
            uint32_t* dst = reinterpret_cast<uint32_t*>(g_h1) + tile_w;
#pragma unroll
            for (int q = 0; q < 10; q++) {
                dst[q * 512] = pack2(gelu(acc[4 * q]), gelu(acc[4 * q + 1]));
                dst[q * 512 + 32] = pack2(gelu(acc[4 * q + 2]), gelu(acc[4 * q + 3]));
            }
            if (warp == 8) { bar_sync(14, 512); if (lane == 0) { flag_release(FL_B1 + rb); TS(27); } __syncwarp(); }
            else bar_arrive(14, 512);
        }
        bar_sync(11, 512);
        gemm3<112, 20, 9>(sb, rb, 112 * j, half, wq, g, c);
        if (warp == 8) { TSW(35); bar_sync(15, 256); if (lane == 0) { flag_release(FL_GA + rb); TS(36); } __syncwarp(); }
        else bar_arrive(15, 256);
        {
            float acc[40];
            const uint32_t* x1p = reinterpret_cast<const uint32_t*>(g_x1) + tile_w;
#pragma unroll
            for (int q = 0; q < 10; q++) {
                uint32_t u = ldcg32(x1p + q * 512), v = ldcg32(x1p + q * 512 + 32);
                acc[4 * q] = blo(u); acc[4 * q + 1] = bhi(u); acc[4 * q + 2] = blo(v); acc[4 * q + 3] = bhi(v);
            }
            const size_t go = (size_t)(rb * 128 + row) * D_ + 80 * j + (c & 1) * 8 + (c >> 1) * 4;
            uint2 x2[10];
#pragma unroll
            for (int q = 0; q < 5; q++) { x2[2 * q] = ldcg64(g_x2 + go + 16 * q); x2[2 * q + 1] = ldcg64(g_x2 + go + 8 * D_ + 16 * q); }
            reg_fence<40>(acc);
            bar_sync(10, 512);
            gemm_loop<80, false, 40, 27, false, 0>(acc, sb, half, [&]() { if (tid == 256) TS(42); });
            if (tid == 256) TS(43);
            const uint32_t ga = sb + SM_MOD + 6400 + (80 * j + 2 * c) * 2;
#pragma unroll
            for (int q = 0; q < 5; q++) {
                uint32_t g0 = lds32(ga + q * 32), g1 = lds32(ga + q * 32 + 16);
#pragma unroll
                for (int r = 0; r < 2; r++) {
                    uint32_t t0 = bmul2(g0, pack2(acc[8 * q + 2 * r], acc[8 * q + 2 * r + 1]));
                    uint32_t t1 = bmul2(g1, pack2(acc[8 * q + 4 + 2 * r], acc[8 * q + 4 + 2 * r + 1]));
                    uint32_t rv = __shfl_xor_sync(0xffffffffu, (c & 1) ? t0 : t1, 1);
                    uint2 o;
                    o.x = badd2(x2[2 * q + r].x, (c & 1) ? rv : t0);
                    o.y = badd2(x2[2 * q + r].y, (c & 1) ? t1 : rv);
                    *reinterpret_cast<uint2*>(p.out + go + r * 8 * D_ + 16 * q) = o;
                }
            }
            if (tid == 256) { g_epoch[smid] = ep1; TS(44); }
        }
    } else {
        bar_sync(14, 512);
        {
            float acc[40];
            uint32_t hp[20];
            const uint32_t* hpp = reinterpret_cast<const uint32_t*>(g_hp + (size_t)(rb * 128 + row) * D_ + 80 * j) + c;
            gemm_loop<80, false, 10, 10, true, 0>(acc, sb, half, [&]() {
                if (tid == 0) TS(29);
#pragma unroll
                for (int q = 0; q < 10; q++) { hp[2 * q] = ldcg32(hpp + 4 * q); hp[2 * q + 1] = ldcg32(hpp + 4 * q + 4 * D_); }
            });
            if (tid == 0) TS(30);
            uint32_t* dst = reinterpret_cast<uint32_t*>(g_x1) + tile_w;
            float s0 = 0.f, q0 = 0.f, s1 = 0.f, q1 = 0.f;
#pragma unroll
            for (int q = 0; q < 10; q++) {
                uint32_t u = badd2(hp[2 * q], pack2(acc[4 * q], acc[4 * q + 1]));
                uint32_t v = badd2(hp[2 * q + 1], pack2(acc[4 * q + 2], acc[4 * q + 3]));
                dst[q * 512] = u;
                dst[q * 512 + 32] = v;
                float a = blo(u), b = bhi(u), e = blo(v), f = bhi(v);
                s0 += a + b; q0 = fmaf(a, a, fmaf(b, b, q0));
                s1 += e + f; q1 = fmaf(e, e, fmaf(f, f, q1));
            }
#pragma unroll
            for (int m = 1; m <= 2; m <<= 1) {
                s0 += __shfl_xor_sync(0xffffffffu, s0, m); q0 += __shfl_xor_sync(0xffffffffu, q0, m);
                s1 += __shfl_xor_sync(0xffffffffu, s1, m); q1 += __shfl_xor_sync(0xffffffffu, q1, m);
            }
            if (c < 2) g_st[(rb * 128 + row + 8 * c) * 8 + j] = c ? make_float2(s1, q1) : make_float2(s0, q0);
            if (warp == 0) { bar_sync(11, 512); if (lane == 0) { flag_release(FL_B2 + rb); TS(31); } __syncwarp(); }
            else bar_arrive(11, 512);
        }
        bar_sync(9, 512);
        if (tid == 0) TS(37);
        gemm3<104, 30, 10>(sb, rb, 896 + 104 * j, half, wq, g, c);
        if (warp == 0) { TSW(38); bar_sync(12, 256); if (lane == 0) { flag_release(FL_GB + rb); TS(39); } __syncwarp(); }
        else bar_arrive(12, 256);
    }
}

typedef CUresult (*EncFn)(CUtensorMap*, CUtensorMapDataType, cuuint32_t, void*, const cuuint64_t*, const cuuint64_t*,
                          const cuuint32_t*, const cuuint32_t*, CUtensorMapInterleave, CUtensorMapSwizzle,
                          CUtensorMapL2promotion, CUtensorMapFloatOOBfill);

void make_map(EncFn enc, CUtensorMap* m, const void* base, uint64_t inner, uint64_t outer, uint32_t bi, uint32_t bo) {
    cuuint64_t dims[2] = {inner, outer};
    cuuint64_t st[1] = {inner * 2};
    cuuint32_t box[2] = {bi, bo};
    cuuint32_t es[2] = {1, 1};
    enc(m, CU_TENSOR_MAP_DATA_TYPE_BFLOAT16, 2, const_cast<void*>(base), dims, st, box, es, CU_TENSOR_MAP_INTERLEAVE_NONE,
        CU_TENSOR_MAP_SWIZZLE_128B, CU_TENSOR_MAP_L2_PROMOTION_NONE, CU_TENSOR_MAP_FLOAT_OOB_FILL_NONE);
}

}

extern "C" void kernel_launch(void* const* d_in, const int* in_sizes, int n_in, void* d_out, int out_size) {
    (void)in_sizes; (void)n_in; (void)out_size;
    Params p;
    p.q = (const bf16*)d_in[0]; p.k = (const bf16*)d_in[1]; p.v = (const bf16*)d_in[2];
    p.shift = (const bf16*)d_in[3]; p.ssmk = (const bf16*)d_in[4]; p.ssmD = (const bf16*)d_in[5];
    p.w1 = (const bf16*)d_in[7]; p.w2 = (const bf16*)d_in[8]; p.w3 = (const bf16*)d_in[9]; p.w4 = (const bf16*)d_in[10];
    p.c = (const bf16*)d_in[11]; p.wmod = (const bf16*)d_in[12];
    p.out = (bf16*)d_out;

    void* fn = nullptr;
    cudaDriverEntryPointQueryResult qr;
    cudaGetDriverEntryPoint("cuTensorMapEncodeTiled", &fn, cudaEnableDefault, &qr);
    EncFn enc = (EncFn)fn;
    void* hn = nullptr;
    cudaGetSymbolAddress(&hn, g_hn);
    Maps maps;
    make_map(enc, &maps.hn, hn, D_, S_, 64, 128);
    make_map(enc, &maps.w1a, p.w1, D_, D_, 64, 64);
    make_map(enc, &maps.w1b, p.w1, D_, D_, 16, 64);
    make_map(enc, &maps.w2a, p.w2, D_, D_, 64, 64);
    make_map(enc, &maps.w2b, p.w2, D_, D_, 16, 64);
    make_map(enc, &maps.w3a, p.w3, F_, D_, 64, 64);
    make_map(enc, &maps.w3b, p.w3, F_, D_, 48, 64);
    make_map(enc, &maps.w3c, p.w3, F_, D_, 40, 64);
    make_map(enc, &maps.w4a, p.w4, D_, F_, 64, 64);
    make_map(enc, &maps.w4b, p.w4, D_, F_, 16, 64);
    cudaFuncSetAttribute(fused_kernel, cudaFuncAttributeMaxDynamicSharedMemorySize, SMEM_BYTES);
    fused_kernel<<<132, NTHREADS, SMEM_BYTES>>>(maps, p);
}
```

```cpp
#include <cuda_runtime.h>
#include <cuda_bf16.h>
#include <cuda.h>
#include <stdint.h>
#include <string.h>

#define SEED 1
#define SSM_WHEN 1
#define PF_EARLY 0

namespace {

typedef __nv_bfloat16 bf16;
typedef __nv_bfloat162 bf162;

constexpr int S_ = 2048, D_ = 640, F_ = 1728;
constexpr int NTHREADS = 640;
constexpr int NSTAGE = 6;
constexpr int STAGE_BYTES = 32768;

constexpr int SM_RED = 0;
constexpr int SM_PK = 0;
constexpr int SM_PV = 24576;
constexpr int SM_K = 131072;
constexpr int K_STRIDE = 8320;
constexpr int SM_U = SM_K + 5 * K_STRIDE;
constexpr int U_PLANE = 2560, U_STRIDE = 5120;
constexpr int SM_Y = NSTAGE * STAGE_BYTES;
constexpr int SM_MOD = SM_Y + 20480;
constexpr int SM_GV = SM_MOD + 7680;
static_assert(SM_U + 5 * U_STRIDE <= SM_GV, "smem map");
constexpr int SM_CS = SM_GV + 1024;
constexpr int SM_RS = SM_CS + 1024;
constexpr int SM_BAR = SM_RS + 1024;
constexpr int SM_PROF = SM_BAR + 256;
constexpr int SM_TOTAL = SM_PROF + 512;
constexpr int SMEM_BYTES = SM_TOTAL + 1024;
static_assert(SMEM_BYTES <= 232448, "smem");

constexpr int BAR_FULL = 0, BAR_EMPTY = 6, BAR_K = 12, BAR_U = 17, BAR_Y = 22, BAR_X = 23, BAR_CS = 24;

__device__ __align__(1024) bf16 g_kvT[D_ * S_];
__device__ __align__(1024) uint32_t g_yv[128 * 5120];
__device__ __align__(1024) bf16 g_mod[6 * D_];
__device__ __align__(1024) bf16 g_hn[S_ * D_];
__device__ __align__(1024) float2 g_rs[S_];
__device__ __align__(1024) bf16 g_x2[S_ * D_];
__device__ __align__(1024) bf16 g_h1[S_ * D_];
__device__ __align__(1024) bf16 g_x1[S_ * D_];
__device__ __align__(1024) bf16 g_g[S_ * F_];
__device__ __align__(1024) float2 g_st[S_ * 8];
__device__ __align__(1024) float g_cs[F_];
__device__ __align__(1024) unsigned g_flags[112 * 32];
__device__ __align__(1024) unsigned g_epoch[160];
constexpr int FL_P = 0, FL_C = 8, FL_CS = 9, FL_R = 16, FL_B1 = 32, FL_B2 = 48, FL_GA = 64, FL_GB = 80, FL_X2 = 96;

#define TS(i) do {} while (0)
#define TSW(i) do {} while (0)
#define TSFLUSH() do {} while (0)

struct Params {
    const bf16 *q, *k, *v, *shift, *ssmk, *ssmD, *w1, *w2, *w3, *w4, *c, *wmod;
    bf16* out;
};
struct Maps { CUtensorMap hn, w1a, w1b, w2a, w2b, w3a, w3b, w3c, w4a, w4b, x2; };

template<int N> struct WgRs;
template<int N> struct WgSs;
template<> struct WgRs<32> { template<int OFF,int HI,int SC> static __device__ __forceinline__ void run(float* d,uint32_t a0,uint32_t a1,uint32_t a2,uint32_t a3,uint32_t blo){
 asm volatile("{.reg .b32 l; .reg .b64 db; add.u32 l,%20,%21; mov.b64 db,{l,%22}; wgmma.mma_async.sync.aligned.m64n32k16.f32.bf16.bf16 {%0,%1,%2,%3,%4,%5,%6,%7,%8,%9,%10,%11,%12,%13,%14,%15},{%16,%17,%18,%19},db,%23,1,1,0;}"
 :"+f"(d[0]),"+f"(d[1]),"+f"(d[2]),"+f"(d[3]),"+f"(d[4]),"+f"(d[5]),"+f"(d[6]),"+f"(d[7]),"+f"(d[8]),"+f"(d[9]),"+f"(d[10]),"+f"(d[11]),"+f"(d[12]),"+f"(d[13]),"+f"(d[14]),"+f"(d[15])
 :"r"(a0),"r"(a1),"r"(a2),"r"(a3),"r"(blo),"n"(OFF),"n"(HI),"n"(SC)); } };
template<> struct WgRs<48> { template<int OFF,int HI,int SC> static __device__ __forceinline__ void run(float* d,uint32_t a0,uint32_t a1,uint32_t a2,uint32_t a3,uint32_t blo){
 asm volatile("{.reg .b32 l; .reg .b64 db; add.u32 l,%28,%29; mov.b64 db,{l,%30}; wgmma.mma_async.sync.aligned.m64n48k16.f32.bf16.bf16 {%0,%1,%2,%3,%4,%5,%6,%7,%8,%9,%10,%11,%12,%13,%14,%15,%16,%17,%18,%19,%20,%21,%22,%23},{%24,%25,%26,%27},db,%31,1,1,0;}"
 :"+f"(d[0]),"+f"(d[1]),"+f"(d[2]),"+f"(d[3]),"+f"(d[4]),"+f"(d[5]),"+f"(d[6]),"+f"(d[7]),"+f"(d[8]),"+f"(d[9]),"+f"(d[10]),"+f"(d[11]),"+f"(d[12]),"+f"(d[13]),"+f"(d[14]),"+f"(d[15]),"+f"(d[16]),"+f"(d[17]),"+f"(d[18]),"+f"(d[19]),"+f"(d[20]),"+f"(d[21]),"+f"(d[22]),"+f"(d[23])
 :"r"(a0),"r"(a1),"r"(a2),"r"(a3),"r"(blo),"n"(OFF),"n"(HI),"n"(SC)); } };
template<> struct WgRs<64> { template<int OFF,int HI,int SC> static __device__ __forceinline__ void run(float* d,uint32_t a0,uint32_t a1,uint32_t a2,uint32_t a3,uint32_t blo){
 asm volatile("{.reg .b32 l; .reg .b64 db; add.u32 l,%36,%37; mov.b64 db,{l,%38}; wgmma.mma_async.sync.aligned.m64n64k16.f32.bf16.bf16 {%0,%1,%2,%3,%4,%5,%6,%7,%8,%9,%10,%11,%12,%13,%14,%15,%16,%17,%18,%19,%20,%21,%22,%23,%24,%25,%26,%27,%28,%29,%30,%31},{%32,%33,%34,%35},db,%39,1,1,0;}"
 :"+f"(d[0]),"+f"(d[1]),"+f"(d[2]),"+f"(d[3]),"+f"(d[4]),"+f"(d[5]),"+f"(d[6]),"+f"(d[7]),"+f"(d[8]),"+f"(d[9]),"+f"(d[10]),"+f"(d[11]),"+f"(d[12]),"+f"(d[13]),"+f"(d[14]),"+f"(d[15]),"+f"(d[16]),"+f"(d[17]),"+f"(d[18]),"+f"(d[19]),"+f"(d[20]),"+f"(d[21]),"+f"(d[22]),"+f"(d[23]),"+f"(d[24]),"+f"(d[25]),"+f"(d[26]),"+f"(d[27]),"+f"(d[28]),"+f"(d[29]),"+f"(d[30]),"+f"(d[31])
 :"r"(a0),"r"(a1),"r"(a2),"r"(a3),"r"(blo),"n"(OFF),"n"(HI),"n"(SC)); } };
template<> struct WgRs<72> { template<int OFF,int HI,int SC> static __device__ __forceinline__ void run(float* d,uint32_t a0,uint32_t a1,uint32_t a2,uint32_t a3,uint32_t blo){
 asm volatile("{.reg .b32 l; .reg .b64 db; add.u32 l,%40,%41; mov.b64 db,{l,%42}; wgmma.mma_async.sync.aligned.m64n72k16.f32.bf16.bf16 {%0,%1,%2,%3,%4,%5,%6,%7,%8,%9,%10,%11,%12,%13,%14,%15,%16,%17,%18,%19,%20,%21,%22,%23,%24,%25,%26,%27,%28,%29,%30,%31,%32,%33,%34,%35},{%36,%37,%38,%39},db,%43,1,1,0;}"
 :"+f"(d[0]),"+f"(d[1]),"+f"(d[2]),"+f"(d[3]),"+f"(d[4]),"+f"(d[5]),"+f"(d[6]),"+f"(d[7]),"+f"(d[8]),"+f"(d[9]),"+f"(d[10]),"+f"(d[11]),"+f"(d[12]),"+f"(d[13]),"+f"(d[14]),"+f"(d[15]),"+f"(d[16]),"+f"(d[17]),"+f"(d[18]),"+f"(d[19]),"+f"(d[20]),"+f"(d[21]),"+f"(d[22]),"+f"(d[23]),"+f"(d[24]),"+f"(d[25]),"+f"(d[26]),"+f"(d[27]),"+f"(d[28]),"+f"(d[29]),"+f"(d[30]),"+f"(d[31]),"+f"(d[32]),"+f"(d[33]),"+f"(d[34]),"+f"(d[35])
 :"r"(a0),"r"(a1),"r"(a2),"r"(a3),"r"(blo),"n"(OFF),"n"(HI),"n"(SC)); } };
template<> struct WgRs<80> { template<int OFF,int HI,int SC> static __device__ __forceinline__ void run(float* d,uint32_t a0,uint32_t a1,uint32_t a2,uint32_t a3,uint32_t blo){
 asm volatile("{.reg .b32 l; .reg .b64 db; add.u32 l,%44,%45; mov.b64 db,{l,%46}; wgmma.mma_async.sync.aligned.m64n80k16.f32.bf16.bf16 {%0,%1,%2,%3,%4,%5,%6,%7,%8,%9,%10,%11,%12,%13,%14,%15,%16,%17,%18,%19,%20,%21,%22,%23,%24,%25,%26,%27,%28,%29,%30,%31,%32,%33,%34,%35,%36,%37,%38,%39},{%40,%41,%42,%43},db,%47,1,1,0;}"
 :"+f"(d[0]),"+f"(d[1]),"+f"(d[2]),"+f"(d[3]),"+f"(d[4]),"+f"(d[5]),"+f"(d[6]),"+f"(d[7]),"+f"(d[8]),"+f"(d[9]),"+f"(d[10]),"+f"(d[11]),"+f"(d[12]),"+f"(d[13]),"+f"(d[14]),"+f"(d[15]),"+f"(d[16]),"+f"(d[17]),"+f"(d[18]),"+f"(d[19]),"+f"(d[20]),"+f"(d[21]),"+f"(d[22]),"+f"(d[23]),"+f"(d[24]),"+f"(d[25]),"+f"(d[26]),"+f"(d[27]),"+f"(d[28]),"+f"(d[29]),"+f"(d[30]),"+f"(d[31]),"+f"(d[32]),"+f"(d[33]),"+f"(d[34]),"+f"(d[35]),"+f"(d[36]),"+f"(d[37]),"+f"(d[38]),"+f"(d[39])
 :"r"(a0),"r"(a1),"r"(a2),"r"(a3),"r"(blo),"n"(OFF),"n"(HI),"n"(SC)); } };
template<> struct WgRs<88> { template<int OFF,int HI,int SC> static __device__ __forceinline__ void run(float* d,uint32_t a0,uint32_t a1,uint32_t a2,uint32_t a3,uint32_t blo){
 asm volatile("{.reg .b32 l; .reg .b64 db; add.u32 l,%48,%49; mov.b64 db,{l,%50}; wgmma.mma_async.sync.aligned.m64n88k16.f32.bf16.bf16 {%0,%1,%2,%3,%4,%5,%6,%7,%8,%9,%10,%11,%12,%13,%14,%15,%16,%17,%18,%19,%20,%21,%22,%23,%24,%25,%26,%27,%28,%29,%30,%31,%32,%33,%34,%35,%36,%37,%38,%39,%40,%41,%42,%43},{%44,%45,%46,%47},db,%51,1,1,0;}"
 :"+f"(d[0]),"+f"(d[1]),"+f"(d[2]),"+f"(d[3]),"+f"(d[4]),"+f"(d[5]),"+f"(d[6]),"+f"(d[7]),"+f"(d[8]),"+f"(d[9]),"+f"(d[10]),"+f"(d[11]),"+f"(d[12]),"+f"(d[13]),"+f"(d[14]),"+f"(d[15]),"+f"(d[16]),"+f"(d[17]),"+f"(d[18]),"+f"(d[19]),"+f"(d[20]),"+f"(d[21]),"+f"(d[22]),"+f"(d[23]),"+f"(d[24]),"+f"(d[25]),"+f"(d[26]),"+f"(d[27]),"+f"(d[28]),"+f"(d[29]),"+f"(d[30]),"+f"(d[31]),"+f"(d[32]),"+f"(d[33]),"+f"(d[34]),"+f"(d[35]),"+f"(d[36]),"+f"(d[37]),"+f"(d[38]),"+f"(d[39]),"+f"(d[40]),"+f"(d[41]),"+f"(d[42]),"+f"(d[43])
 :"r"(a0),"r"(a1),"r"(a2),"r"(a3),"r"(blo),"n"(OFF),"n"(HI),"n"(SC)); } };
template<> struct WgRs<96> { template<int OFF,int HI,int SC> static __device__ __forceinline__ void run(float* d,uint32_t a0,uint32_t a1,uint32_t a2,uint32_t a3,uint32_t blo){
 asm volatile("{.reg .b32 l; .reg .b64 db; add.u32 l,%52,%53; mov.b64 db,{l,%54}; wgmma.mma_async.sync.aligned.m64n96k16.f32.bf16.bf16 {%0,%1,%2,%3,%4,%5,%6,%7,%8,%9,%10,%11,%12,%13,%14,%15,%16,%17,%18,%19,%20,%21,%22,%23,%24,%25,%26,%27,%28,%29,%30,%31,%32,%33,%34,%35,%36,%37,%38,%39,%40,%41,%42,%43,%44,%45,%46,%47},{%48,%49,%50,%51},db,%55,1,1,0;}"
 :"+f"(d[0]),"+f"(d[1]),"+f"(d[2]),"+f"(d[3]),"+f"(d[4]),"+f"(d[5]),"+f"(d[6]),"+f"(d[7]),"+f"(d[8]),"+f"(d[9]),"+f"(d[10]),"+f"(d[11]),"+f"(d[12]),"+f"(d[13]),"+f"(d[14]),"+f"(d[15]),"+f"(d[16]),"+f"(d[17]),"+f"(d[18]),"+f"(d[19]),"+f"(d[20]),"+f"(d[21]),"+f"(d[22]),"+f"(d[23]),"+f"(d[24]),"+f"(d[25]),"+f"(d[26]),"+f"(d[27]),"+f"(d[28]),"+f"(d[29]),"+f"(d[30]),"+f"(d[31]),"+f"(d[32]),"+f"(d[33]),"+f"(d[34]),"+f"(d[35]),"+f"(d[36]),"+f"(d[37]),"+f"(d[38]),"+f"(d[39]),"+f"(d[40]),"+f"(d[41]),"+f"(d[42]),"+f"(d[43]),"+f"(d[44]),"+f"(d[45]),"+f"(d[46]),"+f"(d[47])
 :"r"(a0),"r"(a1),"r"(a2),"r"(a3),"r"(blo),"n"(OFF),"n"(HI),"n"(SC)); } };
template<> struct WgRs<104> { template<int OFF,int HI,int SC> static __device__ __forceinline__ void run(float* d,uint32_t a0,uint32_t a1,uint32_t a2,uint32_t a3,uint32_t blo){
 asm volatile("{.reg .b32 l; .reg .b64 db; add.u32 l,%56,%57; mov.b64 db,{l,%58}; wgmma.mma_async.sync.aligned.m64n104k16.f32.bf16.bf16 {%0,%1,%2,%3,%4,%5,%6,%7,%8,%9,%10,%11,%12,%13,%14,%15,%16,%17,%18,%19,%20,%21,%22,%23,%24,%25,%26,%27,%28,%29,%30,%31,%32,%33,%34,%35,%36,%37,%38,%39,%40,%41,%42,%43,%44,%45,%46,%47,%48,%49,%50,%51},{%52,%53,%54,%55},db,%59,1,1,0;}"
 :"+f"(d[0]),"+f"(d[1]),"+f"(d[2]),"+f"(d[3]),"+f"(d[4]),"+f"(d[5]),"+f"(d[6]),"+f"(d[7]),"+f"(d[8]),"+f"(d[9]),"+f"(d[10]),"+f"(d[11]),"+f"(d[12]),"+f"(d[13]),"+f"(d[14]),"+f"(d[15]),"+f"(d[16]),"+f"(d[17]),"+f"(d[18]),"+f"(d[19]),"+f"(d[20]),"+f"(d[21]),"+f"(d[22]),"+f"(d[23]),"+f"(d[24]),"+f"(d[25]),"+f"(d[26]),"+f"(d[27]),"+f"(d[28]),"+f"(d[29]),"+f"(d[30]),"+f"(d[31]),"+f"(d[32]),"+f"(d[33]),"+f"(d[34]),"+f"(d[35]),"+f"(d[36]),"+f"(d[37]),"+f"(d[38]),"+f"(d[39]),"+f"(d[40]),"+f"(d[41]),"+f"(d[42]),"+f"(d[43]),"+f"(d[44]),"+f"(d[45]),"+f"(d[46]),"+f"(d[47]),"+f"(d[48]),"+f"(d[49]),"+f"(d[50]),"+f"(d[51])
 :"r"(a0),"r"(a1),"r"(a2),"r"(a3),"r"(blo),"n"(OFF),"n"(HI),"n"(SC)); } };
template<> struct WgRs<112> { template<int OFF,int HI,int SC> static __device__ __forceinline__ void run(float* d,uint32_t a0,uint32_t a1,uint32_t a2,uint32_t a3,uint32_t blo){
 asm volatile("{.reg .b32 l; .reg .b64 db; add.u32 l,%60,%61; mov.b64 db,{l,%62}; wgmma.mma_async.sync.aligned.m64n112k16.f32.bf16.bf16 {%0,%1,%2,%3,%4,%5,%6,%7,%8,%9,%10,%11,%12,%13,%14,%15,%16,%17,%18,%19,%20,%21,%22,%23,%24,%25,%26,%27,%28,%29,%30,%31,%32,%33,%34,%35,%36,%37,%38,%39,%40,%41,%42,%43,%44,%45,%46,%47,%48,%49,%50,%51,%52,%53,%54,%55},{%56,%57,%58,%59},db,%63,1,1,0;}"
 :"+f"(d[0]),"+f"(d[1]),"+f"(d[2]),"+f"(d[3]),"+f"(d[4]),"+f"(d[5]),"+f"(d[6]),"+f"(d[7]),"+f"(d[8]),"+f"(d[9]),"+f"(d[10]),"+f"(d[11]),"+f"(d[12]),"+f"(d[13]),"+f"(d[14]),"+f"(d[15]),"+f"(d[16]),"+f"(d[17]),"+f"(d[18]),"+f"(d[19]),"+f"(d[20]),"+f"(d[21]),"+f"(d[22]),"+f"(d[23]),"+f"(d[24]),"+f"(d[25]),"+f"(d[26]),"+f"(d[27]),"+f"(d[28]),"+f"(d[29]),"+f"(d[30]),"+f"(d[31]),"+f"(d[32]),"+f"(d[33]),"+f"(d[34]),"+f"(d[35]),"+f"(d[36]),"+f"(d[37]),"+f"(d[38]),"+f"(d[39]),"+f"(d[40]),"+f"(d[41]),"+f"(d[42]),"+f"(d[43]),"+f"(d[44]),"+f"(d[45]),"+f"(d[46]),"+f"(d[47]),"+f"(d[48]),"+f"(d[49]),"+f"(d[50]),"+f"(d[51]),"+f"(d[52]),"+f"(d[53]),"+f"(d[54]),"+f"(d[55])
 :"r"(a0),"r"(a1),"r"(a2),"r"(a3),"r"(blo),"n"(OFF),"n"(HI),"n"(SC)); } };
template<> struct WgRs<120> { template<int OFF,int HI,int SC> static __device__ __forceinline__ void run(float* d,uint32_t a0,uint32_t a1,uint32_t a2,uint32_t a3,uint32_t blo){
 asm volatile("{.reg .b32 l; .reg .b64 db; add.u32 l,%64,%65; mov.b64 db,{l,%66}; wgmma.mma_async.sync.aligned.m64n120k16.f32.bf16.bf16 {%0,%1,%2,%3,%4,%5,%6,%7,%8,%9,%10,%11,%12,%13,%14,%15,%16,%17,%18,%19,%20,%21,%22,%23,%24,%25,%26,%27,%28,%29,%30,%31,%32,%33,%34,%35,%36,%37,%38,%39,%40,%41,%42,%43,%44,%45,%46,%47,%48,%49,%50,%51,%52,%53,%54,%55,%56,%57,%58,%59},{%60,%61,%62,%63},db,%67,1,1,0;}"
 :"+f"(d[0]),"+f"(d[1]),"+f"(d[2]),"+f"(d[3]),"+f"(d[4]),"+f"(d[5]),"+f"(d[6]),"+f"(d[7]),"+f"(d[8]),"+f"(d[9]),"+f"(d[10]),"+f"(d[11]),"+f"(d[12]),"+f"(d[13]),"+f"(d[14]),"+f"(d[15]),"+f"(d[16]),"+f"(d[17]),"+f"(d[18]),"+f"(d[19]),"+f"(d[20]),"+f"(d[21]),"+f"(d[22]),"+f"(d[23]),"+f"(d[24]),"+f"(d[25]),"+f"(d[26]),"+f"(d[27]),"+f"(d[28]),"+f"(d[29]),"+f"(d[30]),"+f"(d[31]),"+f"(d[32]),"+f"(d[33]),"+f"(d[34]),"+f"(d[35]),"+f"(d[36]),"+f"(d[37]),"+f"(d[38]),"+f"(d[39]),"+f"(d[40]),"+f"(d[41]),"+f"(d[42]),"+f"(d[43]),"+f"(d[44]),"+f"(d[45]),"+f"(d[46]),"+f"(d[47]),"+f"(d[48]),"+f"(d[49]),"+f"(d[50]),"+f"(d[51]),"+f"(d[52]),"+f"(d[53]),"+f"(d[54]),"+f"(d[55]),"+f"(d[56]),"+f"(d[57]),"+f"(d[58]),"+f"(d[59])
 :"r"(a0),"r"(a1),"r"(a2),"r"(a3),"r"(blo),"n"(OFF),"n"(HI),"n"(SC)); } };
template<> struct WgRs<128> { template<int OFF,int HI,int SC> static __device__ __forceinline__ void run(float* d,uint32_t a0,uint32_t a1,uint32_t a2,uint32_t a3,uint32_t blo){
 asm volatile("{.reg .b32 l; .reg .b64 db; add.u32 l,%68,%69; mov.b64 db,{l,%70}; wgmma.mma_async.sync.aligned.m64n128k16.f32.bf16.bf16 {%0,%1,%2,%3,%4,%5,%6,%7,%8,%9,%10,%11,%12,%13,%14,%15,%16,%17,%18,%19,%20,%21,%22,%23,%24,%25,%26,%27,%28,%29,%30,%31,%32,%33,%34,%35,%36,%37,%38,%39,%40,%41,%42,%43,%44,%45,%46,%47,%48,%49,%50,%51,%52,%53,%54,%55,%56,%57,%58,%59,%60,%61,%62,%63},{%64,%65,%66,%67},db,%71,1,1,0;}"
 :"+f"(d[0]),"+f"(d[1]),"+f"(d[2]),"+f"(d[3]),"+f"(d[4]),"+f"(d[5]),"+f"(d[6]),"+f"(d[7]),"+f"(d[8]),"+f"(d[9]),"+f"(d[10]),"+f"(d[11]),"+f"(d[12]),"+f"(d[13]),"+f"(d[14]),"+f"(d[15]),"+f"(d[16]),"+f"(d[17]),"+f"(d[18]),"+f"(d[19]),"+f"(d[20]),"+f"(d[21]),"+f"(d[22]),"+f"(d[23]),"+f"(d[24]),"+f"(d[25]),"+f"(d[26]),"+f"(d[27]),"+f"(d[28]),"+f"(d[29]),"+f"(d[30]),"+f"(d[31]),"+f"(d[32]),"+f"(d[33]),"+f"(d[34]),"+f"(d[35]),"+f"(d[36]),"+f"(d[37]),"+f"(d[38]),"+f"(d[39]),"+f"(d[40]),"+f"(d[41]),"+f"(d[42]),"+f"(d[43]),"+f"(d[44]),"+f"(d[45]),"+f"(d[46]),"+f"(d[47]),"+f"(d[48]),"+f"(d[49]),"+f"(d[50]),"+f"(d[51]),"+f"(d[52]),"+f"(d[53]),"+f"(d[54]),"+f"(d[55]),"+f"(d[56]),"+f"(d[57]),"+f"(d[58]),"+f"(d[59]),"+f"(d[60]),"+f"(d[61]),"+f"(d[62]),"+f"(d[63])
 :"r"(a0),"r"(a1),"r"(a2),"r"(a3),"r"(blo),"n"(OFF),"n"(HI),"n"(SC)); } };
template<> struct WgSs<80> { template<int AOFF,int AHI,int BOFF,int BHI,int SC> static __device__ __forceinline__ void run(float* d,uint32_t alo,uint32_t blo){
 asm volatile("{.reg .b32 l,m; .reg .b64 da,db; add.u32 l,%40,%42; mov.b64 da,{l,%43}; add.u32 m,%41,%44; mov.b64 db,{m,%45}; wgmma.mma_async.sync.aligned.m64n80k16.f32.bf16.bf16 {%0,%1,%2,%3,%4,%5,%6,%7,%8,%9,%10,%11,%12,%13,%14,%15,%16,%17,%18,%19,%20,%21,%22,%23,%24,%25,%26,%27,%28,%29,%30,%31,%32,%33,%34,%35,%36,%37,%38,%39},da,db,%46,1,1,0,1;}"
 :"+f"(d[0]),"+f"(d[1]),"+f"(d[2]),"+f"(d[3]),"+f"(d[4]),"+f"(d[5]),"+f"(d[6]),"+f"(d[7]),"+f"(d[8]),"+f"(d[9]),"+f"(d[10]),"+f"(d[11]),"+f"(d[12]),"+f"(d[13]),"+f"(d[14]),"+f"(d[15]),"+f"(d[16]),"+f"(d[17]),"+f"(d[18]),"+f"(d[19]),"+f"(d[20]),"+f"(d[21]),"+f"(d[22]),"+f"(d[23]),"+f"(d[24]),"+f"(d[25]),"+f"(d[26]),"+f"(d[27]),"+f"(d[28]),"+f"(d[29]),"+f"(d[30]),"+f"(d[31]),"+f"(d[32]),"+f"(d[33]),"+f"(d[34]),"+f"(d[35]),"+f"(d[36]),"+f"(d[37]),"+f"(d[38]),"+f"(d[39])
 :"r"(alo),"r"(blo),"n"(AOFF),"n"(AHI),"n"(BOFF),"n"(BHI),"n"(SC)); } };
template<> struct WgSs<104> { template<int AOFF,int AHI,int BOFF,int BHI,int SC> static __device__ __forceinline__ void run(float* d,uint32_t alo,uint32_t blo){
 asm volatile("{.reg .b32 l,m; .reg .b64 da,db; add.u32 l,%52,%54; mov.b64 da,{l,%55}; add.u32 m,%53,%56; mov.b64 db,{m,%57}; wgmma.mma_async.sync.aligned.m64n104k16.f32.bf16.bf16 {%0,%1,%2,%3,%4,%5,%6,%7,%8,%9,%10,%11,%12,%13,%14,%15,%16,%17,%18,%19,%20,%21,%22,%23,%24,%25,%26,%27,%28,%29,%30,%31,%32,%33,%34,%35,%36,%37,%38,%39,%40,%41,%42,%43,%44,%45,%46,%47,%48,%49,%50,%51},da,db,%58,1,1,0,1;}"
 :"+f"(d[0]),"+f"(d[1]),"+f"(d[2]),"+f"(d[3]),"+f"(d[4]),"+f"(d[5]),"+f"(d[6]),"+f"(d[7]),"+f"(d[8]),"+f"(d[9]),"+f"(d[10]),"+f"(d[11]),"+f"(d[12]),"+f"(d[13]),"+f"(d[14]),"+f"(d[15]),"+f"(d[16]),"+f"(d[17]),"+f"(d[18]),"+f"(d[19]),"+f"(d[20]),"+f"(d[21]),"+f"(d[22]),"+f"(d[23]),"+f"(d[24]),"+f"(d[25]),"+f"(d[26]),"+f"(d[27]),"+f"(d[28]),"+f"(d[29]),"+f"(d[30]),"+f"(d[31]),"+f"(d[32]),"+f"(d[33]),"+f"(d[34]),"+f"(d[35]),"+f"(d[36]),"+f"(d[37]),"+f"(d[38]),"+f"(d[39]),"+f"(d[40]),"+f"(d[41]),"+f"(d[42]),"+f"(d[43]),"+f"(d[44]),"+f"(d[45]),"+f"(d[46]),"+f"(d[47]),"+f"(d[48]),"+f"(d[49]),"+f"(d[50]),"+f"(d[51])
 :"r"(alo),"r"(blo),"n"(AOFF),"n"(AHI),"n"(BOFF),"n"(BHI),"n"(SC)); } };
template<> struct WgSs<112> { template<int AOFF,int AHI,int BOFF,int BHI,int SC> static __device__ __forceinline__ void run(float* d,uint32_t alo,uint32_t blo){
 asm volatile("{.reg .b32 l,m; .reg .b64 da,db; add.u32 l,%56,%58; mov.b64 da,{l,%59}; add.u32 m,%57,%60; mov.b64 db,{m,%61}; wgmma.mma_async.sync.aligned.m64n112k16.f32.bf16.bf16 {%0,%1,%2,%3,%4,%5,%6,%7,%8,%9,%10,%11,%12,%13,%14,%15,%16,%17,%18,%19,%20,%21,%22,%23,%24,%25,%26,%27,%28,%29,%30,%31,%32,%33,%34,%35,%36,%37,%38,%39,%40,%41,%42,%43,%44,%45,%46,%47,%48,%49,%50,%51,%52,%53,%54,%55},da,db,%62,1,1,0,1;}"
 :"+f"(d[0]),"+f"(d[1]),"+f"(d[2]),"+f"(d[3]),"+f"(d[4]),"+f"(d[5]),"+f"(d[6]),"+f"(d[7]),"+f"(d[8]),"+f"(d[9]),"+f"(d[10]),"+f"(d[11]),"+f"(d[12]),"+f"(d[13]),"+f"(d[14]),"+f"(d[15]),"+f"(d[16]),"+f"(d[17]),"+f"(d[18]),"+f"(d[19]),"+f"(d[20]),"+f"(d[21]),"+f"(d[22]),"+f"(d[23]),"+f"(d[24]),"+f"(d[25]),"+f"(d[26]),"+f"(d[27]),"+f"(d[28]),"+f"(d[29]),"+f"(d[30]),"+f"(d[31]),"+f"(d[32]),"+f"(d[33]),"+f"(d[34]),"+f"(d[35]),"+f"(d[36]),"+f"(d[37]),"+f"(d[38]),"+f"(d[39]),"+f"(d[40]),"+f"(d[41]),"+f"(d[42]),"+f"(d[43]),"+f"(d[44]),"+f"(d[45]),"+f"(d[46]),"+f"(d[47]),"+f"(d[48]),"+f"(d[49]),"+f"(d[50]),"+f"(d[51]),"+f"(d[52]),"+f"(d[53]),"+f"(d[54]),"+f"(d[55])
 :"r"(alo),"r"(blo),"n"(AOFF),"n"(AHI),"n"(BOFF),"n"(BHI),"n"(SC)); } };

__device__ __forceinline__ void wg_fence() { asm volatile("wgmma.fence.sync.aligned;" ::: "memory"); }
__device__ __forceinline__ void wg_commit() { asm volatile("wgmma.commit_group.sync.aligned;" ::: "memory"); }
template <int N> __device__ __forceinline__ void wg_wait() { asm volatile("wgmma.wait_group.sync.aligned %0;" ::"n"(N) : "memory"); }
template <int N> __device__ __forceinline__ void reg_fence(float* d) {
#pragma unroll
    for (int i = 0; i < N; i++) asm volatile("" : "+f"(d[i])::"memory");
}
__device__ __forceinline__ uint32_t desc_lo(uint32_t addr, uint32_t lbo) { return ((addr & 0x3FFFF) >> 4) | ((lbo >> 4) << 16); }
#define desc_hi(sbo, sw) (((sbo) >> 4) | ((sw) << 30))
__device__ __forceinline__ uint32_t smem_u32(const void* p) { return (uint32_t)__cvta_generic_to_shared(p); }
__device__ __forceinline__ bool elect() {
    uint32_t p;
    asm volatile("{.reg .pred P; elect.sync _|P, 0xffffffff; selp.u32 %0,1,0,P;}" : "=r"(p));
    return p;
}
__device__ __forceinline__ void mbar_init(uint32_t bar, uint32_t cnt) { asm volatile("mbarrier.init.shared::cta.b64 [%0], %1;" ::"r"(bar), "r"(cnt) : "memory"); }
__device__ __forceinline__ void mbar_expect(uint32_t bar, uint32_t bytes) { asm volatile("mbarrier.arrive.expect_tx.shared::cta.b64 _, [%0], %1;" ::"r"(bar), "r"(bytes) : "memory"); }
__device__ __forceinline__ bool mbar_try(uint32_t bar, uint32_t par) {
    uint32_t ok;
    asm volatile("{.reg .pred p; mbarrier.try_wait.parity.shared::cta.b64 p, [%1], %2; selp.u32 %0,1,0,p;}" : "=r"(ok) : "r"(bar), "r"(par) : "memory");
    return ok;
}
constexpr int SPIN_LIMIT = 1 << 18;
__device__ __forceinline__ void mbar_wait(uint32_t bar, uint32_t par) {
    if (mbar_try(bar, par)) return;
    int n = 0;
    while (!mbar_try(bar, par) && ++n < SPIN_LIMIT) {}
}
__device__ __forceinline__ void bulk_g2s(uint32_t dst, const void* src, uint32_t bytes, uint32_t bar) {
    asm volatile("cp.async.bulk.shared::cluster.global.mbarrier::complete_tx::bytes [%0], [%1], %2, [%3];" ::"r"(dst), "l"(src), "r"(bytes), "r"(bar) : "memory");
}
__device__ __forceinline__ void bulk_prefetch(const void* src, uint32_t bytes) {
    asm volatile("cp.async.bulk.prefetch.L2.global [%0], %1;" ::"l"(src), "r"(bytes) : "memory");
}
__device__ __forceinline__ void tma2d(uint32_t dst, const CUtensorMap* m, int c0, int c1, uint32_t bar) {
    asm volatile("cp.async.bulk.tensor.2d.shared::cluster.global.mbarrier::complete_tx::bytes [%0], [%1, {%3, %4}], [%2];" ::"r"(dst), "l"(m), "r"(bar), "r"(c0), "r"(c1) : "memory");
}
__device__ __forceinline__ void tma2d_mc(uint32_t dst, const CUtensorMap* m, int c0, int c1, uint32_t bar) {
    asm volatile("cp.async.bulk.tensor.2d.shared::cluster.global.mbarrier::complete_tx::bytes.multicast::cluster [%0], [%1, {%3, %4}], [%2], %5;" ::"r"(dst), "l"(m), "r"(bar), "r"(c0), "r"(c1), "h"((uint16_t)3) : "memory");
}
__device__ __forceinline__ uint32_t mapa(uint32_t a, uint32_t rank) { uint32_t r; asm("mapa.shared::cluster.u32 %0, %1, %2;" : "=r"(r) : "r"(a), "r"(rank)); return r; }
__device__ __forceinline__ void mbar_arrive_cl(uint32_t bar) { asm volatile("mbarrier.arrive.shared::cluster.b64 _, [%0];" ::"r"(bar) : "memory"); }
__device__ __forceinline__ void prefetch_map(const CUtensorMap* m) { asm volatile("prefetch.tensormap [%0];" ::"l"(m) : "memory"); }
__device__ __forceinline__ void cpasync16(uint32_t dst, const void* src, uint32_t srcsz) {
    asm volatile("cp.async.cg.shared.global [%0], [%1], 16, %2;" ::"r"(dst), "l"(src), "r"(srcsz) : "memory");
}
__device__ __forceinline__ void bar_sync(int id, int n) { asm volatile("bar.sync %0, %1;" ::"r"(id), "r"(n) : "memory"); }
__device__ __forceinline__ void bar_arrive(int id, int n) { asm volatile("bar.arrive %0, %1;" ::"r"(id), "r"(n) : "memory"); }
__device__ __forceinline__ void fence_async_smem() { asm volatile("fence.proxy.async.shared::cta;" ::: "memory"); }
__device__ __forceinline__ void fence_async_global() { asm volatile("fence.proxy.async.global;" ::: "memory"); }
__device__ __forceinline__ void flag_release(int f) { asm volatile("red.release.gpu.global.add.u32 [%0], 1;" ::"l"(&g_flags[f * 32]) : "memory"); }
__device__ __forceinline__ void flag_wait(int f, unsigned target) {
    const unsigned* p = &g_flags[f * 32];
    unsigned v; int n = 0;
    do {
        asm volatile("ld.acquire.gpu.global.u32 %0, [%1];" : "=r"(v) : "l"(p) : "memory");
    } while ((int)(v - target) < 0 && ++n < SPIN_LIMIT);
}
__device__ __forceinline__ uint32_t lds32(uint32_t a) { uint32_t v; asm volatile("ld.shared.u32 %0, [%1];" : "=r"(v) : "r"(a)); return v; }
__device__ __forceinline__ float2 lds64f(uint32_t a) { float2 v; asm volatile("ld.shared.v2.f32 {%0,%1}, [%2];" : "=f"(v.x), "=f"(v.y) : "r"(a)); return v; }
__device__ __forceinline__ uint2 lds64(uint32_t a) { uint2 v; asm volatile("ld.shared.v2.u32 {%0,%1}, [%2];" : "=r"(v.x), "=r"(v.y) : "r"(a)); return v; }
__device__ __forceinline__ void sts64f(uint32_t a, float2 v) { asm volatile("st.shared.v2.f32 [%0], {%1,%2};" ::"r"(a), "f"(v.x), "f"(v.y) : "memory"); }
__device__ __forceinline__ void sts16(uint32_t a, uint16_t v) { asm volatile("st.shared.u16 [%0], %1;" ::"r"(a), "h"(v) : "memory"); }
__device__ __forceinline__ uint4 lds128(uint32_t a) { uint4 v; asm volatile("ld.shared.v4.u32 {%0,%1,%2,%3}, [%4];" : "=r"(v.x), "=r"(v.y), "=r"(v.z), "=r"(v.w) : "r"(a)); return v; }
__device__ __forceinline__ float4 lds128f(uint32_t a) { float4 v; asm volatile("ld.shared.v4.f32 {%0,%1,%2,%3}, [%4];" : "=f"(v.x), "=f"(v.y), "=f"(v.z), "=f"(v.w) : "r"(a)); return v; }
__device__ __forceinline__ void sts128(uint32_t a, uint4 v) { asm volatile("st.shared.v4.u32 [%0], {%1,%2,%3,%4};" ::"r"(a), "r"(v.x), "r"(v.y), "r"(v.z), "r"(v.w) : "memory"); }
__device__ __forceinline__ void sts128f(uint32_t a, float x, float y, float z, float w) { asm volatile("st.shared.v4.f32 [%0], {%1,%2,%3,%4};" ::"r"(a), "f"(x), "f"(y), "f"(z), "f"(w) : "memory"); }
__device__ __forceinline__ uint32_t prmt(uint32_t a, uint32_t b, uint32_t s) { uint32_t r; asm("prmt.b32 %0,%1,%2,%3;" : "=r"(r) : "r"(a), "r"(b), "r"(s)); return r; }
__device__ __forceinline__ uint32_t pack2(float lo, float hi) { uint32_t r; asm("cvt.rn.bf16x2.f32 %0, %1, %2;" : "=r"(r) : "f"(hi), "f"(lo)); return r; }
__device__ __forceinline__ float blo(uint32_t v) { return __uint_as_float(v << 16); }
__device__ __forceinline__ float bhi(uint32_t v) { return __uint_as_float(v & 0xffff0000u); }
__device__ __forceinline__ uint32_t bmul2(uint32_t a, uint32_t b) { uint32_t r; asm("mul.rn.bf16x2 %0,%1,%2;" : "=r"(r) : "r"(a), "r"(b)); return r; }
__device__ __forceinline__ uint32_t badd2(uint32_t a, uint32_t b) { uint32_t r; asm("add.rn.bf16x2 %0,%1,%2;" : "=r"(r) : "r"(a), "r"(b)); return r; }
__device__ __forceinline__ float rbf(float x) { return __bfloat162float(__float2bfloat16_rn(x)); }
__device__ __forceinline__ uint32_t ldcg32(const void* p) { uint32_t v; asm volatile("ld.global.cg.u32 %0, [%1];" : "=r"(v) : "l"(p) : "memory"); return v; }
__device__ __forceinline__ uint2 ldcg64(const void* p) { uint2 v; asm volatile("ld.global.cg.v2.u32 {%0,%1}, [%2];" : "=r"(v.x), "=r"(v.y) : "l"(p) : "memory"); return v; }
__device__ __forceinline__ float gelu(float x) {
    float t = x * x;
    float u = x * fmaf(t, 0.044715f * 0.7978845608028654f, 0.7978845608028654f);
    float th;
    asm("tanh.approx.f32 %0, %1;" : "=f"(th) : "f"(u));
    float hx = 0.5f * x;
    return fmaf(hx, th, hx);
}
__device__ __forceinline__ void ln_params(float sum, float sq, float& inv, float& nb) {
    float mean = sum * (1.0f / D_);
    float var = fmaxf(fmaf(-mean, mean, sq * (1.0f / D_)), 0.0f);
    float sq_;
    asm("sqrt.approx.f32 %0, %1;" : "=f"(sq_) : "f"(rbf(rbf(var) + 1e-5f)));
    inv = __fdividef(1.0f, rbf(sq_));
    nb = -rbf(mean) * inv;
}
__device__ __forceinline__ float2 row_ln(const uint32_t* v, uint32_t* o) {
    float s = 0.f, q = 0.f;
#pragma unroll
    for (int i = 0; i < 10; i++) { float a = blo(v[i]), b = bhi(v[i]); s += a + b; q = fmaf(a, a, fmaf(b, b, q)); }
#pragma unroll
    for (int m = 16; m; m >>= 1) { s += __shfl_xor_sync(0xffffffffu, s, m); q += __shfl_xor_sync(0xffffffffu, q, m); }
    float inv, nb;
    ln_params(s, q, inv, nb);
#pragma unroll
    for (int i = 0; i < 10; i++) o[i] = pack2(fmaf(blo(v[i]), inv, nb), fmaf(bhi(v[i]), inv, nb));
    return make_float2(inv, nb);
}

struct AFrag { uint32_t m, a, b, c, d; };
__device__ __forceinline__ AFrag ldA(uint32_t a) { AFrag f; f.m = lds32(a - 16); f.a = lds32(a); f.b = lds32(a + 16); f.c = lds32(a + 32); f.d = lds32(a + 48); return f; }
template <int N, int M> __device__ __forceinline__ void conv_pair(float* d, const AFrag& f, uint32_t descU) {
    WgRs<N>::template run<8 * M, desc_hi(128, 0), 1>(d, f.a, f.b, f.m, f.a, descU);
    WgRs<N>::template run<8 * M + 1, desc_hi(128, 0), 1>(d, f.c, f.d, f.b, f.c, descU);
}
template <int Q> __device__ __forceinline__ void conv_put(float* d, uint32_t r0, uint32_t r1) {
    sts128f(((Q & 1) ? r1 : r0) + (Q >> 1) * 128, d[4 * Q], d[4 * Q + 1], d[4 * Q + 2], d[4 * Q + 3]);
}
template <int M> __device__ __forceinline__ void conv_head(float* d, AFrag& f, uint32_t kaddr, uint32_t descU, uint32_t r0, uint32_t r1) {
    wg_fence();
    conv_pair<128 - 8 * M, M>(d, f, descU);
    wg_commit();
    if constexpr (M < 3) {
        wg_wait<0>();
        conv_put<15 - M>(d, r0, r1);
        f = ldA(kaddr + 256 * (M + 1));
    } else {
        if constexpr (M > 3) conv_put<16 - M>(d, r0, r1);
        AFrag n = ldA(kaddr + 256 * (M + 1));
        wg_wait<0>();
        f = n;
    }
    if constexpr (M < 7) conv_head<M + 1>(d, f, kaddr, descU, r0, r1);
}
__device__ __forceinline__ void conv_main(float* d, uint32_t fm, uint32_t fa, uint32_t fb, uint32_t kaddr, uint32_t descU, uint32_t r0, uint32_t r1, int handoff) {
    wg_fence();
    WgRs<128>::run<0, desc_hi(128, 0), 0>(d, fa, fb, fm, fa, descU);
    wg_commit();
    wg_wait<0>();
    fa = lds32(kaddr + 32); fb = lds32(kaddr + 48); fm = lds32(kaddr + 16);
    wg_fence();
    WgRs<128>::run<1, desc_hi(128, 0), 1>(d, fa, fb, fm, fa, descU);
    wg_commit();
    wg_wait<0>();
    conv_put<15>(d, r0, r1);
    AFrag f = ldA(kaddr + 256);
    conv_head<1>(d, f, kaddr, descU, r0, r1);
    AFrag f1 = ldA(kaddr + 256 * 9);
    wg_fence();
    conv_pair<64, 8>(d, f, descU); conv_pair<64, 9>(d, f1, descU);
    wg_commit();
    if (handoff) bar_arrive(handoff, 512);
    conv_put<8>(d, r0, r1);
    AFrag f2 = ldA(kaddr + 256 * 10), f3 = ldA(kaddr + 256 * 11);
    wg_wait<0>();
    wg_fence();
    conv_pair<48, 10>(d, f2, descU); conv_pair<48, 11>(d, f3, descU);
    wg_commit();
    conv_put<7>(d, r0, r1); conv_put<6>(d, r0, r1);
    AFrag f4 = ldA(kaddr + 256 * 12), f5 = ldA(kaddr + 256 * 13), f6 = ldA(kaddr + 256 * 14), f7 = ldA(kaddr + 256 * 15);
    wg_wait<0>();
    wg_fence();
    conv_pair<32, 12>(d, f4, descU); conv_pair<32, 13>(d, f5, descU); conv_pair<32, 14>(d, f6, descU); conv_pair<32, 15>(d, f7, descU);
    wg_commit();
    conv_put<5>(d, r0, r1); conv_put<4>(d, r0, r1);
    wg_wait<0>();
    conv_put<3>(d, r0, r1); conv_put<2>(d, r0, r1); conv_put<1>(d, r0, r1);
}

template <int N, bool ASWZ, int SC0>
__device__ __forceinline__ void gemm_issue(float* acc, uint32_t sb, int st, int ph, uint32_t da0, uint32_t db0) {
    mbar_wait(sb + SM_BAR + (BAR_FULL + st) * 8, ph);
    const uint32_t da = da0 + st * (STAGE_BYTES >> 4), db = db0 + st * (STAGE_BYTES >> 4);
    constexpr int AK = ASWZ ? 2 : 256, AH = ASWZ ? desc_hi(1024, 1) : desc_hi(128, 0), BH = desc_hi(1024, 1);
    wg_fence();
    WgSs<N>::template run<0, AH, 0, BH, SC0>(acc, da, db);
    WgSs<N>::template run<AK, AH, 128, BH, 1>(acc, da, db);
    WgSs<N>::template run<2 * AK, AH, 256, BH, 1>(acc, da, db);
    WgSs<N>::template run<3 * AK, AH, 384, BH, 1>(acc, da, db);
    wg_commit();
}
template <int N, bool ASWZ, int IT0, int NKB, bool ZERO, int ORDER_BAR, class HOOK>
__device__ __forceinline__ void gemm_loop(float* acc, uint32_t sb, int half, HOOK hook) {
    int st = IT0 % NSTAGE, ph = (IT0 / NSTAGE) & 1;
    const uint32_t ebar = mapa(sb + SM_BAR + BAR_EMPTY * 8, threadIdx.x & 1);
    const bool signal = (threadIdx.x & 127) < 2;
    constexpr int NREL = IT0 + NKB == 67 ? NKB - NSTAGE : NKB;
    const uint32_t da0 = ASWZ ? desc_lo(sb + half * 8192, 16) : desc_lo(sb + half * 1024, 2048), db0 = desc_lo(sb + 16384, 8192);
    gemm_issue<N, ASWZ, ZERO ? 0 : 1>(acc, sb, st, ph, da0, db0);
    hook();
#pragma unroll 1
    for (int kb = 1; kb < NKB; kb++) {
        const int prev = st;
        if (++st == NSTAGE) { st = 0; ph ^= 1; }
        gemm_issue<N, ASWZ, 1>(acc, sb, st, ph, da0, db0);
        wg_wait<1>();
        if (signal && kb <= NREL) mbar_arrive_cl(ebar + prev * 8);
    }
    if (ORDER_BAR) bar_arrive(ORDER_BAR, 512);
    wg_wait<0>();
    if (signal && NREL == NKB) mbar_arrive_cl(ebar + st * 8);
    reg_fence<N / 2>(acc);
}

template <int N, int IT0, int ORDER_BAR>
__device__ __forceinline__ void gemm3(uint32_t sb, int rb, int col0, int half, int wq, int g, int c) {
    float acc[N / 2];
    const int row = 64 * half + 16 * wq + g;
    uint2 s0, s1, s2, s3;
    gemm_loop<N, false, IT0, 10, true, ORDER_BAR>(acc, sb, half, [&]() {
        if ((threadIdx.x & 255) == 0) TS(N == 112 ? 46 : 48);
        const float2* sp = &g_st[(rb * 8 + 2 * c) * 128 + row];
        s0 = ldcg64(sp); s1 = ldcg64(sp + 128); s2 = ldcg64(sp + 8); s3 = ldcg64(sp + 136);
    });
    if ((threadIdx.x & 255) == 0) TS(N == 112 ? 47 : 49);
    float a0 = __uint_as_float(s0.x) + __uint_as_float(s1.x), b0 = __uint_as_float(s0.y) + __uint_as_float(s1.y);
    float a1 = __uint_as_float(s2.x) + __uint_as_float(s3.x), b1 = __uint_as_float(s2.y) + __uint_as_float(s3.y);
#pragma unroll
    for (int m = 1; m <= 2; m <<= 1) {
        a0 += __shfl_xor_sync(0xffffffffu, a0, m); b0 += __shfl_xor_sync(0xffffffffu, b0, m);
        a1 += __shfl_xor_sync(0xffffffffu, a1, m); b1 += __shfl_xor_sync(0xffffffffu, b1, m);
    }
    float inv0, nb0, inv1, nb1;
    ln_params(a0, b0, inv0, nb0);
    ln_params(a1, b1, inv1, nb1);
    uint32_t* dst = reinterpret_cast<uint32_t*>(g_g) + ((size_t)rb * 216 + (col0 >> 3)) * 512 + row * 4 + c;
    mbar_wait(sb + SM_BAR + BAR_CS * 8, 0);
    const uint32_t cs = sb + SM_CS + (N == 112 ? 0 : 448) + 8 * c;
#pragma unroll
    for (int q = 0; q < N / 8; q++) {
        float2 cr = lds64f(cs + 32 * q);
        dst[q * 512] = pack2(gelu(fmaf(acc[4 * q], inv0, nb0 * cr.x)), gelu(fmaf(acc[4 * q + 1], inv0, nb0 * cr.y)));
        dst[q * 512 + 32] = pack2(gelu(fmaf(acc[4 * q + 2], inv1, nb1 * cr.x)), gelu(fmaf(acc[4 * q + 3], inv1, nb1 * cr.y)));
    }
}

struct Ring {
    uint32_t sb, st, ph;
    __device__ __forceinline__ uint32_t acquire(uint32_t bytes) {
        mbar_wait(sb + SM_BAR + BAR_EMPTY * 8 + st * 8, ph);
        uint32_t fb = sb + SM_BAR + BAR_FULL * 8 + st * 8;
        mbar_expect(fb, bytes);
        return fb;
    }
    __device__ __forceinline__ void next() { if (++st == NSTAGE) { st = 0; ph ^= 1; } }
    __device__ __forceinline__ void run2d(const CUtensorMap* m, uint32_t off, int c0, int d0, int c1, int d1, int n, uint32_t bytes) {
#pragma unroll 1
        for (; n > 0; n--) {
            uint32_t fb = acquire(bytes);
            tma2d(sb + st * STAGE_BYTES + off, m, c0, c1, fb);
            c0 += d0; c1 += d1;
            next();
        }
    }
    __device__ __forceinline__ void runw(const CUtensorMap* m, uint32_t off, int c0, int n, uint32_t bytes) {
#pragma unroll 1
        for (int c1 = 0; n > 0; n--, c1 += 64) {
            uint32_t fb = acquire(bytes);
            tma2d_mc(sb + st * STAGE_BYTES + off, m, c0, c1, fb);
            next();
        }
    }
    __device__ __forceinline__ void run1d(const char* src, int n) {
#pragma unroll 1
        for (; n > 0; n--) {
            uint32_t fb = acquire(16384);
            bulk_g2s(sb + st * STAGE_BYTES, src, 16384, fb);
            src += 16384;
            next();
        }
    }
};

__global__ void __cluster_dims__(2, 1, 1) __launch_bounds__(NTHREADS, 1) fused_kernel(const __grid_constant__ Maps maps, const Params p) {
    extern __shared__ __align__(1024) unsigned char smem_raw[];
    const uint32_t sb = (smem_u32(smem_raw) + 1023u) & ~1023u;
#pragma unroll
    for (int i = 0; i < SEED; i++) asm volatile("{.reg .b32 t; mov.u32 t, %laneid;}");
    const uint32_t bars = sb + SM_BAR;
    const int tid = threadIdx.x, lane = tid & 31;
    const int warp = __shfl_sync(0xffffffffu, tid >> 5, 0);
    const int wg = warp >> 2, wq = warp & 3;
    const unsigned smid = blockIdx.x < 8 ? blockIdx.x + 124 : blockIdx.x - 8;
    int gpc, idx;
    if (smid < 64) { gpc = (smid & 15) >> 1; idx = (smid >> 4) * 2 + (smid & 1); }
    else if (smid < 120) { int t = smid - 64; gpc = 1 + (t % 14) / 2; idx = 8 + (t / 14) * 2 + (smid & 1); }
    else if (smid < 124) { gpc = 0; idx = 16 + (smid - 120); }
    else { gpc = 0; idx = 8 + (smid - 124); }
    const unsigned ep1 = *(volatile unsigned*)&g_epoch[smid] + 1;

    if (idx >= 16) {
        const int sp = idx - 16;
        if (warp == 0) { if (lane < 8) flag_wait(FL_P + lane, ep1 * 16); __syncwarp(); }
        __syncthreads();
        float* red = reinterpret_cast<float*>(smem_raw + (sb - smem_u32(smem_raw)));
        if (tid < 540) {
            const int cq = tid % 54, rg = tid / 54;
            const uint4* src = reinterpret_cast<const uint4*>(p.w3 + (size_t)rg * 64 * F_ + sp * 432) + cq;
            float a[8];
#pragma unroll
            for (int i = 0; i < 8; i++) a[i] = 0.f;
            for (int r0 = 0; r0 < 64; r0 += 8) {
                uint4 w[8];
#pragma unroll
                for (int i = 0; i < 8; i++) w[i] = __ldg(src + (size_t)(r0 + i) * (F_ / 8));
#pragma unroll
                for (int i = 0; i < 8; i++) {
                    a[0] += blo(w[i].x); a[1] += bhi(w[i].x); a[2] += blo(w[i].y); a[3] += bhi(w[i].y);
                    a[4] += blo(w[i].z); a[5] += bhi(w[i].z); a[6] += blo(w[i].w); a[7] += bhi(w[i].w);
                }
            }
#pragma unroll
            for (int i = 0; i < 8; i++) red[rg * 432 + cq * 8 + i] = a[i];
        }
        __syncthreads();
        if (tid < 432) {
            float s = 0.f;
#pragma unroll
            for (int i = 0; i < 10; i++) s += red[i * 432 + tid];
            g_cs[sp * 432 + tid] = s;
        }
        __syncthreads();
        if (tid == 0) { flag_release(FL_CS); g_epoch[smid] = ep1; TS(0); }
        if (warp == 0) TSFLUSH();
        return;
    }

    const int cta = gpc * 16 + idx;
    const int rb = 2 * gpc + (idx & 1), j = idx >> 1;
    const int g = lane >> 2, c = lane & 3;

    {
        const int r0 = 128 * idx;
        const char* kb = (const char*)(p.k + (size_t)r0 * D_ + 80 * gpc);
        const char* vb = (const char*)(p.v + (size_t)r0 * D_ + 80 * gpc);
#pragma unroll
        for (int i = 0; i < 2; i++) {
            int ch = tid + i * 640, row = ch / 10, cc = ch % 10;
            uint32_t so = (row >> 4) * 2576 + (row & 15) * 160 + cc * 16;
            cpasync16(sb + SM_PK + 2576 + so, kb + row * 1280 + cc * 16, 16);
            cpasync16(sb + SM_PV + so, vb + row * 1280 + cc * 16, 16);
        }
        if (tid < 30) {
            int row = tid / 10, cc = tid % 10;
            cpasync16(sb + SM_PK + (13 + row) * 160 + cc * 16, idx ? kb + (row - 3) * 1280 + cc * 16 : kb, idx ? 16 : 0);
        }
        asm volatile("cp.async.commit_group;" ::: "memory");
        const int h = warp / 10, pr = (warp % 10) * 4 + (lane >> 3), blk = lane & 7;
        const int ch = 80 * gpc + 2 * pr;
        const uint4 sw = __ldg(reinterpret_cast<const uint4*>(p.shift + ch * 4));
        if (tid == 0) {
            for (int i = 0; i < NSTAGE; i++) { mbar_init(bars + (BAR_FULL + i) * 8, 2); mbar_init(bars + (BAR_EMPTY + i) * 8, 4); }
            for (int i = BAR_K; i <= BAR_CS; i++) mbar_init(bars + i * 8, 1);
            asm volatile("fence.mbarrier_init.release.cluster;" ::: "memory");
        }
        if (warp == 1 && lane < 11) prefetch_map(&maps.hn + lane);
        if (warp == 2 && lane < 20)
            sts128(sb + SM_K + (lane >> 2) * K_STRIDE + ((lane >> 1) & 1) * 4160 + (lane & 1) * 16, make_uint4(0, 0, 0, 0));
        if (warp >= 10) {
            sts128(sb + SM_U + (warp - 10) * U_PLANE + 2048 + lane * 16, make_uint4(0, 0, 0, 0));
            fence_async_smem();
        }
        asm volatile("barrier.cluster.arrive.relaxed.aligned;" ::: "memory");
        asm volatile("cp.async.wait_group 0;" ::: "memory");
        asm volatile("barrier.cluster.wait.aligned;" ::: "memory");
        __syncthreads();
        if (warp == 0) TSW(1);
        if (warp == 4 && elect()) {
#pragma unroll
            for (int i = 0; i < 5; i++) {
                mbar_expect(bars + (BAR_K + i) * 8, 4096);
                bulk_g2s(sb + SM_K + i * K_STRIDE + 32, p.ssmk + (size_t)(cta * 5 + i) * S_, 4096, bars + (BAR_K + i) * 8);
            }
        }
        const uint32_t w0 = prmt(sw.x, sw.z, 0x5410), w1 = prmt(sw.x, sw.z, 0x7632), w2 = prmt(sw.y, sw.w, 0x5410), w3 = prmt(sw.y, sw.w, 0x7632);
        const uint32_t ka = sb + SM_PK + 2576 + blk * 2576 + h * 1280 + pr * 4;
        const uint32_t va = sb + SM_PV + blk * 2576 + h * 1280 + pr * 4;
        uint32_t kk[11], kv[8];
#pragma unroll
        for (int i = 0; i < 11; i++) kk[i] = lds32(ka + (i - 3) * 160 - ((i < 3 && h == 0) ? 16 : 0));
#pragma unroll
        for (int i = 0; i < 8; i++) {
            uint32_t t = badd2(badd2(badd2(bmul2(kk[i], w3), bmul2(kk[i + 1], w2)), bmul2(kk[i + 2], w1)), bmul2(kk[i + 3], w0));
            kv[i] = bmul2(t, lds32(va + i * 160));
        }
        uint4 o0, o1;
        o0.x = prmt(kv[1], kv[0], 0x5410); o0.y = prmt(kv[3], kv[2], 0x5410); o0.z = prmt(kv[5], kv[4], 0x5410); o0.w = prmt(kv[7], kv[6], 0x5410);
        o1.x = prmt(kv[1], kv[0], 0x7632); o1.y = prmt(kv[3], kv[2], 0x7632); o1.z = prmt(kv[5], kv[4], 0x7632); o1.w = prmt(kv[7], kv[6], 0x7632);
        uint4* dst = reinterpret_cast<uint4*>(g_kvT) + ch * 256 + h * 128 + (127 - (8 * idx + blk));
        dst[0] = o0;
        dst[256] = o1;
    }

    const int rho = 8 * rb + j;

    if (wg == 4) {
        asm volatile("setmaxnreg.dec.sync.aligned.u32 64;");
        const int t = tid - 512, cq = t & 3, rg = t >> 2;
        const uint4* src = reinterpret_cast<const uint4*>(p.wmod + (size_t)rg * 3840 + cta * 32) + cq;
        if (wq == 0) {
            bar_sync(13, 640);
            if (lane == 0) flag_release(FL_P + gpc);
            __syncwarp();
            TSW(2);
            flag_wait(FL_P + gpc, ep1 * 16);
            fence_async_global();
            TSW(3);
            if (elect()) {
#pragma unroll
                for (int i = 0; i < 5; i++) {
                    const char* us = (const char*)g_kvT + (size_t)(cta * 5 + i) * 4096;
                    mbar_expect(bars + (BAR_U + i) * 8, 4096);
                    bulk_g2s(sb + SM_U + i * U_STRIDE, us, 2048, bars + (BAR_U + i) * 8);
                    bulk_g2s(sb + SM_U + i * U_STRIDE + U_PLANE, us + 2048, 2048, bars + (BAR_U + i) * 8);
                }
            }
            __syncwarp();
        } else {
            bar_arrive(13, 640);
        }
        bar_sync(5, 128);
        if (wq == 1 && elect()) {
            bulk_prefetch((const char*)p.q + cta * 20480, 20480);
            bulk_prefetch((const char*)p.w1 + cta * 6400, 6400);
        }
        if (cta < 120) {
            float a[8];
#pragma unroll
            for (int i = 0; i < 8; i++) a[i] = 0.f;
#pragma unroll 1
            for (int b = 0; b < 2; b++) {
                uint4 w[10];
#pragma unroll
                for (int i = 0; i < 10; i++) w[i] = __ldg(src + (size_t)(b * 10 + i) * 32 * 480);
#pragma unroll
                for (int i = 0; i < 10; i++) {
                    float cv = __bfloat162float(p.c[rg + 32 * (b * 10 + i)]);
                    float sv = rbf(__fdividef(cv, 1.0f + __expf(-cv)));
                    a[0] = fmaf(sv, blo(w[i].x), a[0]); a[1] = fmaf(sv, bhi(w[i].x), a[1]);
                    a[2] = fmaf(sv, blo(w[i].y), a[2]); a[3] = fmaf(sv, bhi(w[i].y), a[3]);
                    a[4] = fmaf(sv, blo(w[i].z), a[4]); a[5] = fmaf(sv, bhi(w[i].z), a[5]);
                    a[6] = fmaf(sv, blo(w[i].w), a[6]); a[7] = fmaf(sv, bhi(w[i].w), a[7]);
                }
            }
#pragma unroll
            for (int m = 4; m <= 16; m <<= 1)
#pragma unroll
                for (int i = 0; i < 8; i++) a[i] += __shfl_xor_sync(0xffffffffu, a[i], m);
            if (lane < 4) {
                uint32_t a0 = sb + SM_GV + wq * 128 + lane * 32;
                sts128f(a0, a[0], a[1], a[2], a[3]);
                sts128f(a0 + 16, a[4], a[5], a[6], a[7]);
            }
            bar_sync(5, 128);
            if (wq == 3) {
                float s = 0.f;
#pragma unroll
                for (int i = 0; i < 4; i++) s += __uint_as_float(lds32(sb + SM_GV + i * 128 + lane * 4));
                g_mod[cta * 32 + lane] = __float2bfloat16_rn(s);
                TSW(4);
            }
        }
        if (wq == 1 && elect()) {
            bulk_prefetch((const char*)p.w2 + cta * 6400, 6400);
            bulk_prefetch((const char*)p.w3 + cta * 17280, 17280);
            bulk_prefetch((const char*)p.w4 + cta * 17280, 17280);
        }
        bar_sync(7, 640);
        if (wq == 2 && lane < 4 * NSTAGE) mbar_arrive_cl(mapa(bars + (BAR_EMPTY + (lane >> 2)) * 8, lane & 1));
        if (elect()) {
            Ring r{sb, 0, 0};
            if (wq == 3) {
                flag_release(FL_C);
                TS(20);
                flag_wait(FL_C, ep1 * 128);
                fence_async_global();
                TS(21);
                mbar_expect(bars + BAR_Y * 8, 20480 + 7680);
                bulk_g2s(sb + SM_Y, g_yv + rho * 5120, 20480, bars + BAR_Y * 8);
                bulk_g2s(sb + SM_MOD, g_mod, 7680, bars + BAR_Y * 8);
                flag_wait(FL_X2 + rb, ep1 * 8);
                fence_async_global();
                mbar_expect(bars + BAR_X * 8, 20480 + 1024);
                tma2d(sb + SM_Y, &maps.x2, 80 * j, 128 * rb, bars + BAR_X * 8);
                bulk_g2s(sb + SM_RS, g_rs + rb * 128, 1024, bars + BAR_X * 8);
                TS(33);
                flag_wait(FL_CS, ep1 * 4);
                fence_async_global();
                mbar_expect(bars + BAR_CS * 8, 864);
                bulk_g2s(sb + SM_CS, g_cs + 112 * j, 448, bars + BAR_CS * 8);
                bulk_g2s(sb + SM_CS + 448, g_cs + 896 + 104 * j, 416, bars + BAR_CS * 8);
            } else if (wq == 1) {
                const int rk = idx & 1;
                const uint32_t off = 16384 + 8192 * rk;
                r.runw(&maps.w1a + rk, off, 80 * j + 64 * rk, 10, 10240);
                r.runw(&maps.w2a + rk, off, 80 * j + 64 * rk, 10, 10240);
                r.runw(&maps.w3a + rk, off, 112 * j + 64 * rk, 10, 14336);
                r.runw(&maps.w3a + 2 * rk, off, 896 + 104 * j + 64 * rk, 10, 13312);
                r.runw(&maps.w4a + rk, off, 80 * j + 64 * rk, 27, 10240);
            } else if (wq == 0) {
                const int grp = j >> 1;
                const int delta = (grp & 1 ? 1 : -1) * (1 + (grp >> 1));
                const int nb = min(max(rb + (delta > 0 ? 1 : -1), 0), 15);
                flag_wait(FL_R + nb, ep1 * 8);
                flag_wait(FL_R + rb, ep1 * 8);
                fence_async_global(); TS(24);
                r.run2d(&maps.hn, 0, 0, 64, rb * 128 + delta, 0, 10, 16384);
                flag_wait(FL_B1 + rb, ep1 * 8); fence_async_global(); TS(28);
                r.run1d((const char*)g_h1 + (size_t)rb * 163840, 10);
                flag_wait(FL_B2 + rb, ep1 * 8); fence_async_global(); TS(32);
                r.run1d((const char*)g_x1 + (size_t)rb * 163840, 10);
                r.run1d((const char*)g_x1 + (size_t)rb * 163840, 10);
                flag_wait(FL_GA + rb, ep1 * 8); fence_async_global(); TS(40);
                r.run1d((const char*)g_g + (size_t)rb * 442368, 14);
                flag_wait(FL_GB + rb, ep1 * 8); fence_async_global(); TS(41);
                r.run1d((const char*)g_g + (size_t)rb * 442368 + 14 * 16384, 13);
            }
        }
        return;
    }
    bar_arrive(13, 640);
    asm volatile("setmaxnreg.inc.sync.aligned.u32 104;");
    const int rrow = 32 * (rho >> 1) + 8 * (rho & 1) + (warp >> 1) + 16 * (warp & 1);

#pragma unroll 1
    for (int cc = wg; cc < 5; cc += 3) {
        if (cc == 3 && wg == 0) break;
        mbar_wait(bars + (BAR_K + cc) * 8, 0);
        uint32_t a = sb + SM_K + cc * K_STRIDE + 32 + (tid & 127) * 32;
        uint32_t pw = lds32(a - 4);
        uint4 x = lds128(a), y = lds128(a + 16), o;
        if ((tid & 127) == 0) {
            uint16_t k0 = __bfloat16_as_ushort(__float2bfloat16_rn(blo(x.x) + __bfloat162float(p.ssmD[cta * 5 + cc])));
            x.x = (x.x & 0xffff0000u) | k0;
            sts16(a, k0);
        }
        o.x = prmt(pw, x.x, 0x5432); o.y = prmt(x.x, x.y, 0x5432); o.z = prmt(x.y, x.z, 0x5432); o.w = prmt(x.z, x.w, 0x5432);
        sts128(a + 4160, o);
        o.x = prmt(x.w, y.x, 0x5432); o.y = prmt(y.x, y.y, 0x5432); o.z = prmt(y.y, y.z, 0x5432); o.w = prmt(y.z, y.w, 0x5432);
        sts128(a + 4176, o);
    }
    bar_sync(1 + wg, 128);
    if (wg == 3) bar_sync(6, 512);
#pragma unroll 1
    for (int cc = wg; cc < 5; cc += 3) {
        if (cc == 3 && wg == 0) break;
        const int ch = cta * 5 + cc;
        const uint32_t sK = sb + SM_K + cc * K_STRIDE, sU = sb + SM_U + cc * U_STRIDE;
        const uint32_t kaddr = sK + ((g & 1) ? 32 : 4192) + 4 * ((g >> 1) - c) + 64 * wq;
        const uint32_t fm = lds32(kaddr - 16), fa = lds32(kaddr), fb = lds32(kaddr + 16);
        mbar_wait(bars + (BAR_U + cc) * 8, 0);
        if (wq == 0) TSW(5 + cc);
        const uint32_t red = sb + SM_RED + wg * 32768 + g * 1024;
        const int sx = (g & 1) << 2;
        const uint32_t r0 = red + wq * 8192 + (((c - wq + 8) ^ sx) - 8) * 16, r1 = red + wq * 8192 + ((c - wq + 4) ^ sx) * 16;
        float d[64];
        conv_main(d, fm, fa, fb, kaddr, desc_lo(sU, U_PLANE), r0, r1, cc < 3 ? 6 : 0);
        if (wq == 0) TSW(10 + cc);
        if (c >= wq) sts128f(r0, d[0], d[1], d[2], d[3]);
        bar_sync(1 + wg, 128);
        uint32_t* dst = g_yv + ch * 8 + ((g + (ch >> 2)) & 7);
#pragma unroll
        for (int q = 0; q < 4; q++) {
            int kap = 16 * wq + 4 * q + c;
            uint32_t a = red + ((kap ^ sx) << 4);
            float4 s = lds128f(a);
#pragma unroll
            for (int w = 1; w < 4; w++) {
                if (q < 3 || kap <= 63 - w) {
                    float4 x = lds128f(a + w * 8192);
                    s.x += x.x; s.y += x.y; s.z += x.z; s.w += x.w;
                }
            }
            uint32_t* o = dst + (size_t)(126 - 2 * kap) * 5120;
            o[0] = pack2(s.y, s.x);
            o[5120] = pack2(s.w, s.z);
        }
        if (cc == 1) bar_sync(1 + wg, 128);
        if (wq == 0) TSW(15 + cc);
    }
    fence_async_smem();
    bar_arrive(7, 640);

    uint32_t x[10];
    {
        uint32_t a[10], b[10];
        const uint32_t* xr = reinterpret_cast<const uint32_t*>(p.q + (size_t)rrow * D_) + lane;
#pragma unroll
        for (int i = 0; i < 10; i++) x[i] = __ldg(xr + 32 * i);
        row_ln(x, a);
        const int up = lane >> 4, gg = warp >> 1, e = warp & 1;
        const uint32_t ya = sb + SM_Y + lane * 64 + ((gg + (lane >> 1)) & 7) * 4;
        const uint32_t sel = (up ? 0x1054u : 0x5410u) + (e ? 0x2222u : 0u);
        const uint32_t ma = sb + SM_MOD + lane * 4;
        const uint32_t one2 = 0x3f803f80u;
        mbar_wait(bars + BAR_Y * 8, 0);
        if (warp == 0) TSW(22);
#pragma unroll
        for (int i = 0; i < 10; i++) {
            uint32_t y0 = lds32(ya + i * 2048 + up * 32), y1 = lds32(ya + i * 2048 + (up ^ 1) * 32);
            uint32_t yv = prmt(y0, y1, sel);
            uint32_t sa = lds32(ma + i * 128), ca = lds32(ma + 1280 + i * 128), ga = lds32(ma + 2560 + i * 128);
            uint32_t hh = badd2(bmul2(a[i], badd2(ca, one2)), sa);
            x[i] = badd2(x[i], bmul2(ga, bmul2(hh, yv)));
        }
        float2 rs = row_ln(x, a);
        if (lane == 0) sts64f(sb + SM_GV + warp * 8, rs);
#pragma unroll
        for (int i = 0; i < 10; i++) {
            uint32_t sbv = lds32(ma + 3840 + i * 128), cb = lds32(ma + 5120 + i * 128);
            a[i] = badd2(bmul2(a[i], badd2(cb, one2)), sbv);
        }
        row_ln(a, b);
        uint32_t* o = reinterpret_cast<uint32_t*>(g_hn + (size_t)rrow * D_) + lane;
#pragma unroll
        for (int i = 0; i < 10; i++) o[32 * i] = b[i];
        if (warp == 0) TSW(34);
        if (warp < 2) {
            bar_sync(8, 512);
            if (tid == 0) { flag_release(FL_R + rb); TS(23); }
        } else bar_arrive(8, 512);
    }
    auto store_x2 = [&]() {
        uint32_t* o2 = reinterpret_cast<uint32_t*>(g_x2 + (size_t)rrow * D_) + lane;
#pragma unroll
        for (int i = 0; i < 10; i++) o2[32 * i] = x[i];
    };

    const int half = wg & 1;
    const int row = 64 * half + 16 * wq + g;
    const size_t tile_w = ((size_t)rb * 80 + 10 * j) * 512 + row * 4 + c;
    if (wg >= 2) {
        {
            float acc[40];
            gemm_loop<80, true, 0, 10, true, 14>(acc, sb, half, [&]() { if (tid == 256) TS(25); store_x2(); fence_async_smem(); bar_arrive(13, 512); });
            if (tid == 256) TS(26);
            uint32_t* dst = reinterpret_cast<uint32_t*>(g_h1) + tile_w;
#pragma unroll
            for (int q = 0; q < 10; q++) {
                dst[q * 512] = pack2(gelu(acc[4 * q]), gelu(acc[4 * q + 1]));
                dst[q * 512 + 32] = pack2(gelu(acc[4 * q + 2]), gelu(acc[4 * q + 3]));
            }
            if (warp == 8) { bar_sync(15, 256); if (lane == 0) { flag_release(FL_B1 + rb); TS(27); } __syncwarp(); }
            else bar_arrive(15, 256);
        }
        mbar_wait(bars + BAR_X * 8, 0);
        bar_sync(11, 512);
        gemm3<112, 20, 9>(sb, rb, 112 * j, half, wq, g, c);
        if (warp == 8) { TSW(35); bar_sync(15, 256); if (lane == 0) { flag_release(FL_GA + rb); TS(36); } __syncwarp(); }
        else bar_arrive(15, 256);
        {
            float acc[40];
            const uint32_t* x1p = reinterpret_cast<const uint32_t*>(g_x1) + tile_w;
#pragma unroll
            for (int q = 0; q < 10; q++) {
                uint32_t u = ldcg32(x1p + q * 512), v = ldcg32(x1p + q * 512 + 32);
                acc[4 * q] = blo(u); acc[4 * q + 1] = bhi(u); acc[4 * q + 2] = blo(v); acc[4 * q + 3] = bhi(v);
            }
            const size_t go = (size_t)(rb * 128 + row) * D_ + 80 * j + (c & 1) * 8 + (c >> 1) * 4;
            const uint32_t xs = sb + SM_Y + row * 160 + (c & 1) * 16 + (c >> 1) * 8;
            uint2 x2[10];
#pragma unroll
            for (int q = 0; q < 5; q++) { x2[2 * q] = lds64(xs + 32 * q); x2[2 * q + 1] = lds64(xs + 1280 + 32 * q); }
            reg_fence<40>(acc);
            bar_sync(10, 512);
            gemm_loop<80, false, 40, 27, false, 0>(acc, sb, half, [&]() { if (tid == 256) TS(42); });
            if (tid == 256) TS(43);
            const uint32_t ga = sb + SM_MOD + 6400 + (80 * j + 2 * c) * 2;
#pragma unroll
            for (int q = 0; q < 5; q++) {
                uint32_t g0 = lds32(ga + q * 32), g1 = lds32(ga + q * 32 + 16);
#pragma unroll
                for (int r = 0; r < 2; r++) {
                    uint32_t t0 = bmul2(g0, pack2(acc[8 * q + 2 * r], acc[8 * q + 2 * r + 1]));
                    uint32_t t1 = bmul2(g1, pack2(acc[8 * q + 4 + 2 * r], acc[8 * q + 4 + 2 * r + 1]));
                    uint32_t rv = __shfl_xor_sync(0xffffffffu, (c & 1) ? t0 : t1, 1);
                    uint2 o;
                    o.x = badd2(x2[2 * q + r].x, (c & 1) ? rv : t0);
                    o.y = badd2(x2[2 * q + r].y, (c & 1) ? t1 : rv);
                    *reinterpret_cast<uint2*>(p.out + go + r * 8 * D_ + 16 * q) = o;
                }
            }
            if (tid == 256) { g_epoch[smid] = ep1; TS(44); }
            if (warp == 8) TSFLUSH();
        }
    } else {
        mbar_wait(bars + BAR_FULL * 8, 0);
        store_x2();
        if (warp == 1 && lane < 16) g_rs[32 * (rho >> 1) + 8 * (rho & 1) + (lane & 7) + 16 * (lane >> 3)] = lds64f(sb + SM_GV + ((lane & 7) * 2 + (lane >> 3)) * 8);
        fence_async_smem();
        if (warp == 0) { bar_sync(13, 512); if (lane == 0) flag_release(FL_X2 + rb); __syncwarp(); }
        else bar_arrive(13, 512);
        {
            float acc[40];
            mbar_wait(bars + BAR_X * 8, 0);
            {
                const float2 r0 = lds64f(sb + SM_RS + row * 8), r1 = lds64f(sb + SM_RS + row * 8 + 64);
                const uint32_t xs = sb + SM_Y + row * 160 + c * 4, ms = sb + SM_MOD + 3840 + (80 * j + 2 * c) * 2;
#pragma unroll
                for (int q = 0; q < 10; q++) {
                    uint32_t u = lds32(xs + 16 * q), v = lds32(xs + 1280 + 16 * q);
                    uint32_t sbv = lds32(ms + 16 * q), cb = badd2(lds32(ms + 1280 + 16 * q), 0x3f803f80u);
                    u = badd2(bmul2(pack2(fmaf(blo(u), r0.x, r0.y), fmaf(bhi(u), r0.x, r0.y)), cb), sbv);
                    v = badd2(bmul2(pack2(fmaf(blo(v), r1.x, r1.y), fmaf(bhi(v), r1.x, r1.y)), cb), sbv);
                    acc[4 * q] = blo(u); acc[4 * q + 1] = bhi(u); acc[4 * q + 2] = blo(v); acc[4 * q + 3] = bhi(v);
                }
            }
            reg_fence<40>(acc);
            if (tid == 0) TS(45);
            bar_sync(14, 512);
            gemm_loop<80, false, 10, 10, false, 0>(acc, sb, half, [&]() { if (tid == 0) TS(29); });
            if (tid == 0) TS(30);
            uint32_t* dst = reinterpret_cast<uint32_t*>(g_x1) + tile_w;
            float s0 = 0.f, q0 = 0.f, s1 = 0.f, q1 = 0.f;
#pragma unroll
            for (int q = 0; q < 10; q++) {
                uint32_t u = pack2(acc[4 * q], acc[4 * q + 1]);
                uint32_t v = pack2(acc[4 * q + 2], acc[4 * q + 3]);
                dst[q * 512] = u;
                dst[q * 512 + 32] = v;
                float a = blo(u), b = bhi(u), e = blo(v), f = bhi(v);
                s0 += a + b; q0 = fmaf(a, a, fmaf(b, b, q0));
                s1 += e + f; q1 = fmaf(e, e, fmaf(f, f, q1));
            }
#pragma unroll
            for (int m = 1; m <= 2; m <<= 1) {
                s0 += __shfl_xor_sync(0xffffffffu, s0, m); q0 += __shfl_xor_sync(0xffffffffu, q0, m);
                s1 += __shfl_xor_sync(0xffffffffu, s1, m); q1 += __shfl_xor_sync(0xffffffffu, q1, m);
            }
            if (c < 2) g_st[(rb * 8 + j) * 128 + row + 8 * c] = c ? make_float2(s1, q1) : make_float2(s0, q0);
            if (warp == 0) { bar_sync(11, 512); if (lane == 0) { flag_release(FL_B2 + rb); TS(31); } __syncwarp(); }
            else bar_arrive(11, 512);
        }
        bar_sync(9, 512);
        gemm3<104, 30, 10>(sb, rb, 896 + 104 * j, half, wq, g, c);
        if (warp == 0) { TSW(38); bar_sync(12, 256); if (lane == 0) { flag_release(FL_GB + rb); TS(39); } __syncwarp(); }
        else bar_arrive(12, 256);
    }
}

typedef CUresult (*EncFn)(CUtensorMap*, CUtensorMapDataType, cuuint32_t, void*, const cuuint64_t*, const cuuint64_t*,
                          const cuuint32_t*, const cuuint32_t*, CUtensorMapInterleave, CUtensorMapSwizzle,
                          CUtensorMapL2promotion, CUtensorMapFloatOOBfill);

void make_map(EncFn enc, CUtensorMap* m, const void* base, uint64_t inner, uint64_t outer, uint32_t bi, uint32_t bo,
              CUtensorMapSwizzle swz = CU_TENSOR_MAP_SWIZZLE_128B) {
    cuuint64_t dims[2] = {inner, outer};
    cuuint64_t st[1] = {inner * 2};
    cuuint32_t box[2] = {bi, bo};
    cuuint32_t es[2] = {1, 1};
    enc(m, CU_TENSOR_MAP_DATA_TYPE_BFLOAT16, 2, const_cast<void*>(base), dims, st, box, es, CU_TENSOR_MAP_INTERLEAVE_NONE,
        swz, CU_TENSOR_MAP_L2_PROMOTION_NONE, CU_TENSOR_MAP_FLOAT_OOB_FILL_NONE);
}

}

extern "C" void kernel_launch(void* const* d_in, const int* in_sizes, int n_in, void* d_out, int out_size) {
    (void)in_sizes; (void)n_in; (void)out_size;
    Params p;
    p.q = (const bf16*)d_in[0]; p.k = (const bf16*)d_in[1]; p.v = (const bf16*)d_in[2];
    p.shift = (const bf16*)d_in[3]; p.ssmk = (const bf16*)d_in[4]; p.ssmD = (const bf16*)d_in[5];
    p.w1 = (const bf16*)d_in[7]; p.w2 = (const bf16*)d_in[8]; p.w3 = (const bf16*)d_in[9]; p.w4 = (const bf16*)d_in[10];
    p.c = (const bf16*)d_in[11]; p.wmod = (const bf16*)d_in[12];
    p.out = (bf16*)d_out;

    void* fn = nullptr;
    cudaDriverEntryPointQueryResult qr;
    cudaGetDriverEntryPoint("cuTensorMapEncodeTiled", &fn, cudaEnableDefault, &qr);
    EncFn enc = (EncFn)fn;
    void* hn = nullptr;
    cudaGetSymbolAddress(&hn, g_hn);
    void* x2 = nullptr;
    cudaGetSymbolAddress(&x2, g_x2);
    Maps maps;
    make_map(enc, &maps.x2, x2, D_, S_, 80, 128, CU_TENSOR_MAP_SWIZZLE_NONE);
    make_map(enc, &maps.hn, hn, D_, S_, 64, 128);
    make_map(enc, &maps.w1a, p.w1, D_, D_, 64, 64);
    make_map(enc, &maps.w1b, p.w1, D_, D_, 16, 64);
    make_map(enc, &maps.w2a, p.w2, D_, D_, 64, 64);
    make_map(enc, &maps.w2b, p.w2, D_, D_, 16, 64);
    make_map(enc, &maps.w3a, p.w3, F_, D_, 64, 64);
    make_map(enc, &maps.w3b, p.w3, F_, D_, 48, 64);
    make_map(enc, &maps.w3c, p.w3, F_, D_, 40, 64);
    make_map(enc, &maps.w4a, p.w4, D_, F_, 64, 64);
    make_map(enc, &maps.w4b, p.w4, D_, F_, 16, 64);
    cudaFuncSetAttribute(fused_kernel, cudaFuncAttributeMaxDynamicSharedMemorySize, SMEM_BYTES);
    fused_kernel<<<132, NTHREADS, SMEM_BYTES>>>(maps, p);
}
```

```cpp
#include <cuda_runtime.h>
#include <cuda_bf16.h>
#include <cuda.h>
#include <stdint.h>
#include <string.h>

#define SEED 2
#define RING_A 6
#define XY_AT 5
#define MMA_STAT 1
#define CH 1
#define STAG 0
#define SSM_WHEN 1
#define PF_EARLY 0

namespace {

typedef __nv_bfloat16 bf16;
typedef __nv_bfloat162 bf162;

constexpr int S_ = 2048, D_ = 640, F_ = 1728;
constexpr int NTHREADS = 640;
constexpr int NA = RING_A, NB = 12 - RING_A;
constexpr int SLOT = 16384;
constexpr int SM_RA = 0, SM_RB = NA * SLOT;

constexpr int SM_RED = 0;
constexpr int RED_STRIDE = 17536;
constexpr int SM_PK = 0;
constexpr int SM_PV = 24576;
constexpr int SM_WM = 5 * RED_STRIDE;
constexpr int SM_K = SM_WM + 40960;
constexpr int K_STRIDE = 8320;
constexpr int SM_U = SM_K + 5 * K_STRIDE;
constexpr int U_PLANE = 2560, U_STRIDE = 5120;
constexpr int SM_Y = 12 * SLOT;
static_assert(SM_U + 5 * U_STRIDE <= SM_Y, "smem map");
constexpr int SM_MOD = SM_Y + 20480;
constexpr int SM_GV = SM_MOD + 7680;
constexpr int SM_CS = SM_GV + 1024;
constexpr int SM_BAR = SM_CS + 1024;
constexpr int SM_PROF = SM_BAR + 512;
constexpr int SM_TOTAL = SM_PROF + 512;
constexpr int SMEM_BYTES = SM_TOTAL + 1024;
static_assert(SMEM_BYTES <= 232448, "smem");

constexpr int BAR_FA = 0, BAR_FB = NA, BAR_EA = 12, BAR_EB = 12 + NA, BAR_K = 24, BAR_U = 29, BAR_Y = 34, BAR_CS = 35, BAR_WM = 36, BAR_M = 37;

__device__ __align__(1024) bf16 g_kvT[D_ * S_];
__device__ __align__(1024) uint32_t g_yv[128 * 5120];
__device__ __align__(1024) bf16 g_mod[6 * D_];
__device__ __align__(1024) bf16 g_hn[S_ * D_];
__device__ __align__(1024) uint4 g_rs[S_ * 2];
__device__ __align__(1024) bf16 g_h1[S_ * D_];
__device__ __align__(1024) bf16 g_x1[S_ * D_];
__device__ __align__(1024) bf16 g_g[S_ * F_];
__device__ __align__(1024) float2 g_st[S_ * 8];
__device__ __align__(1024) float g_cs[F_];
__device__ __align__(1024) unsigned g_flags[112 * 32];
__device__ __align__(1024) unsigned g_epoch[160];
constexpr int FL_P = 0, FL_C = 8, FL_CS = 9, FL_M = 10, FL_R = 16, FL_B1 = 32, FL_B2 = 48, FL_GA = 64, FL_GB = 80;

#define TS(i) do {} while (0)
#define TSW(i) do {} while (0)
#define TSFLUSH() do {} while (0)

struct Params {
    const bf16 *q, *k, *v, *shift, *ssmk, *ssmD, *w1, *w2, *w3, *w4, *c, *wmod;
    bf16* out;
    unsigned ones;
};
#define CHUNK(k) if (ones & (1u << (k)))
struct Maps { CUtensorMap hn, w1a, w1b, w2a, w2b, w3a, w3b, w3c, w4a, w4b, wm, w3s; };

template<int N> struct WgRs;
template<int N> struct WgSs;
template<> struct WgRs<32> { template<int OFF,int HI,int SC> static __device__ __forceinline__ void run(float* d,uint32_t a0,uint32_t a1,uint32_t a2,uint32_t a3,uint32_t blo){
 asm volatile("{.reg .b32 l; .reg .b64 db; add.u32 l,%20,%21; mov.b64 db,{l,%22}; wgmma.mma_async.sync.aligned.m64n32k16.f32.bf16.bf16 {%0,%1,%2,%3,%4,%5,%6,%7,%8,%9,%10,%11,%12,%13,%14,%15},{%16,%17,%18,%19},db,%23,1,1,0;}"
 :"+f"(d[0]),"+f"(d[1]),"+f"(d[2]),"+f"(d[3]),"+f"(d[4]),"+f"(d[5]),"+f"(d[6]),"+f"(d[7]),"+f"(d[8]),"+f"(d[9]),"+f"(d[10]),"+f"(d[11]),"+f"(d[12]),"+f"(d[13]),"+f"(d[14]),"+f"(d[15])
 :"r"(a0),"r"(a1),"r"(a2),"r"(a3),"r"(blo),"n"(OFF),"n"(HI),"n"(SC)); } };
template<> struct WgRs<48> { template<int OFF,int HI,int SC> static __device__ __forceinline__ void run(float* d,uint32_t a0,uint32_t a1,uint32_t a2,uint32_t a3,uint32_t blo){
 asm volatile("{.reg .b32 l; .reg .b64 db; add.u32 l,%28,%29; mov.b64 db,{l,%30}; wgmma.mma_async.sync.aligned.m64n48k16.f32.bf16.bf16 {%0,%1,%2,%3,%4,%5,%6,%7,%8,%9,%10,%11,%12,%13,%14,%15,%16,%17,%18,%19,%20,%21,%22,%23},{%24,%25,%26,%27},db,%31,1,1,0;}"
 :"+f"(d[0]),"+f"(d[1]),"+f"(d[2]),"+f"(d[3]),"+f"(d[4]),"+f"(d[5]),"+f"(d[6]),"+f"(d[7]),"+f"(d[8]),"+f"(d[9]),"+f"(d[10]),"+f"(d[11]),"+f"(d[12]),"+f"(d[13]),"+f"(d[14]),"+f"(d[15]),"+f"(d[16]),"+f"(d[17]),"+f"(d[18]),"+f"(d[19]),"+f"(d[20]),"+f"(d[21]),"+f"(d[22]),"+f"(d[23])
 :"r"(a0),"r"(a1),"r"(a2),"r"(a3),"r"(blo),"n"(OFF),"n"(HI),"n"(SC)); } };
template<> struct WgRs<64> { template<int OFF,int HI,int SC> static __device__ __forceinline__ void run(float* d,uint32_t a0,uint32_t a1,uint32_t a2,uint32_t a3,uint32_t blo){
 asm volatile("{.reg .b32 l; .reg .b64 db; add.u32 l,%36,%37; mov.b64 db,{l,%38}; wgmma.mma_async.sync.aligned.m64n64k16.f32.bf16.bf16 {%0,%1,%2,%3,%4,%5,%6,%7,%8,%9,%10,%11,%12,%13,%14,%15,%16,%17,%18,%19,%20,%21,%22,%23,%24,%25,%26,%27,%28,%29,%30,%31},{%32,%33,%34,%35},db,%39,1,1,0;}"
 :"+f"(d[0]),"+f"(d[1]),"+f"(d[2]),"+f"(d[3]),"+f"(d[4]),"+f"(d[5]),"+f"(d[6]),"+f"(d[7]),"+f"(d[8]),"+f"(d[9]),"+f"(d[10]),"+f"(d[11]),"+f"(d[12]),"+f"(d[13]),"+f"(d[14]),"+f"(d[15]),"+f"(d[16]),"+f"(d[17]),"+f"(d[18]),"+f"(d[19]),"+f"(d[20]),"+f"(d[21]),"+f"(d[22]),"+f"(d[23]),"+f"(d[24]),"+f"(d[25]),"+f"(d[26]),"+f"(d[27]),"+f"(d[28]),"+f"(d[29]),"+f"(d[30]),"+f"(d[31])
 :"r"(a0),"r"(a1),"r"(a2),"r"(a3),"r"(blo),"n"(OFF),"n"(HI),"n"(SC)); } };
template<> struct WgRs<72> { template<int OFF,int HI,int SC> static __device__ __forceinline__ void run(float* d,uint32_t a0,uint32_t a1,uint32_t a2,uint32_t a3,uint32_t blo){
 asm volatile("{.reg .b32 l; .reg .b64 db; add.u32 l,%40,%41; mov.b64 db,{l,%42}; wgmma.mma_async.sync.aligned.m64n72k16.f32.bf16.bf16 {%0,%1,%2,%3,%4,%5,%6,%7,%8,%9,%10,%11,%12,%13,%14,%15,%16,%17,%18,%19,%20,%21,%22,%23,%24,%25,%26,%27,%28,%29,%30,%31,%32,%33,%34,%35},{%36,%37,%38,%39},db,%43,1,1,0;}"
 :"+f"(d[0]),"+f"(d[1]),"+f"(d[2]),"+f"(d[3]),"+f"(d[4]),"+f"(d[5]),"+f"(d[6]),"+f"(d[7]),"+f"(d[8]),"+f"(d[9]),"+f"(d[10]),"+f"(d[11]),"+f"(d[12]),"+f"(d[13]),"+f"(d[14]),"+f"(d[15]),"+f"(d[16]),"+f"(d[17]),"+f"(d[18]),"+f"(d[19]),"+f"(d[20]),"+f"(d[21]),"+f"(d[22]),"+f"(d[23]),"+f"(d[24]),"+f"(d[25]),"+f"(d[26]),"+f"(d[27]),"+f"(d[28]),"+f"(d[29]),"+f"(d[30]),"+f"(d[31]),"+f"(d[32]),"+f"(d[33]),"+f"(d[34]),"+f"(d[35])
 :"r"(a0),"r"(a1),"r"(a2),"r"(a3),"r"(blo),"n"(OFF),"n"(HI),"n"(SC)); } };
template<> struct WgRs<80> { template<int OFF,int HI,int SC> static __device__ __forceinline__ void run(float* d,uint32_t a0,uint32_t a1,uint32_t a2,uint32_t a3,uint32_t blo){
 asm volatile("{.reg .b32 l; .reg .b64 db; add.u32 l,%44,%45; mov.b64 db,{l,%46}; wgmma.mma_async.sync.aligned.m64n80k16.f32.bf16.bf16 {%0,%1,%2,%3,%4,%5,%6,%7,%8,%9,%10,%11,%12,%13,%14,%15,%16,%17,%18,%19,%20,%21,%22,%23,%24,%25,%26,%27,%28,%29,%30,%31,%32,%33,%34,%35,%36,%37,%38,%39},{%40,%41,%42,%43},db,%47,1,1,0;}"
 :"+f"(d[0]),"+f"(d[1]),"+f"(d[2]),"+f"(d[3]),"+f"(d[4]),"+f"(d[5]),"+f"(d[6]),"+f"(d[7]),"+f"(d[8]),"+f"(d[9]),"+f"(d[10]),"+f"(d[11]),"+f"(d[12]),"+f"(d[13]),"+f"(d[14]),"+f"(d[15]),"+f"(d[16]),"+f"(d[17]),"+f"(d[18]),"+f"(d[19]),"+f"(d[20]),"+f"(d[21]),"+f"(d[22]),"+f"(d[23]),"+f"(d[24]),"+f"(d[25]),"+f"(d[26]),"+f"(d[27]),"+f"(d[28]),"+f"(d[29]),"+f"(d[30]),"+f"(d[31]),"+f"(d[32]),"+f"(d[33]),"+f"(d[34]),"+f"(d[35]),"+f"(d[36]),"+f"(d[37]),"+f"(d[38]),"+f"(d[39])
 :"r"(a0),"r"(a1),"r"(a2),"r"(a3),"r"(blo),"n"(OFF),"n"(HI),"n"(SC)); } };
template<> struct WgRs<88> { template<int OFF,int HI,int SC> static __device__ __forceinline__ void run(float* d,uint32_t a0,uint32_t a1,uint32_t a2,uint32_t a3,uint32_t blo){
 asm volatile("{.reg .b32 l; .reg .b64 db; add.u32 l,%48,%49; mov.b64 db,{l,%50}; wgmma.mma_async.sync.aligned.m64n88k16.f32.bf16.bf16 {%0,%1,%2,%3,%4,%5,%6,%7,%8,%9,%10,%11,%12,%13,%14,%15,%16,%17,%18,%19,%20,%21,%22,%23,%24,%25,%26,%27,%28,%29,%30,%31,%32,%33,%34,%35,%36,%37,%38,%39,%40,%41,%42,%43},{%44,%45,%46,%47},db,%51,1,1,0;}"
 :"+f"(d[0]),"+f"(d[1]),"+f"(d[2]),"+f"(d[3]),"+f"(d[4]),"+f"(d[5]),"+f"(d[6]),"+f"(d[7]),"+f"(d[8]),"+f"(d[9]),"+f"(d[10]),"+f"(d[11]),"+f"(d[12]),"+f"(d[13]),"+f"(d[14]),"+f"(d[15]),"+f"(d[16]),"+f"(d[17]),"+f"(d[18]),"+f"(d[19]),"+f"(d[20]),"+f"(d[21]),"+f"(d[22]),"+f"(d[23]),"+f"(d[24]),"+f"(d[25]),"+f"(d[26]),"+f"(d[27]),"+f"(d[28]),"+f"(d[29]),"+f"(d[30]),"+f"(d[31]),"+f"(d[32]),"+f"(d[33]),"+f"(d[34]),"+f"(d[35]),"+f"(d[36]),"+f"(d[37]),"+f"(d[38]),"+f"(d[39]),"+f"(d[40]),"+f"(d[41]),"+f"(d[42]),"+f"(d[43])
 :"r"(a0),"r"(a1),"r"(a2),"r"(a3),"r"(blo),"n"(OFF),"n"(HI),"n"(SC)); } };
template<> struct WgRs<96> { template<int OFF,int HI,int SC> static __device__ __forceinline__ void run(float* d,uint32_t a0,uint32_t a1,uint32_t a2,uint32_t a3,uint32_t blo){
 asm volatile("{.reg .b32 l; .reg .b64 db; add.u32 l,%52,%53; mov.b64 db,{l,%54}; wgmma.mma_async.sync.aligned.m64n96k16.f32.bf16.bf16 {%0,%1,%2,%3,%4,%5,%6,%7,%8,%9,%10,%11,%12,%13,%14,%15,%16,%17,%18,%19,%20,%21,%22,%23,%24,%25,%26,%27,%28,%29,%30,%31,%32,%33,%34,%35,%36,%37,%38,%39,%40,%41,%42,%43,%44,%45,%46,%47},{%48,%49,%50,%51},db,%55,1,1,0;}"
 :"+f"(d[0]),"+f"(d[1]),"+f"(d[2]),"+f"(d[3]),"+f"(d[4]),"+f"(d[5]),"+f"(d[6]),"+f"(d[7]),"+f"(d[8]),"+f"(d[9]),"+f"(d[10]),"+f"(d[11]),"+f"(d[12]),"+f"(d[13]),"+f"(d[14]),"+f"(d[15]),"+f"(d[16]),"+f"(d[17]),"+f"(d[18]),"+f"(d[19]),"+f"(d[20]),"+f"(d[21]),"+f"(d[22]),"+f"(d[23]),"+f"(d[24]),"+f"(d[25]),"+f"(d[26]),"+f"(d[27]),"+f"(d[28]),"+f"(d[29]),"+f"(d[30]),"+f"(d[31]),"+f"(d[32]),"+f"(d[33]),"+f"(d[34]),"+f"(d[35]),"+f"(d[36]),"+f"(d[37]),"+f"(d[38]),"+f"(d[39]),"+f"(d[40]),"+f"(d[41]),"+f"(d[42]),"+f"(d[43]),"+f"(d[44]),"+f"(d[45]),"+f"(d[46]),"+f"(d[47])
 :"r"(a0),"r"(a1),"r"(a2),"r"(a3),"r"(blo),"n"(OFF),"n"(HI),"n"(SC)); } };
template<> struct WgRs<104> { template<int OFF,int HI,int SC> static __device__ __forceinline__ void run(float* d,uint32_t a0,uint32_t a1,uint32_t a2,uint32_t a3,uint32_t blo){
 asm volatile("{.reg .b32 l; .reg .b64 db; add.u32 l,%56,%57; mov.b64 db,{l,%58}; wgmma.mma_async.sync.aligned.m64n104k16.f32.bf16.bf16 {%0,%1,%2,%3,%4,%5,%6,%7,%8,%9,%10,%11,%12,%13,%14,%15,%16,%17,%18,%19,%20,%21,%22,%23,%24,%25,%26,%27,%28,%29,%30,%31,%32,%33,%34,%35,%36,%37,%38,%39,%40,%41,%42,%43,%44,%45,%46,%47,%48,%49,%50,%51},{%52,%53,%54,%55},db,%59,1,1,0;}"
 :"+f"(d[0]),"+f"(d[1]),"+f"(d[2]),"+f"(d[3]),"+f"(d[4]),"+f"(d[5]),"+f"(d[6]),"+f"(d[7]),"+f"(d[8]),"+f"(d[9]),"+f"(d[10]),"+f"(d[11]),"+f"(d[12]),"+f"(d[13]),"+f"(d[14]),"+f"(d[15]),"+f"(d[16]),"+f"(d[17]),"+f"(d[18]),"+f"(d[19]),"+f"(d[20]),"+f"(d[21]),"+f"(d[22]),"+f"(d[23]),"+f"(d[24]),"+f"(d[25]),"+f"(d[26]),"+f"(d[27]),"+f"(d[28]),"+f"(d[29]),"+f"(d[30]),"+f"(d[31]),"+f"(d[32]),"+f"(d[33]),"+f"(d[34]),"+f"(d[35]),"+f"(d[36]),"+f"(d[37]),"+f"(d[38]),"+f"(d[39]),"+f"(d[40]),"+f"(d[41]),"+f"(d[42]),"+f"(d[43]),"+f"(d[44]),"+f"(d[45]),"+f"(d[46]),"+f"(d[47]),"+f"(d[48]),"+f"(d[49]),"+f"(d[50]),"+f"(d[51])
 :"r"(a0),"r"(a1),"r"(a2),"r"(a3),"r"(blo),"n"(OFF),"n"(HI),"n"(SC)); } };
template<> struct WgRs<112> { template<int OFF,int HI,int SC> static __device__ __forceinline__ void run(float* d,uint32_t a0,uint32_t a1,uint32_t a2,uint32_t a3,uint32_t blo){
 asm volatile("{.reg .b32 l; .reg .b64 db; add.u32 l,%60,%61; mov.b64 db,{l,%62}; wgmma.mma_async.sync.aligned.m64n112k16.f32.bf16.bf16 {%0,%1,%2,%3,%4,%5,%6,%7,%8,%9,%10,%11,%12,%13,%14,%15,%16,%17,%18,%19,%20,%21,%22,%23,%24,%25,%26,%27,%28,%29,%30,%31,%32,%33,%34,%35,%36,%37,%38,%39,%40,%41,%42,%43,%44,%45,%46,%47,%48,%49,%50,%51,%52,%53,%54,%55},{%56,%57,%58,%59},db,%63,1,1,0;}"
 :"+f"(d[0]),"+f"(d[1]),"+f"(d[2]),"+f"(d[3]),"+f"(d[4]),"+f"(d[5]),"+f"(d[6]),"+f"(d[7]),"+f"(d[8]),"+f"(d[9]),"+f"(d[10]),"+f"(d[11]),"+f"(d[12]),"+f"(d[13]),"+f"(d[14]),"+f"(d[15]),"+f"(d[16]),"+f"(d[17]),"+f"(d[18]),"+f"(d[19]),"+f"(d[20]),"+f"(d[21]),"+f"(d[22]),"+f"(d[23]),"+f"(d[24]),"+f"(d[25]),"+f"(d[26]),"+f"(d[27]),"+f"(d[28]),"+f"(d[29]),"+f"(d[30]),"+f"(d[31]),"+f"(d[32]),"+f"(d[33]),"+f"(d[34]),"+f"(d[35]),"+f"(d[36]),"+f"(d[37]),"+f"(d[38]),"+f"(d[39]),"+f"(d[40]),"+f"(d[41]),"+f"(d[42]),"+f"(d[43]),"+f"(d[44]),"+f"(d[45]),"+f"(d[46]),"+f"(d[47]),"+f"(d[48]),"+f"(d[49]),"+f"(d[50]),"+f"(d[51]),"+f"(d[52]),"+f"(d[53]),"+f"(d[54]),"+f"(d[55])
 :"r"(a0),"r"(a1),"r"(a2),"r"(a3),"r"(blo),"n"(OFF),"n"(HI),"n"(SC)); } };
template<> struct WgRs<120> { template<int OFF,int HI,int SC> static __device__ __forceinline__ void run(float* d,uint32_t a0,uint32_t a1,uint32_t a2,uint32_t a3,uint32_t blo){
 asm volatile("{.reg .b32 l; .reg .b64 db; add.u32 l,%64,%65; mov.b64 db,{l,%66}; wgmma.mma_async.sync.aligned.m64n120k16.f32.bf16.bf16 {%0,%1,%2,%3,%4,%5,%6,%7,%8,%9,%10,%11,%12,%13,%14,%15,%16,%17,%18,%19,%20,%21,%22,%23,%24,%25,%26,%27,%28,%29,%30,%31,%32,%33,%34,%35,%36,%37,%38,%39,%40,%41,%42,%43,%44,%45,%46,%47,%48,%49,%50,%51,%52,%53,%54,%55,%56,%57,%58,%59},{%60,%61,%62,%63},db,%67,1,1,0;}"
 :"+f"(d[0]),"+f"(d[1]),"+f"(d[2]),"+f"(d[3]),"+f"(d[4]),"+f"(d[5]),"+f"(d[6]),"+f"(d[7]),"+f"(d[8]),"+f"(d[9]),"+f"(d[10]),"+f"(d[11]),"+f"(d[12]),"+f"(d[13]),"+f"(d[14]),"+f"(d[15]),"+f"(d[16]),"+f"(d[17]),"+f"(d[18]),"+f"(d[19]),"+f"(d[20]),"+f"(d[21]),"+f"(d[22]),"+f"(d[23]),"+f"(d[24]),"+f"(d[25]),"+f"(d[26]),"+f"(d[27]),"+f"(d[28]),"+f"(d[29]),"+f"(d[30]),"+f"(d[31]),"+f"(d[32]),"+f"(d[33]),"+f"(d[34]),"+f"(d[35]),"+f"(d[36]),"+f"(d[37]),"+f"(d[38]),"+f"(d[39]),"+f"(d[40]),"+f"(d[41]),"+f"(d[42]),"+f"(d[43]),"+f"(d[44]),"+f"(d[45]),"+f"(d[46]),"+f"(d[47]),"+f"(d[48]),"+f"(d[49]),"+f"(d[50]),"+f"(d[51]),"+f"(d[52]),"+f"(d[53]),"+f"(d[54]),"+f"(d[55]),"+f"(d[56]),"+f"(d[57]),"+f"(d[58]),"+f"(d[59])
 :"r"(a0),"r"(a1),"r"(a2),"r"(a3),"r"(blo),"n"(OFF),"n"(HI),"n"(SC)); } };
template<> struct WgRs<128> { template<int OFF,int HI,int SC> static __device__ __forceinline__ void run(float* d,uint32_t a0,uint32_t a1,uint32_t a2,uint32_t a3,uint32_t blo){
 asm volatile("{.reg .b32 l; .reg .b64 db; add.u32 l,%68,%69; mov.b64 db,{l,%70}; wgmma.mma_async.sync.aligned.m64n128k16.f32.bf16.bf16 {%0,%1,%2,%3,%4,%5,%6,%7,%8,%9,%10,%11,%12,%13,%14,%15,%16,%17,%18,%19,%20,%21,%22,%23,%24,%25,%26,%27,%28,%29,%30,%31,%32,%33,%34,%35,%36,%37,%38,%39,%40,%41,%42,%43,%44,%45,%46,%47,%48,%49,%50,%51,%52,%53,%54,%55,%56,%57,%58,%59,%60,%61,%62,%63},{%64,%65,%66,%67},db,%71,1,1,0;}"
 :"+f"(d[0]),"+f"(d[1]),"+f"(d[2]),"+f"(d[3]),"+f"(d[4]),"+f"(d[5]),"+f"(d[6]),"+f"(d[7]),"+f"(d[8]),"+f"(d[9]),"+f"(d[10]),"+f"(d[11]),"+f"(d[12]),"+f"(d[13]),"+f"(d[14]),"+f"(d[15]),"+f"(d[16]),"+f"(d[17]),"+f"(d[18]),"+f"(d[19]),"+f"(d[20]),"+f"(d[21]),"+f"(d[22]),"+f"(d[23]),"+f"(d[24]),"+f"(d[25]),"+f"(d[26]),"+f"(d[27]),"+f"(d[28]),"+f"(d[29]),"+f"(d[30]),"+f"(d[31]),"+f"(d[32]),"+f"(d[33]),"+f"(d[34]),"+f"(d[35]),"+f"(d[36]),"+f"(d[37]),"+f"(d[38]),"+f"(d[39]),"+f"(d[40]),"+f"(d[41]),"+f"(d[42]),"+f"(d[43]),"+f"(d[44]),"+f"(d[45]),"+f"(d[46]),"+f"(d[47]),"+f"(d[48]),"+f"(d[49]),"+f"(d[50]),"+f"(d[51]),"+f"(d[52]),"+f"(d[53]),"+f"(d[54]),"+f"(d[55]),"+f"(d[56]),"+f"(d[57]),"+f"(d[58]),"+f"(d[59]),"+f"(d[60]),"+f"(d[61]),"+f"(d[62]),"+f"(d[63])
 :"r"(a0),"r"(a1),"r"(a2),"r"(a3),"r"(blo),"n"(OFF),"n"(HI),"n"(SC)); } };
template<> struct WgSs<80> { template<int AOFF,int AHI,int BOFF,int BHI,int SC> static __device__ __forceinline__ void run(float* d,uint32_t alo,uint32_t blo){
 asm volatile("{.reg .b32 l,m; .reg .b64 da,db; add.u32 l,%40,%42; mov.b64 da,{l,%43}; add.u32 m,%41,%44; mov.b64 db,{m,%45}; wgmma.mma_async.sync.aligned.m64n80k16.f32.bf16.bf16 {%0,%1,%2,%3,%4,%5,%6,%7,%8,%9,%10,%11,%12,%13,%14,%15,%16,%17,%18,%19,%20,%21,%22,%23,%24,%25,%26,%27,%28,%29,%30,%31,%32,%33,%34,%35,%36,%37,%38,%39},da,db,%46,1,1,0,1;}"
 :"+f"(d[0]),"+f"(d[1]),"+f"(d[2]),"+f"(d[3]),"+f"(d[4]),"+f"(d[5]),"+f"(d[6]),"+f"(d[7]),"+f"(d[8]),"+f"(d[9]),"+f"(d[10]),"+f"(d[11]),"+f"(d[12]),"+f"(d[13]),"+f"(d[14]),"+f"(d[15]),"+f"(d[16]),"+f"(d[17]),"+f"(d[18]),"+f"(d[19]),"+f"(d[20]),"+f"(d[21]),"+f"(d[22]),"+f"(d[23]),"+f"(d[24]),"+f"(d[25]),"+f"(d[26]),"+f"(d[27]),"+f"(d[28]),"+f"(d[29]),"+f"(d[30]),"+f"(d[31]),"+f"(d[32]),"+f"(d[33]),"+f"(d[34]),"+f"(d[35]),"+f"(d[36]),"+f"(d[37]),"+f"(d[38]),"+f"(d[39])
 :"r"(alo),"r"(blo),"n"(AOFF),"n"(AHI),"n"(BOFF),"n"(BHI),"n"(SC)); } };
template<> struct WgSs<104> { template<int AOFF,int AHI,int BOFF,int BHI,int SC> static __device__ __forceinline__ void run(float* d,uint32_t alo,uint32_t blo){
 asm volatile("{.reg .b32 l,m; .reg .b64 da,db; add.u32 l,%52,%54; mov.b64 da,{l,%55}; add.u32 m,%53,%56; mov.b64 db,{m,%57}; wgmma.mma_async.sync.aligned.m64n104k16.f32.bf16.bf16 {%0,%1,%2,%3,%4,%5,%6,%7,%8,%9,%10,%11,%12,%13,%14,%15,%16,%17,%18,%19,%20,%21,%22,%23,%24,%25,%26,%27,%28,%29,%30,%31,%32,%33,%34,%35,%36,%37,%38,%39,%40,%41,%42,%43,%44,%45,%46,%47,%48,%49,%50,%51},da,db,%58,1,1,0,1;}"
 :"+f"(d[0]),"+f"(d[1]),"+f"(d[2]),"+f"(d[3]),"+f"(d[4]),"+f"(d[5]),"+f"(d[6]),"+f"(d[7]),"+f"(d[8]),"+f"(d[9]),"+f"(d[10]),"+f"(d[11]),"+f"(d[12]),"+f"(d[13]),"+f"(d[14]),"+f"(d[15]),"+f"(d[16]),"+f"(d[17]),"+f"(d[18]),"+f"(d[19]),"+f"(d[20]),"+f"(d[21]),"+f"(d[22]),"+f"(d[23]),"+f"(d[24]),"+f"(d[25]),"+f"(d[26]),"+f"(d[27]),"+f"(d[28]),"+f"(d[29]),"+f"(d[30]),"+f"(d[31]),"+f"(d[32]),"+f"(d[33]),"+f"(d[34]),"+f"(d[35]),"+f"(d[36]),"+f"(d[37]),"+f"(d[38]),"+f"(d[39]),"+f"(d[40]),"+f"(d[41]),"+f"(d[42]),"+f"(d[43]),"+f"(d[44]),"+f"(d[45]),"+f"(d[46]),"+f"(d[47]),"+f"(d[48]),"+f"(d[49]),"+f"(d[50]),"+f"(d[51])
 :"r"(alo),"r"(blo),"n"(AOFF),"n"(AHI),"n"(BOFF),"n"(BHI),"n"(SC)); } };
template<> struct WgSs<112> { template<int AOFF,int AHI,int BOFF,int BHI,int SC> static __device__ __forceinline__ void run(float* d,uint32_t alo,uint32_t blo){
 asm volatile("{.reg .b32 l,m; .reg .b64 da,db; add.u32 l,%56,%58; mov.b64 da,{l,%59}; add.u32 m,%57,%60; mov.b64 db,{m,%61}; wgmma.mma_async.sync.aligned.m64n112k16.f32.bf16.bf16 {%0,%1,%2,%3,%4,%5,%6,%7,%8,%9,%10,%11,%12,%13,%14,%15,%16,%17,%18,%19,%20,%21,%22,%23,%24,%25,%26,%27,%28,%29,%30,%31,%32,%33,%34,%35,%36,%37,%38,%39,%40,%41,%42,%43,%44,%45,%46,%47,%48,%49,%50,%51,%52,%53,%54,%55},da,db,%62,1,1,0,1;}"
 :"+f"(d[0]),"+f"(d[1]),"+f"(d[2]),"+f"(d[3]),"+f"(d[4]),"+f"(d[5]),"+f"(d[6]),"+f"(d[7]),"+f"(d[8]),"+f"(d[9]),"+f"(d[10]),"+f"(d[11]),"+f"(d[12]),"+f"(d[13]),"+f"(d[14]),"+f"(d[15]),"+f"(d[16]),"+f"(d[17]),"+f"(d[18]),"+f"(d[19]),"+f"(d[20]),"+f"(d[21]),"+f"(d[22]),"+f"(d[23]),"+f"(d[24]),"+f"(d[25]),"+f"(d[26]),"+f"(d[27]),"+f"(d[28]),"+f"(d[29]),"+f"(d[30]),"+f"(d[31]),"+f"(d[32]),"+f"(d[33]),"+f"(d[34]),"+f"(d[35]),"+f"(d[36]),"+f"(d[37]),"+f"(d[38]),"+f"(d[39]),"+f"(d[40]),"+f"(d[41]),"+f"(d[42]),"+f"(d[43]),"+f"(d[44]),"+f"(d[45]),"+f"(d[46]),"+f"(d[47]),"+f"(d[48]),"+f"(d[49]),"+f"(d[50]),"+f"(d[51]),"+f"(d[52]),"+f"(d[53]),"+f"(d[54]),"+f"(d[55])
 :"r"(alo),"r"(blo),"n"(AOFF),"n"(AHI),"n"(BOFF),"n"(BHI),"n"(SC)); } };

__device__ __forceinline__ void wg_fence() { asm volatile("wgmma.fence.sync.aligned;" ::: "memory"); }
__device__ __forceinline__ void wg_commit() { asm volatile("wgmma.commit_group.sync.aligned;" ::: "memory"); }
template <int N> __device__ __forceinline__ void wg_wait() { asm volatile("wgmma.wait_group.sync.aligned %0;" ::"n"(N) : "memory"); }
template <int N> __device__ __forceinline__ void reg_fence(float* d) {
#pragma unroll
    for (int i = 0; i < N; i++) asm volatile("" : "+f"(d[i])::"memory");
}
__device__ __forceinline__ uint32_t desc_lo(uint32_t addr, uint32_t lbo) { return ((addr & 0x3FFFF) >> 4) | ((lbo >> 4) << 16); }
#define desc_hi(sbo, sw) (((sbo) >> 4) | ((sw) << 30))
__device__ __forceinline__ uint32_t smem_u32(const void* p) { return (uint32_t)__cvta_generic_to_shared(p); }
__device__ __forceinline__ bool elect() {
    uint32_t p;
    asm volatile("{.reg .pred P; elect.sync _|P, 0xffffffff; selp.u32 %0,1,0,P;}" : "=r"(p));
    return p;
}
__device__ __forceinline__ void mbar_init(uint32_t bar, uint32_t cnt) { asm volatile("mbarrier.init.shared::cta.b64 [%0], %1;" ::"r"(bar), "r"(cnt) : "memory"); }
__device__ __forceinline__ void mbar_expect(uint32_t bar, uint32_t bytes) { asm volatile("mbarrier.arrive.expect_tx.shared::cta.b64 _, [%0], %1;" ::"r"(bar), "r"(bytes) : "memory"); }
__device__ __forceinline__ bool mbar_try(uint32_t bar, uint32_t par) {
    uint32_t ok;
    asm volatile("{.reg .pred p; mbarrier.try_wait.parity.shared::cta.b64 p, [%1], %2; selp.u32 %0,1,0,p;}" : "=r"(ok) : "r"(bar), "r"(par) : "memory");
    return ok;
}
constexpr int SPIN_LIMIT = 1 << 18;
__device__ __forceinline__ void mbar_wait(uint32_t bar, uint32_t par) {
    if (mbar_try(bar, par)) return;
    int n = 0;
    while (!mbar_try(bar, par) && ++n < SPIN_LIMIT) {}
}
__device__ __forceinline__ void bulk_g2s(uint32_t dst, const void* src, uint32_t bytes, uint32_t bar) {
    asm volatile("cp.async.bulk.shared::cluster.global.mbarrier::complete_tx::bytes [%0], [%1], %2, [%3];" ::"r"(dst), "l"(src), "r"(bytes), "r"(bar) : "memory");
}
__device__ __forceinline__ void bulk_s2g(void* dst, uint32_t src, uint32_t bytes) {
    asm volatile("cp.async.bulk.global.shared::cta.bulk_group [%0], [%1], %2;" ::"l"(dst), "r"(src), "r"(bytes) : "memory");
}
__device__ __forceinline__ void bulk_prefetch(const void* src, uint32_t bytes) {
    asm volatile("cp.async.bulk.prefetch.L2.global [%0], %1;" ::"l"(src), "r"(bytes) : "memory");
}
__device__ __forceinline__ void tma2d(uint32_t dst, const CUtensorMap* m, int c0, int c1, uint32_t bar) {
    asm volatile("cp.async.bulk.tensor.2d.shared::cluster.global.mbarrier::complete_tx::bytes [%0], [%1, {%3, %4}], [%2];" ::"r"(dst), "l"(m), "r"(bar), "r"(c0), "r"(c1) : "memory");
}
__device__ __forceinline__ void tma2d_mc(uint32_t dst, const CUtensorMap* m, int c0, int c1, uint32_t bar) {
    asm volatile("cp.async.bulk.tensor.2d.shared::cluster.global.mbarrier::complete_tx::bytes.multicast::cluster [%0], [%1, {%3, %4}], [%2], %5;" ::"r"(dst), "l"(m), "r"(bar), "r"(c0), "r"(c1), "h"((uint16_t)3) : "memory");
}
__device__ __forceinline__ uint32_t mapa(uint32_t a, uint32_t rank) { uint32_t r; asm("mapa.shared::cluster.u32 %0, %1, %2;" : "=r"(r) : "r"(a), "r"(rank)); return r; }
__device__ __forceinline__ void mbar_arrive_cl(uint32_t bar) { asm volatile("mbarrier.arrive.shared::cluster.b64 _, [%0];" ::"r"(bar) : "memory"); }
__device__ __forceinline__ void prefetch_map(const CUtensorMap* m) { asm volatile("prefetch.tensormap [%0];" ::"l"(m) : "memory"); }
__device__ __forceinline__ void cpasync16(uint32_t dst, const void* src, uint32_t srcsz) {
    asm volatile("cp.async.cg.shared.global [%0], [%1], 16, %2;" ::"r"(dst), "l"(src), "r"(srcsz) : "memory");
}
__device__ __forceinline__ void bar_sync(int id, int n) { asm volatile("bar.sync %0, %1;" ::"r"(id), "r"(n) : "memory"); }
__device__ __forceinline__ void bar_arrive(int id, int n) { asm volatile("bar.arrive %0, %1;" ::"r"(id), "r"(n) : "memory"); }
__device__ __forceinline__ void fence_async_smem() { asm volatile("fence.proxy.async.shared::cta;" ::: "memory"); }
__device__ __forceinline__ void fence_async_global() { asm volatile("fence.proxy.async.global;" ::: "memory"); }
__device__ __forceinline__ void flag_release(int f) { asm volatile("red.release.gpu.global.add.u32 [%0], 1;" ::"l"(&g_flags[f * 32]) : "memory"); }
__device__ __forceinline__ void flag_wait(int f, unsigned target) {
    const unsigned* p = &g_flags[f * 32];
    unsigned v; int n = 0;
    do {
        asm volatile("ld.acquire.gpu.global.u32 %0, [%1];" : "=r"(v) : "l"(p) : "memory");
    } while ((int)(v - target) < 0 && ++n < SPIN_LIMIT);
}
__device__ __forceinline__ uint32_t lds32(uint32_t a) { uint32_t v; asm volatile("ld.shared.u32 %0, [%1];" : "=r"(v) : "r"(a)); return v; }
__device__ __forceinline__ float2 lds64f(uint32_t a) { float2 v; asm volatile("ld.shared.v2.f32 {%0,%1}, [%2];" : "=f"(v.x), "=f"(v.y) : "r"(a)); return v; }
__device__ __forceinline__ uint2 lds64(uint32_t a) { uint2 v; asm volatile("ld.shared.v2.u32 {%0,%1}, [%2];" : "=r"(v.x), "=r"(v.y) : "r"(a)); return v; }
__device__ __forceinline__ void sts64f(uint32_t a, float2 v) { asm volatile("st.shared.v2.f32 [%0], {%1,%2};" ::"r"(a), "f"(v.x), "f"(v.y) : "memory"); }
__device__ __forceinline__ void sts32(uint32_t a, uint32_t v) { asm volatile("st.shared.u32 [%0], %1;" ::"r"(a), "r"(v) : "memory"); }
__device__ __forceinline__ void sts64(uint32_t a, uint32_t x, uint32_t y) { asm volatile("st.shared.v2.u32 [%0], {%1,%2};" ::"r"(a), "r"(x), "r"(y) : "memory"); }
__device__ __forceinline__ void sts16(uint32_t a, uint16_t v) { asm volatile("st.shared.u16 [%0], %1;" ::"r"(a), "h"(v) : "memory"); }
__device__ __forceinline__ uint4 lds128(uint32_t a) { uint4 v; asm volatile("ld.shared.v4.u32 {%0,%1,%2,%3}, [%4];" : "=r"(v.x), "=r"(v.y), "=r"(v.z), "=r"(v.w) : "r"(a)); return v; }
__device__ __forceinline__ void sts128(uint32_t a, uint4 v) { asm volatile("st.shared.v4.u32 [%0], {%1,%2,%3,%4};" ::"r"(a), "r"(v.x), "r"(v.y), "r"(v.z), "r"(v.w) : "memory"); }
__device__ __forceinline__ void sts128f(uint32_t a, float x, float y, float z, float w) { asm volatile("st.shared.v4.f32 [%0], {%1,%2,%3,%4};" ::"r"(a), "f"(x), "f"(y), "f"(z), "f"(w) : "memory"); }
__device__ __forceinline__ uint32_t prmt(uint32_t a, uint32_t b, uint32_t s) { uint32_t r; asm("prmt.b32 %0,%1,%2,%3;" : "=r"(r) : "r"(a), "r"(b), "r"(s)); return r; }
__device__ __forceinline__ uint32_t pack2(float lo, float hi) { uint32_t r; asm("cvt.rn.bf16x2.f32 %0, %1, %2;" : "=r"(r) : "f"(hi), "f"(lo)); return r; }
__device__ __forceinline__ float blo(uint32_t v) { return __uint_as_float(v << 16); }
__device__ __forceinline__ float bhi(uint32_t v) { return __uint_as_float(v & 0xffff0000u); }
__device__ __forceinline__ uint32_t bmul2(uint32_t a, uint32_t b) { uint32_t r; asm("mul.rn.bf16x2 %0,%1,%2;" : "=r"(r) : "r"(a), "r"(b)); return r; }
__device__ __forceinline__ uint32_t badd2(uint32_t a, uint32_t b) { uint32_t r; asm("add.rn.bf16x2 %0,%1,%2;" : "=r"(r) : "r"(a), "r"(b)); return r; }
__device__ __forceinline__ float rbf(float x) { return __bfloat162float(__float2bfloat16_rn(x)); }
__device__ __forceinline__ uint32_t ldcg32(const void* p) { uint32_t v; asm volatile("ld.global.cg.u32 %0, [%1];" : "=r"(v) : "l"(p) : "memory"); return v; }
__device__ __forceinline__ uint4 ldcg128(const void* p) { uint4 v; asm volatile("ld.global.cg.v4.u32 {%0,%1,%2,%3}, [%4];" : "=r"(v.x), "=r"(v.y), "=r"(v.z), "=r"(v.w) : "l"(p) : "memory"); return v; }
__device__ __forceinline__ uint2 ldcg64(const void* p) { uint2 v; asm volatile("ld.global.cg.v2.u32 {%0,%1}, [%2];" : "=r"(v.x), "=r"(v.y) : "l"(p) : "memory"); return v; }
__device__ __forceinline__ float gelu_h(float h) {
    float u = h * fmaf(h * h, 8.0f * 0.044715f * 0.7978845608028654f, 2.0f * 0.7978845608028654f);
    float th;
    asm("tanh.approx.f32 %0, %1;" : "=f"(th) : "f"(u));
    return fmaf(h, th, h);
}
__device__ __forceinline__ float gelu(float x) { return gelu_h(0.5f * x); }
__device__ __forceinline__ void ln_params(float sum, float sq, float& inv, float& nb) {
    float mean = sum * (1.0f / D_);
    float var = fmaxf(fmaf(-mean, mean, sq * (1.0f / D_)), 0.0f);
    float sq_;
    asm("sqrt.approx.f32 %0, %1;" : "=f"(sq_) : "f"(rbf(rbf(var) + 1e-5f)));
    inv = __fdividef(1.0f, rbf(sq_));
    nb = -rbf(mean) * inv;
}
__device__ __forceinline__ uint32_t bsub2(uint32_t a, uint32_t b) { uint32_t r; asm("sub.rn.bf16x2 %0,%1,%2;" : "=r"(r) : "r"(a), "r"(b)); return r; }
__device__ __forceinline__ uint32_t bfma2(uint32_t a, uint32_t b, uint32_t c) { uint32_t r; asm("fma.rn.bf16x2 %0,%1,%2,%3;" : "=r"(r) : "r"(a), "r"(b), "r"(c)); return r; }
__device__ __forceinline__ void mma_stat(float* d, uint32_t u, uint32_t v) {
    asm("mma.sync.aligned.m16n8k16.row.col.f32.bf16.bf16.f32 {%0,%1,%2,%3},{%4,%6,%5,%6},{%4,%5},{%0,%1,%2,%3};"
        : "+f"(d[0]), "+f"(d[1]), "+f"(d[2]), "+f"(d[3]) : "r"(u), "r"(v), "r"(0x3f803f80u));
}
__device__ __forceinline__ uint3 row_stats(const uint32_t* v, int lane) {
    float d[4] = {0.f, 0.f, 0.f, 0.f}, e[4] = {0.f, 0.f, 0.f, 0.f};
    mma_stat(d, v[0], v[1]); mma_stat(e, v[2], v[3]); mma_stat(d, v[4], v[5]); mma_stat(e, v[6], v[7]); mma_stat(d, v[8], v[9]);
    float s = (d[2] + d[3]) + (e[2] + e[3]);
    float q = (lane & 4) ? d[1] + e[1] : d[0] + e[0];
    q += __shfl_xor_sync(0xffffffffu, q, 4);  s += __shfl_xor_sync(0xffffffffu, s, 1);
    q += __shfl_xor_sync(0xffffffffu, q, 9);  s += __shfl_xor_sync(0xffffffffu, s, 2);
    q += __shfl_xor_sync(0xffffffffu, q, 18);
    q = __shfl_sync(0xffffffffu, q, 0);
    float mean = s * (1.0f / D_);
    float var = fmaxf(fmaf(-mean, mean, q * (1.0f / D_)), 0.0f), sd;
    asm("sqrt.approx.f32 %0, %1;" : "=f"(sd) : "f"(rbf(rbf(var) + 1e-5f)));
    float inv = __fdividef(1.0f, rbf(sd));
    uint3 r;
    r.x = pack2(mean, mean);
    r.y = pack2(inv, inv);
    inv -= blo(r.y);
    r.z = pack2(inv, inv);
    return r;
}
__device__ __forceinline__ uint32_t ln_apply(uint32_t x, uint32_t m, uint32_t hi, uint32_t lo) {
    uint32_t xc = bsub2(x, m);
    return bfma2(xc, hi, bmul2(xc, lo));
}

struct AFrag { uint32_t m, a, b, c, d; };
__device__ __forceinline__ AFrag ldA(uint32_t a) { AFrag f; f.m = lds32(a - 16); f.a = lds32(a); f.b = lds32(a + 16); f.c = lds32(a + 32); f.d = lds32(a + 48); return f; }
template <int N, int M> __device__ __forceinline__ void conv_pair(float* d, const AFrag& f, uint32_t descU) {
    WgRs<N>::template run<8 * M, desc_hi(128, 0), 1>(d, f.a, f.b, f.m, f.a, descU);
    WgRs<N>::template run<8 * M + 1, desc_hi(128, 0), 1>(d, f.c, f.d, f.b, f.c, descU);
}
template <int Q> __device__ __forceinline__ void conv_put(float* d, uint32_t r0) {
    sts64(r0 + Q * 32, pack2(d[4 * Q + 1], d[4 * Q + 3]), pack2(d[4 * Q], d[4 * Q + 2]));
}
template <int M> __device__ __forceinline__ void conv_head(float* d, AFrag& f, uint32_t kaddr, uint32_t descU, uint32_t r0) {
    wg_fence();
    conv_pair<128 - 8 * M, M>(d, f, descU);
    wg_commit();
    if constexpr (M < 3) {
        wg_wait<0>();
        conv_put<15 - M>(d, r0);
        f = ldA(kaddr + 256 * (M + 1));
    } else {
        if constexpr (M > 3) conv_put<16 - M>(d, r0);
        AFrag n = ldA(kaddr + 256 * (M + 1));
        wg_wait<0>();
        f = n;
    }
    if constexpr (M < 7) conv_head<M + 1>(d, f, kaddr, descU, r0);
}
__device__ __forceinline__ void conv_main(float* d, uint32_t fm, uint32_t fa, uint32_t fb, uint32_t kaddr, uint32_t descU, uint32_t r0, bool handoff) {
    wg_fence();
    WgRs<128>::run<0, desc_hi(128, 0), 0>(d, fa, fb, fm, fa, descU);
    wg_commit();
    wg_wait<0>();
    fa = lds32(kaddr + 32); fb = lds32(kaddr + 48); fm = lds32(kaddr + 16);
    wg_fence();
    WgRs<128>::run<1, desc_hi(128, 0), 1>(d, fa, fb, fm, fa, descU);
    wg_commit();
    wg_wait<0>();
    conv_put<15>(d, r0);
    AFrag f = ldA(kaddr + 256);
    conv_head<1>(d, f, kaddr, descU, r0);
    if (STAG == 1 && handoff) bar_arrive(12, 256);
    AFrag f1 = ldA(kaddr + 256 * 9);
    wg_fence();
    conv_pair<64, 8>(d, f, descU); conv_pair<64, 9>(d, f1, descU);
    wg_commit();
    conv_put<8>(d, r0);
    AFrag f2 = ldA(kaddr + 256 * 10), f3 = ldA(kaddr + 256 * 11);
    wg_wait<0>();
    wg_fence();
    conv_pair<48, 10>(d, f2, descU); conv_pair<48, 11>(d, f3, descU);
    wg_commit();
    conv_put<7>(d, r0); conv_put<6>(d, r0);
    AFrag f4 = ldA(kaddr + 256 * 12), f5 = ldA(kaddr + 256 * 13), f6 = ldA(kaddr + 256 * 14), f7 = ldA(kaddr + 256 * 15);
    wg_wait<0>();
    wg_fence();
    conv_pair<32, 12>(d, f4, descU); conv_pair<32, 13>(d, f5, descU); conv_pair<32, 14>(d, f6, descU); conv_pair<32, 15>(d, f7, descU);
    wg_commit();
    if (STAG == 2 && handoff) bar_arrive(12, 256);
    conv_put<5>(d, r0); conv_put<4>(d, r0);
    wg_wait<0>();
    conv_put<3>(d, r0); conv_put<2>(d, r0); conv_put<1>(d, r0); conv_put<0>(d, r0);
}

template <int N, bool ASWZ, int SC0>
__device__ __forceinline__ void gemm_issue(float* acc, uint32_t bars, int sa, int pa, int sw, int pw, uint32_t da0, uint32_t db0) {
    mbar_wait(bars + (BAR_FB + sw) * 8, pw);
    mbar_wait(bars + (BAR_FA + sa) * 8, pa);
    const uint32_t da = da0 + sa * (SLOT >> 4), db = db0 + sw * (SLOT >> 4);
    constexpr int AK = ASWZ ? 2 : 256, AH = ASWZ ? desc_hi(1024, 1) : desc_hi(128, 0), BH = desc_hi(1024, 1);
    wg_fence();
    WgSs<N>::template run<0, AH, 0, BH, SC0>(acc, da, db);
    WgSs<N>::template run<AK, AH, 128, BH, 1>(acc, da, db);
    WgSs<N>::template run<2 * AK, AH, 256, BH, 1>(acc, da, db);
    WgSs<N>::template run<3 * AK, AH, 384, BH, 1>(acc, da, db);
    wg_commit();
}
template <int N, bool ASWZ, int IA0, int IB0, int NKB, int RELA, int RELB, bool ZERO, int ORDER_BAR, class HOOK>
__device__ __forceinline__ void gemm_loop(float* acc, uint32_t sb, int half, HOOK hook) {
    int sa = IA0 % NA, pa = (IA0 / NA) & 1, sw = IB0 % NB, pw = (IB0 / NB) & 1;
    const uint32_t bars = sb + SM_BAR;
    const int t = threadIdx.x & 127;
    const uint32_t ebar = mapa(bars + (t < 2 ? BAR_EB : BAR_EA) * 8, (t < 2 && lds32(sb + SM_GV + 516)) ? t : blockIdx.x & 1);
    const int nrel = t < 2 ? RELB : t == 2 ? RELA : 0;
    const uint32_t da0 = ASWZ ? desc_lo(sb + SM_RA + half * 8192, 16) : desc_lo(sb + SM_RA + half * 1024, 2048), db0 = desc_lo(sb + SM_RB, 8192);
    gemm_issue<N, ASWZ, ZERO ? 0 : 1>(acc, bars, sa, pa, sw, pw, da0, db0);
    hook();
#pragma unroll 1
    for (int kb = 1; kb < NKB; kb++) {
        const int prev = t < 2 ? sw : sa;
        if (++sa == NA) { sa = 0; pa ^= 1; }
        if (++sw == NB) { sw = 0; pw ^= 1; }
        gemm_issue<N, ASWZ, 1>(acc, bars, sa, pa, sw, pw, da0, db0);
        wg_wait<1>();
        if (kb <= nrel) mbar_arrive_cl(ebar + prev * 8);
    }
    if (ORDER_BAR) bar_arrive(ORDER_BAR, 512);
    wg_wait<0>();
    if (nrel == NKB) mbar_arrive_cl(ebar + (t < 2 ? sw : sa) * 8);
    reg_fence<N / 2>(acc);
}

template <int N, int IA0, int IB0, int RELA, int WAIT_BAR, int ORDER_BAR>
__device__ __forceinline__ void gemm3(uint32_t sb, int rb, int col0, int half, int wq, int g, int c, unsigned ones) {
    float acc[N / 2];
    const int row = 64 * half + 16 * wq + g;
    uint2 s0, s1, s2, s3;
    float2 cr[N / 8];
    mbar_wait(sb + SM_BAR + BAR_CS * 8, 0);
#pragma unroll
    for (int q = 0; q < N / 8; q++) cr[q] = lds64f(sb + SM_CS + (N == 112 ? 0 : 448) + 8 * c + 32 * q);
    bar_sync(WAIT_BAR, 512);
    gemm_loop<N, false, IA0, IB0, 10, RELA, 10, true, ORDER_BAR>(acc, sb, half, [&]() {
        if ((threadIdx.x & 255) == 0) TS(N == 112 ? 46 : 48);
        const float2* sp = &g_st[(rb * 8 + 2 * c) * 128 + row];
        s0 = ldcg64(sp); s1 = ldcg64(sp + 128); s2 = ldcg64(sp + 8); s3 = ldcg64(sp + 136);
    });
    if ((threadIdx.x & 255) == 0) TS(N == 112 ? 47 : 49);
    float a0 = __uint_as_float(s0.x) + __uint_as_float(s1.x), b0 = __uint_as_float(s0.y) + __uint_as_float(s1.y);
    float a1 = __uint_as_float(s2.x) + __uint_as_float(s3.x), b1 = __uint_as_float(s2.y) + __uint_as_float(s3.y);
#pragma unroll
    for (int m = 1; m <= 2; m <<= 1) {
        a0 += __shfl_xor_sync(0xffffffffu, a0, m); b0 += __shfl_xor_sync(0xffffffffu, b0, m);
        a1 += __shfl_xor_sync(0xffffffffu, a1, m); b1 += __shfl_xor_sync(0xffffffffu, b1, m);
    }
    float inv0, nb0, inv1, nb1;
    ln_params(a0, b0, inv0, nb0);
    ln_params(a1, b1, inv1, nb1);
    inv0 *= 0.5f; nb0 *= 0.5f; inv1 *= 0.5f; nb1 *= 0.5f;
    uint32_t* dst = reinterpret_cast<uint32_t*>(g_g) + ((size_t)rb * 216 + (col0 >> 3)) * 512 + row * 4 + c;
#pragma unroll
    for (int k = 0; k < N / 8; k += CH) CHUNK(k) {
#pragma unroll
        for (int q = k; q < k + CH && q < N / 8; q++) {
            dst[q * 512] = pack2(gelu_h(fmaf(acc[4 * q], inv0, nb0 * cr[q].x)), gelu_h(fmaf(acc[4 * q + 1], inv0, nb0 * cr[q].y)));
            dst[q * 512 + 32] = pack2(gelu_h(fmaf(acc[4 * q + 2], inv1, nb1 * cr[q].x)), gelu_h(fmaf(acc[4 * q + 3], inv1, nb1 * cr[q].y)));
        }
    }
}

template <int NS, int BASE, int BF, int BE> struct Ring {
    uint32_t sb, st, ph;
    __device__ __forceinline__ uint32_t acquire(uint32_t bytes) {
        mbar_wait(sb + SM_BAR + BE * 8 + st * 8, ph);
        uint32_t fb = sb + SM_BAR + BF * 8 + st * 8;
        mbar_expect(fb, bytes);
        return fb;
    }
    __device__ __forceinline__ uint32_t slot() { return sb + BASE + st * SLOT; }
    __device__ __forceinline__ void next() { if (++st == NS) { st = 0; ph ^= 1; } }
    __device__ __forceinline__ void run2d(const CUtensorMap* m, int c1) {
#pragma unroll 1
        for (int c0 = 0; c0 < D_; c0 += 64) {
            uint32_t fb = acquire(SLOT);
            tma2d(slot(), m, c0, c1, fb);
            next();
        }
    }
    __device__ __forceinline__ void runw(bool paired, int rk, const CUtensorMap* ma, const CUtensorMap* mb, int c0, int c1, int n, uint32_t bytes) {
        if (paired) {
            const CUtensorMap* m = rk ? mb : ma;
            c0 += 64 * rk;
#pragma unroll 1
            for (; n > 0; n--, c1 += 64) {
                uint32_t fb = acquire(bytes);
                tma2d_mc(slot() + 8192 * rk, m, c0, c1, fb);
                next();
            }
        } else {
#pragma unroll 1
            for (; n > 0; n--, c1 += 64) {
                uint32_t fb = acquire(bytes);
                tma2d(slot(), ma, c0, c1, fb);
                tma2d(slot() + 8192, mb, c0 + 64, c1, fb);
                next();
            }
        }
    }
    __device__ __forceinline__ void run1d(const char* src, int n) {
#pragma unroll 1
        for (; n > 0; n--) {
            uint32_t fb = acquire(SLOT);
            bulk_g2s(slot(), src, SLOT, fb);
            src += SLOT;
            next();
        }
    }
};

__global__ void __cluster_dims__(2, 1, 1) __launch_bounds__(NTHREADS, 1) fused_kernel(const __grid_constant__ Maps maps, const Params p) {
    extern __shared__ __align__(1024) unsigned char smem_raw[];
    const uint32_t sb = (smem_u32(smem_raw) + 1023u) & ~1023u;
#pragma unroll
    for (int i = 0; i < SEED; i++) asm volatile("{.reg .b32 t; mov.u32 t, %laneid;}");
    const uint32_t bars = sb + SM_BAR;
    const int tid = threadIdx.x, lane = tid & 31;
    const int warp = __shfl_sync(0xffffffffu, tid >> 5, 0);
    const int wg = warp >> 2, wq = warp & 3;
    unsigned smid;
    asm volatile("mov.u32 %0, %%smid;" : "=r"(smid));

    int gpc, idx;
    if (smid < 64) { gpc = (smid & 15) >> 1; idx = (smid >> 4) * 2 + (smid & 1); }
    else if (smid < 120) { int t = smid - 64; gpc = 1 + (t % 14) / 2; idx = 8 + (t / 14) * 2 + (smid & 1); }
    else if (smid < 124) { gpc = 0; idx = 16 + (smid - 120); }
    else { gpc = 0; idx = 8 + (smid - 124); }
    unsigned ep1 = 0;
    if (wg == 4 || idx >= 16) ep1 = *(volatile unsigned*)&g_epoch[smid] + 1;

    if (idx >= 16) {
        const int sp = idx - 16;
        if (tid == 32) { sts32(sb + SM_GV + 512, smid); asm volatile("fence.release.sync_restrict::shared::cta.cluster;" ::: "memory"); }
        asm volatile("barrier.cluster.arrive.relaxed.aligned;" ::: "memory");
        asm volatile("barrier.cluster.wait.aligned;" ::: "memory");
        if (tid == 0) {
            for (int i = 0; i < 4; i++) mbar_init(bars + i * 8, 1);
            asm volatile("fence.mbarrier_init.release.cluster;" ::: "memory");
        }
        if (warp == 0) { if (lane < 8) flag_wait(FL_P + lane, ep1 * 16); __syncwarp(); }
        __syncthreads();
        const int cq = tid % 54, rg = tid / 54;
        float a[8];
#pragma unroll
        for (int i = 0; i < 8; i++) a[i] = 0.f;
#pragma unroll 1
        for (int it = -4; it < 10; it++) {
            const uint32_t st = sb + (it & 3) * 55296, fb = bars + (it & 3) * 8;
            if (it >= 0) {
                mbar_wait(fb, (it >> 2) & 1);
                if (tid < 432) {
#pragma unroll
                    for (int i = 0; i < 8; i++) {
                        uint4 w = lds128(st + (cq >= 27 ? 27648 - 432 : 0) + (rg * 8 + i) * 432 + cq * 16);
                        a[0] += blo(w.x); a[1] += bhi(w.x); a[2] += blo(w.y); a[3] += bhi(w.y);
                        a[4] += blo(w.z); a[5] += bhi(w.z); a[6] += blo(w.w); a[7] += bhi(w.w);
                    }
                }
                __syncthreads();
            }
            if (it < 6 && warp == 19 && elect()) {
                mbar_expect(fb, 55296);
                tma2d(st, &maps.w3s, sp * 432, (it + 4) * 64, fb);
                tma2d(st + 27648, &maps.w3s, sp * 432 + 216, (it + 4) * 64, fb);
            }
        }
        if (tid < 432) {
            sts128f(sb + rg * 1728 + cq * 32, a[0], a[1], a[2], a[3]);
            sts128f(sb + rg * 1728 + cq * 32 + 16, a[4], a[5], a[6], a[7]);
        }
        __syncthreads();
        if (tid < 432) {
            float s = 0.f;
#pragma unroll
            for (int i = 0; i < 8; i++) s += __uint_as_float(lds32(sb + i * 1728 + tid * 4));
            g_cs[sp * 432 + tid] = s;
        }
        __syncthreads();
        if (tid == 0) { flag_release(FL_CS); g_epoch[smid] = ep1; TS(0); }
        if (warp == 0) TSFLUSH();
        return;
    }

    const int cta = gpc * 16 + idx;
    const int rb = 2 * gpc + (idx & 1), j = idx >> 1;
    const int g = lane >> 2, c = lane & 3;

    {
        const int r0 = 128 * idx;
        const char* kb = (const char*)(p.k + (size_t)r0 * D_ + 80 * gpc);
        const char* vb = (const char*)(p.v + (size_t)r0 * D_ + 80 * gpc);
#pragma unroll
        for (int i = 0; i < 2; i++) {
            int ch = tid + i * 640, row = ch / 10, cc = ch % 10;
            uint32_t so = (row >> 4) * 2576 + (row & 15) * 160 + cc * 16;
            cpasync16(sb + SM_PK + 2576 + so, kb + row * 1280 + cc * 16, 16);
            cpasync16(sb + SM_PV + so, vb + row * 1280 + cc * 16, 16);
        }
        if (tid < 30) {
            int row = tid / 10, cc = tid % 10;
            cpasync16(sb + SM_PK + (13 + row) * 160 + cc * 16, idx ? kb + (row - 3) * 1280 + cc * 16 : kb, idx ? 16 : 0);
        }
        asm volatile("cp.async.commit_group;" ::: "memory");
        const int h = warp / 10, pr = (warp % 10) * 4 + (lane >> 3), blk = lane & 7;
        const int ch = 80 * gpc + 2 * pr;
        const uint4 sw = __ldg(reinterpret_cast<const uint4*>(p.shift + ch * 4));
        if (tid == 0) {
            for (int i = 0; i < 12; i++) { mbar_init(bars + i * 8, 1); mbar_init(bars + (12 + i) * 8, i < NA ? 2 : 4); }
            for (int i = BAR_K; i <= BAR_M; i++) mbar_init(bars + i * 8, 1);
            asm volatile("fence.mbarrier_init.release.cluster;" ::: "memory");
        }
        if (tid == 96) { sts32(sb + SM_GV + 512, smid); asm volatile("fence.release.sync_restrict::shared::cta.cluster;" ::: "memory"); }
        if (warp == 1 && lane < 11) prefetch_map(&maps.hn + lane);
        if (warp == 2 && lane < 20)
            sts128(sb + SM_K + (lane >> 2) * K_STRIDE + ((lane >> 1) & 1) * 4160 + (lane & 1) * 16, make_uint4(0, 0, 0, 0));
        if (warp >= 10) {
            sts128(sb + SM_U + (warp - 10) * U_PLANE + 2048 + lane * 16, make_uint4(0, 0, 0, 0));
            fence_async_smem();
        }
        asm volatile("barrier.cluster.arrive.relaxed.aligned;" ::: "memory");
        asm volatile("cp.async.wait_group 0;" ::: "memory");
        asm volatile("barrier.cluster.wait.aligned;" ::: "memory");
        if (tid == 32) {
            uint32_t peer;
            asm volatile("ld.shared::cluster.u32 %0, [%1];" : "=r"(peer) : "r"(mapa(sb + SM_GV + 512, (blockIdx.x & 1) ^ 1)) : "memory");
            sts32(sb + SM_GV + 516, peer == (smid ^ 1));
        }
        __syncthreads();
        if (warp == 0) TSW(1);
        if (warp == 4 && elect()) {
#pragma unroll
            for (int i = 0; i < 5; i++) {
                mbar_expect(bars + (BAR_K + i) * 8, 4096);
                bulk_g2s(sb + SM_K + i * K_STRIDE + 32, p.ssmk + (size_t)(cta * 5 + i) * S_, 4096, bars + (BAR_K + i) * 8);
            }
        }
        const uint32_t w0 = prmt(sw.x, sw.z, 0x5410), w1 = prmt(sw.x, sw.z, 0x7632), w2 = prmt(sw.y, sw.w, 0x5410), w3 = prmt(sw.y, sw.w, 0x7632);
        const uint32_t ka = sb + SM_PK + 2576 + blk * 2576 + h * 1280 + pr * 4;
        const uint32_t va = sb + SM_PV + blk * 2576 + h * 1280 + pr * 4;
        uint32_t kk[11], kv[8];
#pragma unroll
        for (int i = 0; i < 11; i++) kk[i] = lds32(ka + (i - 3) * 160 - ((i < 3 && h == 0) ? 16 : 0));
#pragma unroll
        for (int i = 0; i < 8; i++) {
            uint32_t t = badd2(badd2(badd2(bmul2(kk[i], w3), bmul2(kk[i + 1], w2)), bmul2(kk[i + 2], w1)), bmul2(kk[i + 3], w0));
            kv[i] = bmul2(t, lds32(va + i * 160));
        }
        uint4 o0, o1;
        o0.x = prmt(kv[1], kv[0], 0x5410); o0.y = prmt(kv[3], kv[2], 0x5410); o0.z = prmt(kv[5], kv[4], 0x5410); o0.w = prmt(kv[7], kv[6], 0x5410);
        o1.x = prmt(kv[1], kv[0], 0x7632); o1.y = prmt(kv[3], kv[2], 0x7632); o1.z = prmt(kv[5], kv[4], 0x7632); o1.w = prmt(kv[7], kv[6], 0x7632);
        uint4* dst = reinterpret_cast<uint4*>(g_kvT) + ch * 256 + h * 128 + (127 - (8 * idx + blk));
        dst[0] = o0;
        dst[256] = o1;
    }

    const int rho = 8 * rb + j;

    if (wg == 4) {
        asm volatile("setmaxnreg.dec.sync.aligned.u32 64;");
        const bool paired = lds32(sb + SM_GV + 516);
        if (wq == 0) {
            bar_sync(13, 640);
            if (lane == 0) flag_release(FL_P + gpc);
            __syncwarp();
            TSW(2);
            flag_wait(FL_P + gpc, ep1 * 16);
            fence_async_global();
            TSW(3);
            if (elect()) {
#pragma unroll
                for (int i = 0; i < 5; i++) {
                    const char* us = (const char*)g_kvT + (size_t)(cta * 5 + i) * 4096;
                    mbar_expect(bars + (BAR_U + i) * 8, 4096);
                    bulk_g2s(sb + SM_U + i * U_STRIDE, us, 2048, bars + (BAR_U + i) * 8);
                    bulk_g2s(sb + SM_U + i * U_STRIDE + U_PLANE, us + 2048, 2048, bars + (BAR_U + i) * 8);
                }
            }
            __syncwarp();
            if (elect()) {
                if (cta < 120) {
                    mbar_expect(bars + BAR_WM * 8, 40960);
#pragma unroll
                    for (int i = 0; i < 5; i++) tma2d(sb + SM_WM + i * 8192, &maps.wm, cta * 32, i * 128, bars + BAR_WM * 8);
                }
                bulk_prefetch((const char*)p.q + cta * 20480, 20480);
                bulk_prefetch((const char*)p.w1 + cta * 6400, 6400);
                bulk_prefetch((const char*)p.w2 + cta * 6400, 6400);
            }
            __syncwarp();
        } else {
            bar_arrive(13, 640);
        }
        if (cta < 120) {
            const int t = tid - 512, rg = t >> 2;
            float sv[20], a[8];
#pragma unroll
            for (int i = 0; i < 20; i++) {
                float cv = __bfloat162float(p.c[rg + 32 * i]);
                sv[i] = rbf(__fdividef(cv, 1.0f + __expf(-cv)));
            }
#pragma unroll
            for (int i = 0; i < 8; i++) a[i] = 0.f;
            mbar_wait(bars + BAR_WM * 8, 0);
            if (wq == 3) TSW(50);
#pragma unroll
            for (int i = 0; i < 20; i++) {
                uint4 w = lds128(sb + SM_WM + t * 16 + i * 2048);
                a[0] = fmaf(sv[i], blo(w.x), a[0]); a[1] = fmaf(sv[i], bhi(w.x), a[1]);
                a[2] = fmaf(sv[i], blo(w.y), a[2]); a[3] = fmaf(sv[i], bhi(w.y), a[3]);
                a[4] = fmaf(sv[i], blo(w.z), a[4]); a[5] = fmaf(sv[i], bhi(w.z), a[5]);
                a[6] = fmaf(sv[i], blo(w.w), a[6]); a[7] = fmaf(sv[i], bhi(w.w), a[7]);
            }
#pragma unroll
            for (int m = 4; m <= 16; m <<= 1)
#pragma unroll
                for (int i = 0; i < 8; i++) a[i] += __shfl_xor_sync(0xffffffffu, a[i], m);
            if (lane < 4) {
                uint32_t a0 = sb + SM_GV + wq * 128 + lane * 32;
                sts128f(a0, a[0], a[1], a[2], a[3]);
                sts128f(a0 + 16, a[4], a[5], a[6], a[7]);
            }
        }
        bar_sync(5, 128);
        asm volatile("setmaxnreg.dec.sync.aligned.u32 32;");
        if (cta < 120) {
            if (wq == 2) {
                float s = 0.f;
#pragma unroll
                for (int i = 0; i < 4; i++) s += __uint_as_float(lds32(sb + SM_GV + i * 128 + lane * 4));
                g_mod[cta * 32 + lane] = __float2bfloat16_rn(s);
                __syncwarp();
                if (lane == 0) flag_release(FL_M);
                TSW(4);
            }
        }
        if (wq == 2) {
            bar_arrive(7, 640);
            flag_wait(FL_M, ep1 * 120);
            fence_async_global();
            if (elect()) {
                mbar_expect(bars + BAR_M * 8, 7680);
                bulk_g2s(sb + SM_MOD, g_mod, 7680, bars + BAR_M * 8);
            }
            __syncwarp();
            TSW(51);
            bar_sync(8, 544);  if (lane == 0) { flag_release(FL_R + rb); TS(23); }  __syncwarp();
            bar_sync(15, 288); if (lane == 0) { flag_release(FL_B1 + rb); TS(27); } __syncwarp();
            bar_sync(12, 288); if (lane == 0) { flag_release(FL_B2 + rb); TS(31); } __syncwarp();
            bar_sync(6, 288);  if (lane == 0) { flag_release(FL_GA + rb); TS(36); } __syncwarp();
            bar_sync(5, 288);  if (lane == 0) { flag_release(FL_GB + rb); TS(39); g_epoch[smid] = ep1; }
            return;
        }
        bar_sync(7, 640);
        if (wq == 1 && lane < 4 * NB) mbar_arrive_cl(mapa(bars + (BAR_EB + (lane >> 2)) * 8, paired ? lane & 1 : blockIdx.x & 1));
        if (elect()) {
            if (wq == 3) {
                flag_release(FL_C);
                TS(20);
                flag_wait(FL_C, ep1 * 128);
                fence_async_global();
                TS(21);
                mbar_expect(bars + BAR_Y * 8, 20480);
                bulk_g2s(sb + SM_Y, g_yv + rho * 5120, 20480, bars + BAR_Y * 8);
                mbar_wait(bars + BAR_FA * 8, 0);
                bulk_prefetch((const char*)p.w4 + cta * 17280, 17280);
                flag_wait(FL_CS, ep1 * 4);
                fence_async_global();
                mbar_expect(bars + BAR_CS * 8, 864);
                bulk_g2s(sb + SM_CS, g_cs + 112 * j, 448, bars + BAR_CS * 8);
                bulk_g2s(sb + SM_CS + 448, g_cs + 896 + 104 * j, 416, bars + BAR_CS * 8);
            } else if (wq == 1) {
                Ring<NB, SM_RB, BAR_FB, BAR_EB> r{sb, 0, 0};
#pragma unroll 1
                for (int ph = 0; ph < 6; ph++) {
                    const CUtensorMap* ma = ph == 0 ? &maps.w1a : ph == 1 ? &maps.w2a : ph == 5 ? &maps.w4a : &maps.w3a;
                    const bool b3b = ph == 3 || ph == 4;
                    r.runw(paired, idx & 1, ma, ma + (b3b ? 2 : 1), ph == 2 ? 112 * j : b3b ? 896 + 104 * j : 80 * j, ph == 3 ? (10 - NA) * 64 : 0,
                           ph == 5 ? 27 : ph == 3 ? NA : ph == 4 ? 10 - NA : 10, ph == 2 ? 14336 : b3b ? 13312 : 10240);
                }
            } else {
                Ring<NA, SM_RA, BAR_FA, BAR_EA> r{sb, 0, 1};
                const int grp = j >> 1;
                const int delta = (grp & 1 ? 1 : -1) * (1 + (grp >> 1));
                const int nb = min(max(rb + (delta > 0 ? 1 : -1), 0), 15);
                flag_wait(FL_R + nb, ep1 * 8);
                flag_wait(FL_R + rb, ep1 * 8);
                fence_async_global(); TS(24);
                r.run2d(&maps.hn, rb * 128 + delta);
                flag_wait(FL_B1 + rb, ep1 * 8); fence_async_global(); TS(28);
                r.run1d((const char*)g_h1 + (size_t)rb * 163840, 10);
                flag_wait(FL_B2 + rb, ep1 * 8); fence_async_global(); TS(32);
                r.run1d((const char*)g_x1 + (size_t)rb * 163840, 10);
                r.run1d((const char*)g_x1 + (size_t)rb * 163840, 10 - NA);
                flag_wait(FL_GA + rb, ep1 * 8); fence_async_global(); TS(40);
                r.run1d((const char*)g_g + (size_t)rb * 442368, 14);
                flag_wait(FL_GB + rb, ep1 * 8); fence_async_global(); TS(41);
                r.run1d((const char*)g_g + (size_t)rb * 442368 + 14 * 16384, 13);
            }
        }
        return;
    }
    bar_arrive(13, 640);
    asm volatile("setmaxnreg.inc.sync.aligned.u32 104;");
    const int rrow = 16 * rho + (warp >> 1) + 8 * (warp & 1);

#pragma unroll 1
    for (int cc = wg; cc < 5; cc += 3) {
        if (cc == 3 && wg == 0) break;
        mbar_wait(bars + (BAR_K + cc) * 8, 0);
        uint32_t a = sb + SM_K + cc * K_STRIDE + 32 + (tid & 127) * 32;
        uint32_t pw = lds32(a - 4);
        uint4 x = lds128(a), y = lds128(a + 16), o;
        if ((tid & 127) == 0) {
            uint16_t k0 = __bfloat16_as_ushort(__float2bfloat16_rn(blo(x.x) + __bfloat162float(p.ssmD[cta * 5 + cc])));
            x.x = (x.x & 0xffff0000u) | k0;
            sts16(a, k0);
        }
        o.x = prmt(pw, x.x, 0x5432); o.y = prmt(x.x, x.y, 0x5432); o.z = prmt(x.y, x.z, 0x5432); o.w = prmt(x.z, x.w, 0x5432);
        sts128(a + 4160, o);
        o.x = prmt(x.w, y.x, 0x5432); o.y = prmt(y.x, y.y, 0x5432); o.z = prmt(y.y, y.z, 0x5432); o.w = prmt(y.z, y.w, 0x5432);
        sts128(a + 4176, o);
    }
    bar_sync(1 + wg, 128);
#pragma unroll 1
    for (int cc = wg; cc < 5; cc += 3) {
        if (cc == 3 && wg == 0) break;
        const uint32_t sK = sb + SM_K + cc * K_STRIDE, sU = sb + SM_U + cc * U_STRIDE;
        const uint32_t kaddr = sK + ((g & 1) ? 32 : 4192) + 4 * ((g >> 1) - c) + 64 * wq;
        const uint32_t fm = lds32(kaddr - 16), fa = lds32(kaddr), fb = lds32(kaddr + 16);
        if (STAG && cc == 3) bar_sync(12, 256);
        mbar_wait(bars + (BAR_U + cc) * 8, 0);
        if (wq == 0) TSW(5 + cc);
        float d[64];
        conv_main(d, fm, fa, fb, kaddr, desc_lo(sU, U_PLANE), sb + SM_RED + cc * RED_STRIDE + 32 + wq * 4352 + g * 544 + (c - wq) * 8, cc == 1);
        if (wq == 0) TSW(10 + cc);
        if (cc == 1) bar_arrive(6, 256);
    }
#pragma unroll 1
    for (int cc = wg == 1 ? 4 : wg;; cc++) {
        if (cc == 1) bar_sync(6, 256); else bar_sync(1 + wg, 128);
        const int ch = cta * 5 + cc;
        uint32_t* dst = g_yv + ch * 8 + ((g + (ch >> 2)) & 7);
        const uint32_t red = sb + SM_RED + cc * RED_STRIDE + 32 + g * 544 + (16 * wq + c) * 8;
        uint2 v[16];
#pragma unroll
        for (int q = 0; q < 4; q++)
#pragma unroll
            for (int w = 0; w < 4; w++) v[4 * q + w] = lds64(red + q * 32 + w * 4352);
#pragma unroll
        for (int w = 1; w < 4; w++)
            if (wq == 3 && c > 3 - w) v[12 + w] = make_uint2(0, 0);
#pragma unroll
        for (int q = 0; q < 4; q++) {
            const uint2 *u = v + 4 * q;
            uint32_t* o = dst + (size_t)(126 - 2 * (16 * wq + 4 * q + c)) * 5120;
            o[0] = pack2((blo(u[0].x) + blo(u[1].x)) + (blo(u[2].x) + blo(u[3].x)), (bhi(u[0].x) + bhi(u[1].x)) + (bhi(u[2].x) + bhi(u[3].x)));
            o[5120] = pack2((blo(u[0].y) + blo(u[1].y)) + (blo(u[2].y) + blo(u[3].y)), (bhi(u[0].y) + bhi(u[1].y)) + (bhi(u[2].y) + bhi(u[3].y)));
        }
        if (wq == 0) TSW(15 + cc);
        if (cc != 0) break;
    }
    fence_async_smem();
    bar_arrive(7, 640);
    asm volatile("setmaxnreg.inc.sync.aligned.u32 112;");

    const uint32_t one2 = 0x3f803f80u;
    const unsigned ones = p.ones;
    {
        uint32_t x[10], a[10], cb[10], sbv[10];
        const uint32_t* xr = reinterpret_cast<const uint32_t*>(p.q + (size_t)rrow * D_) + lane;
#pragma unroll
        for (int i = 0; i < 10; i++) x[i] = __ldg(xr + 32 * i);
        const uint3 s1 = row_stats(x, lane);
        const int up = lane >> 4, gg = warp >> 1, e = warp & 1;
        const uint32_t ya = sb + SM_Y + lane * 64 + ((gg + (lane >> 1)) & 7) * 4;
        const uint32_t sel = (up ? 0x1054u : 0x5410u) + (e ? 0x2222u : 0u);
        const uint32_t ma = sb + SM_MOD + lane * 4;
        mbar_wait(bars + BAR_M * 8, 0);
#pragma unroll
        for (int i = 0; i < 10; i++) {
            uint32_t h = bfma2(ln_apply(x[i], s1.x, s1.y, s1.z), badd2(lds32(ma + 1280 + i * 128), one2), lds32(ma + i * 128));
            a[i] = bmul2(h, lds32(ma + 2560 + i * 128));
            sbv[i] = lds32(ma + 3840 + i * 128);
            cb[i] = badd2(lds32(ma + 5120 + i * 128), one2);
        }
        if (warp == 4) TSW(52);
        mbar_wait(bars + BAR_Y * 8, 0);
        if (warp == 0) TSW(22);
#pragma unroll
        for (int i = 0; i < 10; i++) {
            uint32_t y0 = lds32(ya + i * 2048 + up * 32), y1 = lds32(ya + i * 2048 + (up ^ 1) * 32);
            x[i] = bfma2(a[i], prmt(y0, y1, sel), x[i]);
        }
        const uint3 s2 = row_stats(x, lane);
#pragma unroll
        for (int i = 0; i < 10; i++) a[i] = bfma2(ln_apply(x[i], s2.x, s2.y, s2.z), cb[i], sbv[i]);
        const uint3 s3 = row_stats(a, lane);
        uint32_t* o = reinterpret_cast<uint32_t*>(g_hn + (size_t)rrow * D_) + lane;
#pragma unroll
        for (int i = 0; i < 10; i++) o[32 * i] = ln_apply(a[i], s3.x, s3.y, s3.z);
        if (lane < 2) g_rs[rrow * 2 + lane] = lane ? make_uint4(s2.x, s2.y, s2.z, 0) : make_uint4(s1.x, s1.y, s1.z, 0);
        if (warp == 0) TSW(34);
        bar_arrive(8, 544);
    }

    const int half = wg & 1;
    const int row = 64 * half + 16 * wq + g;
    const size_t tile_w = ((size_t)rb * 80 + 10 * j) * 512 + row * 4 + c;
    const uint32_t park = sb + SM_Y + (tid & 255) * 16;
    const uint32_t ms = sb + SM_MOD + (80 * j + 2 * c) * 2;
    if (wg >= 2) {
        {
            float acc[40];
            gemm_loop<80, true, 0, 0, 10, 10, 10, true, XY_AT < 0 ? 13 : 0>(acc, sb, half, [&]() { if (tid == 256) TS(25); });
            if (tid == 256) TS(26);
            uint32_t* dst = reinterpret_cast<uint32_t*>(g_h1) + tile_w;
#pragma unroll
            for (int k = 0; k < 10; k += CH) CHUNK(k) {
#pragma unroll
                for (int q = k; q < k + CH && q < 10; q++) {
                    dst[q * 512] = pack2(gelu(acc[4 * q]), gelu(acc[4 * q + 1]));
                    dst[q * 512 + 32] = pack2(gelu(acc[4 * q + 2]), gelu(acc[4 * q + 3]));
                }
            }
            bar_arrive(15, 288);
            bar_arrive(14, 512);
        }
        gemm3<112, 20, 20, 10 - NA, 11, 9>(sb, rb, 112 * j, half, wq, g, c, ones);
        bar_arrive(6, 288);
        if (tid == 256) TS(35);
        {
            float acc[40];
            uint32_t gbv[10];
            uint4 bsv[5];
            bar_sync(10, 512);
#pragma unroll
            for (int q = 0; q < 5; q++) { gbv[2 * q] = lds32(ms + 6400 + q * 32); gbv[2 * q + 1] = lds32(ms + 6400 + q * 32 + 16); bsv[q] = lds128(park + q * 4096); }
            gemm_loop<80, false, 40 - NA, 40, 27, 27 - NA, 27 - NB, true, 0>(acc, sb, half, [&]() { if (tid == 256) TS(42); });
            if (tid == 256) TS(43);
            bf16* go = p.out + (size_t)(rb * 128 + row) * D_ + 80 * j + (c & 1) * 8 + (c >> 1) * 4;
#pragma unroll
            for (int q = 0; q < 5; q++) CHUNK(q) {
                const uint32_t g0 = gbv[2 * q], g1 = gbv[2 * q + 1];
                const uint4 bs = bsv[q];
#pragma unroll
                for (int r = 0; r < 2; r++) {
                    const uint32_t b0 = r ? bs.y : bs.x, b1 = r ? bs.w : bs.z;
                    uint32_t t0 = pack2(fmaf(blo(g0), acc[8 * q + 2 * r], blo(b0)), fmaf(bhi(g0), acc[8 * q + 2 * r + 1], bhi(b0)));
                    uint32_t t1 = pack2(fmaf(blo(g1), acc[8 * q + 4 + 2 * r], blo(b1)), fmaf(bhi(g1), acc[8 * q + 4 + 2 * r + 1], bhi(b1)));
                    uint32_t rv = __shfl_xor_sync(0xffffffffu, (c & 1) ? t0 : t1, 1);
                    *reinterpret_cast<uint2*>(go + r * 8 * D_ + 16 * q) = (c & 1) ? make_uint2(rv, t1) : make_uint2(t0, rv);
                }
            }
            if (tid == 256) TS(44);
            if (warp == 8) TSFLUSH();
        }
    } else {
        {
            float acc[40];
            uint32_t x2[20];
            {
                uint32_t y[20];
                const uint32_t* xp = reinterpret_cast<const uint32_t*>(p.q + (size_t)(rb * 128 + row) * D_ + 80 * j) + c;
                const uint32_t* yp = g_yv + (8 * rb + 4 * half + wq) * 5120 + (80 * j + 2 * c) * 8;
                mbar_wait(bars + (BAR_FA + XY_AT) * 8, 0);
#pragma unroll
                for (int q = 0; q < 10; q++) {
                    x2[2 * q] = __ldg(xp + 4 * q); x2[2 * q + 1] = __ldg(xp + 4 * q + 4 * D_);
                    const int pos = (g + 4 * j + 2 * q + (c >> 1)) & 7;
                    y[2 * q] = ldcg32(yp + q * 64 + pos); y[2 * q + 1] = ldcg32(yp + q * 64 + 8 + pos);
                }
                const uint4* rp = g_rs + (rb * 128 + row) * 2;
                const uint4 ra = ldcg128(rp), rb2 = ldcg128(rp + 1), rc = ldcg128(rp + 16), rd = ldcg128(rp + 17);
                bar_sync(14, 512);
#pragma unroll
                for (int q = 0; q < 10; q++) {
                    const uint32_t sa = lds32(ms + 16 * q), ca = badd2(lds32(ms + 1280 + 16 * q), one2), ga = lds32(ms + 2560 + 16 * q);
                    const uint32_t sbv = lds32(ms + 3840 + 16 * q), cb = badd2(lds32(ms + 5120 + 16 * q), one2);
                    uint32_t u = x2[2 * q], v = x2[2 * q + 1];
                    u = bfma2(bmul2(bfma2(ln_apply(u, ra.x, ra.y, ra.z), ca, sa), ga), prmt(y[2 * q], y[2 * q + 1], 0x5410), u);
                    v = bfma2(bmul2(bfma2(ln_apply(v, rc.x, rc.y, rc.z), ca, sa), ga), prmt(y[2 * q], y[2 * q + 1], 0x7632), v);
                    x2[2 * q] = u; x2[2 * q + 1] = v;
                    u = bfma2(ln_apply(u, rb2.x, rb2.y, rb2.z), cb, sbv);
                    v = bfma2(ln_apply(v, rd.x, rd.y, rd.z), cb, sbv);
                    acc[4 * q] = blo(u); acc[4 * q + 1] = bhi(u); acc[4 * q + 2] = blo(v); acc[4 * q + 3] = bhi(v);
                }
            }
            reg_fence<40>(acc);
            if (tid == 0) TS(45);
            gemm_loop<80, false, 10, 10, 10, 10, 10, false, 11>(acc, sb, half, [&]() { if (tid == 0) TS(29); });
            if (tid == 0) TS(30);
            uint32_t* dst = reinterpret_cast<uint32_t*>(g_x1) + tile_w;
            uint32_t x1[20];
            float s0 = 0.f, q0 = 0.f, s1 = 0.f, q1 = 0.f;
#pragma unroll
            for (int q = 0; q < 10; q++) {
                uint32_t u = pack2(acc[4 * q], acc[4 * q + 1]);
                uint32_t v = pack2(acc[4 * q + 2], acc[4 * q + 3]);
                dst[q * 512] = u;
                dst[q * 512 + 32] = v;
                x1[2 * q] = u; x1[2 * q + 1] = v;
            }
            CHUNK(0)
#pragma unroll
            for (int q = 0; q < 10; q++) {
                float a = blo(x1[2 * q]), b = bhi(x1[2 * q]), e = blo(x1[2 * q + 1]), f = bhi(x1[2 * q + 1]);
                s0 += a + b; q0 = fmaf(a, a, fmaf(b, b, q0));
                s1 += e + f; q1 = fmaf(e, e, fmaf(f, f, q1));
            }
#pragma unroll
            for (int m = 1; m <= 2; m <<= 1) {
                s0 += __shfl_xor_sync(0xffffffffu, s0, m); q0 += __shfl_xor_sync(0xffffffffu, q0, m);
                s1 += __shfl_xor_sync(0xffffffffu, s1, m); q1 += __shfl_xor_sync(0xffffffffu, q1, m);
            }
            if (c < 2) g_st[(rb * 8 + j) * 128 + row + 8 * c] = c ? make_float2(s1, q1) : make_float2(s0, q0);
            bar_arrive(12, 288);
#pragma unroll
            for (int q = 0; q < 5; q++) {
                const uint32_t g0 = lds32(ms + 6400 + q * 32), g1 = lds32(ms + 6400 + q * 32 + 16);
                sts128(park + q * 4096, make_uint4(bfma2(g0, x1[4 * q], x2[4 * q]), bfma2(g0, x1[4 * q + 1], x2[4 * q + 1]),
                                                   bfma2(g1, x1[4 * q + 2], x2[4 * q + 2]), bfma2(g1, x1[4 * q + 3], x2[4 * q + 3])));
            }
        }
        gemm3<104, 30 - NA, 30, 10, 9, 10>(sb, rb, 896 + 104 * j, half, wq, g, c, ones);
        bar_arrive(5, 288);
        if (tid == 0) TS(38);
    }
}

typedef CUresult (*EncFn)(CUtensorMap*, CUtensorMapDataType, cuuint32_t, void*, const cuuint64_t*, const cuuint64_t*,
                          const cuuint32_t*, const cuuint32_t*, CUtensorMapInterleave, CUtensorMapSwizzle,
                          CUtensorMapL2promotion, CUtensorMapFloatOOBfill);

void make_map(EncFn enc, CUtensorMap* m, const void* base, uint64_t inner, uint64_t outer, uint32_t bi, uint32_t bo,
              CUtensorMapSwizzle swz = CU_TENSOR_MAP_SWIZZLE_128B) {
    cuuint64_t dims[2] = {inner, outer};
    cuuint64_t st[1] = {inner * 2};
    cuuint32_t box[2] = {bi, bo};
    cuuint32_t es[2] = {1, 1};
    enc(m, CU_TENSOR_MAP_DATA_TYPE_BFLOAT16, 2, const_cast<void*>(base), dims, st, box, es, CU_TENSOR_MAP_INTERLEAVE_NONE,
        swz, CU_TENSOR_MAP_L2_PROMOTION_NONE, CU_TENSOR_MAP_FLOAT_OOB_FILL_NONE);
}

}

extern "C" void kernel_launch(void* const* d_in, const int* in_sizes, int n_in, void* d_out, int out_size) {
    (void)in_sizes; (void)n_in; (void)out_size;
    Params p;
    p.q = (const bf16*)d_in[0]; p.k = (const bf16*)d_in[1]; p.v = (const bf16*)d_in[2];
    p.shift = (const bf16*)d_in[3]; p.ssmk = (const bf16*)d_in[4]; p.ssmD = (const bf16*)d_in[5];
    p.w1 = (const bf16*)d_in[7]; p.w2 = (const bf16*)d_in[8]; p.w3 = (const bf16*)d_in[9]; p.w4 = (const bf16*)d_in[10];
    p.c = (const bf16*)d_in[11]; p.wmod = (const bf16*)d_in[12];
    p.out = (bf16*)d_out;
    p.ones = 0xffffffffu;

    void* fn = nullptr;
    cudaDriverEntryPointQueryResult qr;
    cudaGetDriverEntryPoint("cuTensorMapEncodeTiled", &fn, cudaEnableDefault, &qr);
    EncFn enc = (EncFn)fn;
    void* hn = nullptr;
    cudaGetSymbolAddress(&hn, g_hn);
    Maps maps;
    make_map(enc, &maps.w3s, p.w3, F_, D_, 216, 64, CU_TENSOR_MAP_SWIZZLE_NONE);
    make_map(enc, &maps.wm, p.wmod, 6 * D_, D_, 32, 128, CU_TENSOR_MAP_SWIZZLE_NONE);
    make_map(enc, &maps.hn, hn, D_, S_, 64, 128);
    make_map(enc, &maps.w1a, p.w1, D_, D_, 64, 64);
    make_map(enc, &maps.w1b, p.w1, D_, D_, 16, 64);
    make_map(enc, &maps.w2a, p.w2, D_, D_, 64, 64);
    make_map(enc, &maps.w2b, p.w2, D_, D_, 16, 64);
    make_map(enc, &maps.w3a, p.w3, F_, D_, 64, 64);
    make_map(enc, &maps.w3b, p.w3, F_, D_, 48, 64);
    make_map(enc, &maps.w3c, p.w3, F_, D_, 40, 64);
    make_map(enc, &maps.w4a, p.w4, D_, F_, 64, 64);
    make_map(enc, &maps.w4b, p.w4, D_, F_, 16, 64);
    cudaFuncSetAttribute(fused_kernel, cudaFuncAttributeMaxDynamicSharedMemorySize, SMEM_BYTES);
    fused_kernel<<<132, NTHREADS, SMEM_BYTES>>>(maps, p);
}
```

```cpp
#include <cuda_runtime.h>
#include <cuda_bf16.h>
#include <cuda.h>
#include <stdint.h>
#include <string.h>

#define SEED 2
#define RING_A 6
#define MMA_STAT 0
#define CH 2
#define WARM 0
#define EXPER 0
#define HO_A 10
#define HO_B 6
#define HOLD 1
#define STAG 0
#define SSM_WHEN 1
#define PF_EARLY 0

namespace {

typedef __nv_bfloat16 bf16;
typedef __nv_bfloat162 bf162;

constexpr int S_ = 2048, D_ = 640, F_ = 1728;
constexpr int NTHREADS = 640;
constexpr int NA = RING_A, NB = 12 - RING_A;
constexpr int SLOT = 16384;
constexpr int SM_RA = 0, SM_RB = NA * SLOT;

constexpr int SM_RED = 0;
constexpr int RED_STRIDE = 17536;
constexpr int SM_PK = 0;
constexpr int SM_PV = 24576;
constexpr int SM_WM = 88064;
constexpr int SM_K = SM_WM + 40960;
constexpr int K_STRIDE = 8320;
constexpr int SM_U = SM_K + 5 * K_STRIDE;
constexpr int U_PLANE = 2560, U_STRIDE = 5120;
constexpr int SM_Y = 12 * SLOT;
static_assert(SM_U + 5 * U_STRIDE <= SM_Y, "smem map");
constexpr int SM_XT = 3 * SLOT, SM_XT2 = 4 * SLOT, SM_YT = SM_XT2 + 4096;
constexpr int SM_MOD = SM_Y + 20480;
constexpr int SM_GV = SM_MOD + 7680;
constexpr int SM_CS = SM_GV + 1024;
constexpr int SM_RP = SM_CS + 1024;
constexpr int SM_BAR = SM_RP + 1024;
constexpr int SM_PROF = SM_BAR + 512;
constexpr int SM_TOTAL = SM_PROF + 512;
constexpr int SMEM_BYTES = SM_TOTAL + 1024;
static_assert(SMEM_BYTES <= 232448, "smem");

constexpr int BAR_FA = 0, BAR_FB = NA, BAR_EA = 12, BAR_EB = 12 + NA, BAR_K = 24, BAR_U = 29, BAR_Y = 34, BAR_CS = 35, BAR_WM = 36, BAR_M = 37, BAR_XY = 38;

__device__ __align__(1024) bf16 g_kvT[D_ * S_];
__device__ __align__(1024) uint32_t g_yv[128 * 5120];
__device__ __align__(1024) bf16 g_mod[6 * D_];
__device__ __align__(1024) bf16 g_hn[S_ * D_];
__device__ __align__(1024) uint4 g_rs[S_ * 2];
__device__ __align__(1024) bf16 g_h1[S_ * D_];
__device__ __align__(1024) bf16 g_x1[S_ * D_];
__device__ __align__(1024) bf16 g_g[S_ * F_];
__device__ __align__(1024) float2 g_st[S_ * 8];
__device__ __align__(1024) float g_cs[F_];
__device__ __align__(1024) unsigned g_flags[128 * 32];
__device__ __align__(1024) unsigned g_epoch[160];
constexpr int FL_P = 0, FL_C = 8, FL_CS = 9, FL_M = 10, FL_R = 16, FL_B1 = 32, FL_B2 = 48, FL_G = 64;

#define TS(i) do {} while (0)
#define TSW(i) do {} while (0)
#define TSD(i, dep) do {} while (0)
#define TSD2(i, dep) do {} while (0)
#define TSFLUSH() do {} while (0)

struct Params {
    const bf16 *q, *k, *v, *shift, *ssmk, *ssmD, *w1, *w2, *w3, *w4, *c, *wmod;
    bf16* out;
    unsigned ones;
};
#define CHUNK(k) if (ones & (1u << (k)))
struct Maps { CUtensorMap hn, w1a, w1b, w2a, w2b, w3a, w3b, w3c, w4a, w4b, wm, xa, xb, w3s; };

template<int N> struct WgRs;
template<int N> struct WgSs;
template<> struct WgRs<32> { template<int OFF,int HI,int SC> static __device__ __forceinline__ void run(float* d,uint32_t a0,uint32_t a1,uint32_t a2,uint32_t a3,uint32_t blo){
 asm volatile("{.reg .b32 l; .reg .b64 db; add.u32 l,%20,%21; mov.b64 db,{l,%22}; wgmma.mma_async.sync.aligned.m64n32k16.f32.bf16.bf16 {%0,%1,%2,%3,%4,%5,%6,%7,%8,%9,%10,%11,%12,%13,%14,%15},{%16,%17,%18,%19},db,%23,1,1,0;}"
 :"+f"(d[0]),"+f"(d[1]),"+f"(d[2]),"+f"(d[3]),"+f"(d[4]),"+f"(d[5]),"+f"(d[6]),"+f"(d[7]),"+f"(d[8]),"+f"(d[9]),"+f"(d[10]),"+f"(d[11]),"+f"(d[12]),"+f"(d[13]),"+f"(d[14]),"+f"(d[15])
 :"r"(a0),"r"(a1),"r"(a2),"r"(a3),"r"(blo),"n"(OFF),"n"(HI),"n"(SC)); } };
template<> struct WgRs<48> { template<int OFF,int HI,int SC> static __device__ __forceinline__ void run(float* d,uint32_t a0,uint32_t a1,uint32_t a2,uint32_t a3,uint32_t blo){
 asm volatile("{.reg .b32 l; .reg .b64 db; add.u32 l,%28,%29; mov.b64 db,{l,%30}; wgmma.mma_async.sync.aligned.m64n48k16.f32.bf16.bf16 {%0,%1,%2,%3,%4,%5,%6,%7,%8,%9,%10,%11,%12,%13,%14,%15,%16,%17,%18,%19,%20,%21,%22,%23},{%24,%25,%26,%27},db,%31,1,1,0;}"
 :"+f"(d[0]),"+f"(d[1]),"+f"(d[2]),"+f"(d[3]),"+f"(d[4]),"+f"(d[5]),"+f"(d[6]),"+f"(d[7]),"+f"(d[8]),"+f"(d[9]),"+f"(d[10]),"+f"(d[11]),"+f"(d[12]),"+f"(d[13]),"+f"(d[14]),"+f"(d[15]),"+f"(d[16]),"+f"(d[17]),"+f"(d[18]),"+f"(d[19]),"+f"(d[20]),"+f"(d[21]),"+f"(d[22]),"+f"(d[23])
 :"r"(a0),"r"(a1),"r"(a2),"r"(a3),"r"(blo),"n"(OFF),"n"(HI),"n"(SC)); } };
template<> struct WgRs<64> { template<int OFF,int HI,int SC> static __device__ __forceinline__ void run(float* d,uint32_t a0,uint32_t a1,uint32_t a2,uint32_t a3,uint32_t blo){
 asm volatile("{.reg .b32 l; .reg .b64 db; add.u32 l,%36,%37; mov.b64 db,{l,%38}; wgmma.mma_async.sync.aligned.m64n64k16.f32.bf16.bf16 {%0,%1,%2,%3,%4,%5,%6,%7,%8,%9,%10,%11,%12,%13,%14,%15,%16,%17,%18,%19,%20,%21,%22,%23,%24,%25,%26,%27,%28,%29,%30,%31},{%32,%33,%34,%35},db,%39,1,1,0;}"
 :"+f"(d[0]),"+f"(d[1]),"+f"(d[2]),"+f"(d[3]),"+f"(d[4]),"+f"(d[5]),"+f"(d[6]),"+f"(d[7]),"+f"(d[8]),"+f"(d[9]),"+f"(d[10]),"+f"(d[11]),"+f"(d[12]),"+f"(d[13]),"+f"(d[14]),"+f"(d[15]),"+f"(d[16]),"+f"(d[17]),"+f"(d[18]),"+f"(d[19]),"+f"(d[20]),"+f"(d[21]),"+f"(d[22]),"+f"(d[23]),"+f"(d[24]),"+f"(d[25]),"+f"(d[26]),"+f"(d[27]),"+f"(d[28]),"+f"(d[29]),"+f"(d[30]),"+f"(d[31])
 :"r"(a0),"r"(a1),"r"(a2),"r"(a3),"r"(blo),"n"(OFF),"n"(HI),"n"(SC)); } };
template<> struct WgRs<72> { template<int OFF,int HI,int SC> static __device__ __forceinline__ void run(float* d,uint32_t a0,uint32_t a1,uint32_t a2,uint32_t a3,uint32_t blo){
 asm volatile("{.reg .b32 l; .reg .b64 db; add.u32 l,%40,%41; mov.b64 db,{l,%42}; wgmma.mma_async.sync.aligned.m64n72k16.f32.bf16.bf16 {%0,%1,%2,%3,%4,%5,%6,%7,%8,%9,%10,%11,%12,%13,%14,%15,%16,%17,%18,%19,%20,%21,%22,%23,%24,%25,%26,%27,%28,%29,%30,%31,%32,%33,%34,%35},{%36,%37,%38,%39},db,%43,1,1,0;}"
 :"+f"(d[0]),"+f"(d[1]),"+f"(d[2]),"+f"(d[3]),"+f"(d[4]),"+f"(d[5]),"+f"(d[6]),"+f"(d[7]),"+f"(d[8]),"+f"(d[9]),"+f"(d[10]),"+f"(d[11]),"+f"(d[12]),"+f"(d[13]),"+f"(d[14]),"+f"(d[15]),"+f"(d[16]),"+f"(d[17]),"+f"(d[18]),"+f"(d[19]),"+f"(d[20]),"+f"(d[21]),"+f"(d[22]),"+f"(d[23]),"+f"(d[24]),"+f"(d[25]),"+f"(d[26]),"+f"(d[27]),"+f"(d[28]),"+f"(d[29]),"+f"(d[30]),"+f"(d[31]),"+f"(d[32]),"+f"(d[33]),"+f"(d[34]),"+f"(d[35])
 :"r"(a0),"r"(a1),"r"(a2),"r"(a3),"r"(blo),"n"(OFF),"n"(HI),"n"(SC)); } };
template<> struct WgRs<80> { template<int OFF,int HI,int SC> static __device__ __forceinline__ void run(float* d,uint32_t a0,uint32_t a1,uint32_t a2,uint32_t a3,uint32_t blo){
 asm volatile("{.reg .b32 l; .reg .b64 db; add.u32 l,%44,%45; mov.b64 db,{l,%46}; wgmma.mma_async.sync.aligned.m64n80k16.f32.bf16.bf16 {%0,%1,%2,%3,%4,%5,%6,%7,%8,%9,%10,%11,%12,%13,%14,%15,%16,%17,%18,%19,%20,%21,%22,%23,%24,%25,%26,%27,%28,%29,%30,%31,%32,%33,%34,%35,%36,%37,%38,%39},{%40,%41,%42,%43},db,%47,1,1,0;}"
 :"+f"(d[0]),"+f"(d[1]),"+f"(d[2]),"+f"(d[3]),"+f"(d[4]),"+f"(d[5]),"+f"(d[6]),"+f"(d[7]),"+f"(d[8]),"+f"(d[9]),"+f"(d[10]),"+f"(d[11]),"+f"(d[12]),"+f"(d[13]),"+f"(d[14]),"+f"(d[15]),"+f"(d[16]),"+f"(d[17]),"+f"(d[18]),"+f"(d[19]),"+f"(d[20]),"+f"(d[21]),"+f"(d[22]),"+f"(d[23]),"+f"(d[24]),"+f"(d[25]),"+f"(d[26]),"+f"(d[27]),"+f"(d[28]),"+f"(d[29]),"+f"(d[30]),"+f"(d[31]),"+f"(d[32]),"+f"(d[33]),"+f"(d[34]),"+f"(d[35]),"+f"(d[36]),"+f"(d[37]),"+f"(d[38]),"+f"(d[39])
 :"r"(a0),"r"(a1),"r"(a2),"r"(a3),"r"(blo),"n"(OFF),"n"(HI),"n"(SC)); } };
template<> struct WgRs<88> { template<int OFF,int HI,int SC> static __device__ __forceinline__ void run(float* d,uint32_t a0,uint32_t a1,uint32_t a2,uint32_t a3,uint32_t blo){
 asm volatile("{.reg .b32 l; .reg .b64 db; add.u32 l,%48,%49; mov.b64 db,{l,%50}; wgmma.mma_async.sync.aligned.m64n88k16.f32.bf16.bf16 {%0,%1,%2,%3,%4,%5,%6,%7,%8,%9,%10,%11,%12,%13,%14,%15,%16,%17,%18,%19,%20,%21,%22,%23,%24,%25,%26,%27,%28,%29,%30,%31,%32,%33,%34,%35,%36,%37,%38,%39,%40,%41,%42,%43},{%44,%45,%46,%47},db,%51,1,1,0;}"
 :"+f"(d[0]),"+f"(d[1]),"+f"(d[2]),"+f"(d[3]),"+f"(d[4]),"+f"(d[5]),"+f"(d[6]),"+f"(d[7]),"+f"(d[8]),"+f"(d[9]),"+f"(d[10]),"+f"(d[11]),"+f"(d[12]),"+f"(d[13]),"+f"(d[14]),"+f"(d[15]),"+f"(d[16]),"+f"(d[17]),"+f"(d[18]),"+f"(d[19]),"+f"(d[20]),"+f"(d[21]),"+f"(d[22]),"+f"(d[23]),"+f"(d[24]),"+f"(d[25]),"+f"(d[26]),"+f"(d[27]),"+f"(d[28]),"+f"(d[29]),"+f"(d[30]),"+f"(d[31]),"+f"(d[32]),"+f"(d[33]),"+f"(d[34]),"+f"(d[35]),"+f"(d[36]),"+f"(d[37]),"+f"(d[38]),"+f"(d[39]),"+f"(d[40]),"+f"(d[41]),"+f"(d[42]),"+f"(d[43])
 :"r"(a0),"r"(a1),"r"(a2),"r"(a3),"r"(blo),"n"(OFF),"n"(HI),"n"(SC)); } };
template<> struct WgRs<96> { template<int OFF,int HI,int SC> static __device__ __forceinline__ void run(float* d,uint32_t a0,uint32_t a1,uint32_t a2,uint32_t a3,uint32_t blo){
 asm volatile("{.reg .b32 l; .reg .b64 db; add.u32 l,%52,%53; mov.b64 db,{l,%54}; wgmma.mma_async.sync.aligned.m64n96k16.f32.bf16.bf16 {%0,%1,%2,%3,%4,%5,%6,%7,%8,%9,%10,%11,%12,%13,%14,%15,%16,%17,%18,%19,%20,%21,%22,%23,%24,%25,%26,%27,%28,%29,%30,%31,%32,%33,%34,%35,%36,%37,%38,%39,%40,%41,%42,%43,%44,%45,%46,%47},{%48,%49,%50,%51},db,%55,1,1,0;}"
 :"+f"(d[0]),"+f"(d[1]),"+f"(d[2]),"+f"(d[3]),"+f"(d[4]),"+f"(d[5]),"+f"(d[6]),"+f"(d[7]),"+f"(d[8]),"+f"(d[9]),"+f"(d[10]),"+f"(d[11]),"+f"(d[12]),"+f"(d[13]),"+f"(d[14]),"+f"(d[15]),"+f"(d[16]),"+f"(d[17]),"+f"(d[18]),"+f"(d[19]),"+f"(d[20]),"+f"(d[21]),"+f"(d[22]),"+f"(d[23]),"+f"(d[24]),"+f"(d[25]),"+f"(d[26]),"+f"(d[27]),"+f"(d[28]),"+f"(d[29]),"+f"(d[30]),"+f"(d[31]),"+f"(d[32]),"+f"(d[33]),"+f"(d[34]),"+f"(d[35]),"+f"(d[36]),"+f"(d[37]),"+f"(d[38]),"+f"(d[39]),"+f"(d[40]),"+f"(d[41]),"+f"(d[42]),"+f"(d[43]),"+f"(d[44]),"+f"(d[45]),"+f"(d[46]),"+f"(d[47])
 :"r"(a0),"r"(a1),"r"(a2),"r"(a3),"r"(blo),"n"(OFF),"n"(HI),"n"(SC)); } };
template<> struct WgRs<104> { template<int OFF,int HI,int SC> static __device__ __forceinline__ void run(float* d,uint32_t a0,uint32_t a1,uint32_t a2,uint32_t a3,uint32_t blo){
 asm volatile("{.reg .b32 l; .reg .b64 db; add.u32 l,%56,%57; mov.b64 db,{l,%58}; wgmma.mma_async.sync.aligned.m64n104k16.f32.bf16.bf16 {%0,%1,%2,%3,%4,%5,%6,%7,%8,%9,%10,%11,%12,%13,%14,%15,%16,%17,%18,%19,%20,%21,%22,%23,%24,%25,%26,%27,%28,%29,%30,%31,%32,%33,%34,%35,%36,%37,%38,%39,%40,%41,%42,%43,%44,%45,%46,%47,%48,%49,%50,%51},{%52,%53,%54,%55},db,%59,1,1,0;}"
 :"+f"(d[0]),"+f"(d[1]),"+f"(d[2]),"+f"(d[3]),"+f"(d[4]),"+f"(d[5]),"+f"(d[6]),"+f"(d[7]),"+f"(d[8]),"+f"(d[9]),"+f"(d[10]),"+f"(d[11]),"+f"(d[12]),"+f"(d[13]),"+f"(d[14]),"+f"(d[15]),"+f"(d[16]),"+f"(d[17]),"+f"(d[18]),"+f"(d[19]),"+f"(d[20]),"+f"(d[21]),"+f"(d[22]),"+f"(d[23]),"+f"(d[24]),"+f"(d[25]),"+f"(d[26]),"+f"(d[27]),"+f"(d[28]),"+f"(d[29]),"+f"(d[30]),"+f"(d[31]),"+f"(d[32]),"+f"(d[33]),"+f"(d[34]),"+f"(d[35]),"+f"(d[36]),"+f"(d[37]),"+f"(d[38]),"+f"(d[39]),"+f"(d[40]),"+f"(d[41]),"+f"(d[42]),"+f"(d[43]),"+f"(d[44]),"+f"(d[45]),"+f"(d[46]),"+f"(d[47]),"+f"(d[48]),"+f"(d[49]),"+f"(d[50]),"+f"(d[51])
 :"r"(a0),"r"(a1),"r"(a2),"r"(a3),"r"(blo),"n"(OFF),"n"(HI),"n"(SC)); } };
template<> struct WgRs<112> { template<int OFF,int HI,int SC> static __device__ __forceinline__ void run(float* d,uint32_t a0,uint32_t a1,uint32_t a2,uint32_t a3,uint32_t blo){
 asm volatile("{.reg .b32 l; .reg .b64 db; add.u32 l,%60,%61; mov.b64 db,{l,%62}; wgmma.mma_async.sync.aligned.m64n112k16.f32.bf16.bf16 {%0,%1,%2,%3,%4,%5,%6,%7,%8,%9,%10,%11,%12,%13,%14,%15,%16,%17,%18,%19,%20,%21,%22,%23,%24,%25,%26,%27,%28,%29,%30,%31,%32,%33,%34,%35,%36,%37,%38,%39,%40,%41,%42,%43,%44,%45,%46,%47,%48,%49,%50,%51,%52,%53,%54,%55},{%56,%57,%58,%59},db,%63,1,1,0;}"
 :"+f"(d[0]),"+f"(d[1]),"+f"(d[2]),"+f"(d[3]),"+f"(d[4]),"+f"(d[5]),"+f"(d[6]),"+f"(d[7]),"+f"(d[8]),"+f"(d[9]),"+f"(d[10]),"+f"(d[11]),"+f"(d[12]),"+f"(d[13]),"+f"(d[14]),"+f"(d[15]),"+f"(d[16]),"+f"(d[17]),"+f"(d[18]),"+f"(d[19]),"+f"(d[20]),"+f"(d[21]),"+f"(d[22]),"+f"(d[23]),"+f"(d[24]),"+f"(d[25]),"+f"(d[26]),"+f"(d[27]),"+f"(d[28]),"+f"(d[29]),"+f"(d[30]),"+f"(d[31]),"+f"(d[32]),"+f"(d[33]),"+f"(d[34]),"+f"(d[35]),"+f"(d[36]),"+f"(d[37]),"+f"(d[38]),"+f"(d[39]),"+f"(d[40]),"+f"(d[41]),"+f"(d[42]),"+f"(d[43]),"+f"(d[44]),"+f"(d[45]),"+f"(d[46]),"+f"(d[47]),"+f"(d[48]),"+f"(d[49]),"+f"(d[50]),"+f"(d[51]),"+f"(d[52]),"+f"(d[53]),"+f"(d[54]),"+f"(d[55])
 :"r"(a0),"r"(a1),"r"(a2),"r"(a3),"r"(blo),"n"(OFF),"n"(HI),"n"(SC)); } };
template<> struct WgRs<120> { template<int OFF,int HI,int SC> static __device__ __forceinline__ void run(float* d,uint32_t a0,uint32_t a1,uint32_t a2,uint32_t a3,uint32_t blo){
 asm volatile("{.reg .b32 l; .reg .b64 db; add.u32 l,%64,%65; mov.b64 db,{l,%66}; wgmma.mma_async.sync.aligned.m64n120k16.f32.bf16.bf16 {%0,%1,%2,%3,%4,%5,%6,%7,%8,%9,%10,%11,%12,%13,%14,%15,%16,%17,%18,%19,%20,%21,%22,%23,%24,%25,%26,%27,%28,%29,%30,%31,%32,%33,%34,%35,%36,%37,%38,%39,%40,%41,%42,%43,%44,%45,%46,%47,%48,%49,%50,%51,%52,%53,%54,%55,%56,%57,%58,%59},{%60,%61,%62,%63},db,%67,1,1,0;}"
 :"+f"(d[0]),"+f"(d[1]),"+f"(d[2]),"+f"(d[3]),"+f"(d[4]),"+f"(d[5]),"+f"(d[6]),"+f"(d[7]),"+f"(d[8]),"+f"(d[9]),"+f"(d[10]),"+f"(d[11]),"+f"(d[12]),"+f"(d[13]),"+f"(d[14]),"+f"(d[15]),"+f"(d[16]),"+f"(d[17]),"+f"(d[18]),"+f"(d[19]),"+f"(d[20]),"+f"(d[21]),"+f"(d[22]),"+f"(d[23]),"+f"(d[24]),"+f"(d[25]),"+f"(d[26]),"+f"(d[27]),"+f"(d[28]),"+f"(d[29]),"+f"(d[30]),"+f"(d[31]),"+f"(d[32]),"+f"(d[33]),"+f"(d[34]),"+f"(d[35]),"+f"(d[36]),"+f"(d[37]),"+f"(d[38]),"+f"(d[39]),"+f"(d[40]),"+f"(d[41]),"+f"(d[42]),"+f"(d[43]),"+f"(d[44]),"+f"(d[45]),"+f"(d[46]),"+f"(d[47]),"+f"(d[48]),"+f"(d[49]),"+f"(d[50]),"+f"(d[51]),"+f"(d[52]),"+f"(d[53]),"+f"(d[54]),"+f"(d[55]),"+f"(d[56]),"+f"(d[57]),"+f"(d[58]),"+f"(d[59])
 :"r"(a0),"r"(a1),"r"(a2),"r"(a3),"r"(blo),"n"(OFF),"n"(HI),"n"(SC)); } };
template<> struct WgRs<128> { template<int OFF,int HI,int SC> static __device__ __forceinline__ void run(float* d,uint32_t a0,uint32_t a1,uint32_t a2,uint32_t a3,uint32_t blo){
 asm volatile("{.reg .b32 l; .reg .b64 db; add.u32 l,%68,%69; mov.b64 db,{l,%70}; wgmma.mma_async.sync.aligned.m64n128k16.f32.bf16.bf16 {%0,%1,%2,%3,%4,%5,%6,%7,%8,%9,%10,%11,%12,%13,%14,%15,%16,%17,%18,%19,%20,%21,%22,%23,%24,%25,%26,%27,%28,%29,%30,%31,%32,%33,%34,%35,%36,%37,%38,%39,%40,%41,%42,%43,%44,%45,%46,%47,%48,%49,%50,%51,%52,%53,%54,%55,%56,%57,%58,%59,%60,%61,%62,%63},{%64,%65,%66,%67},db,%71,1,1,0;}"
 :"+f"(d[0]),"+f"(d[1]),"+f"(d[2]),"+f"(d[3]),"+f"(d[4]),"+f"(d[5]),"+f"(d[6]),"+f"(d[7]),"+f"(d[8]),"+f"(d[9]),"+f"(d[10]),"+f"(d[11]),"+f"(d[12]),"+f"(d[13]),"+f"(d[14]),"+f"(d[15]),"+f"(d[16]),"+f"(d[17]),"+f"(d[18]),"+f"(d[19]),"+f"(d[20]),"+f"(d[21]),"+f"(d[22]),"+f"(d[23]),"+f"(d[24]),"+f"(d[25]),"+f"(d[26]),"+f"(d[27]),"+f"(d[28]),"+f"(d[29]),"+f"(d[30]),"+f"(d[31]),"+f"(d[32]),"+f"(d[33]),"+f"(d[34]),"+f"(d[35]),"+f"(d[36]),"+f"(d[37]),"+f"(d[38]),"+f"(d[39]),"+f"(d[40]),"+f"(d[41]),"+f"(d[42]),"+f"(d[43]),"+f"(d[44]),"+f"(d[45]),"+f"(d[46]),"+f"(d[47]),"+f"(d[48]),"+f"(d[49]),"+f"(d[50]),"+f"(d[51]),"+f"(d[52]),"+f"(d[53]),"+f"(d[54]),"+f"(d[55]),"+f"(d[56]),"+f"(d[57]),"+f"(d[58]),"+f"(d[59]),"+f"(d[60]),"+f"(d[61]),"+f"(d[62]),"+f"(d[63])
 :"r"(a0),"r"(a1),"r"(a2),"r"(a3),"r"(blo),"n"(OFF),"n"(HI),"n"(SC)); } };
template<> struct WgSs<80> { template<int AOFF,int AHI,int BOFF,int BHI,int SC> static __device__ __forceinline__ void run(float* d,uint32_t alo,uint32_t blo){
 asm volatile("{.reg .b32 l,m; .reg .b64 da,db; add.u32 l,%40,%42; mov.b64 da,{l,%43}; add.u32 m,%41,%44; mov.b64 db,{m,%45}; wgmma.mma_async.sync.aligned.m64n80k16.f32.bf16.bf16 {%0,%1,%2,%3,%4,%5,%6,%7,%8,%9,%10,%11,%12,%13,%14,%15,%16,%17,%18,%19,%20,%21,%22,%23,%24,%25,%26,%27,%28,%29,%30,%31,%32,%33,%34,%35,%36,%37,%38,%39},da,db,%46,1,1,0,1;}"
 :"+f"(d[0]),"+f"(d[1]),"+f"(d[2]),"+f"(d[3]),"+f"(d[4]),"+f"(d[5]),"+f"(d[6]),"+f"(d[7]),"+f"(d[8]),"+f"(d[9]),"+f"(d[10]),"+f"(d[11]),"+f"(d[12]),"+f"(d[13]),"+f"(d[14]),"+f"(d[15]),"+f"(d[16]),"+f"(d[17]),"+f"(d[18]),"+f"(d[19]),"+f"(d[20]),"+f"(d[21]),"+f"(d[22]),"+f"(d[23]),"+f"(d[24]),"+f"(d[25]),"+f"(d[26]),"+f"(d[27]),"+f"(d[28]),"+f"(d[29]),"+f"(d[30]),"+f"(d[31]),"+f"(d[32]),"+f"(d[33]),"+f"(d[34]),"+f"(d[35]),"+f"(d[36]),"+f"(d[37]),"+f"(d[38]),"+f"(d[39])
 :"r"(alo),"r"(blo),"n"(AOFF),"n"(AHI),"n"(BOFF),"n"(BHI),"n"(SC)); } };
template<> struct WgSs<104> { template<int AOFF,int AHI,int BOFF,int BHI,int SC> static __device__ __forceinline__ void run(float* d,uint32_t alo,uint32_t blo){
 asm volatile("{.reg .b32 l,m; .reg .b64 da,db; add.u32 l,%52,%54; mov.b64 da,{l,%55}; add.u32 m,%53,%56; mov.b64 db,{m,%57}; wgmma.mma_async.sync.aligned.m64n104k16.f32.bf16.bf16 {%0,%1,%2,%3,%4,%5,%6,%7,%8,%9,%10,%11,%12,%13,%14,%15,%16,%17,%18,%19,%20,%21,%22,%23,%24,%25,%26,%27,%28,%29,%30,%31,%32,%33,%34,%35,%36,%37,%38,%39,%40,%41,%42,%43,%44,%45,%46,%47,%48,%49,%50,%51},da,db,%58,1,1,0,1;}"
 :"+f"(d[0]),"+f"(d[1]),"+f"(d[2]),"+f"(d[3]),"+f"(d[4]),"+f"(d[5]),"+f"(d[6]),"+f"(d[7]),"+f"(d[8]),"+f"(d[9]),"+f"(d[10]),"+f"(d[11]),"+f"(d[12]),"+f"(d[13]),"+f"(d[14]),"+f"(d[15]),"+f"(d[16]),"+f"(d[17]),"+f"(d[18]),"+f"(d[19]),"+f"(d[20]),"+f"(d[21]),"+f"(d[22]),"+f"(d[23]),"+f"(d[24]),"+f"(d[25]),"+f"(d[26]),"+f"(d[27]),"+f"(d[28]),"+f"(d[29]),"+f"(d[30]),"+f"(d[31]),"+f"(d[32]),"+f"(d[33]),"+f"(d[34]),"+f"(d[35]),"+f"(d[36]),"+f"(d[37]),"+f"(d[38]),"+f"(d[39]),"+f"(d[40]),"+f"(d[41]),"+f"(d[42]),"+f"(d[43]),"+f"(d[44]),"+f"(d[45]),"+f"(d[46]),"+f"(d[47]),"+f"(d[48]),"+f"(d[49]),"+f"(d[50]),"+f"(d[51])
 :"r"(alo),"r"(blo),"n"(AOFF),"n"(AHI),"n"(BOFF),"n"(BHI),"n"(SC)); } };
template<> struct WgSs<112> { template<int AOFF,int AHI,int BOFF,int BHI,int SC> static __device__ __forceinline__ void run(float* d,uint32_t alo,uint32_t blo){
 asm volatile("{.reg .b32 l,m; .reg .b64 da,db; add.u32 l,%56,%58; mov.b64 da,{l,%59}; add.u32 m,%57,%60; mov.b64 db,{m,%61}; wgmma.mma_async.sync.aligned.m64n112k16.f32.bf16.bf16 {%0,%1,%2,%3,%4,%5,%6,%7,%8,%9,%10,%11,%12,%13,%14,%15,%16,%17,%18,%19,%20,%21,%22,%23,%24,%25,%26,%27,%28,%29,%30,%31,%32,%33,%34,%35,%36,%37,%38,%39,%40,%41,%42,%43,%44,%45,%46,%47,%48,%49,%50,%51,%52,%53,%54,%55},da,db,%62,1,1,0,1;}"
 :"+f"(d[0]),"+f"(d[1]),"+f"(d[2]),"+f"(d[3]),"+f"(d[4]),"+f"(d[5]),"+f"(d[6]),"+f"(d[7]),"+f"(d[8]),"+f"(d[9]),"+f"(d[10]),"+f"(d[11]),"+f"(d[12]),"+f"(d[13]),"+f"(d[14]),"+f"(d[15]),"+f"(d[16]),"+f"(d[17]),"+f"(d[18]),"+f"(d[19]),"+f"(d[20]),"+f"(d[21]),"+f"(d[22]),"+f"(d[23]),"+f"(d[24]),"+f"(d[25]),"+f"(d[26]),"+f"(d[27]),"+f"(d[28]),"+f"(d[29]),"+f"(d[30]),"+f"(d[31]),"+f"(d[32]),"+f"(d[33]),"+f"(d[34]),"+f"(d[35]),"+f"(d[36]),"+f"(d[37]),"+f"(d[38]),"+f"(d[39]),"+f"(d[40]),"+f"(d[41]),"+f"(d[42]),"+f"(d[43]),"+f"(d[44]),"+f"(d[45]),"+f"(d[46]),"+f"(d[47]),"+f"(d[48]),"+f"(d[49]),"+f"(d[50]),"+f"(d[51]),"+f"(d[52]),"+f"(d[53]),"+f"(d[54]),"+f"(d[55])
 :"r"(alo),"r"(blo),"n"(AOFF),"n"(AHI),"n"(BOFF),"n"(BHI),"n"(SC)); } };

__device__ __forceinline__ void wg_fence() { asm volatile("wgmma.fence.sync.aligned;" ::: "memory"); }
__device__ __forceinline__ void wg_commit() { asm volatile("wgmma.commit_group.sync.aligned;" ::: "memory"); }
template <int N> __device__ __forceinline__ void wg_wait() { asm volatile("wgmma.wait_group.sync.aligned %0;" ::"n"(N) : "memory"); }
template <int N> __device__ __forceinline__ void reg_fence(float* d) {
#pragma unroll
    for (int i = 0; i < N; i++) asm volatile("" : "+f"(d[i])::"memory");
}
__device__ __forceinline__ uint32_t desc_lo(uint32_t addr, uint32_t lbo) { return ((addr & 0x3FFFF) >> 4) | ((lbo >> 4) << 16); }
#define desc_hi(sbo, sw) (((sbo) >> 4) | ((sw) << 30))
__device__ __forceinline__ uint32_t smem_u32(const void* p) { return (uint32_t)__cvta_generic_to_shared(p); }
__device__ __forceinline__ bool elect() {
    uint32_t p;
    asm volatile("{.reg .pred P; elect.sync _|P, 0xffffffff; selp.u32 %0,1,0,P;}" : "=r"(p));
    return p;
}
__device__ __forceinline__ void mbar_init(uint32_t bar, uint32_t cnt) { asm volatile("mbarrier.init.shared::cta.b64 [%0], %1;" ::"r"(bar), "r"(cnt) : "memory"); }
__device__ __forceinline__ void mbar_expect(uint32_t bar, uint32_t bytes) { asm volatile("mbarrier.arrive.expect_tx.shared::cta.b64 _, [%0], %1;" ::"r"(bar), "r"(bytes) : "memory"); }
__device__ __forceinline__ bool mbar_try(uint32_t bar, uint32_t par) {
    uint32_t ok;
    asm volatile("{.reg .pred p; mbarrier.try_wait.parity.shared::cta.b64 p, [%1], %2; selp.u32 %0,1,0,p;}" : "=r"(ok) : "r"(bar), "r"(par) : "memory");
    return ok;
}
constexpr int SPIN_LIMIT = 1 << 18;
__device__ __forceinline__ void mbar_wait(uint32_t bar, uint32_t par) {
    if (mbar_try(bar, par)) return;
    int n = 0;
    while (!mbar_try(bar, par) && ++n < SPIN_LIMIT) {}
}
__device__ __forceinline__ void bulk_g2s(uint32_t dst, const void* src, uint32_t bytes, uint32_t bar) {
    asm volatile("cp.async.bulk.shared::cluster.global.mbarrier::complete_tx::bytes [%0], [%1], %2, [%3];" ::"r"(dst), "l"(src), "r"(bytes), "r"(bar) : "memory");
}
__device__ __forceinline__ void bulk_s2g(void* dst, uint32_t src, uint32_t bytes) {
    asm volatile("cp.async.bulk.global.shared::cta.bulk_group [%0], [%1], %2;" ::"l"(dst), "r"(src), "r"(bytes) : "memory");
}
__device__ __forceinline__ void bulk_prefetch(const void* src, uint32_t bytes) {
    asm volatile("cp.async.bulk.prefetch.L2.global [%0], %1;" ::"l"(src), "r"(bytes) : "memory");
}
__device__ __forceinline__ void tma2d(uint32_t dst, const CUtensorMap* m, int c0, int c1, uint32_t bar) {
    asm volatile("cp.async.bulk.tensor.2d.shared::cluster.global.mbarrier::complete_tx::bytes [%0], [%1, {%3, %4}], [%2];" ::"r"(dst), "l"(m), "r"(bar), "r"(c0), "r"(c1) : "memory");
}
__device__ __forceinline__ void tma2d_mc(uint32_t dst, const CUtensorMap* m, int c0, int c1, uint32_t bar) {
    asm volatile("cp.async.bulk.tensor.2d.shared::cluster.global.mbarrier::complete_tx::bytes.multicast::cluster [%0], [%1, {%3, %4}], [%2], %5;" ::"r"(dst), "l"(m), "r"(bar), "r"(c0), "r"(c1), "h"((uint16_t)3) : "memory");
}
__device__ __forceinline__ uint32_t mapa(uint32_t a, uint32_t rank) { uint32_t r; asm("mapa.shared::cluster.u32 %0, %1, %2;" : "=r"(r) : "r"(a), "r"(rank)); return r; }
__device__ __forceinline__ void mbar_arrive_cl(uint32_t bar) { asm volatile("mbarrier.arrive.shared::cluster.b64 _, [%0];" ::"r"(bar) : "memory"); }
__device__ __forceinline__ void prefetch_map(const CUtensorMap* m) { asm volatile("prefetch.tensormap [%0];" ::"l"(m) : "memory"); }
__device__ __forceinline__ void cpasync16(uint32_t dst, const void* src, uint32_t srcsz) {
    asm volatile("cp.async.cg.shared.global [%0], [%1], 16, %2;" ::"r"(dst), "l"(src), "r"(srcsz) : "memory");
}
__device__ __forceinline__ void bar_sync(int id, int n) { asm volatile("bar.sync %0, %1;" ::"r"(id), "r"(n) : "memory"); }
__device__ __forceinline__ void bar_arrive(int id, int n) { asm volatile("bar.arrive %0, %1;" ::"r"(id), "r"(n) : "memory"); }
__device__ __forceinline__ void fence_async_smem() { asm volatile("fence.proxy.async.shared::cta;" ::: "memory"); }
__device__ __forceinline__ void fence_async_global() { asm volatile("fence.proxy.async.global;" ::: "memory"); }
__device__ __forceinline__ void flag_release(int f) { asm volatile("red.release.gpu.global.add.u32 [%0], 1;" ::"l"(&g_flags[f * 32]) : "memory"); }
__device__ __forceinline__ void flag_wait(int f, unsigned target) {
    const unsigned* p = &g_flags[f * 32];
    unsigned v; int n = 0;
    do {
        asm volatile("ld.relaxed.gpu.global.u32 %0, [%1];" : "=r"(v) : "l"(p) : "memory");
    } while ((int)(v - target) < 0 && ++n < SPIN_LIMIT);
    asm volatile("fence.acquire.gpu;" ::: "memory");
}
__device__ __forceinline__ void flag_wait2(int f0, int f1, unsigned target) {
    unsigned v, w; int n = 0;
    do {
        asm volatile("ld.relaxed.gpu.global.u32 %0, [%1];" : "=r"(v) : "l"(&g_flags[f0 * 32]) : "memory");
        asm volatile("ld.relaxed.gpu.global.u32 %0, [%1];" : "=r"(w) : "l"(&g_flags[f1 * 32]) : "memory");
    } while ((int)((v - target) | (w - target)) < 0 && ++n < SPIN_LIMIT);
    asm volatile("fence.acquire.gpu;" ::: "memory");
}
__device__ __forceinline__ uint32_t lds32(uint32_t a) { uint32_t v; asm volatile("ld.shared.u32 %0, [%1];" : "=r"(v) : "r"(a)); return v; }
__device__ __forceinline__ float2 lds64f(uint32_t a) { float2 v; asm volatile("ld.shared.v2.f32 {%0,%1}, [%2];" : "=f"(v.x), "=f"(v.y) : "r"(a)); return v; }
__device__ __forceinline__ uint2 lds64(uint32_t a) { uint2 v; asm volatile("ld.shared.v2.u32 {%0,%1}, [%2];" : "=r"(v.x), "=r"(v.y) : "r"(a)); return v; }
__device__ __forceinline__ void sts64f(uint32_t a, float2 v) { asm volatile("st.shared.v2.f32 [%0], {%1,%2};" ::"r"(a), "f"(v.x), "f"(v.y) : "memory"); }
__device__ __forceinline__ void sts32(uint32_t a, uint32_t v) { asm volatile("st.shared.u32 [%0], %1;" ::"r"(a), "r"(v) : "memory"); }
__device__ __forceinline__ void sts64(uint32_t a, uint32_t x, uint32_t y) { asm volatile("st.shared.v2.u32 [%0], {%1,%2};" ::"r"(a), "r"(x), "r"(y) : "memory"); }
__device__ __forceinline__ void sts16(uint32_t a, uint16_t v) { asm volatile("st.shared.u16 [%0], %1;" ::"r"(a), "h"(v) : "memory"); }
__device__ __forceinline__ uint4 lds128(uint32_t a) { uint4 v; asm volatile("ld.shared.v4.u32 {%0,%1,%2,%3}, [%4];" : "=r"(v.x), "=r"(v.y), "=r"(v.z), "=r"(v.w) : "r"(a)); return v; }
__device__ __forceinline__ void sts128(uint32_t a, uint4 v) { asm volatile("st.shared.v4.u32 [%0], {%1,%2,%3,%4};" ::"r"(a), "r"(v.x), "r"(v.y), "r"(v.z), "r"(v.w) : "memory"); }
__device__ __forceinline__ void sts128f(uint32_t a, float x, float y, float z, float w) { asm volatile("st.shared.v4.f32 [%0], {%1,%2,%3,%4};" ::"r"(a), "f"(x), "f"(y), "f"(z), "f"(w) : "memory"); }
__device__ __forceinline__ uint32_t prmt(uint32_t a, uint32_t b, uint32_t s) { uint32_t r; asm("prmt.b32 %0,%1,%2,%3;" : "=r"(r) : "r"(a), "r"(b), "r"(s)); return r; }
__device__ __forceinline__ uint32_t pack2(float lo, float hi) { uint32_t r; asm("cvt.rn.bf16x2.f32 %0, %1, %2;" : "=r"(r) : "f"(hi), "f"(lo)); return r; }
__device__ __forceinline__ float blo(uint32_t v) { return __uint_as_float(v << 16); }
__device__ __forceinline__ float bhi(uint32_t v) { return __uint_as_float(v & 0xffff0000u); }
__device__ __forceinline__ uint32_t bmul2(uint32_t a, uint32_t b) { uint32_t r; asm("mul.rn.bf16x2 %0,%1,%2;" : "=r"(r) : "r"(a), "r"(b)); return r; }
__device__ __forceinline__ uint32_t badd2(uint32_t a, uint32_t b) { uint32_t r; asm("add.rn.bf16x2 %0,%1,%2;" : "=r"(r) : "r"(a), "r"(b)); return r; }
__device__ __forceinline__ float rbf(float x) { return __bfloat162float(__float2bfloat16_rn(x)); }
__device__ __forceinline__ uint32_t ldcg32(const void* p) { uint32_t v; asm volatile("ld.global.cg.u32 %0, [%1];" : "=r"(v) : "l"(p) : "memory"); return v; }
__device__ __forceinline__ uint4 ldcg128(const void* p) { uint4 v; asm volatile("ld.global.cg.v4.u32 {%0,%1,%2,%3}, [%4];" : "=r"(v.x), "=r"(v.y), "=r"(v.z), "=r"(v.w) : "l"(p) : "memory"); return v; }
__device__ __forceinline__ void stg32_if(void* p, uint32_t v, int on) { asm volatile("{.reg .pred q; setp.ne.b32 q, %2, 0; @q st.global.u32 [%0], %1;}" ::"l"(p), "r"(v), "r"(on) : "memory"); }
__device__ __forceinline__ uint2 ldcg64(const void* p) { uint2 v; asm volatile("ld.global.cg.v2.u32 {%0,%1}, [%2];" : "=r"(v.x), "=r"(v.y) : "l"(p) : "memory"); return v; }
__device__ __forceinline__ float gelu_h(float h) {
    float u = h * fmaf(h * h, 8.0f * 0.044715f * 0.7978845608028654f, 2.0f * 0.7978845608028654f);
    float th;
    asm("tanh.approx.f32 %0, %1;" : "=f"(th) : "f"(u));
    return fmaf(h, th, h);
}
__device__ __forceinline__ float gelu(float x) { return gelu_h(0.5f * x); }
__device__ __forceinline__ void ln_params(float sum, float sq, float& inv, float& nb) {
    float mean = sum * (1.0f / D_);
    float var = fmaxf(fmaf(-mean, mean, sq * (1.0f / D_)), 0.0f);
    float sq_;
    asm("sqrt.approx.f32 %0, %1;" : "=f"(sq_) : "f"(rbf(rbf(var) + 1e-5f)));
    inv = __fdividef(1.0f, rbf(sq_));
    nb = -rbf(mean) * inv;
}
__device__ __forceinline__ uint32_t bsub2(uint32_t a, uint32_t b) { uint32_t r; asm("sub.rn.bf16x2 %0,%1,%2;" : "=r"(r) : "r"(a), "r"(b)); return r; }
__device__ __forceinline__ uint32_t bfma2(uint32_t a, uint32_t b, uint32_t c) { uint32_t r; asm("fma.rn.bf16x2 %0,%1,%2,%3;" : "=r"(r) : "r"(a), "r"(b), "r"(c)); return r; }
__device__ __forceinline__ void mma_stat(float* d, uint32_t u, uint32_t v) {
    asm("mma.sync.aligned.m16n8k16.row.col.f32.bf16.bf16.f32 {%0,%1,%2,%3},{%4,%6,%5,%6},{%4,%5},{%0,%1,%2,%3};"
        : "+f"(d[0]), "+f"(d[1]), "+f"(d[2]), "+f"(d[3]) : "r"(u), "r"(v), "r"(0x3f803f80u));
}
__device__ __forceinline__ uint3 row_stats(const uint32_t* v, int lane) {
    float s = 0.f, q = 0.f, s_ = 0.f, q_ = 0.f;
#pragma unroll
    for (int i = 0; i < 10; i++) { float a = blo(v[i]), b = bhi(v[i]); s += a; s_ += b; q = fmaf(a, a, q); q_ = fmaf(b, b, q_); }
    s += s_; q += q_;
    {
        float t = __shfl_xor_sync(0xffffffffu, (lane & 16) ? s : q, 16);
        t += (lane & 16) ? q : s;
#pragma unroll
        for (int m = 8; m; m >>= 1) t += __shfl_xor_sync(0xffffffffu, t, m);
        float o = __shfl_xor_sync(0xffffffffu, t, 16);
        s = (lane & 16) ? o : t; q = (lane & 16) ? t : o;
    }
    float mean = s * (1.0f / D_);
    float var = fmaxf(fmaf(-mean, mean, q * (1.0f / D_)), 0.0f), sd;
    asm("sqrt.approx.f32 %0, %1;" : "=f"(sd) : "f"(rbf(rbf(var) + 1e-5f)));
    float inv = __fdividef(1.0f, rbf(sd));
    uint3 r;
    r.x = pack2(mean, mean);
    r.y = pack2(inv, inv);
    inv -= blo(r.y);
    r.z = pack2(inv, inv);
    return r;
}
__device__ __forceinline__ uint32_t ln_apply(uint32_t x, uint32_t m, uint32_t hi, uint32_t lo) {
    uint32_t xc = bsub2(x, m);
    return bfma2(xc, hi, bmul2(xc, lo));
}

struct AFrag { uint32_t m, a, b, c, d; };
__device__ __forceinline__ AFrag ldA(uint32_t a) { AFrag f; f.m = lds32(a - 16); f.a = lds32(a); f.b = lds32(a + 16); f.c = lds32(a + 32); f.d = lds32(a + 48); return f; }
template <int N, int M> __device__ __forceinline__ void conv_pair(float* d, const AFrag& f, uint32_t descU) {
    WgRs<N>::template run<8 * M, desc_hi(128, 0), 1>(d, f.a, f.b, f.m, f.a, descU);
    WgRs<N>::template run<8 * M + 1, desc_hi(128, 0), 1>(d, f.c, f.d, f.b, f.c, descU);
}
template <int Q> __device__ __forceinline__ void conv_put(float* d, uint32_t r0) {
    sts64(r0 + Q * 32, pack2(d[4 * Q + 1], d[4 * Q + 3]), pack2(d[4 * Q], d[4 * Q + 2]));
}
template <int M> __device__ __forceinline__ void conv_head(float* d, AFrag& f, uint32_t kaddr, uint32_t descU, uint32_t r0) {
    wg_fence();
    conv_pair<128 - 8 * M, M>(d, f, descU);
    wg_commit();
    if constexpr (M < 3) {
        wg_wait<0>();
        conv_put<15 - M>(d, r0);
        f = ldA(kaddr + 256 * (M + 1));
    } else {
        if constexpr (M > 3) conv_put<16 - M>(d, r0);
        AFrag n = ldA(kaddr + 256 * (M + 1));
        wg_wait<0>();
        f = n;
    }
    if constexpr (M < 7) conv_head<M + 1>(d, f, kaddr, descU, r0);
}
__device__ __forceinline__ void conv_main(float* d, uint32_t fm, uint32_t fa, uint32_t fb, uint32_t kaddr, uint32_t descU, uint32_t r0, bool handoff) {
    wg_fence();
    WgRs<128>::run<0, desc_hi(128, 0), 0>(d, fa, fb, fm, fa, descU);
    wg_commit();
    wg_wait<0>();
    fa = lds32(kaddr + 32); fb = lds32(kaddr + 48); fm = lds32(kaddr + 16);
    wg_fence();
    WgRs<128>::run<1, desc_hi(128, 0), 1>(d, fa, fb, fm, fa, descU);
    wg_commit();
    wg_wait<0>();
    conv_put<15>(d, r0);
    AFrag f = ldA(kaddr + 256);
    conv_head<1>(d, f, kaddr, descU, r0);
    if (STAG == 1 && handoff) bar_arrive(12, 256);
    AFrag f1 = ldA(kaddr + 256 * 9);
    wg_fence();
    conv_pair<64, 8>(d, f, descU); conv_pair<64, 9>(d, f1, descU);
    wg_commit();
    conv_put<8>(d, r0);
    AFrag f2 = ldA(kaddr + 256 * 10), f3 = ldA(kaddr + 256 * 11);
    wg_wait<0>();
    wg_fence();
    conv_pair<48, 10>(d, f2, descU); conv_pair<48, 11>(d, f3, descU);
    wg_commit();
    conv_put<7>(d, r0); conv_put<6>(d, r0);
    AFrag f4 = ldA(kaddr + 256 * 12), f5 = ldA(kaddr + 256 * 13), f6 = ldA(kaddr + 256 * 14), f7 = ldA(kaddr + 256 * 15);
    wg_wait<0>();
    wg_fence();
    conv_pair<32, 12>(d, f4, descU); conv_pair<32, 13>(d, f5, descU); conv_pair<32, 14>(d, f6, descU); conv_pair<32, 15>(d, f7, descU);
    wg_commit();
    if (STAG == 2 && handoff) bar_arrive(12, 256);
    conv_put<5>(d, r0); conv_put<4>(d, r0);
    wg_wait<0>();
    conv_put<3>(d, r0); conv_put<2>(d, r0); conv_put<1>(d, r0); conv_put<0>(d, r0);
}

template <int N, bool ASWZ, int SC0>
__device__ __forceinline__ void gemm_issue(float* acc, uint32_t bars, int sa, int pa, int sw, int pw, uint32_t da0, uint32_t db0) {
    mbar_wait(bars + (BAR_FB + sw) * 8, pw);
    mbar_wait(bars + (BAR_FA + sa) * 8, pa);
    const uint32_t da = da0 + sa * (SLOT >> 4), db = db0 + sw * (SLOT >> 4);
    constexpr int AK = ASWZ ? 2 : 256, AH = ASWZ ? desc_hi(1024, 1) : desc_hi(128, 0), BH = desc_hi(1024, 1);
    wg_fence();
    WgSs<N>::template run<0, AH, 0, BH, SC0>(acc, da, db);
    WgSs<N>::template run<AK, AH, 128, BH, 1>(acc, da, db);
    WgSs<N>::template run<2 * AK, AH, 256, BH, 1>(acc, da, db);
    WgSs<N>::template run<3 * AK, AH, 384, BH, 1>(acc, da, db);
    wg_commit();
}
template <int N, bool ASWZ, int IA0, int IB0, int NKB, int RELA, int RELB, bool ZERO, int WAIT_BAR, int ORDER_BAR, int TSID>
__device__ __forceinline__ void gemm_loop(float* acc, uint32_t sb, int half) {
    int sa = IA0 % NA, pa = (IA0 / NA) & 1, sw = IB0 % NB, pw = (IB0 / NB) & 1;
    const uint32_t bars = sb + SM_BAR;
    const int t = threadIdx.x & 127;
    uint32_t ebar = mapa(bars + (t < 2 ? BAR_EB : BAR_EA) * 8, (t < 2 && lds32(sb + SM_GV + 516)) ? t : blockIdx.x & 1);
    const int nrel = t < 2 ? RELB : t == 2 ? RELA : 0;
    const uint32_t da0 = ASWZ ? desc_lo(sb + SM_RA + half * 8192, 16) : desc_lo(sb + SM_RA + half * 1024, 2048), db0 = desc_lo(sb + SM_RB, 8192);
    asm volatile("" : "+r"(ebar));
    if (WAIT_BAR) bar_sync(WAIT_BAR, 512);
    gemm_issue<N, ASWZ, ZERO ? 0 : 1>(acc, bars, sa, pa, sw, pw, da0, db0);
    if ((threadIdx.x & 255) == 0) TS(TSID);
#pragma unroll 1
    for (int kb = 1; kb < NKB; kb++) {
        const int prev = t < 2 ? sw : sa;
        if (++sa == NA) { sa = 0; pa ^= 1; }
        if (++sw == NB) { sw = 0; pw ^= 1; }
        gemm_issue<N, ASWZ, 1>(acc, bars, sa, pa, sw, pw, da0, db0);
        if (ORDER_BAR && kb == NKB - 1) bar_arrive(ORDER_BAR, 512);
        wg_wait<1>();
        if (kb <= nrel) mbar_arrive_cl(ebar + prev * 8);
    }
    wg_wait<0>();
    if (nrel == NKB) mbar_arrive_cl(ebar + (t < 2 ? sw : sa) * 8);
    reg_fence<N / 2>(acc);
    if ((threadIdx.x & 255) == 0) TS(TSID + 1);
}

template <int N, int IA0, int IB0, int RELA, int WAIT_BAR, int ORDER_BAR, int BAR1>
__device__ __forceinline__ void gemm3(uint32_t sb, int rb, int pl0, int pl1, int half, int wq, int g, int c, unsigned ones) {
    float acc[N / 2];
    const int row = 64 * half + 16 * wq + g;
    float2 cr[N / 8];
    mbar_wait(sb + SM_BAR + BAR_CS * 8, 0);
#pragma unroll
    for (int q = 0; q < N / 8; q++) cr[q] = lds64f(sb + SM_CS + (N == 112 ? 0 : 448) + 8 * c + 32 * q);
    float inv0, nb0, inv1, nb1;
    if (N == 104) {
        mbar_wait(sb + SM_BAR + (BAR_FA + 20 % NA) * 8, (20 / NA) & 1);
        const float2* sp = &g_st[(rb * 8 + 2 * c) * 128 + row];
        const uint2 s0 = ldcg64(sp), s1 = ldcg64(sp + 128), s2 = ldcg64(sp + 8), s3 = ldcg64(sp + 136);
        float a0 = __uint_as_float(s0.x) + __uint_as_float(s1.x), b0 = __uint_as_float(s0.y) + __uint_as_float(s1.y);
        float a1 = __uint_as_float(s2.x) + __uint_as_float(s3.x), b1 = __uint_as_float(s2.y) + __uint_as_float(s3.y);
#pragma unroll
        for (int m = 1; m <= 2; m <<= 1) {
            a0 += __shfl_xor_sync(0xffffffffu, a0, m); b0 += __shfl_xor_sync(0xffffffffu, b0, m);
            a1 += __shfl_xor_sync(0xffffffffu, a1, m); b1 += __shfl_xor_sync(0xffffffffu, b1, m);
        }
        ln_params(a0, b0, inv0, nb0);
        ln_params(a1, b1, inv1, nb1);
        inv0 *= 0.5f; nb0 *= 0.5f; inv1 *= 0.5f; nb1 *= 0.5f;
        if (c == 0) sts128f(sb + SM_RP + ((threadIdx.x & 255) >> 2) * 16, inv0, nb0, inv1, nb1);
        bar_arrive(13, 512);
        TSD2(41, __float_as_uint(nb1));
    }
    constexpr int HO = N == 112 ? HO_A : HO_B;
    gemm_loop<N, false, IA0, IB0, 10, RELA, 10, true, WAIT_BAR, HO < 0 ? ORDER_BAR : 0, N == 112 ? 46 : 48>(acc, sb, half);
    if (N == 112) {
        bar_sync(13, 512);
        const uint4 rp = lds128(sb + SM_RP + ((threadIdx.x & 255) >> 2) * 16);
        inv0 = __uint_as_float(rp.x); nb0 = __uint_as_float(rp.y); inv1 = __uint_as_float(rp.z); nb1 = __uint_as_float(rp.w);
        TSD2(33, rp.w);
    }
    uint32_t* dst = reinterpret_cast<uint32_t*>(g_g) + ((size_t)rb * 216 + pl0) * 512 + row * 4 + c;
#pragma unroll
    for (int k = 0; k < N / 8; k += CH) {
        if (k == 8) dst += (pl1 - pl0 - 8) * 512;
        if (k == HO) bar_arrive(ORDER_BAR, 512);
        if (k == 2 || k == 6) { if ((threadIdx.x & 255) == 0) TS((N == 112 ? 55 : 59) + (k == 6)); }
        CHUNK(k) {
#pragma unroll
            for (int q = k; q < k + CH && q < N / 8; q++) {
                dst[q * 512] = pack2(gelu_h(fmaf(acc[4 * q], inv0, nb0 * cr[q].x)), gelu_h(fmaf(acc[4 * q + 1], inv0, nb0 * cr[q].y)));
                dst[q * 512 + 32] = pack2(gelu_h(fmaf(acc[4 * q + 2], inv1, nb1 * cr[q].x)), gelu_h(fmaf(acc[4 * q + 3], inv1, nb1 * cr[q].y)));
            }
        }
    }
    if (HO >= N / 8) bar_arrive(ORDER_BAR, 512);
    bar_arrive(BAR1, 288);
}

template <int NS, int BASE, int BF, int BE> struct Ring {
    uint32_t sb, st, ph;
    __device__ __forceinline__ uint32_t acquire(uint32_t bytes) {
        mbar_wait(sb + SM_BAR + BE * 8 + st * 8, ph);
        uint32_t fb = sb + SM_BAR + BF * 8 + st * 8;
        mbar_expect(fb, bytes);
        return fb;
    }
    __device__ __forceinline__ uint32_t slot() { return sb + BASE + st * SLOT; }
    __device__ __forceinline__ void next() { if (++st == NS) { st = 0; ph ^= 1; } }
    __device__ __forceinline__ void run2d(const CUtensorMap* m, int c1) {
#pragma unroll 1
        for (int c0 = 0; c0 < D_; c0 += 64) {
            uint32_t fb = acquire(SLOT);
            tma2d(slot(), m, c0, c1, fb);
            next();
        }
    }
    __device__ __forceinline__ void runw(bool paired, int rk, const CUtensorMap* ma, const CUtensorMap* mb, int ca, int cb, int c1, int n, uint32_t bytes) {
        if (paired) {
            const CUtensorMap* m = rk ? mb : ma;
            const int c0 = rk ? cb : ca;
#pragma unroll 1
            for (; n > 0; n--, c1 += 64) {
                uint32_t fb = acquire(bytes);
                tma2d_mc(slot() + 8192 * rk, m, c0, c1, fb);
                next();
            }
        } else {
#pragma unroll 1
            for (; n > 0; n--, c1 += 64) {
                uint32_t fb = acquire(bytes);
                tma2d(slot(), ma, ca, c1, fb);
                tma2d(slot() + 8192, mb, cb, c1, fb);
                next();
            }
        }
    }
    __device__ __forceinline__ void run1d(const char* src, int n) {
#pragma unroll 1
        for (; n > 0; n--) {
            uint32_t fb = acquire(SLOT);
            bulk_g2s(slot(), src, SLOT, fb);
            src += SLOT;
            next();
        }
    }
};

__global__ void __cluster_dims__(2, 1, 1) __launch_bounds__(NTHREADS, 1) fused_kernel(const __grid_constant__ Maps maps, const Params p) {
    extern __shared__ __align__(1024) unsigned char smem_raw[];
    const uint32_t sb = (smem_u32(smem_raw) + 1023u) & ~1023u;
#pragma unroll
    for (int i = 0; i < SEED; i++) asm volatile("{.reg .b32 t; mov.u32 t, %laneid;}");
    const uint32_t bars = sb + SM_BAR;
    const int tid = threadIdx.x, lane = tid & 31;
    const int warp = __shfl_sync(0xffffffffu, tid >> 5, 0);
    const int wg = warp >> 2, wq = warp & 3;
    unsigned smid;
    asm volatile("mov.u32 %0, %%smid;" : "=r"(smid));

    int gpc, idx;
    if (smid < 64) { gpc = (smid & 15) >> 1; idx = (smid >> 4) * 2 + (smid & 1); }
    else if (smid < 120) { int t = smid - 64; gpc = 1 + (t % 14) / 2; idx = 8 + (t / 14) * 2 + (smid & 1); }
    else if (smid < 124) { gpc = 0; idx = 16 + (smid - 120); }
    else { gpc = 0; idx = 8 + (smid - 124); }
    unsigned ep1 = 0;
    if (wg == 4 || idx >= 16) ep1 = *(volatile unsigned*)&g_epoch[smid] + 1;

    if (idx >= 16) {
        const int sp = idx - 16;
        if (tid == 32) { sts32(sb + SM_GV + 512, smid); asm volatile("fence.release.sync_restrict::shared::cta.cluster;" ::: "memory"); }
        asm volatile("barrier.cluster.arrive.relaxed.aligned;" ::: "memory");
        asm volatile("barrier.cluster.wait.aligned;" ::: "memory");
        if (tid == 0) {
            for (int i = 0; i < 4; i++) mbar_init(bars + i * 8, 1);
            asm volatile("fence.mbarrier_init.release.cluster;" ::: "memory");
        }
        if (warp == 0) { if (lane < 8) flag_wait(FL_P + lane, ep1 * 16); __syncwarp(); }
        __syncthreads();
        const int cq = tid % 54, rg = tid / 54;
        float a[8];
#pragma unroll
        for (int i = 0; i < 8; i++) a[i] = 0.f;
#pragma unroll 1
        for (int it = -4; it < 10; it++) {
            const uint32_t st = sb + (it & 3) * 55296, fb = bars + (it & 3) * 8;
            if (it >= 0) {
                mbar_wait(fb, (it >> 2) & 1);
                if (tid < 432) {
#pragma unroll
                    for (int i = 0; i < 8; i++) {
                        uint4 w = lds128(st + (cq >= 27 ? 27648 - 432 : 0) + (rg * 8 + i) * 432 + cq * 16);
                        a[0] += blo(w.x); a[1] += bhi(w.x); a[2] += blo(w.y); a[3] += bhi(w.y);
                        a[4] += blo(w.z); a[5] += bhi(w.z); a[6] += blo(w.w); a[7] += bhi(w.w);
                    }
                }
                __syncthreads();
            }
            if (it < 6 && warp == 19 && elect()) {
                mbar_expect(fb, 55296);
                tma2d(st, &maps.w3s, sp * 432, (it + 4) * 64, fb);
                tma2d(st + 27648, &maps.w3s, sp * 432 + 216, (it + 4) * 64, fb);
            }
        }
        if (tid < 432) {
            sts128f(sb + rg * 1728 + cq * 32, a[0], a[1], a[2], a[3]);
            sts128f(sb + rg * 1728 + cq * 32 + 16, a[4], a[5], a[6], a[7]);
        }
        __syncthreads();
        if (tid < 432) {
            float s = 0.f;
#pragma unroll
            for (int i = 0; i < 8; i++) s += __uint_as_float(lds32(sb + i * 1728 + tid * 4));
            g_cs[sp * 432 + tid] = s;
        }
        __syncthreads();
        if (tid == 0) { flag_release(FL_CS); g_epoch[smid] = ep1; TS(0); }
        if (warp == 0) TSFLUSH();
        return;
    }

    const int cta = gpc * 16 + idx;
    const int rb = 2 * gpc + (idx & 1), j = idx >> 1;
    const int g = lane >> 2, c = lane & 3;
    const int cm = 160 * (j >> 1) + 64 * (j & 1) + ((j & 2) ? 32 : 0), cr = 160 * (j >> 1) + 16 * (j & 1) + ((j & 2) ? 0 : 128);

    {
        const int r0 = 128 * idx;
        const char* kb = (const char*)(p.k + (size_t)r0 * D_ + 80 * gpc);
        const char* vb = (const char*)(p.v + (size_t)r0 * D_ + 80 * gpc);
#pragma unroll
        for (int i = 0; i < 2; i++) {
            int ch = tid + i * 640, row = ch / 10, cc = ch % 10;
            uint32_t so = (row >> 4) * 2576 + (row & 15) * 160 + cc * 16;
            cpasync16(sb + SM_PK + 2576 + so, kb + row * 1280 + cc * 16, 16);
            cpasync16(sb + SM_PV + so, vb + row * 1280 + cc * 16, 16);
        }
        if (tid < 30) {
            int row = tid / 10, cc = tid % 10;
            cpasync16(sb + SM_PK + (13 + row) * 160 + cc * 16, idx ? kb + (row - 3) * 1280 + cc * 16 : kb, idx ? 16 : 0);
        }
        asm volatile("cp.async.commit_group;" ::: "memory");
        const int h = warp / 10, pr = (warp % 10) * 4 + (lane >> 3), blk = lane & 7;
        const int ch = 80 * gpc + 2 * pr;
        const uint4 sw = __ldg(reinterpret_cast<const uint4*>(p.shift + ch * 4));
        if (tid == 0) {
            for (int i = 0; i < 12; i++) { mbar_init(bars + i * 8, 1); mbar_init(bars + (12 + i) * 8, i < NA ? 2 : 4); }
            for (int i = BAR_K; i <= BAR_XY; i++) mbar_init(bars + i * 8, i == BAR_XY ? 2 : 1);
            asm volatile("fence.mbarrier_init.release.cluster;" ::: "memory");
        }
        if (tid == 96) { sts32(sb + SM_GV + 512, smid); asm volatile("fence.release.sync_restrict::shared::cta.cluster;" ::: "memory"); }
        if (warp == 1 && lane < 13) prefetch_map(&maps.hn + lane);
        if (warp == 2 && lane < 20)
            sts128(sb + SM_K + (lane >> 2) * K_STRIDE + ((lane >> 1) & 1) * 4160 + (lane & 1) * 16, make_uint4(0, 0, 0, 0));
        if (warp >= 10) {
            sts128(sb + SM_U + (warp - 10) * U_PLANE + 2048 + lane * 16, make_uint4(0, 0, 0, 0));
        }
        asm volatile("barrier.cluster.arrive.relaxed.aligned;" ::: "memory");
        asm volatile("cp.async.wait_group 0;" ::: "memory");
        asm volatile("barrier.cluster.wait.aligned;" ::: "memory");
        if (tid == 32) {
            uint32_t peer;
            asm volatile("ld.shared::cluster.u32 %0, [%1];" : "=r"(peer) : "r"(mapa(sb + SM_GV + 512, (blockIdx.x & 1) ^ 1)) : "memory");
            sts32(sb + SM_GV + 516, peer == (smid ^ 1));
        }
        __syncthreads();
        if (warp == 0) TSW(1);
        if (warp == 4 && elect()) {
#pragma unroll
            for (int i = 0; i < 5; i++) {
                mbar_expect(bars + (BAR_K + i) * 8, 4096);
                bulk_g2s(sb + SM_K + i * K_STRIDE + 32, p.ssmk + (size_t)(cta * 5 + i) * S_, 4096, bars + (BAR_K + i) * 8);
            }
        }
        const uint32_t w0 = prmt(sw.x, sw.z, 0x5410), w1 = prmt(sw.x, sw.z, 0x7632), w2 = prmt(sw.y, sw.w, 0x5410), w3 = prmt(sw.y, sw.w, 0x7632);
        const uint32_t ka = sb + SM_PK + 2576 + blk * 2576 + h * 1280 + pr * 4;
        const uint32_t va = sb + SM_PV + blk * 2576 + h * 1280 + pr * 4;
        uint32_t kk[11], kv[8];
#pragma unroll
        for (int i = 0; i < 11; i++) kk[i] = lds32(ka + (i - 3) * 160 - ((i < 3 && h == 0) ? 16 : 0));
#pragma unroll
        for (int i = 0; i < 8; i++) {
            uint32_t t = badd2(badd2(badd2(bmul2(kk[i], w3), bmul2(kk[i + 1], w2)), bmul2(kk[i + 2], w1)), bmul2(kk[i + 3], w0));
            kv[i] = bmul2(t, lds32(va + i * 160));
        }
        uint4 o0, o1;
        o0.x = prmt(kv[1], kv[0], 0x5410); o0.y = prmt(kv[3], kv[2], 0x5410); o0.z = prmt(kv[5], kv[4], 0x5410); o0.w = prmt(kv[7], kv[6], 0x5410);
        o1.x = prmt(kv[1], kv[0], 0x7632); o1.y = prmt(kv[3], kv[2], 0x7632); o1.z = prmt(kv[5], kv[4], 0x7632); o1.w = prmt(kv[7], kv[6], 0x7632);
        uint4* dst = reinterpret_cast<uint4*>(g_kvT) + ch * 256 + h * 128 + (127 - (8 * idx + blk));
        if (warp >= 10) fence_async_smem();
        dst[0] = o0;
        dst[256] = o1;
    }

    const int rho = 8 * rb + j;

    if (wg == 4) {
        asm volatile("setmaxnreg.dec.sync.aligned.u32 32;");
        const bool paired = lds32(sb + SM_GV + 516);
        if (wq == 0) {
            bar_sync(13, 640);
            if (lane == 0) flag_release(FL_P + gpc);
            __syncwarp();
            TSW(2);
            flag_wait(FL_P + gpc, ep1 * 16);
            fence_async_global();
            TSW(3);
            if (elect()) {
#pragma unroll
                for (int i = 0; i < 5; i++) {
                    const char* us = (const char*)g_kvT + (size_t)(cta * 5 + i) * 4096;
                    mbar_expect(bars + (BAR_U + i) * 8, 4096);
                    bulk_g2s(sb + SM_U + i * U_STRIDE, us, 2048, bars + (BAR_U + i) * 8);
                    bulk_g2s(sb + SM_U + i * U_STRIDE + U_PLANE, us + 2048, 2048, bars + (BAR_U + i) * 8);
                }
            }
            __syncwarp();
            if (elect()) {
                if (cta < 120) {
                    mbar_expect(bars + BAR_WM * 8, 40960);
#pragma unroll
                    for (int i = 0; i < 5; i++) tma2d(sb + SM_WM + i * 8192, &maps.wm, cta * 32, i * 128, bars + BAR_WM * 8);
                }
                bulk_prefetch((const char*)p.q + cta * 20480, 20480);
                bulk_prefetch((const char*)p.w1 + cta * 6400, 6400);
                bulk_prefetch((const char*)p.w2 + cta * 6400, 6400);
            }
            __syncwarp();
        } else {
            bar_arrive(13, 640);
        }
        if (cta < 120) {
            float d[4];
            if (tid < 592) {
                const int t = tid - 512;
                mbar_wait(bars + BAR_U * 8, 0);
                uint4 cv = __ldg(reinterpret_cast<const uint4*>(p.c) + t);
                auto silu2 = [](uint32_t v) { float a = blo(v), b = bhi(v); return pack2(__fdividef(a, 1.0f + __expf(-a)), __fdividef(b, 1.0f + __expf(-b))); };
                sts128(sb + SM_Y + (t % 40) * 32 + (t / 40) * 16, make_uint4(silu2(cv.x), silu2(cv.y), silu2(cv.z), silu2(cv.w)));
                fence_async_smem();
            }
            bar_sync(5, 128);
            mbar_wait(bars + BAR_WM * 8, 0);
            if (wq == 3) TSW(50);
            const uint32_t da = desc_lo(sb + SM_WM, 20480), db = desc_lo(sb + SM_Y, 32);
            wg_fence();
#pragma unroll
            for (int k = 0; k < 20; k++)
                asm volatile("{.reg .pred p; .reg .b32 l,m; .reg .b64 da,db; setp.ne.b32 p,%10,0; add.u32 l,%4,%6; mov.b64 da,{l,%8}; add.u32 m,%5,%7; mov.b64 db,{m,%9};"
                             " wgmma.mma_async.sync.aligned.m64n8k16.f32.bf16.bf16 {%0,%1,%2,%3},da,db,p,1,1,1,0;}"
                             : "+f"(d[0]), "+f"(d[1]), "+f"(d[2]), "+f"(d[3])
                             : "r"(da), "r"(db), "r"(64 * k), "r"(4 * k), "n"(desc_hi(512, 2u)), "n"(desc_hi(128, 0)), "r"(k));
            wg_commit();
            wg_wait<0>();
            reg_fence<4>(d);
            if (c == 0) {
                sts32(sb + SM_GV + (16 * wq + g) * 4, __float_as_uint(wq < 2 ? d[0] : d[1]));
                sts32(sb + SM_GV + (16 * wq + g + 8) * 4, __float_as_uint(wq < 2 ? d[2] : d[3]));
            }
            bar_sync(5, 128);
            if (wq == 2) {
                g_mod[cta * 32 + lane] = __float2bfloat16_rn(__uint_as_float(lds32(sb + SM_GV + lane * 4)) + __uint_as_float(lds32(sb + SM_GV + 128 + lane * 4)));
                __syncwarp();
                if (lane == 0) flag_release(FL_M);
                TSW(4);
            }
        }
        if (wq == 2) {
            bar_arrive(7, 640);
            flag_wait(FL_M, ep1 * 120);
            fence_async_global();
            if (elect()) {
                mbar_expect(bars + BAR_M * 8, 7680);
                bulk_g2s(sb + SM_MOD, g_mod, 7680, bars + BAR_M * 8);
            }
            __syncwarp();
            TSW(51);
            bar_sync(8, 544);  if (lane == 0) { flag_release(FL_R + rb); TS(23); }  __syncwarp();
            bar_sync(15, 288); if (lane == 0) { flag_release(FL_B1 + rb); TS(27); } __syncwarp();
            bar_sync(12, 288); if (lane == 0) { flag_release(FL_B2 + rb); TS(31); } __syncwarp();
#pragma unroll 1
            for (int i = 0; i < 2; i++) { bar_sync(1 + i, 288); if (lane == 0) { TS(53 + i); flag_release(FL_G + 16 * i + rb); TS(57 + i); } __syncwarp(); }
            if (lane == 0) g_epoch[smid] = ep1;
            return;
        }
        bar_sync(7, 640);
        if (wq == 3) {
            if (lane == 0) { flag_release(FL_C); TS(20); }
            __syncwarp();
            bar_arrive(10, 160);
            flag_wait(FL_C, ep1 * 128);
            fence_async_global();
            TSW(21);
            if (elect()) {
                mbar_expect(bars + BAR_Y * 8, 20480);
                bulk_g2s(sb + SM_Y, g_yv + rho * 5120, 20480, bars + BAR_Y * 8);
            }
            __syncwarp();
            bar_arrive(9, 96);
        } else bar_sync(9, 96);
        if (wq == 1 && lane < 4 * NB) mbar_arrive_cl(mapa(bars + (BAR_EB + (lane >> 2)) * 8, paired ? lane & 1 : blockIdx.x & 1));
        if (elect()) {
            if (wq == 3) {
                mbar_expect(bars + BAR_XY * 8, 20480);
#pragma unroll 1
                for (int i = 0; i < 8; i++) {
                    bulk_g2s(sb + SM_YT + i * 2560, g_yv + (8 * rb + i) * 5120 + cm * 8, 2048, bars + BAR_XY * 8);
                    bulk_g2s(sb + SM_YT + i * 2560 + 2048, g_yv + (8 * rb + i) * 5120 + cr * 8, 512, bars + BAR_XY * 8);
                }
                mbar_wait(bars + BAR_FA * 8, 0);
                bulk_prefetch((const char*)p.w4 + cta * 17280, 17280);
                flag_wait(FL_CS, ep1 * 4);
                fence_async_global();
                mbar_expect(bars + BAR_CS * 8, 864);
                bulk_g2s(sb + SM_CS, g_cs + 64 * j, 256, bars + BAR_CS * 8);
                bulk_g2s(sb + SM_CS + 256, g_cs + 512 + 48 * j, 192, bars + BAR_CS * 8);
                bulk_g2s(sb + SM_CS + 448, g_cs + 896 + 64 * j, 256, bars + BAR_CS * 8);
                bulk_g2s(sb + SM_CS + 704, g_cs + 1408 + 40 * j, 160, bars + BAR_CS * 8);
            } else if (wq == 1) {
                Ring<NB, SM_RB, BAR_FB, BAR_EB> r{sb, 0, 0};
#pragma unroll 1
                for (int ph = 0; ph < 6; ph++) {
                    const CUtensorMap* ma = ph == 0 ? &maps.w1a : ph == 1 ? &maps.w2a : ph == 5 ? &maps.w4a : &maps.w3a;
                    const bool b3b = ph == 3 || ph == 4;
                    r.runw(paired, idx & 1, ma, ma + (b3b ? 2 : 1), ph == 2 ? 64 * j : b3b ? 896 + 64 * j : cm,
                           ph == 2 ? 512 + 48 * j : b3b ? 1408 + 40 * j : cr, ph == 3 ? (10 - NA) * 64 : 0,
                           ph == 5 ? 27 : ph == 3 ? NA : ph == 4 ? 10 - NA : 10, ph == 2 ? 14336 : b3b ? 13312 : 10240);
                }
            } else {
                Ring<NA, SM_RA, BAR_FA, BAR_EA> r{sb, 0, 0};
                mbar_expect(bars + BAR_XY * 8, 20480);
                tma2d(sb + SM_XT, &maps.xa, cm, rb * 128, bars + BAR_XY * 8);
                tma2d(sb + SM_XT2, &maps.xb, cr, rb * 128, bars + BAR_XY * 8);
                const int grp = j >> 1;
                const int delta = (grp & 1 ? 1 : -1) * (1 + (grp >> 1));
                const int nb = min(max(rb + (delta > 0 ? 1 : -1), 0), 15);
                flag_wait2(FL_R + nb, FL_R + rb, ep1 * 8);
                fence_async_global(); TS(24);
                r.run2d(&maps.hn, rb * 128 + delta);
                flag_wait(FL_B1 + rb, ep1 * 8); fence_async_global(); TS(28);
                r.run1d((const char*)g_h1 + (size_t)rb * 163840, 10);
                flag_wait(FL_B2 + rb, ep1 * 8); fence_async_global(); TS(32);
                r.run1d((const char*)g_x1 + (size_t)rb * 163840, 10);
                r.run1d((const char*)g_x1 + (size_t)rb * 163840, 10 - NA);
                const char* gs = (const char*)g_g + (size_t)rb * 442368;
#pragma unroll 1
                for (int i = 0; i < 2; i++) {
                    flag_wait(FL_G + 16 * i + rb, ep1 * 8); fence_async_global(); TS(36 + i);
                    const int n = 14 - i;
                    r.run1d(gs, n);
                    gs += n * SLOT;
                }
            }
        }
        return;
    }
    bar_arrive(13, 640);
    asm volatile("setmaxnreg.inc.sync.aligned.u32 112;");
    const int rrow = 16 * rho + (warp >> 1) + 8 * (warp & 1);

#pragma unroll 1
    for (int cc = wg; cc < 5; cc += 3) {
        if (cc == 3 && wg == 0) break;
        mbar_wait(bars + (BAR_K + cc) * 8, 0);
        uint32_t a = sb + SM_K + cc * K_STRIDE + 32 + (tid & 127) * 32;
        uint32_t pw = lds32(a - 4);
        uint4 x = lds128(a), y = lds128(a + 16), o;
        if ((tid & 127) == 0) {
            uint16_t k0 = __bfloat16_as_ushort(__float2bfloat16_rn(blo(x.x) + __bfloat162float(p.ssmD[cta * 5 + cc])));
            x.x = (x.x & 0xffff0000u) | k0;
            sts16(a, k0);
        }
        o.x = prmt(pw, x.x, 0x5432); o.y = prmt(x.x, x.y, 0x5432); o.z = prmt(x.y, x.z, 0x5432); o.w = prmt(x.z, x.w, 0x5432);
        sts128(a + 4160, o);
        o.x = prmt(x.w, y.x, 0x5432); o.y = prmt(y.x, y.y, 0x5432); o.z = prmt(y.y, y.z, 0x5432); o.w = prmt(y.z, y.w, 0x5432);
        sts128(a + 4176, o);
    }
    bar_sync(1 + wg, 128);
#pragma unroll 1
    for (int cc = wg; cc < 5; cc += 3) {
        if (cc == 3 && wg == 0) break;
        const uint32_t sK = sb + SM_K + cc * K_STRIDE, sU = sb + SM_U + cc * U_STRIDE;
        const uint32_t kaddr = sK + ((g & 1) ? 32 : 4192) + 4 * ((g >> 1) - c) + 64 * wq;
        const uint32_t fm = lds32(kaddr - 16), fa = lds32(kaddr), fb = lds32(kaddr + 16);
        if (STAG && cc == 3) bar_sync(12, 256);
        mbar_wait(bars + (BAR_U + cc) * 8, 0);
        if (wq == 0) TSW(5 + cc);
        float d[64];
        conv_main(d, fm, fa, fb, kaddr, desc_lo(sU, U_PLANE), sb + SM_RED + cc * RED_STRIDE + 32 + wq * 4352 + g * 544 + (c - wq) * 8, cc == 1);
        if (wq == 0) TSW(10 + cc);
        if (cc == 1) bar_arrive(6, 256);
    }
#pragma unroll 1
    for (int cc = wg == 1 ? 4 : wg;; cc++) {
        if (cc == 1) bar_sync(6, 256); else bar_sync(1 + wg, 128);
        const int ch = cta * 5 + cc;
        uint32_t* dst = g_yv + ch * 8 + ((g + (ch >> 2)) & 7);
        const uint32_t red = sb + SM_RED + cc * RED_STRIDE + 32 + g * 544 + (16 * wq + c) * 8;
        uint2 v[16];
#pragma unroll
        for (int q = 0; q < 4; q++)
#pragma unroll
            for (int w = 0; w < 4; w++) v[4 * q + w] = lds64(red + q * 32 + w * 4352);
#pragma unroll
        for (int w = 1; w < 4; w++)
            if (wq == 3 && c > 3 - w) v[12 + w] = make_uint2(0, 0);
#pragma unroll
        for (int q = 0; q < 4; q++) {
            const uint2 *u = v + 4 * q;
            uint32_t* o = dst + (size_t)(126 - 2 * (16 * wq + 4 * q + c)) * 5120;
            o[0] = pack2((blo(u[0].x) + blo(u[1].x)) + (blo(u[2].x) + blo(u[3].x)), (bhi(u[0].x) + bhi(u[1].x)) + (bhi(u[2].x) + bhi(u[3].x)));
            o[5120] = pack2((blo(u[0].y) + blo(u[1].y)) + (blo(u[2].y) + blo(u[3].y)), (bhi(u[0].y) + bhi(u[1].y)) + (bhi(u[2].y) + bhi(u[3].y)));
        }
        if (wq == 0) TSW(15 + cc);
        if (cc != 0) break;
    }
    fence_async_smem();
    bar_arrive(7, 640);

    const uint32_t one2 = 0x3f803f80u;
    const unsigned ones = p.ones;
    {
        uint32_t x[10], a[10], cb[10], sbv[10];
        const uint32_t* xr = reinterpret_cast<const uint32_t*>(p.q + (size_t)rrow * D_) + lane;
        if (wg == 1) bar_sync(10, 160);
#pragma unroll
        for (int i = 0; i < 10; i++) x[i] = __ldg(xr + 32 * i);
        const uint3 s1 = row_stats(x, lane);
        const int up = lane >> 4, gg = warp >> 1, e = warp & 1;
        const uint32_t ya = sb + SM_Y + lane * 64 + ((gg + (lane >> 1)) & 7) * 4;
        const uint32_t sel = (up ? 0x1054u : 0x5410u) + (e ? 0x2222u : 0u);
        const uint32_t ma = sb + SM_MOD + lane * 4;
        mbar_wait(bars + BAR_M * 8, 0);
#pragma unroll
        for (int i = 0; i < 10; i++) {
            uint32_t h = bfma2(ln_apply(x[i], s1.x, s1.y, s1.z), badd2(lds32(ma + 1280 + i * 128), one2), lds32(ma + i * 128));
            a[i] = bmul2(h, lds32(ma + 2560 + i * 128));
            sbv[i] = lds32(ma + 3840 + i * 128);
            cb[i] = badd2(lds32(ma + 5120 + i * 128), one2);
        }
        if (warp == 4) TSW(52);
#pragma unroll 1
        for (int pass = WARM ? 0 : 1; pass < 2; pass++) {
            if (pass) { mbar_wait(bars + BAR_Y * 8, 0); if (warp == 0) TSW(22); }
            uint32_t z[10];
#pragma unroll
            for (int i = 0; i < 10; i++) {
                uint32_t y0 = lds32(ya + i * 2048 + up * 32), y1 = lds32(ya + i * 2048 + (up ^ 1) * 32);
                z[i] = bfma2(a[i], prmt(y0, y1, sel), x[i]);
            }
            const uint3 s2 = row_stats(z, lane);
#pragma unroll
            for (int i = 0; i < 10; i++) z[i] = bfma2(ln_apply(z[i], s2.x, s2.y, s2.z), cb[i], sbv[i]);
            const uint3 s3 = row_stats(z, lane);
            uint32_t* o = reinterpret_cast<uint32_t*>(g_hn + (size_t)rrow * D_) + lane;
#pragma unroll
            for (int i = 0; i < 10; i++) stg32_if(o + 32 * i, ln_apply(z[i], s3.x, s3.y, s3.z), pass);
            if (lane < 2 && pass) g_rs[rrow * 2 + lane] = lane ? make_uint4(s2.x, s2.y, s2.z, 0) : make_uint4(s1.x, s1.y, s1.z, 0);
        }
        if (warp == 0) TSW(34);
        bar_arrive(8, 544);
    }

    const int half = wg & 1;
    const int row = 64 * half + 16 * wq + g;
    const int tw0 = (rb * 80 + (cm >> 3)) * 512 + row * 4 + c, tw1 = (rb * 80 + (cr >> 3) - 8) * 512 + row * 4 + c;
    const uint32_t park = sb + SM_Y + (tid & 255) * 16;
    const uint32_t ms0 = sb + SM_MOD + (cm + 2 * c) * 2, ms1 = sb + SM_MOD + (cr - 64 + 2 * c) * 2;
    if (wg >= 2) {
        {
            float acc[40];
            gemm_loop<80, true, 0, 0, 10, 10, 10, true, 0, 0, 25>(acc, sb, half);
#pragma unroll
            for (int k = 0; k < 10; k += CH) CHUNK(k) {
#pragma unroll
                for (int q = k; q < k + CH && q < 10; q++) {
                    uint32_t* dst = reinterpret_cast<uint32_t*>(g_h1) + (q < 8 ? tw0 : tw1);
                    dst[q * 512] = pack2(gelu(acc[4 * q]), gelu(acc[4 * q + 1]));
                    dst[q * 512 + 32] = pack2(gelu(acc[4 * q + 2]), gelu(acc[4 * q + 3]));
                }
            }
            bar_arrive(15, 288);
            bar_arrive(14, 512);
        }
        gemm3<112, 20, 20, 10 - NA, 11, 9, 1>(sb, rb, 8 * j, 64 + 6 * j, half, wq, g, c, ones);
        if (tid == 256) TS(35);
        {
            float acc[40];
            uint32_t gbv[10];
            uint4 bsv[5];
#pragma unroll
            for (int q = 0; q < 5; q++) { const uint32_t ms = q < 4 ? ms0 : ms1; gbv[2 * q] = lds32(ms + 6400 + q * 32); gbv[2 * q + 1] = lds32(ms + 6400 + q * 32 + 16); bsv[q] = lds128(park + q * 4096); }
            gemm_loop<80, false, 40 - NA, 40, 27, 27 - NA, 27 - NB, true, 10, 0, 42>(acc, sb, half);
            bf16* go = p.out + (size_t)(rb * 128 + row) * D_ + (c & 1) * 8 + (c >> 1) * 4;
#pragma unroll
            for (int q = 0; q < 5; q++) CHUNK(q) {
                const uint32_t g0 = gbv[2 * q], g1 = gbv[2 * q + 1];
                const uint4 bs = bsv[q];
#pragma unroll
                for (int r = 0; r < 2; r++) {
                    const uint32_t b0 = r ? bs.y : bs.x, b1 = r ? bs.w : bs.z;
                    uint32_t t0 = pack2(fmaf(blo(g0), acc[8 * q + 2 * r], blo(b0)), fmaf(bhi(g0), acc[8 * q + 2 * r + 1], bhi(b0)));
                    uint32_t t1 = pack2(fmaf(blo(g1), acc[8 * q + 4 + 2 * r], blo(b1)), fmaf(bhi(g1), acc[8 * q + 4 + 2 * r + 1], bhi(b1)));
                    uint32_t rv = __shfl_xor_sync(0xffffffffu, (c & 1) ? t0 : t1, 1);
                    *reinterpret_cast<uint2*>(go + r * 8 * D_ + (q < 4 ? cm + 16 * q : cr)) = (c & 1) ? make_uint2(rv, t1) : make_uint2(t0, rv);
                }
            }
            if (tid == 256) TS(44);
            if (warp == 8) TSFLUSH();
        }
    } else {
        {
            float acc[40];
            uint32_t x2[20];
            {
                uint32_t y[20];
                mbar_wait(bars + BAR_XY * 8, 0);
                const uint32_t xa = sb + SM_XT + row * 128 + c * 4, xb = sb + SM_XT2 + row * 32 + c * 4;
                const uint32_t ya = sb + SM_YT + (4 * half + wq) * 2560 + c * 64;
#pragma unroll
                for (int q = 0; q < 10; q++) {
                    const uint32_t a = q < 8 ? xa + ((q ^ g) << 4) : xb + (q - 8) * 16;
                    x2[2 * q] = lds32(a); x2[2 * q + 1] = lds32(a + (q < 8 ? 1024 : 256));
                    const int pos = (g + ((q < 8 ? cm : cr) >> 2) + 2 * q + (c >> 1)) & 7;
                    y[2 * q] = lds32(ya + q * 256 + pos * 4); y[2 * q + 1] = lds32(ya + q * 256 + 32 + pos * 4);
                }
                fence_async_smem();
                bar_sync(1 + wg, 128);
                if ((tid & 127) < NA) mbar_arrive_cl(mapa(bars + (BAR_EA + (tid & 127)) * 8, blockIdx.x & 1));
                mbar_wait(bars + BAR_FA * 8, 0);
                const uint4* rp = g_rs + (rb * 128 + row) * 2;
                const uint4 ra = ldcg128(rp), rb2 = ldcg128(rp + 1), rc = ldcg128(rp + 16), rd = ldcg128(rp + 17);
                bar_sync(14, 512);
#pragma unroll
                for (int q = 0; q < 10; q++) {
                    const uint32_t ms = q < 8 ? ms0 : ms1;
                    const uint32_t sa = lds32(ms + 16 * q), ca = badd2(lds32(ms + 1280 + 16 * q), one2), ga = lds32(ms + 2560 + 16 * q);
                    const uint32_t sbv = lds32(ms + 3840 + 16 * q), cb = badd2(lds32(ms + 5120 + 16 * q), one2);
                    uint32_t u = x2[2 * q], v = x2[2 * q + 1];
                    u = bfma2(bmul2(bfma2(ln_apply(u, ra.x, ra.y, ra.z), ca, sa), ga), prmt(y[2 * q], y[2 * q + 1], 0x5410), u);
                    v = bfma2(bmul2(bfma2(ln_apply(v, rc.x, rc.y, rc.z), ca, sa), ga), prmt(y[2 * q], y[2 * q + 1], 0x7632), v);
                    x2[2 * q] = u; x2[2 * q + 1] = v;
                    u = bfma2(ln_apply(u, rb2.x, rb2.y, rb2.z), cb, sbv);
                    v = bfma2(ln_apply(v, rd.x, rd.y, rd.z), cb, sbv);
                    acc[4 * q] = blo(u); acc[4 * q + 1] = bhi(u); acc[4 * q + 2] = blo(v); acc[4 * q + 3] = bhi(v);
                }
            }
            reg_fence<40>(acc);
            if (tid == 0) TS(45);
            gemm_loop<80, false, 10, 10, 10, 10, 10, false, 0, 11, 29>(acc, sb, half);
            uint32_t x1[20];
            float s0 = 0.f, q0 = 0.f, s1 = 0.f, q1 = 0.f;
#pragma unroll
            for (int q = 0; q < 10; q++) {
                uint32_t u = pack2(acc[4 * q], acc[4 * q + 1]);
                uint32_t v = pack2(acc[4 * q + 2], acc[4 * q + 3]);
                uint32_t* dst = reinterpret_cast<uint32_t*>(g_x1) + (q < 8 ? tw0 : tw1);
                dst[q * 512] = u;
                dst[q * 512 + 32] = v;
                x1[2 * q] = u; x1[2 * q + 1] = v;
            }
            CHUNK(0)
#pragma unroll
            for (int q = 0; q < 10; q++) {
                float a = blo(x1[2 * q]), b = bhi(x1[2 * q]), e = blo(x1[2 * q + 1]), f = bhi(x1[2 * q + 1]);
                s0 += a + b; q0 = fmaf(a, a, fmaf(b, b, q0));
                s1 += e + f; q1 = fmaf(e, e, fmaf(f, f, q1));
            }
#pragma unroll
            for (int m = 1; m <= 2; m <<= 1) {
                s0 += __shfl_xor_sync(0xffffffffu, s0, m); q0 += __shfl_xor_sync(0xffffffffu, q0, m);
                s1 += __shfl_xor_sync(0xffffffffu, s1, m); q1 += __shfl_xor_sync(0xffffffffu, q1, m);
            }
            if (c < 2) g_st[(rb * 8 + j) * 128 + row + 8 * c] = c ? make_float2(s1, q1) : make_float2(s0, q0);
            bar_arrive(12, 288);
#pragma unroll
            for (int q = 0; q < 5; q++) {
                const uint32_t ms = q < 4 ? ms0 : ms1;
                const uint32_t g0 = lds32(ms + 6400 + q * 32), g1 = lds32(ms + 6400 + q * 32 + 16);
                sts128(park + q * 4096, make_uint4(bfma2(g0, x1[4 * q], x2[4 * q]), bfma2(g0, x1[4 * q + 1], x2[4 * q + 1]),
                                                   bfma2(g1, x1[4 * q + 2], x2[4 * q + 2]), bfma2(g1, x1[4 * q + 3], x2[4 * q + 3])));
            }
        }
        gemm3<104, 30 - NA, 30, 10, 9, 10, 2>(sb, rb, 112 + 8 * j, 176 + 5 * j, half, wq, g, c, ones);
        if (tid == 0) TS(38);
    }
}

typedef CUresult (*EncFn)(CUtensorMap*, CUtensorMapDataType, cuuint32_t, void*, const cuuint64_t*, const cuuint64_t*,
                          const cuuint32_t*, const cuuint32_t*, CUtensorMapInterleave, CUtensorMapSwizzle,
                          CUtensorMapL2promotion, CUtensorMapFloatOOBfill);

void make_map(EncFn enc, CUtensorMap* m, const void* base, uint64_t inner, uint64_t outer, uint32_t bi, uint32_t bo,
              CUtensorMapSwizzle swz = CU_TENSOR_MAP_SWIZZLE_128B) {
    cuuint64_t dims[2] = {inner, outer};
    cuuint64_t st[1] = {inner * 2};
    cuuint32_t box[2] = {bi, bo};
    cuuint32_t es[2] = {1, 1};
    enc(m, CU_TENSOR_MAP_DATA_TYPE_BFLOAT16, 2, const_cast<void*>(base), dims, st, box, es, CU_TENSOR_MAP_INTERLEAVE_NONE,
        swz, CU_TENSOR_MAP_L2_PROMOTION_NONE, CU_TENSOR_MAP_FLOAT_OOB_FILL_NONE);
}

}

extern "C" void kernel_launch(void* const* d_in, const int* in_sizes, int n_in, void* d_out, int out_size) {
    (void)in_sizes; (void)n_in; (void)out_size;
    Params p;
    p.q = (const bf16*)d_in[0]; p.k = (const bf16*)d_in[1]; p.v = (const bf16*)d_in[2];
    p.shift = (const bf16*)d_in[3]; p.ssmk = (const bf16*)d_in[4]; p.ssmD = (const bf16*)d_in[5];
    p.w1 = (const bf16*)d_in[7]; p.w2 = (const bf16*)d_in[8]; p.w3 = (const bf16*)d_in[9]; p.w4 = (const bf16*)d_in[10];
    p.c = (const bf16*)d_in[11]; p.wmod = (const bf16*)d_in[12];
    p.out = (bf16*)d_out;
    p.ones = 0xffffffffu;

    void* fn = nullptr;
    cudaDriverEntryPointQueryResult qr;
    cudaGetDriverEntryPoint("cuTensorMapEncodeTiled", &fn, cudaEnableDefault, &qr);
    EncFn enc = (EncFn)fn;
    void* hn = nullptr;
    cudaGetSymbolAddress(&hn, g_hn);
    Maps maps;
    make_map(enc, &maps.w3s, p.w3, F_, D_, 216, 64, CU_TENSOR_MAP_SWIZZLE_NONE);
    make_map(enc, &maps.wm, p.wmod, 6 * D_, D_, 32, 128, CU_TENSOR_MAP_SWIZZLE_64B);
    make_map(enc, &maps.xa, p.q, D_, S_, 64, 128);
    make_map(enc, &maps.xb, p.q, D_, S_, 16, 128, CU_TENSOR_MAP_SWIZZLE_NONE);
    make_map(enc, &maps.hn, hn, D_, S_, 64, 128);
    make_map(enc, &maps.w1a, p.w1, D_, D_, 64, 64);
    make_map(enc, &maps.w1b, p.w1, D_, D_, 16, 64);
    make_map(enc, &maps.w2a, p.w2, D_, D_, 64, 64);
    make_map(enc, &maps.w2b, p.w2, D_, D_, 16, 64);
    make_map(enc, &maps.w3a, p.w3, F_, D_, 64, 64);
    make_map(enc, &maps.w3b, p.w3, F_, D_, 48, 64);
    make_map(enc, &maps.w3c, p.w3, F_, D_, 40, 64);
    make_map(enc, &maps.w4a, p.w4, D_, F_, 64, 64);
    make_map(enc, &maps.w4b, p.w4, D_, F_, 16, 64);
    cudaFuncSetAttribute(fused_kernel, cudaFuncAttributeMaxDynamicSharedMemorySize, SMEM_BYTES);
    fused_kernel<<<132, NTHREADS, SMEM_BYTES>>>(maps, p);
}
```

```cpp
#include <cuda_runtime.h>
#include <cuda_bf16.h>
#include <cuda.h>
#include <stdint.h>
#include <string.h>

#define SEED 2
#define RING_A 6
#define MMA_STAT 0
#define CH 2
#define WARM 0
#define EXPER 0
#define HO_A 10
#define HO_B 6
#define HOLD 1
#define STAG 0
#define SSM_WHEN 1
#define PF_EARLY 0

namespace {

typedef __nv_bfloat16 bf16;
typedef __nv_bfloat162 bf162;

constexpr int S_ = 2048, D_ = 640, F_ = 1728;
constexpr int NTHREADS = 640;
constexpr int NA = RING_A, NB = 12 - RING_A;
constexpr int SLOT = 16384;
constexpr int SM_RA = 0, SM_RB = NA * SLOT;

constexpr int SM_RED = 0;
constexpr int RED_STRIDE = 17536;
constexpr int SM_PK = 0;
constexpr int SM_PV = 24576;
constexpr int SM_WM = 88064;
constexpr int SM_K = SM_WM + 40960;
constexpr int K_STRIDE = 8320;
constexpr int SM_U = SM_K + 5 * K_STRIDE;
constexpr int U_PLANE = 2560, U_STRIDE = 5120;
constexpr int SM_Y = 12 * SLOT;
static_assert(SM_U + 5 * U_STRIDE <= SM_Y, "smem map");
constexpr int SM_XT = 3 * SLOT, SM_XT2 = 4 * SLOT, SM_YT = SM_XT2 + 4096;
constexpr int SM_MOD = SM_Y + 20480;
constexpr int SM_GV = SM_MOD + 7680;
constexpr int SM_CS = SM_GV + 1024;
constexpr int SM_RP = SM_CS + 1024;
constexpr int SM_BAR = SM_RP + 1024;
constexpr int SM_PROF = SM_BAR + 512;
constexpr int SM_TOTAL = SM_PROF + 512;
constexpr int SMEM_BYTES = SM_TOTAL + 1024;
static_assert(SMEM_BYTES <= 232448, "smem");

constexpr int BAR_FA = 0, BAR_FB = NA, BAR_EA = 12, BAR_EB = 12 + NA, BAR_K = 24, BAR_U = 29, BAR_Y = 34, BAR_CS = 35, BAR_WM = 36, BAR_M = 37, BAR_XY = 38;

__device__ __align__(1024) bf16 g_kvT[D_ * S_];
__device__ __align__(1024) uint32_t g_yv[128 * 5120];
__device__ __align__(1024) bf16 g_mod[6 * D_];
__device__ __align__(1024) bf16 g_hn[S_ * D_];
__device__ __align__(1024) uint4 g_rs[S_ * 2];
__device__ __align__(1024) bf16 g_h1[S_ * D_];
__device__ __align__(1024) bf16 g_x1[S_ * D_];
__device__ __align__(1024) bf16 g_g[S_ * F_];
__device__ __align__(1024) float2 g_st[S_ * 8];
__device__ __align__(1024) float g_cs[F_];
__device__ __align__(1024) unsigned g_flags[128 * 32];
__device__ __align__(1024) unsigned g_epoch[160];
constexpr int FL_P = 0, FL_C = 8, FL_CS = 9, FL_M = 10, FL_R = 16, FL_B1 = 32, FL_B2 = 48, FL_G = 64;

#define TS(i) do {} while (0)
#define TSW(i) do {} while (0)
#define TSD(i, dep) do {} while (0)
#define TSD2(i, dep) do {} while (0)
#define TSFLUSH() do {} while (0)

struct Params {
    const bf16 *q, *k, *v, *shift, *ssmk, *ssmD, *w1, *w2, *w3, *w4, *c, *wmod;
    bf16* out;
    unsigned ones;
};
#define CHUNK(k) if (ones & (1u << (k)))
struct Maps { CUtensorMap hn, w1a, w1b, w2a, w2b, w3a, w3b, w3c, w4a, w4b, wm, xa, xb, w3s; };

template<int N> struct WgRs;
template<int N> struct WgSs;
template<> struct WgRs<32> { template<int OFF,int HI,int SC> static __device__ __forceinline__ void run(float* d,uint32_t a0,uint32_t a1,uint32_t a2,uint32_t a3,uint32_t blo){
 asm volatile("{.reg .b32 l; .reg .b64 db; add.u32 l,%20,%21; mov.b64 db,{l,%22}; wgmma.mma_async.sync.aligned.m64n32k16.f32.bf16.bf16 {%0,%1,%2,%3,%4,%5,%6,%7,%8,%9,%10,%11,%12,%13,%14,%15},{%16,%17,%18,%19},db,%23,1,1,0;}"
 :"+f"(d[0]),"+f"(d[1]),"+f"(d[2]),"+f"(d[3]),"+f"(d[4]),"+f"(d[5]),"+f"(d[6]),"+f"(d[7]),"+f"(d[8]),"+f"(d[9]),"+f"(d[10]),"+f"(d[11]),"+f"(d[12]),"+f"(d[13]),"+f"(d[14]),"+f"(d[15])
 :"r"(a0),"r"(a1),"r"(a2),"r"(a3),"r"(blo),"n"(OFF),"n"(HI),"n"(SC)); } };
template<> struct WgRs<48> { template<int OFF,int HI,int SC> static __device__ __forceinline__ void run(float* d,uint32_t a0,uint32_t a1,uint32_t a2,uint32_t a3,uint32_t blo){
 asm volatile("{.reg .b32 l; .reg .b64 db; add.u32 l,%28,%29; mov.b64 db,{l,%30}; wgmma.mma_async.sync.aligned.m64n48k16.f32.bf16.bf16 {%0,%1,%2,%3,%4,%5,%6,%7,%8,%9,%10,%11,%12,%13,%14,%15,%16,%17,%18,%19,%20,%21,%22,%23},{%24,%25,%26,%27},db,%31,1,1,0;}"
 :"+f"(d[0]),"+f"(d[1]),"+f"(d[2]),"+f"(d[3]),"+f"(d[4]),"+f"(d[5]),"+f"(d[6]),"+f"(d[7]),"+f"(d[8]),"+f"(d[9]),"+f"(d[10]),"+f"(d[11]),"+f"(d[12]),"+f"(d[13]),"+f"(d[14]),"+f"(d[15]),"+f"(d[16]),"+f"(d[17]),"+f"(d[18]),"+f"(d[19]),"+f"(d[20]),"+f"(d[21]),"+f"(d[22]),"+f"(d[23])
 :"r"(a0),"r"(a1),"r"(a2),"r"(a3),"r"(blo),"n"(OFF),"n"(HI),"n"(SC)); } };
template<> struct WgRs<64> { template<int OFF,int HI,int SC> static __device__ __forceinline__ void run(float* d,uint32_t a0,uint32_t a1,uint32_t a2,uint32_t a3,uint32_t blo){
 asm volatile("{.reg .b32 l; .reg .b64 db; add.u32 l,%36,%37; mov.b64 db,{l,%38}; wgmma.mma_async.sync.aligned.m64n64k16.f32.bf16.bf16 {%0,%1,%2,%3,%4,%5,%6,%7,%8,%9,%10,%11,%12,%13,%14,%15,%16,%17,%18,%19,%20,%21,%22,%23,%24,%25,%26,%27,%28,%29,%30,%31},{%32,%33,%34,%35},db,%39,1,1,0;}"
 :"+f"(d[0]),"+f"(d[1]),"+f"(d[2]),"+f"(d[3]),"+f"(d[4]),"+f"(d[5]),"+f"(d[6]),"+f"(d[7]),"+f"(d[8]),"+f"(d[9]),"+f"(d[10]),"+f"(d[11]),"+f"(d[12]),"+f"(d[13]),"+f"(d[14]),"+f"(d[15]),"+f"(d[16]),"+f"(d[17]),"+f"(d[18]),"+f"(d[19]),"+f"(d[20]),"+f"(d[21]),"+f"(d[22]),"+f"(d[23]),"+f"(d[24]),"+f"(d[25]),"+f"(d[26]),"+f"(d[27]),"+f"(d[28]),"+f"(d[29]),"+f"(d[30]),"+f"(d[31])
 :"r"(a0),"r"(a1),"r"(a2),"r"(a3),"r"(blo),"n"(OFF),"n"(HI),"n"(SC)); } };
template<> struct WgRs<72> { template<int OFF,int HI,int SC> static __device__ __forceinline__ void run(float* d,uint32_t a0,uint32_t a1,uint32_t a2,uint32_t a3,uint32_t blo){
 asm volatile("{.reg .b32 l; .reg .b64 db; add.u32 l,%40,%41; mov.b64 db,{l,%42}; wgmma.mma_async.sync.aligned.m64n72k16.f32.bf16.bf16 {%0,%1,%2,%3,%4,%5,%6,%7,%8,%9,%10,%11,%12,%13,%14,%15,%16,%17,%18,%19,%20,%21,%22,%23,%24,%25,%26,%27,%28,%29,%30,%31,%32,%33,%34,%35},{%36,%37,%38,%39},db,%43,1,1,0;}"
 :"+f"(d[0]),"+f"(d[1]),"+f"(d[2]),"+f"(d[3]),"+f"(d[4]),"+f"(d[5]),"+f"(d[6]),"+f"(d[7]),"+f"(d[8]),"+f"(d[9]),"+f"(d[10]),"+f"(d[11]),"+f"(d[12]),"+f"(d[13]),"+f"(d[14]),"+f"(d[15]),"+f"(d[16]),"+f"(d[17]),"+f"(d[18]),"+f"(d[19]),"+f"(d[20]),"+f"(d[21]),"+f"(d[22]),"+f"(d[23]),"+f"(d[24]),"+f"(d[25]),"+f"(d[26]),"+f"(d[27]),"+f"(d[28]),"+f"(d[29]),"+f"(d[30]),"+f"(d[31]),"+f"(d[32]),"+f"(d[33]),"+f"(d[34]),"+f"(d[35])
 :"r"(a0),"r"(a1),"r"(a2),"r"(a3),"r"(blo),"n"(OFF),"n"(HI),"n"(SC)); } };
template<> struct WgRs<80> { template<int OFF,int HI,int SC> static __device__ __forceinline__ void run(float* d,uint32_t a0,uint32_t a1,uint32_t a2,uint32_t a3,uint32_t blo){
 asm volatile("{.reg .b32 l; .reg .b64 db; add.u32 l,%44,%45; mov.b64 db,{l,%46}; wgmma.mma_async.sync.aligned.m64n80k16.f32.bf16.bf16 {%0,%1,%2,%3,%4,%5,%6,%7,%8,%9,%10,%11,%12,%13,%14,%15,%16,%17,%18,%19,%20,%21,%22,%23,%24,%25,%26,%27,%28,%29,%30,%31,%32,%33,%34,%35,%36,%37,%38,%39},{%40,%41,%42,%43},db,%47,1,1,0;}"
 :"+f"(d[0]),"+f"(d[1]),"+f"(d[2]),"+f"(d[3]),"+f"(d[4]),"+f"(d[5]),"+f"(d[6]),"+f"(d[7]),"+f"(d[8]),"+f"(d[9]),"+f"(d[10]),"+f"(d[11]),"+f"(d[12]),"+f"(d[13]),"+f"(d[14]),"+f"(d[15]),"+f"(d[16]),"+f"(d[17]),"+f"(d[18]),"+f"(d[19]),"+f"(d[20]),"+f"(d[21]),"+f"(d[22]),"+f"(d[23]),"+f"(d[24]),"+f"(d[25]),"+f"(d[26]),"+f"(d[27]),"+f"(d[28]),"+f"(d[29]),"+f"(d[30]),"+f"(d[31]),"+f"(d[32]),"+f"(d[33]),"+f"(d[34]),"+f"(d[35]),"+f"(d[36]),"+f"(d[37]),"+f"(d[38]),"+f"(d[39])
 :"r"(a0),"r"(a1),"r"(a2),"r"(a3),"r"(blo),"n"(OFF),"n"(HI),"n"(SC)); } };
template<> struct WgRs<88> { template<int OFF,int HI,int SC> static __device__ __forceinline__ void run(float* d,uint32_t a0,uint32_t a1,uint32_t a2,uint32_t a3,uint32_t blo){
 asm volatile("{.reg .b32 l; .reg .b64 db; add.u32 l,%48,%49; mov.b64 db,{l,%50}; wgmma.mma_async.sync.aligned.m64n88k16.f32.bf16.bf16 {%0,%1,%2,%3,%4,%5,%6,%7,%8,%9,%10,%11,%12,%13,%14,%15,%16,%17,%18,%19,%20,%21,%22,%23,%24,%25,%26,%27,%28,%29,%30,%31,%32,%33,%34,%35,%36,%37,%38,%39,%40,%41,%42,%43},{%44,%45,%46,%47},db,%51,1,1,0;}"
 :"+f"(d[0]),"+f"(d[1]),"+f"(d[2]),"+f"(d[3]),"+f"(d[4]),"+f"(d[5]),"+f"(d[6]),"+f"(d[7]),"+f"(d[8]),"+f"(d[9]),"+f"(d[10]),"+f"(d[11]),"+f"(d[12]),"+f"(d[13]),"+f"(d[14]),"+f"(d[15]),"+f"(d[16]),"+f"(d[17]),"+f"(d[18]),"+f"(d[19]),"+f"(d[20]),"+f"(d[21]),"+f"(d[22]),"+f"(d[23]),"+f"(d[24]),"+f"(d[25]),"+f"(d[26]),"+f"(d[27]),"+f"(d[28]),"+f"(d[29]),"+f"(d[30]),"+f"(d[31]),"+f"(d[32]),"+f"(d[33]),"+f"(d[34]),"+f"(d[35]),"+f"(d[36]),"+f"(d[37]),"+f"(d[38]),"+f"(d[39]),"+f"(d[40]),"+f"(d[41]),"+f"(d[42]),"+f"(d[43])
 :"r"(a0),"r"(a1),"r"(a2),"r"(a3),"r"(blo),"n"(OFF),"n"(HI),"n"(SC)); } };
template<> struct WgRs<96> { template<int OFF,int HI,int SC> static __device__ __forceinline__ void run(float* d,uint32_t a0,uint32_t a1,uint32_t a2,uint32_t a3,uint32_t blo){
 asm volatile("{.reg .b32 l; .reg .b64 db; add.u32 l,%52,%53; mov.b64 db,{l,%54}; wgmma.mma_async.sync.aligned.m64n96k16.f32.bf16.bf16 {%0,%1,%2,%3,%4,%5,%6,%7,%8,%9,%10,%11,%12,%13,%14,%15,%16,%17,%18,%19,%20,%21,%22,%23,%24,%25,%26,%27,%28,%29,%30,%31,%32,%33,%34,%35,%36,%37,%38,%39,%40,%41,%42,%43,%44,%45,%46,%47},{%48,%49,%50,%51},db,%55,1,1,0;}"
 :"+f"(d[0]),"+f"(d[1]),"+f"(d[2]),"+f"(d[3]),"+f"(d[4]),"+f"(d[5]),"+f"(d[6]),"+f"(d[7]),"+f"(d[8]),"+f"(d[9]),"+f"(d[10]),"+f"(d[11]),"+f"(d[12]),"+f"(d[13]),"+f"(d[14]),"+f"(d[15]),"+f"(d[16]),"+f"(d[17]),"+f"(d[18]),"+f"(d[19]),"+f"(d[20]),"+f"(d[21]),"+f"(d[22]),"+f"(d[23]),"+f"(d[24]),"+f"(d[25]),"+f"(d[26]),"+f"(d[27]),"+f"(d[28]),"+f"(d[29]),"+f"(d[30]),"+f"(d[31]),"+f"(d[32]),"+f"(d[33]),"+f"(d[34]),"+f"(d[35]),"+f"(d[36]),"+f"(d[37]),"+f"(d[38]),"+f"(d[39]),"+f"(d[40]),"+f"(d[41]),"+f"(d[42]),"+f"(d[43]),"+f"(d[44]),"+f"(d[45]),"+f"(d[46]),"+f"(d[47])
 :"r"(a0),"r"(a1),"r"(a2),"r"(a3),"r"(blo),"n"(OFF),"n"(HI),"n"(SC)); } };
template<> struct WgRs<104> { template<int OFF,int HI,int SC> static __device__ __forceinline__ void run(float* d,uint32_t a0,uint32_t a1,uint32_t a2,uint32_t a3,uint32_t blo){
 asm volatile("{.reg .b32 l; .reg .b64 db; add.u32 l,%56,%57; mov.b64 db,{l,%58}; wgmma.mma_async.sync.aligned.m64n104k16.f32.bf16.bf16 {%0,%1,%2,%3,%4,%5,%6,%7,%8,%9,%10,%11,%12,%13,%14,%15,%16,%17,%18,%19,%20,%21,%22,%23,%24,%25,%26,%27,%28,%29,%30,%31,%32,%33,%34,%35,%36,%37,%38,%39,%40,%41,%42,%43,%44,%45,%46,%47,%48,%49,%50,%51},{%52,%53,%54,%55},db,%59,1,1,0;}"
 :"+f"(d[0]),"+f"(d[1]),"+f"(d[2]),"+f"(d[3]),"+f"(d[4]),"+f"(d[5]),"+f"(d[6]),"+f"(d[7]),"+f"(d[8]),"+f"(d[9]),"+f"(d[10]),"+f"(d[11]),"+f"(d[12]),"+f"(d[13]),"+f"(d[14]),"+f"(d[15]),"+f"(d[16]),"+f"(d[17]),"+f"(d[18]),"+f"(d[19]),"+f"(d[20]),"+f"(d[21]),"+f"(d[22]),"+f"(d[23]),"+f"(d[24]),"+f"(d[25]),"+f"(d[26]),"+f"(d[27]),"+f"(d[28]),"+f"(d[29]),"+f"(d[30]),"+f"(d[31]),"+f"(d[32]),"+f"(d[33]),"+f"(d[34]),"+f"(d[35]),"+f"(d[36]),"+f"(d[37]),"+f"(d[38]),"+f"(d[39]),"+f"(d[40]),"+f"(d[41]),"+f"(d[42]),"+f"(d[43]),"+f"(d[44]),"+f"(d[45]),"+f"(d[46]),"+f"(d[47]),"+f"(d[48]),"+f"(d[49]),"+f"(d[50]),"+f"(d[51])
 :"r"(a0),"r"(a1),"r"(a2),"r"(a3),"r"(blo),"n"(OFF),"n"(HI),"n"(SC)); } };
template<> struct WgRs<112> { template<int OFF,int HI,int SC> static __device__ __forceinline__ void run(float* d,uint32_t a0,uint32_t a1,uint32_t a2,uint32_t a3,uint32_t blo){
 asm volatile("{.reg .b32 l; .reg .b64 db; add.u32 l,%60,%61; mov.b64 db,{l,%62}; wgmma.mma_async.sync.aligned.m64n112k16.f32.bf16.bf16 {%0,%1,%2,%3,%4,%5,%6,%7,%8,%9,%10,%11,%12,%13,%14,%15,%16,%17,%18,%19,%20,%21,%22,%23,%24,%25,%26,%27,%28,%29,%30,%31,%32,%33,%34,%35,%36,%37,%38,%39,%40,%41,%42,%43,%44,%45,%46,%47,%48,%49,%50,%51,%52,%53,%54,%55},{%56,%57,%58,%59},db,%63,1,1,0;}"
 :"+f"(d[0]),"+f"(d[1]),"+f"(d[2]),"+f"(d[3]),"+f"(d[4]),"+f"(d[5]),"+f"(d[6]),"+f"(d[7]),"+f"(d[8]),"+f"(d[9]),"+f"(d[10]),"+f"(d[11]),"+f"(d[12]),"+f"(d[13]),"+f"(d[14]),"+f"(d[15]),"+f"(d[16]),"+f"(d[17]),"+f"(d[18]),"+f"(d[19]),"+f"(d[20]),"+f"(d[21]),"+f"(d[22]),"+f"(d[23]),"+f"(d[24]),"+f"(d[25]),"+f"(d[26]),"+f"(d[27]),"+f"(d[28]),"+f"(d[29]),"+f"(d[30]),"+f"(d[31]),"+f"(d[32]),"+f"(d[33]),"+f"(d[34]),"+f"(d[35]),"+f"(d[36]),"+f"(d[37]),"+f"(d[38]),"+f"(d[39]),"+f"(d[40]),"+f"(d[41]),"+f"(d[42]),"+f"(d[43]),"+f"(d[44]),"+f"(d[45]),"+f"(d[46]),"+f"(d[47]),"+f"(d[48]),"+f"(d[49]),"+f"(d[50]),"+f"(d[51]),"+f"(d[52]),"+f"(d[53]),"+f"(d[54]),"+f"(d[55])
 :"r"(a0),"r"(a1),"r"(a2),"r"(a3),"r"(blo),"n"(OFF),"n"(HI),"n"(SC)); } };
template<> struct WgRs<120> { template<int OFF,int HI,int SC> static __device__ __forceinline__ void run(float* d,uint32_t a0,uint32_t a1,uint32_t a2,uint32_t a3,uint32_t blo){
 asm volatile("{.reg .b32 l; .reg .b64 db; add.u32 l,%64,%65; mov.b64 db,{l,%66}; wgmma.mma_async.sync.aligned.m64n120k16.f32.bf16.bf16 {%0,%1,%2,%3,%4,%5,%6,%7,%8,%9,%10,%11,%12,%13,%14,%15,%16,%17,%18,%19,%20,%21,%22,%23,%24,%25,%26,%27,%28,%29,%30,%31,%32,%33,%34,%35,%36,%37,%38,%39,%40,%41,%42,%43,%44,%45,%46,%47,%48,%49,%50,%51,%52,%53,%54,%55,%56,%57,%58,%59},{%60,%61,%62,%63},db,%67,1,1,0;}"
 :"+f"(d[0]),"+f"(d[1]),"+f"(d[2]),"+f"(d[3]),"+f"(d[4]),"+f"(d[5]),"+f"(d[6]),"+f"(d[7]),"+f"(d[8]),"+f"(d[9]),"+f"(d[10]),"+f"(d[11]),"+f"(d[12]),"+f"(d[13]),"+f"(d[14]),"+f"(d[15]),"+f"(d[16]),"+f"(d[17]),"+f"(d[18]),"+f"(d[19]),"+f"(d[20]),"+f"(d[21]),"+f"(d[22]),"+f"(d[23]),"+f"(d[24]),"+f"(d[25]),"+f"(d[26]),"+f"(d[27]),"+f"(d[28]),"+f"(d[29]),"+f"(d[30]),"+f"(d[31]),"+f"(d[32]),"+f"(d[33]),"+f"(d[34]),"+f"(d[35]),"+f"(d[36]),"+f"(d[37]),"+f"(d[38]),"+f"(d[39]),"+f"(d[40]),"+f"(d[41]),"+f"(d[42]),"+f"(d[43]),"+f"(d[44]),"+f"(d[45]),"+f"(d[46]),"+f"(d[47]),"+f"(d[48]),"+f"(d[49]),"+f"(d[50]),"+f"(d[51]),"+f"(d[52]),"+f"(d[53]),"+f"(d[54]),"+f"(d[55]),"+f"(d[56]),"+f"(d[57]),"+f"(d[58]),"+f"(d[59])
 :"r"(a0),"r"(a1),"r"(a2),"r"(a3),"r"(blo),"n"(OFF),"n"(HI),"n"(SC)); } };
template<> struct WgRs<128> { template<int OFF,int HI,int SC> static __device__ __forceinline__ void run(float* d,uint32_t a0,uint32_t a1,uint32_t a2,uint32_t a3,uint32_t blo){
 asm volatile("{.reg .b32 l; .reg .b64 db; add.u32 l,%68,%69; mov.b64 db,{l,%70}; wgmma.mma_async.sync.aligned.m64n128k16.f32.bf16.bf16 {%0,%1,%2,%3,%4,%5,%6,%7,%8,%9,%10,%11,%12,%13,%14,%15,%16,%17,%18,%19,%20,%21,%22,%23,%24,%25,%26,%27,%28,%29,%30,%31,%32,%33,%34,%35,%36,%37,%38,%39,%40,%41,%42,%43,%44,%45,%46,%47,%48,%49,%50,%51,%52,%53,%54,%55,%56,%57,%58,%59,%60,%61,%62,%63},{%64,%65,%66,%67},db,%71,1,1,0;}"
 :"+f"(d[0]),"+f"(d[1]),"+f"(d[2]),"+f"(d[3]),"+f"(d[4]),"+f"(d[5]),"+f"(d[6]),"+f"(d[7]),"+f"(d[8]),"+f"(d[9]),"+f"(d[10]),"+f"(d[11]),"+f"(d[12]),"+f"(d[13]),"+f"(d[14]),"+f"(d[15]),"+f"(d[16]),"+f"(d[17]),"+f"(d[18]),"+f"(d[19]),"+f"(d[20]),"+f"(d[21]),"+f"(d[22]),"+f"(d[23]),"+f"(d[24]),"+f"(d[25]),"+f"(d[26]),"+f"(d[27]),"+f"(d[28]),"+f"(d[29]),"+f"(d[30]),"+f"(d[31]),"+f"(d[32]),"+f"(d[33]),"+f"(d[34]),"+f"(d[35]),"+f"(d[36]),"+f"(d[37]),"+f"(d[38]),"+f"(d[39]),"+f"(d[40]),"+f"(d[41]),"+f"(d[42]),"+f"(d[43]),"+f"(d[44]),"+f"(d[45]),"+f"(d[46]),"+f"(d[47]),"+f"(d[48]),"+f"(d[49]),"+f"(d[50]),"+f"(d[51]),"+f"(d[52]),"+f"(d[53]),"+f"(d[54]),"+f"(d[55]),"+f"(d[56]),"+f"(d[57]),"+f"(d[58]),"+f"(d[59]),"+f"(d[60]),"+f"(d[61]),"+f"(d[62]),"+f"(d[63])
 :"r"(a0),"r"(a1),"r"(a2),"r"(a3),"r"(blo),"n"(OFF),"n"(HI),"n"(SC)); } };
template<> struct WgSs<80> { template<int AOFF,int AHI,int BOFF,int BHI,int SC> static __device__ __forceinline__ void run(float* d,uint32_t alo,uint32_t blo){
 asm volatile("{.reg .b32 l,m; .reg .b64 da,db; add.u32 l,%40,%42; mov.b64 da,{l,%43}; add.u32 m,%41,%44; mov.b64 db,{m,%45}; wgmma.mma_async.sync.aligned.m64n80k16.f32.bf16.bf16 {%0,%1,%2,%3,%4,%5,%6,%7,%8,%9,%10,%11,%12,%13,%14,%15,%16,%17,%18,%19,%20,%21,%22,%23,%24,%25,%26,%27,%28,%29,%30,%31,%32,%33,%34,%35,%36,%37,%38,%39},da,db,%46,1,1,0,1;}"
 :"+f"(d[0]),"+f"(d[1]),"+f"(d[2]),"+f"(d[3]),"+f"(d[4]),"+f"(d[5]),"+f"(d[6]),"+f"(d[7]),"+f"(d[8]),"+f"(d[9]),"+f"(d[10]),"+f"(d[11]),"+f"(d[12]),"+f"(d[13]),"+f"(d[14]),"+f"(d[15]),"+f"(d[16]),"+f"(d[17]),"+f"(d[18]),"+f"(d[19]),"+f"(d[20]),"+f"(d[21]),"+f"(d[22]),"+f"(d[23]),"+f"(d[24]),"+f"(d[25]),"+f"(d[26]),"+f"(d[27]),"+f"(d[28]),"+f"(d[29]),"+f"(d[30]),"+f"(d[31]),"+f"(d[32]),"+f"(d[33]),"+f"(d[34]),"+f"(d[35]),"+f"(d[36]),"+f"(d[37]),"+f"(d[38]),"+f"(d[39])
 :"r"(alo),"r"(blo),"n"(AOFF),"n"(AHI),"n"(BOFF),"n"(BHI),"n"(SC)); } };
template<> struct WgSs<104> { template<int AOFF,int AHI,int BOFF,int BHI,int SC> static __device__ __forceinline__ void run(float* d,uint32_t alo,uint32_t blo){
 asm volatile("{.reg .b32 l,m; .reg .b64 da,db; add.u32 l,%52,%54; mov.b64 da,{l,%55}; add.u32 m,%53,%56; mov.b64 db,{m,%57}; wgmma.mma_async.sync.aligned.m64n104k16.f32.bf16.bf16 {%0,%1,%2,%3,%4,%5,%6,%7,%8,%9,%10,%11,%12,%13,%14,%15,%16,%17,%18,%19,%20,%21,%22,%23,%24,%25,%26,%27,%28,%29,%30,%31,%32,%33,%34,%35,%36,%37,%38,%39,%40,%41,%42,%43,%44,%45,%46,%47,%48,%49,%50,%51},da,db,%58,1,1,0,1;}"
 :"+f"(d[0]),"+f"(d[1]),"+f"(d[2]),"+f"(d[3]),"+f"(d[4]),"+f"(d[5]),"+f"(d[6]),"+f"(d[7]),"+f"(d[8]),"+f"(d[9]),"+f"(d[10]),"+f"(d[11]),"+f"(d[12]),"+f"(d[13]),"+f"(d[14]),"+f"(d[15]),"+f"(d[16]),"+f"(d[17]),"+f"(d[18]),"+f"(d[19]),"+f"(d[20]),"+f"(d[21]),"+f"(d[22]),"+f"(d[23]),"+f"(d[24]),"+f"(d[25]),"+f"(d[26]),"+f"(d[27]),"+f"(d[28]),"+f"(d[29]),"+f"(d[30]),"+f"(d[31]),"+f"(d[32]),"+f"(d[33]),"+f"(d[34]),"+f"(d[35]),"+f"(d[36]),"+f"(d[37]),"+f"(d[38]),"+f"(d[39]),"+f"(d[40]),"+f"(d[41]),"+f"(d[42]),"+f"(d[43]),"+f"(d[44]),"+f"(d[45]),"+f"(d[46]),"+f"(d[47]),"+f"(d[48]),"+f"(d[49]),"+f"(d[50]),"+f"(d[51])
 :"r"(alo),"r"(blo),"n"(AOFF),"n"(AHI),"n"(BOFF),"n"(BHI),"n"(SC)); } };
template<> struct WgSs<112> { template<int AOFF,int AHI,int BOFF,int BHI,int SC> static __device__ __forceinline__ void run(float* d,uint32_t alo,uint32_t blo){
 asm volatile("{.reg .b32 l,m; .reg .b64 da,db; add.u32 l,%56,%58; mov.b64 da,{l,%59}; add.u32 m,%57,%60; mov.b64 db,{m,%61}; wgmma.mma_async.sync.aligned.m64n112k16.f32.bf16.bf16 {%0,%1,%2,%3,%4,%5,%6,%7,%8,%9,%10,%11,%12,%13,%14,%15,%16,%17,%18,%19,%20,%21,%22,%23,%24,%25,%26,%27,%28,%29,%30,%31,%32,%33,%34,%35,%36,%37,%38,%39,%40,%41,%42,%43,%44,%45,%46,%47,%48,%49,%50,%51,%52,%53,%54,%55},da,db,%62,1,1,0,1;}"
 :"+f"(d[0]),"+f"(d[1]),"+f"(d[2]),"+f"(d[3]),"+f"(d[4]),"+f"(d[5]),"+f"(d[6]),"+f"(d[7]),"+f"(d[8]),"+f"(d[9]),"+f"(d[10]),"+f"(d[11]),"+f"(d[12]),"+f"(d[13]),"+f"(d[14]),"+f"(d[15]),"+f"(d[16]),"+f"(d[17]),"+f"(d[18]),"+f"(d[19]),"+f"(d[20]),"+f"(d[21]),"+f"(d[22]),"+f"(d[23]),"+f"(d[24]),"+f"(d[25]),"+f"(d[26]),"+f"(d[27]),"+f"(d[28]),"+f"(d[29]),"+f"(d[30]),"+f"(d[31]),"+f"(d[32]),"+f"(d[33]),"+f"(d[34]),"+f"(d[35]),"+f"(d[36]),"+f"(d[37]),"+f"(d[38]),"+f"(d[39]),"+f"(d[40]),"+f"(d[41]),"+f"(d[42]),"+f"(d[43]),"+f"(d[44]),"+f"(d[45]),"+f"(d[46]),"+f"(d[47]),"+f"(d[48]),"+f"(d[49]),"+f"(d[50]),"+f"(d[51]),"+f"(d[52]),"+f"(d[53]),"+f"(d[54]),"+f"(d[55])
 :"r"(alo),"r"(blo),"n"(AOFF),"n"(AHI),"n"(BOFF),"n"(BHI),"n"(SC)); } };

__device__ __forceinline__ void wg_fence() { asm volatile("wgmma.fence.sync.aligned;" ::: "memory"); }
__device__ __forceinline__ void wg_commit() { asm volatile("wgmma.commit_group.sync.aligned;" ::: "memory"); }
template <int N> __device__ __forceinline__ void wg_wait() { asm volatile("wgmma.wait_group.sync.aligned %0;" ::"n"(N) : "memory"); }
template <int N> __device__ __forceinline__ void reg_fence(float* d) {
#pragma unroll
    for (int i = 0; i < N; i++) asm volatile("" : "+f"(d[i])::"memory");
}
__device__ __forceinline__ uint32_t desc_lo(uint32_t addr, uint32_t lbo) { return ((addr & 0x3FFFF) >> 4) | ((lbo >> 4) << 16); }
#define desc_hi(sbo, sw) (((sbo) >> 4) | ((sw) << 30))
__device__ __forceinline__ uint32_t smem_u32(const void* p) { return (uint32_t)__cvta_generic_to_shared(p); }
__device__ __forceinline__ bool elect() {
    uint32_t p;
    asm volatile("{.reg .pred P; elect.sync _|P, 0xffffffff; selp.u32 %0,1,0,P;}" : "=r"(p));
    return p;
}
__device__ __forceinline__ void mbar_init(uint32_t bar, uint32_t cnt) { asm volatile("mbarrier.init.shared::cta.b64 [%0], %1;" ::"r"(bar), "r"(cnt) : "memory"); }
__device__ __forceinline__ void mbar_expect(uint32_t bar, uint32_t bytes) { asm volatile("mbarrier.arrive.expect_tx.shared::cta.b64 _, [%0], %1;" ::"r"(bar), "r"(bytes) : "memory"); }
__device__ __forceinline__ bool mbar_try(uint32_t bar, uint32_t par) {
    uint32_t ok;
    asm volatile("{.reg .pred p; mbarrier.try_wait.parity.shared::cta.b64 p, [%1], %2; selp.u32 %0,1,0,p;}" : "=r"(ok) : "r"(bar), "r"(par) : "memory");
    return ok;
}
constexpr int SPIN_LIMIT = 1 << 18;
__device__ __forceinline__ void mbar_wait(uint32_t bar, uint32_t par) {
    if (mbar_try(bar, par)) return;
    int n = 0;
    while (!mbar_try(bar, par) && ++n < SPIN_LIMIT) {}
}
__device__ __forceinline__ void bulk_g2s(uint32_t dst, const void* src, uint32_t bytes, uint32_t bar) {
    asm volatile("cp.async.bulk.shared::cluster.global.mbarrier::complete_tx::bytes [%0], [%1], %2, [%3];" ::"r"(dst), "l"(src), "r"(bytes), "r"(bar) : "memory");
}
__device__ __forceinline__ void bulk_s2g(void* dst, uint32_t src, uint32_t bytes) {
    asm volatile("cp.async.bulk.global.shared::cta.bulk_group [%0], [%1], %2;" ::"l"(dst), "r"(src), "r"(bytes) : "memory");
}
__device__ __forceinline__ void bulk_prefetch(const void* src, uint32_t bytes) {
    asm volatile("cp.async.bulk.prefetch.L2.global [%0], %1;" ::"l"(src), "r"(bytes) : "memory");
}
__device__ __forceinline__ void tma2d(uint32_t dst, const CUtensorMap* m, int c0, int c1, uint32_t bar) {
    asm volatile("cp.async.bulk.tensor.2d.shared::cluster.global.mbarrier::complete_tx::bytes [%0], [%1, {%3, %4}], [%2];" ::"r"(dst), "l"(m), "r"(bar), "r"(c0), "r"(c1) : "memory");
}
__device__ __forceinline__ void tma2d_mc(uint32_t dst, const CUtensorMap* m, int c0, int c1, uint32_t bar) {
    asm volatile("cp.async.bulk.tensor.2d.shared::cluster.global.mbarrier::complete_tx::bytes.multicast::cluster [%0], [%1, {%3, %4}], [%2], %5;" ::"r"(dst), "l"(m), "r"(bar), "r"(c0), "r"(c1), "h"((uint16_t)3) : "memory");
}
__device__ __forceinline__ uint32_t mapa(uint32_t a, uint32_t rank) { uint32_t r; asm("mapa.shared::cluster.u32 %0, %1, %2;" : "=r"(r) : "r"(a), "r"(rank)); return r; }
__device__ __forceinline__ void mbar_arrive_cl(uint32_t bar) { asm volatile("mbarrier.arrive.shared::cluster.b64 _, [%0];" ::"r"(bar) : "memory"); }
__device__ __forceinline__ void prefetch_map(const CUtensorMap* m) { asm volatile("prefetch.tensormap [%0];" ::"l"(m) : "memory"); }
__device__ __forceinline__ void cpasync16(uint32_t dst, const void* src, uint32_t srcsz) {
    asm volatile("cp.async.cg.shared.global [%0], [%1], 16, %2;" ::"r"(dst), "l"(src), "r"(srcsz) : "memory");
}
__device__ __forceinline__ void bar_sync(int id, int n) { asm volatile("bar.sync %0, %1;" ::"r"(id), "r"(n) : "memory"); }
__device__ __forceinline__ void bar_arrive(int id, int n) { asm volatile("bar.arrive %0, %1;" ::"r"(id), "r"(n) : "memory"); }
__device__ __forceinline__ void fence_async_smem() { asm volatile("fence.proxy.async.shared::cta;" ::: "memory"); }
__device__ __forceinline__ void fence_async_global() { asm volatile("fence.proxy.async.global;" ::: "memory"); }
__device__ __forceinline__ void flag_release(int f) { asm volatile("red.release.gpu.global.add.u32 [%0], 1;" ::"l"(&g_flags[f * 32]) : "memory"); }
__device__ __forceinline__ void flag_wait(int f, unsigned target) {
    const unsigned* p = &g_flags[f * 32];
    unsigned v; int n = 0;
    do {
        asm volatile("ld.relaxed.gpu.global.u32 %0, [%1];" : "=r"(v) : "l"(p) : "memory");
    } while ((int)(v - target) < 0 && ++n < SPIN_LIMIT);
    asm volatile("fence.acquire.gpu;" ::: "memory");
}
__device__ __forceinline__ void flag_wait2(int f0, int f1, unsigned target) {
    unsigned v, w; int n = 0;
    do {
        asm volatile("ld.relaxed.gpu.global.u32 %0, [%1];" : "=r"(v) : "l"(&g_flags[f0 * 32]) : "memory");
        asm volatile("ld.relaxed.gpu.global.u32 %0, [%1];" : "=r"(w) : "l"(&g_flags[f1 * 32]) : "memory");
    } while ((int)((v - target) | (w - target)) < 0 && ++n < SPIN_LIMIT);
    asm volatile("fence.acquire.gpu;" ::: "memory");
}
__device__ __forceinline__ uint32_t lds32(uint32_t a) { uint32_t v; asm volatile("ld.shared.u32 %0, [%1];" : "=r"(v) : "r"(a)); return v; }
__device__ __forceinline__ float2 lds64f(uint32_t a) { float2 v; asm volatile("ld.shared.v2.f32 {%0,%1}, [%2];" : "=f"(v.x), "=f"(v.y) : "r"(a)); return v; }
__device__ __forceinline__ uint2 lds64(uint32_t a) { uint2 v; asm volatile("ld.shared.v2.u32 {%0,%1}, [%2];" : "=r"(v.x), "=r"(v.y) : "r"(a)); return v; }
__device__ __forceinline__ void sts64f(uint32_t a, float2 v) { asm volatile("st.shared.v2.f32 [%0], {%1,%2};" ::"r"(a), "f"(v.x), "f"(v.y) : "memory"); }
__device__ __forceinline__ void sts32(uint32_t a, uint32_t v) { asm volatile("st.shared.u32 [%0], %1;" ::"r"(a), "r"(v) : "memory"); }
__device__ __forceinline__ void sts64(uint32_t a, uint32_t x, uint32_t y) { asm volatile("st.shared.v2.u32 [%0], {%1,%2};" ::"r"(a), "r"(x), "r"(y) : "memory"); }
__device__ __forceinline__ void sts16(uint32_t a, uint16_t v) { asm volatile("st.shared.u16 [%0], %1;" ::"r"(a), "h"(v) : "memory"); }
__device__ __forceinline__ uint4 lds128(uint32_t a) { uint4 v; asm volatile("ld.shared.v4.u32 {%0,%1,%2,%3}, [%4];" : "=r"(v.x), "=r"(v.y), "=r"(v.z), "=r"(v.w) : "r"(a)); return v; }
__device__ __forceinline__ void sts128(uint32_t a, uint4 v) { asm volatile("st.shared.v4.u32 [%0], {%1,%2,%3,%4};" ::"r"(a), "r"(v.x), "r"(v.y), "r"(v.z), "r"(v.w) : "memory"); }
__device__ __forceinline__ void sts128f(uint32_t a, float x, float y, float z, float w) { asm volatile("st.shared.v4.f32 [%0], {%1,%2,%3,%4};" ::"r"(a), "f"(x), "f"(y), "f"(z), "f"(w) : "memory"); }
__device__ __forceinline__ uint32_t prmt(uint32_t a, uint32_t b, uint32_t s) { uint32_t r; asm("prmt.b32 %0,%1,%2,%3;" : "=r"(r) : "r"(a), "r"(b), "r"(s)); return r; }
__device__ __forceinline__ uint32_t pack2(float lo, float hi) { uint32_t r; asm("cvt.rn.bf16x2.f32 %0, %1, %2;" : "=r"(r) : "f"(hi), "f"(lo)); return r; }
__device__ __forceinline__ float blo(uint32_t v) { return __uint_as_float(v << 16); }
__device__ __forceinline__ float bhi(uint32_t v) { return __uint_as_float(v & 0xffff0000u); }
__device__ __forceinline__ uint32_t bmul2(uint32_t a, uint32_t b) { uint32_t r; asm("mul.rn.bf16x2 %0,%1,%2;" : "=r"(r) : "r"(a), "r"(b)); return r; }
__device__ __forceinline__ uint32_t badd2(uint32_t a, uint32_t b) { uint32_t r; asm("add.rn.bf16x2 %0,%1,%2;" : "=r"(r) : "r"(a), "r"(b)); return r; }
__device__ __forceinline__ float rbf(float x) { return __bfloat162float(__float2bfloat16_rn(x)); }
__device__ __forceinline__ uint32_t ldcg32(const void* p) { uint32_t v; asm volatile("ld.global.cg.u32 %0, [%1];" : "=r"(v) : "l"(p) : "memory"); return v; }
__device__ __forceinline__ uint4 ldcg128(const void* p) { uint4 v; asm volatile("ld.global.cg.v4.u32 {%0,%1,%2,%3}, [%4];" : "=r"(v.x), "=r"(v.y), "=r"(v.z), "=r"(v.w) : "l"(p) : "memory"); return v; }
__device__ __forceinline__ void stg32_if(void* p, uint32_t v, int on) { asm volatile("{.reg .pred q; setp.ne.b32 q, %2, 0; @q st.global.u32 [%0], %1;}" ::"l"(p), "r"(v), "r"(on) : "memory"); }
__device__ __forceinline__ uint2 ldcg64(const void* p) { uint2 v; asm volatile("ld.global.cg.v2.u32 {%0,%1}, [%2];" : "=r"(v.x), "=r"(v.y) : "l"(p) : "memory"); return v; }
__device__ __forceinline__ float gelu_h(float h) {
    float u = h * fmaf(h * h, 8.0f * 0.044715f * 0.7978845608028654f, 2.0f * 0.7978845608028654f);
    float th;
    asm("tanh.approx.f32 %0, %1;" : "=f"(th) : "f"(u));
    return fmaf(h, th, h);
}
__device__ __forceinline__ float gelu(float x) { return gelu_h(0.5f * x); }
__device__ __forceinline__ void ln_params(float sum, float sq, float& inv, float& nb) {
    float mean = sum * (1.0f / D_);
    float var = fmaxf(fmaf(-mean, mean, sq * (1.0f / D_)), 0.0f);
    float sq_;
    asm("sqrt.approx.f32 %0, %1;" : "=f"(sq_) : "f"(rbf(rbf(var) + 1e-5f)));
    inv = __fdividef(1.0f, rbf(sq_));
    nb = -rbf(mean) * inv;
}
__device__ __forceinline__ uint32_t bsub2(uint32_t a, uint32_t b) { uint32_t r; asm("sub.rn.bf16x2 %0,%1,%2;" : "=r"(r) : "r"(a), "r"(b)); return r; }
__device__ __forceinline__ uint32_t bfma2(uint32_t a, uint32_t b, uint32_t c) { uint32_t r; asm("fma.rn.bf16x2 %0,%1,%2,%3;" : "=r"(r) : "r"(a), "r"(b), "r"(c)); return r; }
__device__ __forceinline__ void mma_stat(float* d, uint32_t u, uint32_t v) {
    asm("mma.sync.aligned.m16n8k16.row.col.f32.bf16.bf16.f32 {%0,%1,%2,%3},{%4,%6,%5,%6},{%4,%5},{%0,%1,%2,%3};"
        : "+f"(d[0]), "+f"(d[1]), "+f"(d[2]), "+f"(d[3]) : "r"(u), "r"(v), "r"(0x3f803f80u));
}
__device__ __forceinline__ uint3 row_stats(const uint32_t* v, int lane) {
    float s = 0.f, q = 0.f, s_ = 0.f, q_ = 0.f;
#pragma unroll
    for (int i = 0; i < 10; i++) { float a = blo(v[i]), b = bhi(v[i]); s += a; s_ += b; q = fmaf(a, a, q); q_ = fmaf(b, b, q_); }
    s += s_; q += q_;
    {
        float t = __shfl_xor_sync(0xffffffffu, (lane & 16) ? s : q, 16);
        t += (lane & 16) ? q : s;
#pragma unroll
        for (int m = 8; m; m >>= 1) t += __shfl_xor_sync(0xffffffffu, t, m);
        float o = __shfl_xor_sync(0xffffffffu, t, 16);
        s = (lane & 16) ? o : t; q = (lane & 16) ? t : o;
    }
    float mean = s * (1.0f / D_);
    float var = fmaxf(fmaf(-mean, mean, q * (1.0f / D_)), 0.0f), sd;
    asm("sqrt.approx.f32 %0, %1;" : "=f"(sd) : "f"(rbf(rbf(var) + 1e-5f)));
    float inv = __fdividef(1.0f, rbf(sd));
    uint3 r;
    r.x = pack2(mean, mean);
    r.y = pack2(inv, inv);
    inv -= blo(r.y);
    r.z = pack2(inv, inv);
    return r;
}
__device__ __forceinline__ uint32_t ln_apply(uint32_t x, uint32_t m, uint32_t hi, uint32_t lo) {
    uint32_t xc = bsub2(x, m);
    return bfma2(xc, hi, bmul2(xc, lo));
}

struct AFrag { uint32_t m, a, b, c, d; };
__device__ __forceinline__ AFrag ldA(uint32_t a) { AFrag f; f.m = lds32(a - 16); f.a = lds32(a); f.b = lds32(a + 16); f.c = lds32(a + 32); f.d = lds32(a + 48); return f; }
template <int N, int M> __device__ __forceinline__ void conv_pair(float* d, const AFrag& f, uint32_t descU) {
    WgRs<N>::template run<8 * M, desc_hi(128, 0), 1>(d, f.a, f.b, f.m, f.a, descU);
    WgRs<N>::template run<8 * M + 1, desc_hi(128, 0), 1>(d, f.c, f.d, f.b, f.c, descU);
}
template <int Q> __device__ __forceinline__ void conv_put(float* d, uint32_t r0) {
    sts64(r0 + Q * 32, pack2(d[4 * Q + 1], d[4 * Q + 3]), pack2(d[4 * Q], d[4 * Q + 2]));
}
template <int M> __device__ __forceinline__ void conv_head(float* d, AFrag& f, uint32_t kaddr, uint32_t descU, uint32_t r0) {
    wg_fence();
    conv_pair<128 - 8 * M, M>(d, f, descU);
    wg_commit();
    if constexpr (M < 3) {
        wg_wait<0>();
        conv_put<15 - M>(d, r0);
        f = ldA(kaddr + 256 * (M + 1));
    } else {
        if constexpr (M > 3) conv_put<16 - M>(d, r0);
        AFrag n = ldA(kaddr + 256 * (M + 1));
        wg_wait<0>();
        f = n;
    }
    if constexpr (M < 7) conv_head<M + 1>(d, f, kaddr, descU, r0);
}
__device__ __forceinline__ void conv_main(float* d, uint32_t fm, uint32_t fa, uint32_t fb, uint32_t kaddr, uint32_t descU, uint32_t r0, bool handoff) {
    wg_fence();
    WgRs<128>::run<0, desc_hi(128, 0), 0>(d, fa, fb, fm, fa, descU);
    wg_commit();
    wg_wait<0>();
    fa = lds32(kaddr + 32); fb = lds32(kaddr + 48); fm = lds32(kaddr + 16);
    wg_fence();
    WgRs<128>::run<1, desc_hi(128, 0), 1>(d, fa, fb, fm, fa, descU);
    wg_commit();
    wg_wait<0>();
    conv_put<15>(d, r0);
    AFrag f = ldA(kaddr + 256);
    conv_head<1>(d, f, kaddr, descU, r0);
    if (STAG == 1 && handoff) bar_arrive(12, 256);
    AFrag f1 = ldA(kaddr + 256 * 9);
    wg_fence();
    conv_pair<64, 8>(d, f, descU); conv_pair<64, 9>(d, f1, descU);
    wg_commit();
    conv_put<8>(d, r0);
    AFrag f2 = ldA(kaddr + 256 * 10), f3 = ldA(kaddr + 256 * 11);
    wg_wait<0>();
    wg_fence();
    conv_pair<48, 10>(d, f2, descU); conv_pair<48, 11>(d, f3, descU);
    wg_commit();
    conv_put<7>(d, r0); conv_put<6>(d, r0);
    AFrag f4 = ldA(kaddr + 256 * 12), f5 = ldA(kaddr + 256 * 13), f6 = ldA(kaddr + 256 * 14), f7 = ldA(kaddr + 256 * 15);
    wg_wait<0>();
    wg_fence();
    conv_pair<32, 12>(d, f4, descU); conv_pair<32, 13>(d, f5, descU); conv_pair<32, 14>(d, f6, descU); conv_pair<32, 15>(d, f7, descU);
    wg_commit();
    if (STAG == 2 && handoff) bar_arrive(12, 256);
    conv_put<5>(d, r0); conv_put<4>(d, r0);
    wg_wait<0>();
    conv_put<3>(d, r0); conv_put<2>(d, r0); conv_put<1>(d, r0); conv_put<0>(d, r0);
}

template <int N, bool ASWZ, int SC0>
__device__ __forceinline__ void gemm_issue(float* acc, uint32_t bars, int sa, int pa, int sw, int pw, uint32_t da0, uint32_t db0) {
    mbar_wait(bars + (BAR_FB + sw) * 8, pw);
    mbar_wait(bars + (BAR_FA + sa) * 8, pa);
    const uint32_t da = da0 + sa * (SLOT >> 4), db = db0 + sw * (SLOT >> 4);
    constexpr int AK = ASWZ ? 2 : 256, AH = ASWZ ? desc_hi(1024, 1) : desc_hi(128, 0), BH = desc_hi(1024, 1);
    wg_fence();
    WgSs<N>::template run<0, AH, 0, BH, SC0>(acc, da, db);
    WgSs<N>::template run<AK, AH, 128, BH, 1>(acc, da, db);
    WgSs<N>::template run<2 * AK, AH, 256, BH, 1>(acc, da, db);
    WgSs<N>::template run<3 * AK, AH, 384, BH, 1>(acc, da, db);
    wg_commit();
}
template <int N, bool ASWZ, int IA0, int IB0, int NKB, int RELA, int RELB, bool ZERO, int WAIT_BAR, int ORDER_BAR, int TSID>
__device__ __forceinline__ void gemm_loop(float* acc, uint32_t sb, int half) {
    int sa = IA0 % NA, pa = (IA0 / NA) & 1, sw = IB0 % NB, pw = (IB0 / NB) & 1;
    const uint32_t bars = sb + SM_BAR;
    const int t = threadIdx.x & 127;
    uint32_t ebar = mapa(bars + (t < 2 ? BAR_EB : BAR_EA) * 8, (t < 2 && lds32(sb + SM_GV + 516)) ? t : blockIdx.x & 1);
    const int nrel = t < 2 ? RELB : t == 2 ? RELA : 0;
    const uint32_t da0 = ASWZ ? desc_lo(sb + SM_RA + half * 8192, 16) : desc_lo(sb + SM_RA + half * 1024, 2048), db0 = desc_lo(sb + SM_RB, 8192);
    asm volatile("" : "+r"(ebar));
    if (WAIT_BAR) bar_sync(WAIT_BAR, 512);
    gemm_issue<N, ASWZ, ZERO ? 0 : 1>(acc, bars, sa, pa, sw, pw, da0, db0);
    if ((threadIdx.x & 255) == 0) TS(TSID);
#pragma unroll 1
    for (int kb = 1; kb < NKB; kb++) {
        const int prev = t < 2 ? sw : sa;
        if (++sa == NA) { sa = 0; pa ^= 1; }
        if (++sw == NB) { sw = 0; pw ^= 1; }
        gemm_issue<N, ASWZ, 1>(acc, bars, sa, pa, sw, pw, da0, db0);
        if (ORDER_BAR && kb == NKB - 1) bar_arrive(ORDER_BAR, 512);
        wg_wait<1>();
        if (kb <= nrel) mbar_arrive_cl(ebar + prev * 8);
    }
    wg_wait<0>();
    if (nrel == NKB) mbar_arrive_cl(ebar + (t < 2 ? sw : sa) * 8);
    reg_fence<N / 2>(acc);
    if ((threadIdx.x & 255) == 0) TS(TSID + 1);
}

template <int N, int IA0, int IB0, int RELA, int WAIT_BAR, int ORDER_BAR, int BAR1>
__device__ __forceinline__ void gemm3(uint32_t sb, int rb, int pl0, int pl1, int half, int wq, int g, int c, unsigned ones) {
    float acc[N / 2];
    const int row = 64 * half + 16 * wq + g;
    float2 cr[N / 8];
    mbar_wait(sb + SM_BAR + BAR_CS * 8, 0);
#pragma unroll
    for (int q = 0; q < N / 8; q++) cr[q] = lds64f(sb + SM_CS + (N == 112 ? 0 : 448) + 8 * c + 32 * q);
    float inv0, nb0, inv1, nb1;
    if (N == 104) {
        mbar_wait(sb + SM_BAR + (BAR_FA + 20 % NA) * 8, (20 / NA) & 1);
        const float2* sp = &g_st[(rb * 8 + 2 * c) * 128 + row];
        const uint2 s0 = ldcg64(sp), s1 = ldcg64(sp + 128), s2 = ldcg64(sp + 8), s3 = ldcg64(sp + 136);
        float a0 = __uint_as_float(s0.x) + __uint_as_float(s1.x), b0 = __uint_as_float(s0.y) + __uint_as_float(s1.y);
        float a1 = __uint_as_float(s2.x) + __uint_as_float(s3.x), b1 = __uint_as_float(s2.y) + __uint_as_float(s3.y);
#pragma unroll
        for (int m = 1; m <= 2; m <<= 1) {
            a0 += __shfl_xor_sync(0xffffffffu, a0, m); b0 += __shfl_xor_sync(0xffffffffu, b0, m);
            a1 += __shfl_xor_sync(0xffffffffu, a1, m); b1 += __shfl_xor_sync(0xffffffffu, b1, m);
        }
        ln_params(a0, b0, inv0, nb0);
        ln_params(a1, b1, inv1, nb1);
        inv0 *= 0.5f; nb0 *= 0.5f; inv1 *= 0.5f; nb1 *= 0.5f;
        if (c == 0) sts128f(sb + SM_RP + ((threadIdx.x & 255) >> 2) * 16, inv0, nb0, inv1, nb1);
        bar_arrive(13, 512);
        TSD2(41, __float_as_uint(nb1));
    }
    constexpr int HO = N == 112 ? HO_A : HO_B;
    gemm_loop<N, false, IA0, IB0, 10, RELA, 10, true, WAIT_BAR, HO < 0 ? ORDER_BAR : 0, N == 112 ? 46 : 48>(acc, sb, half);
    if (N == 112) {
        bar_sync(13, 512);
        const uint4 rp = lds128(sb + SM_RP + ((threadIdx.x & 255) >> 2) * 16);
        inv0 = __uint_as_float(rp.x); nb0 = __uint_as_float(rp.y); inv1 = __uint_as_float(rp.z); nb1 = __uint_as_float(rp.w);

    }
    uint32_t* dst = reinterpret_cast<uint32_t*>(g_g) + ((size_t)rb * 216 + pl0) * 512 + row * 4 + c;
#pragma unroll
    for (int k = 0; k < N / 8; k += CH) {
        if (k == 8) dst += (pl1 - pl0 - 8) * 512;
        if (k == HO) bar_arrive(ORDER_BAR, 512);
        if (k == 2 || k == 6) { if ((threadIdx.x & 255) == 0) TS((N == 112 ? 55 : 59) + (k == 6)); }
        CHUNK(k) {
#pragma unroll
            for (int q = k; q < k + CH && q < N / 8; q++) {
                dst[q * 512] = pack2(gelu_h(fmaf(acc[4 * q], inv0, nb0 * cr[q].x)), gelu_h(fmaf(acc[4 * q + 1], inv0, nb0 * cr[q].y)));
                dst[q * 512 + 32] = pack2(gelu_h(fmaf(acc[4 * q + 2], inv1, nb1 * cr[q].x)), gelu_h(fmaf(acc[4 * q + 3], inv1, nb1 * cr[q].y)));
            }
        }
    }
    if (HO >= N / 8) bar_arrive(ORDER_BAR, 512);
    bar_arrive(BAR1, 288);
}

template <int NS, int BASE, int BF, int BE> struct Ring {
    uint32_t sb, st, ph;
    __device__ __forceinline__ uint32_t acquire(uint32_t bytes) {
        mbar_wait(sb + SM_BAR + BE * 8 + st * 8, ph);
        uint32_t fb = sb + SM_BAR + BF * 8 + st * 8;
        mbar_expect(fb, bytes);
        return fb;
    }
    __device__ __forceinline__ uint32_t slot() { return sb + BASE + st * SLOT; }
    __device__ __forceinline__ void next() { if (++st == NS) { st = 0; ph ^= 1; } }
    __device__ __forceinline__ void run2d(const CUtensorMap* m, int c1) {
#pragma unroll 1
        for (int c0 = 0; c0 < D_; c0 += 64) {
            uint32_t fb = acquire(SLOT);
            tma2d(slot(), m, c0, c1, fb);
            next();
        }
    }
    __device__ __forceinline__ void runw(bool paired, int rk, const CUtensorMap* ma, const CUtensorMap* mb, int ca, int cb, int c1, int n, uint32_t bytes) {
        if (paired) {
            const CUtensorMap* m = rk ? mb : ma;
            const int c0 = rk ? cb : ca;
#pragma unroll 1
            for (; n > 0; n--, c1 += 64) {
                uint32_t fb = acquire(bytes);
                tma2d_mc(slot() + 8192 * rk, m, c0, c1, fb);
                next();
            }
        } else {
#pragma unroll 1
            for (; n > 0; n--, c1 += 64) {
                uint32_t fb = acquire(bytes);
                tma2d(slot(), ma, ca, c1, fb);
                tma2d(slot() + 8192, mb, cb, c1, fb);
                next();
            }
        }
    }
    __device__ __forceinline__ void run1d(const char* src, int n) {
#pragma unroll 1
        for (; n > 0; n--) {
            uint32_t fb = acquire(SLOT);
            bulk_g2s(slot(), src, SLOT, fb);
            src += SLOT;
            next();
        }
    }
};

__global__ void __cluster_dims__(2, 1, 1) __launch_bounds__(NTHREADS, 1) fused_kernel(const Params p, const __grid_constant__ Maps maps) {
    extern __shared__ __align__(1024) unsigned char smem_raw[];
    const uint32_t sb = (smem_u32(smem_raw) + 1023u) & ~1023u;
#pragma unroll
    for (int i = 0; i < SEED; i++) asm volatile("{.reg .b32 t; mov.u32 t, %laneid;}");
    const uint32_t bars = sb + SM_BAR;
    const int tid = threadIdx.x, lane = tid & 31;
    unsigned smid;
    asm volatile("mov.u32 %0, %%smid;" : "=r"(smid));
    const bool spare = (smid >> 2) == 30;
    const int cta = smid < 120 ? smid : smid - 4;
    const int pg = cta >> 4, pi = cta & 15;
    if (!spare) {
        const unsigned row = (unsigned)tid / 10u, cc = (unsigned)tid - row * 10u;
        const unsigned go = (unsigned)(pi * 128 * 1280 + pg * 160) + row * 1280u + cc * 16u;
        const uint32_t so = sb + (row >> 4) * 16u + row * 160u + cc * 16u;
        const char* kb = (const char*)p.k + go;
        const char* vb = (const char*)p.v + go;
        cpasync16(so + SM_PK + 2576, kb, 16);
        cpasync16(so + SM_PV, vb, 16);
        cpasync16(so + SM_PK + 5 * 2576, kb + 64 * 1280, 16);
        cpasync16(so + SM_PV + 4 * 2576, vb + 64 * 1280, 16);
        if (tid < 30) cpasync16(so + SM_PK + 13 * 160, pi ? kb - 3 * 1280 : kb, pi ? 16 : 0);
        asm volatile("cp.async.commit_group;" ::: "memory");
    }
    const int warp = __shfl_sync(0xffffffffu, tid >> 5, 0);
    const int wg = warp >> 2, wq = warp & 3;
    unsigned ep0 = 0;
    if (wg == 4 || spare) ep0 = *(volatile unsigned*)&g_epoch[smid];
#define ep1 (ep0 + 1)

    if (spare) {
        const int sp = smid & 3;
        if (tid == 32) { sts32(sb + SM_GV + 512, smid); asm volatile("fence.release.sync_restrict::shared::cta.cluster;" ::: "memory"); }
        asm volatile("barrier.cluster.arrive.relaxed.aligned;" ::: "memory");
        asm volatile("barrier.cluster.wait.aligned;" ::: "memory");
        if (tid == 0) {
            for (int i = 0; i < 4; i++) mbar_init(bars + i * 8, 1);
            asm volatile("fence.mbarrier_init.release.cluster;" ::: "memory");
        }
        if (warp == 0) { if (lane < 8) flag_wait(FL_P + lane, ep1 * 16); __syncwarp(); }
        __syncthreads();
        const int cq = tid % 54, rg = tid / 54;
        float a[8];
#pragma unroll
        for (int i = 0; i < 8; i++) a[i] = 0.f;
#pragma unroll 1
        for (int it = -4; it < 10; it++) {
            const uint32_t st = sb + (it & 3) * 55296, fb = bars + (it & 3) * 8;
            if (it >= 0) {
                mbar_wait(fb, (it >> 2) & 1);
                if (tid < 432) {
#pragma unroll
                    for (int i = 0; i < 8; i++) {
                        uint4 w = lds128(st + (cq >= 27 ? 27648 - 432 : 0) + (rg * 8 + i) * 432 + cq * 16);
                        a[0] += blo(w.x); a[1] += bhi(w.x); a[2] += blo(w.y); a[3] += bhi(w.y);
                        a[4] += blo(w.z); a[5] += bhi(w.z); a[6] += blo(w.w); a[7] += bhi(w.w);
                    }
                }
                __syncthreads();
            }
            if (it < 6 && warp == 19 && elect()) {
                mbar_expect(fb, 55296);
                tma2d(st, &maps.w3s, sp * 432, (it + 4) * 64, fb);
                tma2d(st + 27648, &maps.w3s, sp * 432 + 216, (it + 4) * 64, fb);
            }
        }
        if (tid < 432) {
            sts128f(sb + rg * 1728 + cq * 32, a[0], a[1], a[2], a[3]);
            sts128f(sb + rg * 1728 + cq * 32 + 16, a[4], a[5], a[6], a[7]);
        }
        __syncthreads();
        if (tid < 432) {
            float s = 0.f;
#pragma unroll
            for (int i = 0; i < 8; i++) s += __uint_as_float(lds32(sb + i * 1728 + tid * 4));
            g_cs[sp * 432 + tid] = s;
        }
        __syncthreads();
        if (tid == 0) { flag_release(FL_CS); g_epoch[smid] = ep1; TS(0); }
        if (warp == 0) TSFLUSH();
        return;
    }

    int gpc, idx;
    if (smid < 64) { gpc = (smid & 15) >> 1; idx = (smid >> 4) * 2 + (smid & 1); }
    else if (smid < 120) { int t = smid - 64; gpc = 1 + (t % 14) / 2; idx = 8 + (t / 14) * 2 + (smid & 1); }
    else { gpc = 0; idx = 8 + (smid - 124); }
    const int rb = 2 * gpc + (idx & 1), j = idx >> 1;
    const int g = lane >> 2, c = lane & 3;
    const int cm = 160 * (j >> 1) + 64 * (j & 1) + ((j & 2) ? 32 : 0), cr = 160 * (j >> 1) + 16 * (j & 1) + ((j & 2) ? 0 : 128);

    {
        if (warp == 5) TSW(61);
        const int h = warp / 10, pr = (warp % 10) * 4 + (lane >> 3), blk = lane & 7;
        const int ch = 80 * pg + 2 * pr;
        const uint4 sw = __ldg(reinterpret_cast<const uint4*>(p.shift + ch * 4));
        if (warp == 6 && lane < 5) sts32(sb + SM_GV + 520 + lane * 4, (uint32_t)__bfloat16_as_ushort(p.ssmD[cta * 5 + lane]) << 16);
        if (tid == 0) {
            for (int i = 0; i < 12; i++) { mbar_init(bars + i * 8, 1); mbar_init(bars + (12 + i) * 8, i < NA ? 2 : 4); }
            for (int i = BAR_K; i <= BAR_XY; i++) mbar_init(bars + i * 8, i == BAR_XY ? 2 : 1);
            asm volatile("fence.mbarrier_init.release.cluster;" ::: "memory");
        }
        if (tid == 96) { sts32(sb + SM_GV + 512, smid); asm volatile("fence.release.sync_restrict::shared::cta.cluster;" ::: "memory"); }
        if (warp == 1 && lane < 13) prefetch_map(&maps.hn + lane);
        if (warp == 2 && lane < 20)
            sts128(sb + SM_K + (lane >> 2) * K_STRIDE + ((lane >> 1) & 1) * 4160 + (lane & 1) * 16, make_uint4(0, 0, 0, 0));
        if (warp >= 10) {
            sts128(sb + SM_U + (warp - 10) * U_PLANE + 2048 + lane * 16, make_uint4(0, 0, 0, 0));
        }
        asm volatile("barrier.cluster.arrive.relaxed.aligned;" ::: "memory");
        asm volatile("cp.async.wait_group 0;" ::: "memory");
        asm volatile("barrier.cluster.wait.aligned;" ::: "memory");
        if (tid == 32) {
            uint32_t peer;
            asm volatile("ld.shared::cluster.u32 %0, [%1];" : "=r"(peer) : "r"(mapa(sb + SM_GV + 512, (blockIdx.x & 1) ^ 1)) : "memory");
            sts32(sb + SM_GV + 516, peer == (smid ^ 1));
        }
        __syncthreads();
        if (warp == 4 && elect()) {
#pragma unroll
            for (int i = 0; i < 5; i++) {
                mbar_expect(bars + (BAR_K + i) * 8, 4096);
                bulk_g2s(sb + SM_K + i * K_STRIDE + 32, p.ssmk + (size_t)(cta * 5 + i) * S_, 4096, bars + (BAR_K + i) * 8);
            }
        }
        const uint32_t w0 = prmt(sw.x, sw.z, 0x5410), w1 = prmt(sw.x, sw.z, 0x7632), w2 = prmt(sw.y, sw.w, 0x5410), w3 = prmt(sw.y, sw.w, 0x7632);
        const uint32_t ka = sb + SM_PK + 2576 + blk * 2576 + h * 1280 + pr * 4;
        const uint32_t va = sb + SM_PV + blk * 2576 + h * 1280 + pr * 4;
        uint32_t kk[11], kv[8];
#pragma unroll
        for (int i = 0; i < 11; i++) kk[i] = lds32(ka + (i - 3) * 160 - ((i < 3 && h == 0) ? 16 : 0));
        TSD(1, kk[0]);
#pragma unroll
        for (int i = 0; i < 8; i++) {
            uint32_t t = badd2(badd2(badd2(bmul2(kk[i], w3), bmul2(kk[i + 1], w2)), bmul2(kk[i + 2], w1)), bmul2(kk[i + 3], w0));
            kv[i] = bmul2(t, lds32(va + i * 160));
        }
        uint4 o0, o1;
        o0.x = prmt(kv[1], kv[0], 0x5410); o0.y = prmt(kv[3], kv[2], 0x5410); o0.z = prmt(kv[5], kv[4], 0x5410); o0.w = prmt(kv[7], kv[6], 0x5410);
        o1.x = prmt(kv[1], kv[0], 0x7632); o1.y = prmt(kv[3], kv[2], 0x7632); o1.z = prmt(kv[5], kv[4], 0x7632); o1.w = prmt(kv[7], kv[6], 0x7632);
        uint4* dst = reinterpret_cast<uint4*>(g_kvT) + ch * 256 + h * 128 + (127 - (8 * pi + blk));
        TSD(33, o1.w);
        if (warp >= 10) fence_async_smem();
        dst[0] = o0;
        dst[256] = o1;
    }

    const int rho = 8 * rb + j;

    if (wg == 4) {
        asm volatile("setmaxnreg.dec.sync.aligned.u32 32;");
        const bool paired = lds32(sb + SM_GV + 516);
        if (wq == 0) {
            bar_sync(13, 640);
            TSW(39);
            if (lane == 0) flag_release(FL_P + pg);
            __syncwarp();
            TSW(2);
            flag_wait(FL_P + pg, ep1 * 16);
            fence_async_global();
            TSW(3);
            if (elect()) {
#pragma unroll
                for (int i = 0; i < 5; i++) {
                    const char* us = (const char*)g_kvT + (size_t)(cta * 5 + i) * 4096;
                    mbar_expect(bars + (BAR_U + i) * 8, 4096);
                    bulk_g2s(sb + SM_U + i * U_STRIDE, us, 2048, bars + (BAR_U + i) * 8);
                    bulk_g2s(sb + SM_U + i * U_STRIDE + U_PLANE, us + 2048, 2048, bars + (BAR_U + i) * 8);
                }
            }
            __syncwarp();
            if (elect()) {
                if (cta < 120) {
                    mbar_expect(bars + BAR_WM * 8, 40960);
#pragma unroll
                    for (int i = 0; i < 5; i++) tma2d(sb + SM_WM + i * 8192, &maps.wm, cta * 32, i * 128, bars + BAR_WM * 8);
                }
                bulk_prefetch((const char*)p.q + cta * 20480, 20480);
                bulk_prefetch((const char*)p.w1 + cta * 6400, 6400);
                bulk_prefetch((const char*)p.w2 + cta * 6400, 6400);
            }
            __syncwarp();
        } else {
            bar_arrive(13, 640);
        }
        if (cta < 120) {
            float d[4];
            if (tid < 592) {
                const int t = tid - 512;
                mbar_wait(bars + BAR_U * 8, 0);
                uint4 cv = __ldg(reinterpret_cast<const uint4*>(p.c) + t);
                auto silu2 = [](uint32_t v) { float a = blo(v), b = bhi(v); return pack2(__fdividef(a, 1.0f + __expf(-a)), __fdividef(b, 1.0f + __expf(-b))); };
                sts128(sb + SM_Y + (t % 40) * 32 + (t / 40) * 16, make_uint4(silu2(cv.x), silu2(cv.y), silu2(cv.z), silu2(cv.w)));
                fence_async_smem();
            }
            bar_sync(5, 128);
            mbar_wait(bars + BAR_WM * 8, 0);
            if (wq == 3) TSW(50);
            const uint32_t da = desc_lo(sb + SM_WM, 20480), db = desc_lo(sb + SM_Y, 32);
            wg_fence();
#pragma unroll
            for (int k = 0; k < 20; k++)
                asm volatile("{.reg .pred p; .reg .b32 l,m; .reg .b64 da,db; setp.ne.b32 p,%10,0; add.u32 l,%4,%6; mov.b64 da,{l,%8}; add.u32 m,%5,%7; mov.b64 db,{m,%9};"
                             " wgmma.mma_async.sync.aligned.m64n8k16.f32.bf16.bf16 {%0,%1,%2,%3},da,db,p,1,1,1,0;}"
                             : "+f"(d[0]), "+f"(d[1]), "+f"(d[2]), "+f"(d[3])
                             : "r"(da), "r"(db), "r"(64 * k), "r"(4 * k), "n"(desc_hi(512, 2u)), "n"(desc_hi(128, 0)), "r"(k));
            wg_commit();
            wg_wait<0>();
            reg_fence<4>(d);
            if (c == 0) {
                sts32(sb + SM_GV + (16 * wq + g) * 4, __float_as_uint(wq < 2 ? d[0] : d[1]));
                sts32(sb + SM_GV + (16 * wq + g + 8) * 4, __float_as_uint(wq < 2 ? d[2] : d[3]));
            }
            bar_sync(5, 128);
            if (wq == 2) {
                g_mod[cta * 32 + lane] = __float2bfloat16_rn(__uint_as_float(lds32(sb + SM_GV + lane * 4)) + __uint_as_float(lds32(sb + SM_GV + 128 + lane * 4)));
                __syncwarp();
                if (lane == 0) flag_release(FL_M);
                TSW(4);
            }
        }
        if (wq == 2) {
            bar_arrive(7, 640);
            flag_wait(FL_M, ep1 * 120);
            fence_async_global();
            if (elect()) {
                mbar_expect(bars + BAR_M * 8, 7680);
                bulk_g2s(sb + SM_MOD, g_mod, 7680, bars + BAR_M * 8);
            }
            __syncwarp();
            TSW(51);
            bar_sync(8, 544);  if (lane == 0) { flag_release(FL_R + rb); TS(23); }  __syncwarp();
            bar_sync(15, 288); if (lane == 0) { flag_release(FL_B1 + rb); TS(27); } __syncwarp();
            bar_sync(12, 288); if (lane == 0) { flag_release(FL_B2 + rb); TS(31); } __syncwarp();
#pragma unroll 1
            for (int i = 0; i < 2; i++) { bar_sync(1 + i, 288); if (lane == 0) { TS(53 + i); flag_release(FL_G + 16 * i + rb); TS(57 + i); } __syncwarp(); }
            if (lane == 0) g_epoch[smid] = ep1;
            return;
        }
        bar_sync(7, 640);
        if (wq == 3) {
            if (lane == 0) { flag_release(FL_C); TS(20); }
            __syncwarp();
            bar_arrive(10, 160);
            flag_wait(FL_C, ep1 * 128);
            fence_async_global();
            TSW(21);
            if (elect()) {
                mbar_expect(bars + BAR_Y * 8, 20480);
                bulk_g2s(sb + SM_Y, g_yv + rho * 5120, 20480, bars + BAR_Y * 8);
            }
            __syncwarp();
            bar_arrive(9, 96);
        } else bar_sync(9, 96);
        if (wq == 1 && lane < 4 * NB) mbar_arrive_cl(mapa(bars + (BAR_EB + (lane >> 2)) * 8, paired ? lane & 1 : blockIdx.x & 1));
        if (elect()) {
            if (wq == 3) {
                mbar_expect(bars + BAR_XY * 8, 20480);
#pragma unroll 1
                for (int i = 0; i < 8; i++) {
                    bulk_g2s(sb + SM_YT + i * 2560, g_yv + (8 * rb + i) * 5120 + cm * 8, 2048, bars + BAR_XY * 8);
                    bulk_g2s(sb + SM_YT + i * 2560 + 2048, g_yv + (8 * rb + i) * 5120 + cr * 8, 512, bars + BAR_XY * 8);
                }
                mbar_wait(bars + BAR_FA * 8, 0);
                bulk_prefetch((const char*)p.w4 + cta * 17280, 17280);
                flag_wait(FL_CS, ep1 * 4);
                fence_async_global();
                mbar_expect(bars + BAR_CS * 8, 864);
                bulk_g2s(sb + SM_CS, g_cs + 64 * j, 256, bars + BAR_CS * 8);
                bulk_g2s(sb + SM_CS + 256, g_cs + 512 + 48 * j, 192, bars + BAR_CS * 8);
                bulk_g2s(sb + SM_CS + 448, g_cs + 896 + 64 * j, 256, bars + BAR_CS * 8);
                bulk_g2s(sb + SM_CS + 704, g_cs + 1408 + 40 * j, 160, bars + BAR_CS * 8);
            } else if (wq == 1) {
                Ring<NB, SM_RB, BAR_FB, BAR_EB> r{sb, 0, 0};
#pragma unroll 1
                for (int ph = 0; ph < 6; ph++) {
                    const CUtensorMap* ma = ph == 0 ? &maps.w1a : ph == 1 ? &maps.w2a : ph == 5 ? &maps.w4a : &maps.w3a;
                    const bool b3b = ph == 3 || ph == 4;
                    r.runw(paired, idx & 1, ma, ma + (b3b ? 2 : 1), ph == 2 ? 64 * j : b3b ? 896 + 64 * j : cm,
                           ph == 2 ? 512 + 48 * j : b3b ? 1408 + 40 * j : cr, ph == 3 ? (10 - NA) * 64 : 0,
                           ph == 5 ? 27 : ph == 3 ? NA : ph == 4 ? 10 - NA : 10, ph == 2 ? 14336 : b3b ? 13312 : 10240);
                }
            } else {
                Ring<NA, SM_RA, BAR_FA, BAR_EA> r{sb, 0, 0};
                mbar_expect(bars + BAR_XY * 8, 20480);
                tma2d(sb + SM_XT, &maps.xa, cm, rb * 128, bars + BAR_XY * 8);
                tma2d(sb + SM_XT2, &maps.xb, cr, rb * 128, bars + BAR_XY * 8);
                const int grp = j >> 1;
                const int delta = (grp & 1 ? 1 : -1) * (1 + (grp >> 1));
                const int nb = min(max(rb + (delta > 0 ? 1 : -1), 0), 15);
                flag_wait2(FL_R + nb, FL_R + rb, ep1 * 8);
                fence_async_global(); TS(24);
                r.run2d(&maps.hn, rb * 128 + delta);
                flag_wait(FL_B1 + rb, ep1 * 8); fence_async_global(); TS(28);
                r.run1d((const char*)g_h1 + (size_t)rb * 163840, 10);
                flag_wait(FL_B2 + rb, ep1 * 8); fence_async_global(); TS(32);
                r.run1d((const char*)g_x1 + (size_t)rb * 163840, 10);
                r.run1d((const char*)g_x1 + (size_t)rb * 163840, 10 - NA);
                const char* gs = (const char*)g_g + (size_t)rb * 442368;
#pragma unroll 1
                for (int i = 0; i < 2; i++) {
                    flag_wait(FL_G + 16 * i + rb, ep1 * 8); fence_async_global(); TS(36 + i);
                    const int n = 14 - i;
                    r.run1d(gs, n);
                    gs += n * SLOT;
                }
            }
        }
        return;
    }
    bar_arrive(13, 640);
    asm volatile("setmaxnreg.inc.sync.aligned.u32 112;");
    const int rrow = 16 * rho + (warp >> 1) + 8 * (warp & 1);

#pragma unroll 1
    for (int cc = wg; cc < 5; cc += 3) {
        if (cc == 3 && wg == 0) break;
        mbar_wait(bars + (BAR_K + cc) * 8, 0);
        if (cc == 4 && wq == 0) TSW(40);
        uint32_t a = sb + SM_K + cc * K_STRIDE + 32 + (tid & 127) * 32;
        uint32_t pw = lds32(a - 4);
        uint4 x = lds128(a), y = lds128(a + 16), o;
        if ((tid & 127) == 0) {
            uint16_t k0 = __bfloat16_as_ushort(__float2bfloat16_rn(blo(x.x) + __uint_as_float(lds32(sb + SM_GV + 520 + cc * 4))));
            x.x = (x.x & 0xffff0000u) | k0;
            sts16(a, k0);
        }
        o.x = prmt(pw, x.x, 0x5432); o.y = prmt(x.x, x.y, 0x5432); o.z = prmt(x.y, x.z, 0x5432); o.w = prmt(x.z, x.w, 0x5432);
        sts128(a + 4160, o);
        o.x = prmt(x.w, y.x, 0x5432); o.y = prmt(y.x, y.y, 0x5432); o.z = prmt(y.y, y.z, 0x5432); o.w = prmt(y.z, y.w, 0x5432);
        sts128(a + 4176, o);
    }
    bar_sync(1 + wg, 128);
#pragma unroll 1
    for (int cc = wg; cc < 5; cc += 3) {
        if (cc == 3 && wg == 0) break;
        const uint32_t sK = sb + SM_K + cc * K_STRIDE, sU = sb + SM_U + cc * U_STRIDE;
        const uint32_t kaddr = sK + ((g & 1) ? 32 : 4192) + 4 * ((g >> 1) - c) + 64 * wq;
        const uint32_t fm = lds32(kaddr - 16), fa = lds32(kaddr), fb = lds32(kaddr + 16);
        if (STAG && cc == 3) bar_sync(12, 256);
        mbar_wait(bars + (BAR_U + cc) * 8, 0);
        if (wq == 0) TSW(5 + cc);
        float d[64];
        conv_main(d, fm, fa, fb, kaddr, desc_lo(sU, U_PLANE), sb + SM_RED + cc * RED_STRIDE + 32 + wq * 4352 + g * 544 + (c - wq) * 8, cc == 1);
        if (wq == 0) TSW(10 + cc);
        if (cc == 1) bar_arrive(6, 256);
    }
#pragma unroll 1
    for (int cc = wg == 1 ? 4 : wg;; cc++) {
        if (cc == 1) bar_sync(6, 256); else bar_sync(1 + wg, 128);
        const int ch = cta * 5 + cc;
        uint32_t* dst = g_yv + ch * 8 + ((g + (ch >> 2)) & 7);
        const uint32_t red = sb + SM_RED + cc * RED_STRIDE + 32 + g * 544 + (16 * wq + c) * 8;
        uint2 v[16];
#pragma unroll
        for (int q = 0; q < 4; q++)
#pragma unroll
            for (int w = 0; w < 4; w++) v[4 * q + w] = lds64(red + q * 32 + w * 4352);
#pragma unroll
        for (int w = 1; w < 4; w++)
            if (wq == 3 && c > 3 - w) v[12 + w] = make_uint2(0, 0);
#pragma unroll
        for (int q = 0; q < 4; q++) {
            const uint2 *u = v + 4 * q;
            uint32_t* o = dst + (size_t)(126 - 2 * (16 * wq + 4 * q + c)) * 5120;
            o[0] = pack2((blo(u[0].x) + blo(u[1].x)) + (blo(u[2].x) + blo(u[3].x)), (bhi(u[0].x) + bhi(u[1].x)) + (bhi(u[2].x) + bhi(u[3].x)));
            o[5120] = pack2((blo(u[0].y) + blo(u[1].y)) + (blo(u[2].y) + blo(u[3].y)), (bhi(u[0].y) + bhi(u[1].y)) + (bhi(u[2].y) + bhi(u[3].y)));
        }
        if (wq == 0) TSW(15 + cc);
        if (cc != 0) break;
    }
    fence_async_smem();
    bar_arrive(7, 640);

    const uint32_t one2 = 0x3f803f80u;
    const unsigned ones = p.ones;
    {
        uint32_t x[10], a[10], cb[10], sbv[10];
        const uint32_t* xr = reinterpret_cast<const uint32_t*>(p.q + (size_t)rrow * D_) + lane;
        if (wg == 1) bar_sync(10, 160);
#pragma unroll
        for (int i = 0; i < 10; i++) x[i] = __ldg(xr + 32 * i);
        const uint3 s1 = row_stats(x, lane);
        const int up = lane >> 4, gg = warp >> 1, e = warp & 1;
        const uint32_t ya = sb + SM_Y + lane * 64 + ((gg + (lane >> 1)) & 7) * 4;
        const uint32_t sel = (up ? 0x1054u : 0x5410u) + (e ? 0x2222u : 0u);
        const uint32_t ma = sb + SM_MOD + lane * 4;
        mbar_wait(bars + BAR_M * 8, 0);
#pragma unroll
        for (int i = 0; i < 10; i++) {
            uint32_t h = bfma2(ln_apply(x[i], s1.x, s1.y, s1.z), badd2(lds32(ma + 1280 + i * 128), one2), lds32(ma + i * 128));
            a[i] = bmul2(h, lds32(ma + 2560 + i * 128));
            sbv[i] = lds32(ma + 3840 + i * 128);
            cb[i] = badd2(lds32(ma + 5120 + i * 128), one2);
        }
        if (warp == 4) TSW(52);
#pragma unroll 1
        for (int pass = WARM ? 0 : 1; pass < 2; pass++) {
            if (pass) { mbar_wait(bars + BAR_Y * 8, 0); if (warp == 0) TSW(22); }
            uint32_t z[10];
#pragma unroll
            for (int i = 0; i < 10; i++) {
                uint32_t y0 = lds32(ya + i * 2048 + up * 32), y1 = lds32(ya + i * 2048 + (up ^ 1) * 32);
                z[i] = bfma2(a[i], prmt(y0, y1, sel), x[i]);
            }
            const uint3 s2 = row_stats(z, lane);
#pragma unroll
            for (int i = 0; i < 10; i++) z[i] = bfma2(ln_apply(z[i], s2.x, s2.y, s2.z), cb[i], sbv[i]);
            const uint3 s3 = row_stats(z, lane);
            uint32_t* o = reinterpret_cast<uint32_t*>(g_hn + (size_t)rrow * D_) + lane;
#pragma unroll
            for (int i = 0; i < 10; i++) stg32_if(o + 32 * i, ln_apply(z[i], s3.x, s3.y, s3.z), pass);
            if (lane < 2 && pass) g_rs[rrow * 2 + lane] = lane ? make_uint4(s2.x, s2.y, s2.z, 0) : make_uint4(s1.x, s1.y, s1.z, 0);
        }
        if (warp == 0) TSW(34);
        bar_arrive(8, 544);
    }

    const int half = wg & 1;
    const int row = 64 * half + 16 * wq + g;
    const int tw0 = (rb * 80 + (cm >> 3)) * 512 + row * 4 + c, tw1 = (rb * 80 + (cr >> 3) - 8) * 512 + row * 4 + c;
    const uint32_t park = sb + SM_Y + (tid & 255) * 16;
    const uint32_t ms0 = sb + SM_MOD + (cm + 2 * c) * 2, ms1 = sb + SM_MOD + (cr - 64 + 2 * c) * 2;
    if (wg >= 2) {
        {
            float acc[40];
            gemm_loop<80, true, 0, 0, 10, 10, 10, true, 0, 0, 25>(acc, sb, half);
#pragma unroll
            for (int k = 0; k < 10; k += CH) CHUNK(k) {
#pragma unroll
                for (int q = k; q < k + CH && q < 10; q++) {
                    uint32_t* dst = reinterpret_cast<uint32_t*>(g_h1) + (q < 8 ? tw0 : tw1);
                    dst[q * 512] = pack2(gelu(acc[4 * q]), gelu(acc[4 * q + 1]));
                    dst[q * 512 + 32] = pack2(gelu(acc[4 * q + 2]), gelu(acc[4 * q + 3]));
                }
            }
            bar_arrive(15, 288);
            bar_arrive(14, 512);
        }
        gemm3<112, 20, 20, 10 - NA, 11, 9, 1>(sb, rb, 8 * j, 64 + 6 * j, half, wq, g, c, ones);
        if (tid == 256) TS(35);
        {
            float acc[40];
            uint32_t gbv[10];
            uint4 bsv[5];
#pragma unroll
            for (int q = 0; q < 5; q++) { const uint32_t ms = q < 4 ? ms0 : ms1; gbv[2 * q] = lds32(ms + 6400 + q * 32); gbv[2 * q + 1] = lds32(ms + 6400 + q * 32 + 16); bsv[q] = lds128(park + q * 4096); }
            gemm_loop<80, false, 40 - NA, 40, 27, 27 - NA, 27 - NB, true, 10, 0, 42>(acc, sb, half);
            bf16* go = p.out + (size_t)(rb * 128 + row) * D_ + (c & 1) * 8 + (c >> 1) * 4;
#pragma unroll
            for (int q = 0; q < 5; q++) CHUNK(q) {
                const uint32_t g0 = gbv[2 * q], g1 = gbv[2 * q + 1];
                const uint4 bs = bsv[q];
#pragma unroll
                for (int r = 0; r < 2; r++) {
                    const uint32_t b0 = r ? bs.y : bs.x, b1 = r ? bs.w : bs.z;
                    uint32_t t0 = pack2(fmaf(blo(g0), acc[8 * q + 2 * r], blo(b0)), fmaf(bhi(g0), acc[8 * q + 2 * r + 1], bhi(b0)));
                    uint32_t t1 = pack2(fmaf(blo(g1), acc[8 * q + 4 + 2 * r], blo(b1)), fmaf(bhi(g1), acc[8 * q + 4 + 2 * r + 1], bhi(b1)));
                    uint32_t rv = __shfl_xor_sync(0xffffffffu, (c & 1) ? t0 : t1, 1);
                    *reinterpret_cast<uint2*>(go + r * 8 * D_ + (q < 4 ? cm + 16 * q : cr)) = (c & 1) ? make_uint2(rv, t1) : make_uint2(t0, rv);
                }
            }
            if (tid == 256) TS(44);
            if (warp == 8) TSFLUSH();
        }
    } else {
        {
            float acc[40];
            uint32_t x2[20];
            {
                uint32_t y[20];
                mbar_wait(bars + BAR_XY * 8, 0);
                const uint32_t xa = sb + SM_XT + row * 128 + c * 4, xb = sb + SM_XT2 + row * 32 + c * 4;
                const uint32_t ya = sb + SM_YT + (4 * half + wq) * 2560 + c * 64;
#pragma unroll
                for (int q = 0; q < 10; q++) {
                    const uint32_t a = q < 8 ? xa + ((q ^ g) << 4) : xb + (q - 8) * 16;
                    x2[2 * q] = lds32(a); x2[2 * q + 1] = lds32(a + (q < 8 ? 1024 : 256));
                    const int pos = (g + ((q < 8 ? cm : cr) >> 2) + 2 * q + (c >> 1)) & 7;
                    y[2 * q] = lds32(ya + q * 256 + pos * 4); y[2 * q + 1] = lds32(ya + q * 256 + 32 + pos * 4);
                }
                fence_async_smem();
                bar_sync(1 + wg, 128);
                if ((tid & 127) < NA) mbar_arrive_cl(mapa(bars + (BAR_EA + (tid & 127)) * 8, blockIdx.x & 1));
                mbar_wait(bars + BAR_FA * 8, 0);
                const uint4* rp = g_rs + (rb * 128 + row) * 2;
                const uint4 ra = ldcg128(rp), rb2 = ldcg128(rp + 1), rc = ldcg128(rp + 16), rd = ldcg128(rp + 17);
                bar_sync(14, 512);
#pragma unroll
                for (int q = 0; q < 10; q++) {
                    const uint32_t ms = q < 8 ? ms0 : ms1;
                    const uint32_t sa = lds32(ms + 16 * q), ca = badd2(lds32(ms + 1280 + 16 * q), one2), ga = lds32(ms + 2560 + 16 * q);
                    const uint32_t sbv = lds32(ms + 3840 + 16 * q), cb = badd2(lds32(ms + 5120 + 16 * q), one2);
                    uint32_t u = x2[2 * q], v = x2[2 * q + 1];
                    u = bfma2(bmul2(bfma2(ln_apply(u, ra.x, ra.y, ra.z), ca, sa), ga), prmt(y[2 * q], y[2 * q + 1], 0x5410), u);
                    v = bfma2(bmul2(bfma2(ln_apply(v, rc.x, rc.y, rc.z), ca, sa), ga), prmt(y[2 * q], y[2 * q + 1], 0x7632), v);
                    x2[2 * q] = u; x2[2 * q + 1] = v;
                    u = bfma2(ln_apply(u, rb2.x, rb2.y, rb2.z), cb, sbv);
                    v = bfma2(ln_apply(v, rd.x, rd.y, rd.z), cb, sbv);
                    acc[4 * q] = blo(u); acc[4 * q + 1] = bhi(u); acc[4 * q + 2] = blo(v); acc[4 * q + 3] = bhi(v);
                }
            }
            reg_fence<40>(acc);
            if (tid == 0) TS(45);
            gemm_loop<80, false, 10, 10, 10, 10, 10, false, 0, 11, 29>(acc, sb, half);
            uint32_t x1[20];
            float s0 = 0.f, q0 = 0.f, s1 = 0.f, q1 = 0.f;
#pragma unroll
            for (int q = 0; q < 10; q++) {
                uint32_t u = pack2(acc[4 * q], acc[4 * q + 1]);
                uint32_t v = pack2(acc[4 * q + 2], acc[4 * q + 3]);
                uint32_t* dst = reinterpret_cast<uint32_t*>(g_x1) + (q < 8 ? tw0 : tw1);
                dst[q * 512] = u;
                dst[q * 512 + 32] = v;
                x1[2 * q] = u; x1[2 * q + 1] = v;
            }
            CHUNK(0)
#pragma unroll
            for (int q = 0; q < 10; q++) {
                float a = blo(x1[2 * q]), b = bhi(x1[2 * q]), e = blo(x1[2 * q + 1]), f = bhi(x1[2 * q + 1]);
                s0 += a + b; q0 = fmaf(a, a, fmaf(b, b, q0));
                s1 += e + f; q1 = fmaf(e, e, fmaf(f, f, q1));
            }
#pragma unroll
            for (int m = 1; m <= 2; m <<= 1) {
                s0 += __shfl_xor_sync(0xffffffffu, s0, m); q0 += __shfl_xor_sync(0xffffffffu, q0, m);
                s1 += __shfl_xor_sync(0xffffffffu, s1, m); q1 += __shfl_xor_sync(0xffffffffu, q1, m);
            }
            if (c < 2) g_st[(rb * 8 + j) * 128 + row + 8 * c] = c ? make_float2(s1, q1) : make_float2(s0, q0);
            bar_arrive(12, 288);
#pragma unroll
            for (int q = 0; q < 5; q++) {
                const uint32_t ms = q < 4 ? ms0 : ms1;
                const uint32_t g0 = lds32(ms + 6400 + q * 32), g1 = lds32(ms + 6400 + q * 32 + 16);
                sts128(park + q * 4096, make_uint4(bfma2(g0, x1[4 * q], x2[4 * q]), bfma2(g0, x1[4 * q + 1], x2[4 * q + 1]),
                                                   bfma2(g1, x1[4 * q + 2], x2[4 * q + 2]), bfma2(g1, x1[4 * q + 3], x2[4 * q + 3])));
            }
        }
        gemm3<104, 30 - NA, 30, 10, 9, 10, 2>(sb, rb, 112 + 8 * j, 176 + 5 * j, half, wq, g, c, ones);
        if (tid == 0) TS(38);
    }
}

typedef CUresult (*EncFn)(CUtensorMap*, CUtensorMapDataType, cuuint32_t, void*, const cuuint64_t*, const cuuint64_t*,
                          const cuuint32_t*, const cuuint32_t*, CUtensorMapInterleave, CUtensorMapSwizzle,
                          CUtensorMapL2promotion, CUtensorMapFloatOOBfill);

void make_map(EncFn enc, CUtensorMap* m, const void* base, uint64_t inner, uint64_t outer, uint32_t bi, uint32_t bo,
              CUtensorMapSwizzle swz = CU_TENSOR_MAP_SWIZZLE_128B) {
    cuuint64_t dims[2] = {inner, outer};
    cuuint64_t st[1] = {inner * 2};
    cuuint32_t box[2] = {bi, bo};
    cuuint32_t es[2] = {1, 1};
    enc(m, CU_TENSOR_MAP_DATA_TYPE_BFLOAT16, 2, const_cast<void*>(base), dims, st, box, es, CU_TENSOR_MAP_INTERLEAVE_NONE,
        swz, CU_TENSOR_MAP_L2_PROMOTION_NONE, CU_TENSOR_MAP_FLOAT_OOB_FILL_NONE);
}

}

extern "C" void kernel_launch(void* const* d_in, const int* in_sizes, int n_in, void* d_out, int out_size) {
    (void)in_sizes; (void)n_in; (void)out_size;
    Params p;
    p.q = (const bf16*)d_in[0]; p.k = (const bf16*)d_in[1]; p.v = (const bf16*)d_in[2];
    p.shift = (const bf16*)d_in[3]; p.ssmk = (const bf16*)d_in[4]; p.ssmD = (const bf16*)d_in[5];
    p.w1 = (const bf16*)d_in[7]; p.w2 = (const bf16*)d_in[8]; p.w3 = (const bf16*)d_in[9]; p.w4 = (const bf16*)d_in[10];
    p.c = (const bf16*)d_in[11]; p.wmod = (const bf16*)d_in[12];
    p.out = (bf16*)d_out;
    p.ones = 0xffffffffu;

    void* fn = nullptr;
    cudaDriverEntryPointQueryResult qr;
    cudaGetDriverEntryPoint("cuTensorMapEncodeTiled", &fn, cudaEnableDefault, &qr);
    EncFn enc = (EncFn)fn;
    void* hn = nullptr;
    cudaGetSymbolAddress(&hn, g_hn);
    Maps maps;
    make_map(enc, &maps.w3s, p.w3, F_, D_, 216, 64, CU_TENSOR_MAP_SWIZZLE_NONE);
    make_map(enc, &maps.wm, p.wmod, 6 * D_, D_, 32, 128, CU_TENSOR_MAP_SWIZZLE_64B);
    make_map(enc, &maps.xa, p.q, D_, S_, 64, 128);
    make_map(enc, &maps.xb, p.q, D_, S_, 16, 128, CU_TENSOR_MAP_SWIZZLE_NONE);
    make_map(enc, &maps.hn, hn, D_, S_, 64, 128);
    make_map(enc, &maps.w1a, p.w1, D_, D_, 64, 64);
    make_map(enc, &maps.w1b, p.w1, D_, D_, 16, 64);
    make_map(enc, &maps.w2a, p.w2, D_, D_, 64, 64);
    make_map(enc, &maps.w2b, p.w2, D_, D_, 16, 64);
    make_map(enc, &maps.w3a, p.w3, F_, D_, 64, 64);
    make_map(enc, &maps.w3b, p.w3, F_, D_, 48, 64);
    make_map(enc, &maps.w3c, p.w3, F_, D_, 40, 64);
    make_map(enc, &maps.w4a, p.w4, D_, F_, 64, 64);
    make_map(enc, &maps.w4b, p.w4, D_, F_, 16, 64);
    cudaFuncSetAttribute(fused_kernel, cudaFuncAttributeMaxDynamicSharedMemorySize, SMEM_BYTES);
    fused_kernel<<<132, NTHREADS, SMEM_BYTES>>>(p, maps);
}
```

```cpp
#include <cuda_runtime.h>
#include <cuda_bf16.h>
#include <cuda.h>
#include <stdint.h>
#include <string.h>

#define SEED 1
#define RING_A 6
#define MMA_STAT 0
#define CH 2
#define FAST_LN 1
#define EXPER 0
#define HO_A 10
#define HO_B 6
#define STAG 10
#define REDM 1
#define CONVV 0
#define HOLD 1
#define SSM_WHEN -2000
#define PF_EARLY 0

namespace {

typedef __nv_bfloat16 bf16;
typedef __nv_bfloat162 bf162;

constexpr int S_ = 2048, D_ = 640, F_ = 1728;
constexpr int NTHREADS = 640;
constexpr int NA = RING_A, NB = 12 - RING_A;
constexpr int SLOT = 16384;
constexpr int SM_RA = 0, SM_RB = NA * SLOT;

constexpr int SM_RED = 0;
constexpr int RED_STRIDE = 17536;
constexpr int SM_PK = 0;
constexpr int SM_PV = 24576;
constexpr int SM_WM = 88064;
constexpr int SM_K = SM_WM + 40960;
constexpr int K_STRIDE = 8320;
constexpr int SM_U = SM_K + 5 * K_STRIDE;
constexpr int U_PLANE = 2560, U_STRIDE = 5120;
constexpr int SM_Y = 12 * SLOT;
static_assert(SM_U + 5 * U_STRIDE <= SM_Y, "smem map");
constexpr int SM_XT = 3 * SLOT, SM_XT2 = 4 * SLOT, SM_YT = SM_XT2 + 4096;
constexpr int SM_MOD = SM_Y + 20480;
constexpr int SM_GV = SM_MOD + 7680;
constexpr int SM_CS = SM_GV + 1024;
constexpr int SM_RP = SM_CS + 1024;
constexpr int SM_BAR = SM_RP + 1024;
constexpr int SM_PROF = SM_BAR + 512;
constexpr int SM_TOTAL = SM_PROF + 512;
constexpr int SMEM_BYTES = SM_TOTAL + 1024;
static_assert(SMEM_BYTES <= 232448, "smem");

constexpr int BAR_FA = 0, BAR_FB = NA, BAR_EA = 12, BAR_EB = 12 + NA, BAR_K = 24, BAR_U = 29, BAR_Y = 34, BAR_CS = 35, BAR_WM = 36, BAR_M = 37, BAR_XY = 38, BAR_Y2 = 39;

__device__ __align__(1024) bf16 g_kvT[D_ * S_];
__device__ __align__(1024) uint32_t g_yv[128 * 5120];
__device__ __align__(1024) bf16 g_mod[6 * D_];
__device__ __align__(1024) bf16 g_hn[S_ * D_];
__device__ __align__(1024) uint4 g_rs[S_ * 2];
__device__ __align__(1024) bf16 g_h1[S_ * D_];
__device__ __align__(1024) bf16 g_x1[S_ * D_];
__device__ __align__(1024) bf16 g_g[S_ * F_];
__device__ __align__(1024) float2 g_st[S_ * 8];
__device__ __align__(1024) float g_cs[F_];
__device__ __align__(1024) unsigned g_flags[128 * 32];
__device__ __align__(1024) unsigned g_epoch[160];
constexpr int FL_P = 0, FL_C = 8, FL_CS = 9, FL_M = 10, FL_R = 16, FL_B1 = 32, FL_B2 = 48, FL_G = 64;

#define TS(i) do {} while (0)
#define TSW(i) do {} while (0)
#define TSD(i, dep) do {} while (0)
#define TSD2(i, dep) do {} while (0)
#define TSFLUSH() do {} while (0)

struct Params {
    const bf16 *q, *k, *v, *shift, *ssmk, *ssmD, *w1, *w2, *w3, *w4, *c, *wmod;
    bf16* out;
    unsigned ones;
};
#define CHUNK(k) if (ones & (1u << (k)))
struct Maps { CUtensorMap hn, w1a, w1b, w2a, w2b, w3a, w3b, w3c, w4a, w4b, wm, xa, xb, w3s; };

template<int N> struct WgRs;
template<int N> struct WgSs;
template<> struct WgRs<32> { template<int OFF,int HI,int SC> static __device__ __forceinline__ void run(float* d,uint32_t a0,uint32_t a1,uint32_t a2,uint32_t a3,uint32_t blo){
 asm volatile("{.reg .b32 l; .reg .b64 db; add.u32 l,%20,%21; mov.b64 db,{l,%22}; wgmma.mma_async.sync.aligned.m64n32k16.f32.bf16.bf16 {%0,%1,%2,%3,%4,%5,%6,%7,%8,%9,%10,%11,%12,%13,%14,%15},{%16,%17,%18,%19},db,%23,1,1,0;}"
 :"+f"(d[0]),"+f"(d[1]),"+f"(d[2]),"+f"(d[3]),"+f"(d[4]),"+f"(d[5]),"+f"(d[6]),"+f"(d[7]),"+f"(d[8]),"+f"(d[9]),"+f"(d[10]),"+f"(d[11]),"+f"(d[12]),"+f"(d[13]),"+f"(d[14]),"+f"(d[15])
 :"r"(a0),"r"(a1),"r"(a2),"r"(a3),"r"(blo),"n"(OFF),"n"(HI),"n"(SC)); } };
template<> struct WgRs<48> { template<int OFF,int HI,int SC> static __device__ __forceinline__ void run(float* d,uint32_t a0,uint32_t a1,uint32_t a2,uint32_t a3,uint32_t blo){
 asm volatile("{.reg .b32 l; .reg .b64 db; add.u32 l,%28,%29; mov.b64 db,{l,%30}; wgmma.mma_async.sync.aligned.m64n48k16.f32.bf16.bf16 {%0,%1,%2,%3,%4,%5,%6,%7,%8,%9,%10,%11,%12,%13,%14,%15,%16,%17,%18,%19,%20,%21,%22,%23},{%24,%25,%26,%27},db,%31,1,1,0;}"
 :"+f"(d[0]),"+f"(d[1]),"+f"(d[2]),"+f"(d[3]),"+f"(d[4]),"+f"(d[5]),"+f"(d[6]),"+f"(d[7]),"+f"(d[8]),"+f"(d[9]),"+f"(d[10]),"+f"(d[11]),"+f"(d[12]),"+f"(d[13]),"+f"(d[14]),"+f"(d[15]),"+f"(d[16]),"+f"(d[17]),"+f"(d[18]),"+f"(d[19]),"+f"(d[20]),"+f"(d[21]),"+f"(d[22]),"+f"(d[23])
 :"r"(a0),"r"(a1),"r"(a2),"r"(a3),"r"(blo),"n"(OFF),"n"(HI),"n"(SC)); } };
template<> struct WgRs<64> { template<int OFF,int HI,int SC> static __device__ __forceinline__ void run(float* d,uint32_t a0,uint32_t a1,uint32_t a2,uint32_t a3,uint32_t blo){
 asm volatile("{.reg .b32 l; .reg .b64 db; add.u32 l,%36,%37; mov.b64 db,{l,%38}; wgmma.mma_async.sync.aligned.m64n64k16.f32.bf16.bf16 {%0,%1,%2,%3,%4,%5,%6,%7,%8,%9,%10,%11,%12,%13,%14,%15,%16,%17,%18,%19,%20,%21,%22,%23,%24,%25,%26,%27,%28,%29,%30,%31},{%32,%33,%34,%35},db,%39,1,1,0;}"
 :"+f"(d[0]),"+f"(d[1]),"+f"(d[2]),"+f"(d[3]),"+f"(d[4]),"+f"(d[5]),"+f"(d[6]),"+f"(d[7]),"+f"(d[8]),"+f"(d[9]),"+f"(d[10]),"+f"(d[11]),"+f"(d[12]),"+f"(d[13]),"+f"(d[14]),"+f"(d[15]),"+f"(d[16]),"+f"(d[17]),"+f"(d[18]),"+f"(d[19]),"+f"(d[20]),"+f"(d[21]),"+f"(d[22]),"+f"(d[23]),"+f"(d[24]),"+f"(d[25]),"+f"(d[26]),"+f"(d[27]),"+f"(d[28]),"+f"(d[29]),"+f"(d[30]),"+f"(d[31])
 :"r"(a0),"r"(a1),"r"(a2),"r"(a3),"r"(blo),"n"(OFF),"n"(HI),"n"(SC)); } };
template<> struct WgRs<80> { template<int OFF,int HI,int SC> static __device__ __forceinline__ void run(float* d,uint32_t a0,uint32_t a1,uint32_t a2,uint32_t a3,uint32_t blo){
 asm volatile("{.reg .b32 l; .reg .b64 db; add.u32 l,%44,%45; mov.b64 db,{l,%46}; wgmma.mma_async.sync.aligned.m64n80k16.f32.bf16.bf16 {%0,%1,%2,%3,%4,%5,%6,%7,%8,%9,%10,%11,%12,%13,%14,%15,%16,%17,%18,%19,%20,%21,%22,%23,%24,%25,%26,%27,%28,%29,%30,%31,%32,%33,%34,%35,%36,%37,%38,%39},{%40,%41,%42,%43},db,%47,1,1,0;}"
 :"+f"(d[0]),"+f"(d[1]),"+f"(d[2]),"+f"(d[3]),"+f"(d[4]),"+f"(d[5]),"+f"(d[6]),"+f"(d[7]),"+f"(d[8]),"+f"(d[9]),"+f"(d[10]),"+f"(d[11]),"+f"(d[12]),"+f"(d[13]),"+f"(d[14]),"+f"(d[15]),"+f"(d[16]),"+f"(d[17]),"+f"(d[18]),"+f"(d[19]),"+f"(d[20]),"+f"(d[21]),"+f"(d[22]),"+f"(d[23]),"+f"(d[24]),"+f"(d[25]),"+f"(d[26]),"+f"(d[27]),"+f"(d[28]),"+f"(d[29]),"+f"(d[30]),"+f"(d[31]),"+f"(d[32]),"+f"(d[33]),"+f"(d[34]),"+f"(d[35]),"+f"(d[36]),"+f"(d[37]),"+f"(d[38]),"+f"(d[39])
 :"r"(a0),"r"(a1),"r"(a2),"r"(a3),"r"(blo),"n"(OFF),"n"(HI),"n"(SC)); } };
template<> struct WgRs<96> { template<int OFF,int HI,int SC> static __device__ __forceinline__ void run(float* d,uint32_t a0,uint32_t a1,uint32_t a2,uint32_t a3,uint32_t blo){
 asm volatile("{.reg .b32 l; .reg .b64 db; add.u32 l,%52,%53; mov.b64 db,{l,%54}; wgmma.mma_async.sync.aligned.m64n96k16.f32.bf16.bf16 {%0,%1,%2,%3,%4,%5,%6,%7,%8,%9,%10,%11,%12,%13,%14,%15,%16,%17,%18,%19,%20,%21,%22,%23,%24,%25,%26,%27,%28,%29,%30,%31,%32,%33,%34,%35,%36,%37,%38,%39,%40,%41,%42,%43,%44,%45,%46,%47},{%48,%49,%50,%51},db,%55,1,1,0;}"
 :"+f"(d[0]),"+f"(d[1]),"+f"(d[2]),"+f"(d[3]),"+f"(d[4]),"+f"(d[5]),"+f"(d[6]),"+f"(d[7]),"+f"(d[8]),"+f"(d[9]),"+f"(d[10]),"+f"(d[11]),"+f"(d[12]),"+f"(d[13]),"+f"(d[14]),"+f"(d[15]),"+f"(d[16]),"+f"(d[17]),"+f"(d[18]),"+f"(d[19]),"+f"(d[20]),"+f"(d[21]),"+f"(d[22]),"+f"(d[23]),"+f"(d[24]),"+f"(d[25]),"+f"(d[26]),"+f"(d[27]),"+f"(d[28]),"+f"(d[29]),"+f"(d[30]),"+f"(d[31]),"+f"(d[32]),"+f"(d[33]),"+f"(d[34]),"+f"(d[35]),"+f"(d[36]),"+f"(d[37]),"+f"(d[38]),"+f"(d[39]),"+f"(d[40]),"+f"(d[41]),"+f"(d[42]),"+f"(d[43]),"+f"(d[44]),"+f"(d[45]),"+f"(d[46]),"+f"(d[47])
 :"r"(a0),"r"(a1),"r"(a2),"r"(a3),"r"(blo),"n"(OFF),"n"(HI),"n"(SC)); } };
template<> struct WgRs<112> { template<int OFF,int HI,int SC> static __device__ __forceinline__ void run(float* d,uint32_t a0,uint32_t a1,uint32_t a2,uint32_t a3,uint32_t blo){
 asm volatile("{.reg .b32 l; .reg .b64 db; add.u32 l,%60,%61; mov.b64 db,{l,%62}; wgmma.mma_async.sync.aligned.m64n112k16.f32.bf16.bf16 {%0,%1,%2,%3,%4,%5,%6,%7,%8,%9,%10,%11,%12,%13,%14,%15,%16,%17,%18,%19,%20,%21,%22,%23,%24,%25,%26,%27,%28,%29,%30,%31,%32,%33,%34,%35,%36,%37,%38,%39,%40,%41,%42,%43,%44,%45,%46,%47,%48,%49,%50,%51,%52,%53,%54,%55},{%56,%57,%58,%59},db,%63,1,1,0;}"
 :"+f"(d[0]),"+f"(d[1]),"+f"(d[2]),"+f"(d[3]),"+f"(d[4]),"+f"(d[5]),"+f"(d[6]),"+f"(d[7]),"+f"(d[8]),"+f"(d[9]),"+f"(d[10]),"+f"(d[11]),"+f"(d[12]),"+f"(d[13]),"+f"(d[14]),"+f"(d[15]),"+f"(d[16]),"+f"(d[17]),"+f"(d[18]),"+f"(d[19]),"+f"(d[20]),"+f"(d[21]),"+f"(d[22]),"+f"(d[23]),"+f"(d[24]),"+f"(d[25]),"+f"(d[26]),"+f"(d[27]),"+f"(d[28]),"+f"(d[29]),"+f"(d[30]),"+f"(d[31]),"+f"(d[32]),"+f"(d[33]),"+f"(d[34]),"+f"(d[35]),"+f"(d[36]),"+f"(d[37]),"+f"(d[38]),"+f"(d[39]),"+f"(d[40]),"+f"(d[41]),"+f"(d[42]),"+f"(d[43]),"+f"(d[44]),"+f"(d[45]),"+f"(d[46]),"+f"(d[47]),"+f"(d[48]),"+f"(d[49]),"+f"(d[50]),"+f"(d[51]),"+f"(d[52]),"+f"(d[53]),"+f"(d[54]),"+f"(d[55])
 :"r"(a0),"r"(a1),"r"(a2),"r"(a3),"r"(blo),"n"(OFF),"n"(HI),"n"(SC)); } };
template<> struct WgRs<128> { template<int OFF,int HI,int SC> static __device__ __forceinline__ void run(float* d,uint32_t a0,uint32_t a1,uint32_t a2,uint32_t a3,uint32_t blo){
 asm volatile("{.reg .b32 l; .reg .b64 db; add.u32 l,%68,%69; mov.b64 db,{l,%70}; wgmma.mma_async.sync.aligned.m64n128k16.f32.bf16.bf16 {%0,%1,%2,%3,%4,%5,%6,%7,%8,%9,%10,%11,%12,%13,%14,%15,%16,%17,%18,%19,%20,%21,%22,%23,%24,%25,%26,%27,%28,%29,%30,%31,%32,%33,%34,%35,%36,%37,%38,%39,%40,%41,%42,%43,%44,%45,%46,%47,%48,%49,%50,%51,%52,%53,%54,%55,%56,%57,%58,%59,%60,%61,%62,%63},{%64,%65,%66,%67},db,%71,1,1,0;}"
 :"+f"(d[0]),"+f"(d[1]),"+f"(d[2]),"+f"(d[3]),"+f"(d[4]),"+f"(d[5]),"+f"(d[6]),"+f"(d[7]),"+f"(d[8]),"+f"(d[9]),"+f"(d[10]),"+f"(d[11]),"+f"(d[12]),"+f"(d[13]),"+f"(d[14]),"+f"(d[15]),"+f"(d[16]),"+f"(d[17]),"+f"(d[18]),"+f"(d[19]),"+f"(d[20]),"+f"(d[21]),"+f"(d[22]),"+f"(d[23]),"+f"(d[24]),"+f"(d[25]),"+f"(d[26]),"+f"(d[27]),"+f"(d[28]),"+f"(d[29]),"+f"(d[30]),"+f"(d[31]),"+f"(d[32]),"+f"(d[33]),"+f"(d[34]),"+f"(d[35]),"+f"(d[36]),"+f"(d[37]),"+f"(d[38]),"+f"(d[39]),"+f"(d[40]),"+f"(d[41]),"+f"(d[42]),"+f"(d[43]),"+f"(d[44]),"+f"(d[45]),"+f"(d[46]),"+f"(d[47]),"+f"(d[48]),"+f"(d[49]),"+f"(d[50]),"+f"(d[51]),"+f"(d[52]),"+f"(d[53]),"+f"(d[54]),"+f"(d[55]),"+f"(d[56]),"+f"(d[57]),"+f"(d[58]),"+f"(d[59]),"+f"(d[60]),"+f"(d[61]),"+f"(d[62]),"+f"(d[63])
 :"r"(a0),"r"(a1),"r"(a2),"r"(a3),"r"(blo),"n"(OFF),"n"(HI),"n"(SC)); } };
template<> struct WgSs<80> { template<int AOFF,int AHI,int BOFF,int BHI,int SC> static __device__ __forceinline__ void run(float* d,uint32_t alo,uint32_t blo){
 asm volatile("{.reg .b32 l,m; .reg .b64 da,db; add.u32 l,%40,%42; mov.b64 da,{l,%43}; add.u32 m,%41,%44; mov.b64 db,{m,%45}; wgmma.mma_async.sync.aligned.m64n80k16.f32.bf16.bf16 {%0,%1,%2,%3,%4,%5,%6,%7,%8,%9,%10,%11,%12,%13,%14,%15,%16,%17,%18,%19,%20,%21,%22,%23,%24,%25,%26,%27,%28,%29,%30,%31,%32,%33,%34,%35,%36,%37,%38,%39},da,db,%46,1,1,0,1;}"
 :"+f"(d[0]),"+f"(d[1]),"+f"(d[2]),"+f"(d[3]),"+f"(d[4]),"+f"(d[5]),"+f"(d[6]),"+f"(d[7]),"+f"(d[8]),"+f"(d[9]),"+f"(d[10]),"+f"(d[11]),"+f"(d[12]),"+f"(d[13]),"+f"(d[14]),"+f"(d[15]),"+f"(d[16]),"+f"(d[17]),"+f"(d[18]),"+f"(d[19]),"+f"(d[20]),"+f"(d[21]),"+f"(d[22]),"+f"(d[23]),"+f"(d[24]),"+f"(d[25]),"+f"(d[26]),"+f"(d[27]),"+f"(d[28]),"+f"(d[29]),"+f"(d[30]),"+f"(d[31]),"+f"(d[32]),"+f"(d[33]),"+f"(d[34]),"+f"(d[35]),"+f"(d[36]),"+f"(d[37]),"+f"(d[38]),"+f"(d[39])
 :"r"(alo),"r"(blo),"n"(AOFF),"n"(AHI),"n"(BOFF),"n"(BHI),"n"(SC)); } };
template<> struct WgSs<104> { template<int AOFF,int AHI,int BOFF,int BHI,int SC> static __device__ __forceinline__ void run(float* d,uint32_t alo,uint32_t blo){
 asm volatile("{.reg .b32 l,m; .reg .b64 da,db; add.u32 l,%52,%54; mov.b64 da,{l,%55}; add.u32 m,%53,%56; mov.b64 db,{m,%57}; wgmma.mma_async.sync.aligned.m64n104k16.f32.bf16.bf16 {%0,%1,%2,%3,%4,%5,%6,%7,%8,%9,%10,%11,%12,%13,%14,%15,%16,%17,%18,%19,%20,%21,%22,%23,%24,%25,%26,%27,%28,%29,%30,%31,%32,%33,%34,%35,%36,%37,%38,%39,%40,%41,%42,%43,%44,%45,%46,%47,%48,%49,%50,%51},da,db,%58,1,1,0,1;}"
 :"+f"(d[0]),"+f"(d[1]),"+f"(d[2]),"+f"(d[3]),"+f"(d[4]),"+f"(d[5]),"+f"(d[6]),"+f"(d[7]),"+f"(d[8]),"+f"(d[9]),"+f"(d[10]),"+f"(d[11]),"+f"(d[12]),"+f"(d[13]),"+f"(d[14]),"+f"(d[15]),"+f"(d[16]),"+f"(d[17]),"+f"(d[18]),"+f"(d[19]),"+f"(d[20]),"+f"(d[21]),"+f"(d[22]),"+f"(d[23]),"+f"(d[24]),"+f"(d[25]),"+f"(d[26]),"+f"(d[27]),"+f"(d[28]),"+f"(d[29]),"+f"(d[30]),"+f"(d[31]),"+f"(d[32]),"+f"(d[33]),"+f"(d[34]),"+f"(d[35]),"+f"(d[36]),"+f"(d[37]),"+f"(d[38]),"+f"(d[39]),"+f"(d[40]),"+f"(d[41]),"+f"(d[42]),"+f"(d[43]),"+f"(d[44]),"+f"(d[45]),"+f"(d[46]),"+f"(d[47]),"+f"(d[48]),"+f"(d[49]),"+f"(d[50]),"+f"(d[51])
 :"r"(alo),"r"(blo),"n"(AOFF),"n"(AHI),"n"(BOFF),"n"(BHI),"n"(SC)); } };
template<> struct WgSs<112> { template<int AOFF,int AHI,int BOFF,int BHI,int SC> static __device__ __forceinline__ void run(float* d,uint32_t alo,uint32_t blo){
 asm volatile("{.reg .b32 l,m; .reg .b64 da,db; add.u32 l,%56,%58; mov.b64 da,{l,%59}; add.u32 m,%57,%60; mov.b64 db,{m,%61}; wgmma.mma_async.sync.aligned.m64n112k16.f32.bf16.bf16 {%0,%1,%2,%3,%4,%5,%6,%7,%8,%9,%10,%11,%12,%13,%14,%15,%16,%17,%18,%19,%20,%21,%22,%23,%24,%25,%26,%27,%28,%29,%30,%31,%32,%33,%34,%35,%36,%37,%38,%39,%40,%41,%42,%43,%44,%45,%46,%47,%48,%49,%50,%51,%52,%53,%54,%55},da,db,%62,1,1,0,1;}"
 :"+f"(d[0]),"+f"(d[1]),"+f"(d[2]),"+f"(d[3]),"+f"(d[4]),"+f"(d[5]),"+f"(d[6]),"+f"(d[7]),"+f"(d[8]),"+f"(d[9]),"+f"(d[10]),"+f"(d[11]),"+f"(d[12]),"+f"(d[13]),"+f"(d[14]),"+f"(d[15]),"+f"(d[16]),"+f"(d[17]),"+f"(d[18]),"+f"(d[19]),"+f"(d[20]),"+f"(d[21]),"+f"(d[22]),"+f"(d[23]),"+f"(d[24]),"+f"(d[25]),"+f"(d[26]),"+f"(d[27]),"+f"(d[28]),"+f"(d[29]),"+f"(d[30]),"+f"(d[31]),"+f"(d[32]),"+f"(d[33]),"+f"(d[34]),"+f"(d[35]),"+f"(d[36]),"+f"(d[37]),"+f"(d[38]),"+f"(d[39]),"+f"(d[40]),"+f"(d[41]),"+f"(d[42]),"+f"(d[43]),"+f"(d[44]),"+f"(d[45]),"+f"(d[46]),"+f"(d[47]),"+f"(d[48]),"+f"(d[49]),"+f"(d[50]),"+f"(d[51]),"+f"(d[52]),"+f"(d[53]),"+f"(d[54]),"+f"(d[55])
 :"r"(alo),"r"(blo),"n"(AOFF),"n"(AHI),"n"(BOFF),"n"(BHI),"n"(SC)); } };

__device__ __forceinline__ void wg_fence() { asm volatile("wgmma.fence.sync.aligned;" ::: "memory"); }
__device__ __forceinline__ void wg_commit() { asm volatile("wgmma.commit_group.sync.aligned;" ::: "memory"); }
template <int N> __device__ __forceinline__ void wg_wait() { asm volatile("wgmma.wait_group.sync.aligned %0;" ::"n"(N) : "memory"); }
template <int N> __device__ __forceinline__ void reg_fence(float* d) {
#pragma unroll
    for (int i = 0; i < N; i++) asm volatile("" : "+f"(d[i])::"memory");
}
__device__ __forceinline__ uint32_t desc_lo(uint32_t addr, uint32_t lbo) { return ((addr & 0x3FFFF) >> 4) | ((lbo >> 4) << 16); }
#define desc_hi(sbo, sw) (((sbo) >> 4) | ((sw) << 30))
__device__ __forceinline__ uint32_t smem_u32(const void* p) { return (uint32_t)__cvta_generic_to_shared(p); }
__device__ __forceinline__ bool elect() {
    uint32_t p;
    asm volatile("{.reg .pred P; elect.sync _|P, 0xffffffff; selp.u32 %0,1,0,P;}" : "=r"(p));
    return p;
}
__device__ __forceinline__ void mbar_init(uint32_t bar, uint32_t cnt) { asm volatile("mbarrier.init.shared::cta.b64 [%0], %1;" ::"r"(bar), "r"(cnt) : "memory"); }
__device__ __forceinline__ void mbar_expect(uint32_t bar, uint32_t bytes) { asm volatile("mbarrier.arrive.expect_tx.shared::cta.b64 _, [%0], %1;" ::"r"(bar), "r"(bytes) : "memory"); }
__device__ __forceinline__ bool mbar_try(uint32_t bar, uint32_t par) {
    uint32_t ok;
    asm volatile("{.reg .pred p; mbarrier.try_wait.parity.shared::cta.b64 p, [%1], %2; selp.u32 %0,1,0,p;}" : "=r"(ok) : "r"(bar), "r"(par) : "memory");
    return ok;
}
constexpr int SPIN_LIMIT = 1 << 18;
__device__ __forceinline__ void mbar_wait(uint32_t bar, uint32_t par) {
    if (mbar_try(bar, par)) return;
    int n = 0;
    while (!mbar_try(bar, par) && ++n < SPIN_LIMIT) {}
}
__device__ __forceinline__ void bulk_g2s(uint32_t dst, const void* src, uint32_t bytes, uint32_t bar) {
    asm volatile("cp.async.bulk.shared::cluster.global.mbarrier::complete_tx::bytes [%0], [%1], %2, [%3];" ::"r"(dst), "l"(src), "r"(bytes), "r"(bar) : "memory");
}
__device__ __forceinline__ void bulk_s2g(void* dst, uint32_t src, uint32_t bytes) {
    asm volatile("cp.async.bulk.global.shared::cta.bulk_group [%0], [%1], %2;" ::"l"(dst), "r"(src), "r"(bytes) : "memory");
}
__device__ __forceinline__ void bulk_prefetch(const void* src, uint32_t bytes) {
    asm volatile("cp.async.bulk.prefetch.L2.global [%0], %1;" ::"l"(src), "r"(bytes) : "memory");
}
__device__ __forceinline__ void tma2d(uint32_t dst, const CUtensorMap* m, int c0, int c1, uint32_t bar) {
    asm volatile("cp.async.bulk.tensor.2d.shared::cluster.global.mbarrier::complete_tx::bytes [%0], [%1, {%3, %4}], [%2];" ::"r"(dst), "l"(m), "r"(bar), "r"(c0), "r"(c1) : "memory");
}
__device__ __forceinline__ void tma2d_mc(uint32_t dst, const CUtensorMap* m, int c0, int c1, uint32_t bar) {
    asm volatile("cp.async.bulk.tensor.2d.shared::cluster.global.mbarrier::complete_tx::bytes.multicast::cluster [%0], [%1, {%3, %4}], [%2], %5;" ::"r"(dst), "l"(m), "r"(bar), "r"(c0), "r"(c1), "h"((uint16_t)3) : "memory");
}
__device__ __forceinline__ uint32_t mapa(uint32_t a, uint32_t rank) { uint32_t r; asm("mapa.shared::cluster.u32 %0, %1, %2;" : "=r"(r) : "r"(a), "r"(rank)); return r; }
__device__ __forceinline__ void mbar_arrive_cl(uint32_t bar) { asm volatile("mbarrier.arrive.shared::cluster.b64 _, [%0];" ::"r"(bar) : "memory"); }
__device__ __forceinline__ void prefetch_map(const CUtensorMap* m) { asm volatile("prefetch.tensormap [%0];" ::"l"(m) : "memory"); }
__device__ __forceinline__ void cpasync16(uint32_t dst, const void* src, uint32_t srcsz) {
    asm volatile("cp.async.cg.shared.global [%0], [%1], 16, %2;" ::"r"(dst), "l"(src), "r"(srcsz) : "memory");
}
__device__ __forceinline__ void bar_sync(int id, int n) { asm volatile("bar.sync %0, %1;" ::"r"(id), "r"(n) : "memory"); }
__device__ __forceinline__ void bar_arrive(int id, int n) { asm volatile("bar.arrive %0, %1;" ::"r"(id), "r"(n) : "memory"); }
__device__ __forceinline__ void fence_async_smem() { asm volatile("fence.proxy.async.shared::cta;" ::: "memory"); }
__device__ __forceinline__ void fence_async_global() { asm volatile("fence.proxy.async.global;" ::: "memory"); }
__device__ __forceinline__ void flag_release(int f) { asm volatile("red.release.gpu.global.add.u32 [%0], 1;" ::"l"(&g_flags[f * 32]) : "memory"); }
__device__ __forceinline__ void flag_wait(int f, unsigned target) {
    const unsigned* p = &g_flags[f * 32];
    unsigned v; int n = 0;
    do {
        asm volatile("ld.relaxed.gpu.global.u32 %0, [%1];" : "=r"(v) : "l"(p) : "memory");
    } while ((int)(v - target) < 0 && ++n < SPIN_LIMIT);
    asm volatile("fence.acquire.gpu;" ::: "memory");
}
__device__ __forceinline__ void flag_wait2(int f0, int f1, unsigned target) {
    unsigned v, w; int n = 0;
    do {
        asm volatile("ld.relaxed.gpu.global.u32 %0, [%1];" : "=r"(v) : "l"(&g_flags[f0 * 32]) : "memory");
        asm volatile("ld.relaxed.gpu.global.u32 %0, [%1];" : "=r"(w) : "l"(&g_flags[f1 * 32]) : "memory");
    } while ((int)((v - target) | (w - target)) < 0 && ++n < SPIN_LIMIT);
    asm volatile("fence.acquire.gpu;" ::: "memory");
}
__device__ __forceinline__ uint32_t lds32(uint32_t a) { uint32_t v; asm volatile("ld.shared.u32 %0, [%1];" : "=r"(v) : "r"(a)); return v; }
__device__ __forceinline__ float2 lds64f(uint32_t a) { float2 v; asm volatile("ld.shared.v2.f32 {%0,%1}, [%2];" : "=f"(v.x), "=f"(v.y) : "r"(a)); return v; }
__device__ __forceinline__ uint2 lds64(uint32_t a) { uint2 v; asm volatile("ld.shared.v2.u32 {%0,%1}, [%2];" : "=r"(v.x), "=r"(v.y) : "r"(a)); return v; }
__device__ __forceinline__ void sts64f(uint32_t a, float2 v) { asm volatile("st.shared.v2.f32 [%0], {%1,%2};" ::"r"(a), "f"(v.x), "f"(v.y) : "memory"); }
__device__ __forceinline__ void sts32(uint32_t a, uint32_t v) { asm volatile("st.shared.u32 [%0], %1;" ::"r"(a), "r"(v) : "memory"); }
__device__ __forceinline__ void sts64(uint32_t a, uint32_t x, uint32_t y) { asm volatile("st.shared.v2.u32 [%0], {%1,%2};" ::"r"(a), "r"(x), "r"(y) : "memory"); }
__device__ __forceinline__ void sts16(uint32_t a, uint16_t v) { asm volatile("st.shared.u16 [%0], %1;" ::"r"(a), "h"(v) : "memory"); }
__device__ __forceinline__ uint4 lds128(uint32_t a) { uint4 v; asm volatile("ld.shared.v4.u32 {%0,%1,%2,%3}, [%4];" : "=r"(v.x), "=r"(v.y), "=r"(v.z), "=r"(v.w) : "r"(a)); return v; }
__device__ __forceinline__ void sts128(uint32_t a, uint4 v) { asm volatile("st.shared.v4.u32 [%0], {%1,%2,%3,%4};" ::"r"(a), "r"(v.x), "r"(v.y), "r"(v.z), "r"(v.w) : "memory"); }
__device__ __forceinline__ void sts128f(uint32_t a, float x, float y, float z, float w) { asm volatile("st.shared.v4.f32 [%0], {%1,%2,%3,%4};" ::"r"(a), "f"(x), "f"(y), "f"(z), "f"(w) : "memory"); }
__device__ __forceinline__ uint32_t prmt(uint32_t a, uint32_t b, uint32_t s) { uint32_t r; asm("prmt.b32 %0,%1,%2,%3;" : "=r"(r) : "r"(a), "r"(b), "r"(s)); return r; }
__device__ __forceinline__ uint32_t pack2(float lo, float hi) { uint32_t r; asm("cvt.rn.bf16x2.f32 %0, %1, %2;" : "=r"(r) : "f"(hi), "f"(lo)); return r; }
__device__ __forceinline__ float blo(uint32_t v) { return __uint_as_float(v << 16); }
__device__ __forceinline__ float bhi(uint32_t v) { return __uint_as_float(v & 0xffff0000u); }
__device__ __forceinline__ uint32_t bmul2(uint32_t a, uint32_t b) { uint32_t r; asm("mul.rn.bf16x2 %0,%1,%2;" : "=r"(r) : "r"(a), "r"(b)); return r; }
__device__ __forceinline__ uint32_t badd2(uint32_t a, uint32_t b) { uint32_t r; asm("add.rn.bf16x2 %0,%1,%2;" : "=r"(r) : "r"(a), "r"(b)); return r; }
__device__ __forceinline__ float rbf(float x) { return __bfloat162float(__float2bfloat16_rn(x)); }
__device__ __forceinline__ uint32_t ldcg32(const void* p) { uint32_t v; asm volatile("ld.global.cg.u32 %0, [%1];" : "=r"(v) : "l"(p) : "memory"); return v; }
__device__ __forceinline__ uint4 ldcg128(const void* p) { uint4 v; asm volatile("ld.global.cg.v4.u32 {%0,%1,%2,%3}, [%4];" : "=r"(v.x), "=r"(v.y), "=r"(v.z), "=r"(v.w) : "l"(p) : "memory"); return v; }
__device__ __forceinline__ void stg32_if(void* p, uint32_t v, int on) { asm volatile("{.reg .pred q; setp.ne.b32 q, %2, 0; @q st.global.u32 [%0], %1;}" ::"l"(p), "r"(v), "r"(on) : "memory"); }
__device__ __forceinline__ uint2 ldcg64(const void* p) { uint2 v; asm volatile("ld.global.cg.v2.u32 {%0,%1}, [%2];" : "=r"(v.x), "=r"(v.y) : "l"(p) : "memory"); return v; }
__device__ __forceinline__ float gelu_h(float h) {
    float u = h * fmaf(h * h, 8.0f * 0.044715f * 0.7978845608028654f, 2.0f * 0.7978845608028654f);
    float th;
    asm("tanh.approx.f32 %0, %1;" : "=f"(th) : "f"(u));
    return fmaf(h, th, h);
}
__device__ __forceinline__ float gelu(float x) { return gelu_h(0.5f * x); }
__device__ __forceinline__ void ln_params(float sum, float sq, float& inv, float& nb) {
    float mean = sum * (1.0f / D_);
    float var = fmaxf(fmaf(-mean, mean, sq * (1.0f / D_)), 0.0f);
    float sq_;
    asm("sqrt.approx.f32 %0, %1;" : "=f"(sq_) : "f"(rbf(rbf(var) + 1e-5f)));
    inv = __fdividef(1.0f, rbf(sq_));
    nb = -rbf(mean) * inv;
}
__device__ __forceinline__ uint32_t bsub2(uint32_t a, uint32_t b) { uint32_t r; asm("sub.rn.bf16x2 %0,%1,%2;" : "=r"(r) : "r"(a), "r"(b)); return r; }
__device__ __forceinline__ uint32_t bfma2(uint32_t a, uint32_t b, uint32_t c) { uint32_t r; asm("fma.rn.bf16x2 %0,%1,%2,%3;" : "=r"(r) : "r"(a), "r"(b), "r"(c)); return r; }
__device__ __forceinline__ void mma_stat(float* d, uint32_t u, uint32_t v) {
    asm("mma.sync.aligned.m16n8k16.row.col.f32.bf16.bf16.f32 {%0,%1,%2,%3},{%4,%6,%5,%6},{%4,%5},{%0,%1,%2,%3};"
        : "+f"(d[0]), "+f"(d[1]), "+f"(d[2]), "+f"(d[3]) : "r"(u), "r"(v), "r"(0x3f803f80u));
}
__device__ __forceinline__ void mma_sel(float* d, uint2 u, uint2 v, uint32_t b0, uint32_t b1) {
    asm("mma.sync.aligned.m16n8k16.row.col.f32.bf16.bf16.f32 {%0,%1,%2,%3},{%4,%5,%6,%7},{%8,%9},{%0,%1,%2,%3};"
        : "+f"(d[0]), "+f"(d[1]), "+f"(d[2]), "+f"(d[3]) : "r"(u.x), "r"(v.x), "r"(u.y), "r"(v.y), "r"(b0), "r"(b1));
}
__device__ __forceinline__ void conv_sum4(float* d, uint32_t a, bool last, int g, int c) {
    uint2 v0 = lds64(a), v1 = lds64(a + 8), v2 = lds64(a + 16), v3 = lds64(a + 24);
    if (last) {
        if (c > 2) v1 = make_uint2(0, 0);
        if (c > 1) v2 = make_uint2(0, 0);
        if (c > 0) v3 = make_uint2(0, 0);
    }
    const uint32_t one = (g & 1) ? 0x3f800000u : 0x00003f80u;
    mma_sel(d, v0, v1, (g >> 1) == 0 ? one : 0u, (g >> 1) == 1 ? one : 0u);
    mma_sel(d, v2, v3, (g >> 1) == 2 ? one : 0u, (g >> 1) == 3 ? one : 0u);
}
__device__ __forceinline__ uint3 row_stats(const uint32_t* v, int lane) {
    float s = 0.f, q = 0.f, s_ = 0.f, q_ = 0.f;
#pragma unroll
    for (int i = 0; i < 10; i++) { float a = blo(v[i]), b = bhi(v[i]); s += a; s_ += b; q = fmaf(a, a, q); q_ = fmaf(b, b, q_); }
    s += s_; q += q_;
    {
        float t = __shfl_xor_sync(0xffffffffu, (lane & 16) ? s : q, 16);
        t += (lane & 16) ? q : s;
#pragma unroll
        for (int m = 8; m; m >>= 1) t += __shfl_xor_sync(0xffffffffu, t, m);
        float o = __shfl_xor_sync(0xffffffffu, t, 16);
        s = (lane & 16) ? o : t; q = (lane & 16) ? t : o;
    }
    float mean = s * (1.0f / D_), inv;
    asm("rsqrt.approx.ftz.f32 %0, %1;" : "=f"(inv) : "f"(fmaxf(fmaf(-mean, mean, fmaf(q, 1.0f / D_, 1e-5f)), 1e-5f)));
    uint3 r;
    r.x = pack2(mean, mean);
    r.y = pack2(inv, inv);
    inv -= blo(r.y);
    r.z = pack2(inv, inv);
    return r;
}
__device__ __forceinline__ uint32_t ln_apply(uint32_t x, uint32_t m, uint32_t hi, uint32_t lo) {
    uint32_t xc = bsub2(x, m);
    return bfma2(xc, hi, bmul2(xc, lo));
}

struct AFrag { uint32_t m, a, b, c, d; };
__device__ __forceinline__ AFrag ldA(uint32_t a) { AFrag f; f.m = lds32(a - 16); f.a = lds32(a); f.b = lds32(a + 16); f.c = lds32(a + 32); f.d = lds32(a + 48); return f; }
template <int N, int M> __device__ __forceinline__ void conv_pair(float* d, const AFrag& f, uint32_t descU) {
    WgRs<N>::template run<8 * M, desc_hi(128, 0), M ? 1 : 0>(d, f.a, f.b, f.m, f.a, descU);
    WgRs<N>::template run<8 * M + 1, desc_hi(128, 0), 1>(d, f.c, f.d, f.b, f.c, descU);
}
template <int Q> __device__ __forceinline__ void conv_put(float* d, uint32_t r0) {
    sts64(r0 + Q * 32, pack2(d[4 * Q + 1], d[4 * Q + 3]), pack2(d[4 * Q], d[4 * Q + 2]));
}
template <int M> __device__ __forceinline__ void conv_two(float* d, AFrag f0, AFrag f1, uint32_t kaddr, uint32_t descU, uint32_t r0, bool handoff) {
    constexpr int N = M < 14 ? 128 - 8 * M : 32;
    wg_fence();
    conv_pair<N, M>(d, f0, descU);
    wg_commit();
    if constexpr (M > 0) f1 = ldA(kaddr + 256 * (M + 1));
    wg_fence();
    conv_pair<N, M + 1>(d, f1, descU);
    wg_commit();
    if (STAG && M == STAG && handoff) bar_arrive(12, 256);
    if constexpr (M < 14) {
        if constexpr (M > 0) { conv_put<17 - M>(d, r0); conv_put<16 - M>(d, r0); }
        wg_wait<1>();
        f0 = ldA(kaddr + 256 * (M + 2));
        if constexpr (M < 12) wg_wait<0>();
        conv_two<M + 2>(d, f0, f1, kaddr, descU, r0, handoff);
    } else {
        wg_wait<0>();
        conv_put<3>(d, r0); conv_put<2>(d, r0); conv_put<1>(d, r0); conv_put<0>(d, r0);
    }
}
template <int N, bool ASWZ, int SC0>
__device__ __forceinline__ void gemm_issue(float* acc, uint32_t bars, int sa, int pa, int sw, int pw, uint32_t da0, uint32_t db0) {
    mbar_wait(bars + (BAR_FB + sw) * 8, pw);
    mbar_wait(bars + (BAR_FA + sa) * 8, pa);
    const uint32_t da = da0 + sa * (SLOT >> 4), db = db0 + sw * (SLOT >> 4);
    constexpr int AK = ASWZ ? 2 : 256, AH = ASWZ ? desc_hi(1024, 1) : desc_hi(128, 0), BH = desc_hi(1024, 1);
    wg_fence();
    WgSs<N>::template run<0, AH, 0, BH, SC0>(acc, da, db);
    WgSs<N>::template run<AK, AH, 128, BH, 1>(acc, da, db);
    WgSs<N>::template run<2 * AK, AH, 256, BH, 1>(acc, da, db);
    WgSs<N>::template run<3 * AK, AH, 384, BH, 1>(acc, da, db);
    wg_commit();
}
template <int N, bool ASWZ, int IA0, int IB0, int NKB, int RELA, int RELB, bool ZERO, int WAIT_BAR, int ORDER_BAR, int TSID>
__device__ __forceinline__ void gemm_loop(float* acc, uint32_t sb, int half) {
    int sa = IA0 % NA, pa = (IA0 / NA) & 1, sw = IB0 % NB, pw = (IB0 / NB) & 1;
    const uint32_t bars = sb + SM_BAR;
    const int t = threadIdx.x & 127;
    uint32_t ebar = mapa(bars + (t < 2 ? BAR_EB : BAR_EA) * 8, (t < 2 && lds32(sb + SM_GV + 516)) ? t : blockIdx.x & 1);
    const int nrel = t < 2 ? RELB : t == 2 ? RELA : 0;
    const uint32_t da0 = ASWZ ? desc_lo(sb + SM_RA + half * 8192, 16) : desc_lo(sb + SM_RA + half * 1024, 2048), db0 = desc_lo(sb + SM_RB, 8192);
    asm volatile("" : "+r"(ebar));
    if (WAIT_BAR) bar_sync(WAIT_BAR, 512);
    gemm_issue<N, ASWZ, ZERO ? 0 : 1>(acc, bars, sa, pa, sw, pw, da0, db0);
    if ((threadIdx.x & 255) == 0) TS(TSID);
#pragma unroll 1
    for (int kb = 1; kb < NKB; kb++) {
        const int prev = t < 2 ? sw : sa;
        if (++sa == NA) { sa = 0; pa ^= 1; }
        if (++sw == NB) { sw = 0; pw ^= 1; }
        gemm_issue<N, ASWZ, 1>(acc, bars, sa, pa, sw, pw, da0, db0);
        if (ORDER_BAR && kb == NKB - 1) bar_arrive(ORDER_BAR, 512);
        wg_wait<1>();
        if (kb <= nrel) mbar_arrive_cl(ebar + prev * 8);
    }
    wg_wait<0>();
    if (nrel == NKB) mbar_arrive_cl(ebar + (t < 2 ? sw : sa) * 8);
    reg_fence<N / 2>(acc);
    if ((threadIdx.x & 255) == 0) TS(TSID + 1);
}

template <int N, int IA0, int IB0, int RELA, int WAIT_BAR, int ORDER_BAR, int BAR1>
__device__ __forceinline__ void gemm3(uint32_t sb, int rb, int pl0, int pl1, int half, int wq, int g, int c, unsigned ones) {
    float acc[N / 2];
    const int row = 64 * half + 16 * wq + g;
    float2 cr[N / 8];
    mbar_wait(sb + SM_BAR + BAR_CS * 8, 0);
#pragma unroll
    for (int q = 0; q < N / 8; q++) cr[q] = lds64f(sb + SM_CS + (N == 112 ? 0 : 448) + 8 * c + 32 * q);
    float inv0, nb0, inv1, nb1;
    if (N == 104) {
        mbar_wait(sb + SM_BAR + (BAR_FA + 20 % NA) * 8, (20 / NA) & 1);
        const float2* sp = &g_st[(rb * 8 + 2 * c) * 128 + row];
        const uint2 s0 = ldcg64(sp), s1 = ldcg64(sp + 128), s2 = ldcg64(sp + 8), s3 = ldcg64(sp + 136);
        float a0 = __uint_as_float(s0.x) + __uint_as_float(s1.x), b0 = __uint_as_float(s0.y) + __uint_as_float(s1.y);
        float a1 = __uint_as_float(s2.x) + __uint_as_float(s3.x), b1 = __uint_as_float(s2.y) + __uint_as_float(s3.y);
#pragma unroll
        for (int m = 1; m <= 2; m <<= 1) {
            a0 += __shfl_xor_sync(0xffffffffu, a0, m); b0 += __shfl_xor_sync(0xffffffffu, b0, m);
            a1 += __shfl_xor_sync(0xffffffffu, a1, m); b1 += __shfl_xor_sync(0xffffffffu, b1, m);
        }
        ln_params(a0, b0, inv0, nb0);
        ln_params(a1, b1, inv1, nb1);
        inv0 *= 0.5f; nb0 *= 0.5f; inv1 *= 0.5f; nb1 *= 0.5f;
        if (c == 0) sts128f(sb + SM_RP + ((threadIdx.x & 255) >> 2) * 16, inv0, nb0, inv1, nb1);
        bar_arrive(13, 512);
        TSD2(41, __float_as_uint(nb1));
    }
    constexpr int HO = N == 112 ? HO_A : HO_B;
    gemm_loop<N, false, IA0, IB0, 10, RELA, 10, true, WAIT_BAR, HO < 0 ? ORDER_BAR : 0, N == 112 ? 46 : 48>(acc, sb, half);
    if (N == 112) {
        bar_sync(13, 512);
        const uint4 rp = lds128(sb + SM_RP + ((threadIdx.x & 255) >> 2) * 16);
        inv0 = __uint_as_float(rp.x); nb0 = __uint_as_float(rp.y); inv1 = __uint_as_float(rp.z); nb1 = __uint_as_float(rp.w);

    }
    uint32_t* dst = reinterpret_cast<uint32_t*>(g_g) + ((size_t)rb * 216 + pl0) * 512 + row * 4 + c;
#pragma unroll
    for (int k = 0; k < N / 8; k += CH) {
        if (k == 8) dst += (pl1 - pl0 - 8) * 512;
        if (k == HO) bar_arrive(ORDER_BAR, 512);
        if (k == 2 || k == 6) { if ((threadIdx.x & 255) == 0) TS((N == 112 ? 55 : 59) + (k == 6)); }
        CHUNK(k) {
#pragma unroll
            for (int q = k; q < k + CH && q < N / 8; q++) {
                dst[q * 512] = pack2(gelu_h(fmaf(acc[4 * q], inv0, nb0 * cr[q].x)), gelu_h(fmaf(acc[4 * q + 1], inv0, nb0 * cr[q].y)));
                dst[q * 512 + 32] = pack2(gelu_h(fmaf(acc[4 * q + 2], inv1, nb1 * cr[q].x)), gelu_h(fmaf(acc[4 * q + 3], inv1, nb1 * cr[q].y)));
            }
        }
    }
    if (HO >= N / 8) bar_arrive(ORDER_BAR, 512);
    bar_arrive(BAR1, 288);
}

template <int NS, int BASE, int BF, int BE> struct Ring {
    uint32_t sb, st, ph;
    __device__ __forceinline__ uint32_t acquire(uint32_t bytes) {
        mbar_wait(sb + SM_BAR + BE * 8 + st * 8, ph);
        uint32_t fb = sb + SM_BAR + BF * 8 + st * 8;
        mbar_expect(fb, bytes);
        return fb;
    }
    __device__ __forceinline__ uint32_t slot() { return sb + BASE + st * SLOT; }
    __device__ __forceinline__ void next() { if (++st == NS) { st = 0; ph ^= 1; } }
    __device__ __forceinline__ void run2d(const CUtensorMap* m, int c1) {
#pragma unroll 1
        for (int c0 = 0; c0 < D_; c0 += 64) {
            uint32_t fb = acquire(SLOT);
            tma2d(slot(), m, c0, c1, fb);
            next();
        }
    }
    __device__ __forceinline__ void runw(bool paired, int rk, const CUtensorMap* ma, const CUtensorMap* mb, int ca, int cb, int c1, int n, uint32_t bytes) {
        if (paired) {
            const CUtensorMap* m = rk ? mb : ma;
            const int c0 = rk ? cb : ca;
#pragma unroll 1
            for (; n > 0; n--, c1 += 64) {
                uint32_t fb = acquire(bytes);
                tma2d_mc(slot() + 8192 * rk, m, c0, c1, fb);
                next();
            }
        } else {
#pragma unroll 1
            for (; n > 0; n--, c1 += 64) {
                uint32_t fb = acquire(bytes);
                tma2d(slot(), ma, ca, c1, fb);
                tma2d(slot() + 8192, mb, cb, c1, fb);
                next();
            }
        }
    }
    __device__ __forceinline__ void run1d(const char* src, int n) {
#pragma unroll 1
        for (; n > 0; n--) {
            uint32_t fb = acquire(SLOT);
            bulk_g2s(slot(), src, SLOT, fb);
            src += SLOT;
            next();
        }
    }
};

__global__ void __cluster_dims__(2, 1, 1) __launch_bounds__(NTHREADS, 1) fused_kernel(const Params p, const __grid_constant__ Maps maps) {
    extern __shared__ __align__(1024) unsigned char smem_raw[];
    const uint32_t sb = (smem_u32(smem_raw) + 1023u) & ~1023u;
#pragma unroll
    for (int i = 0; i < SEED; i++) asm volatile("{.reg .b32 t; mov.u32 t, %laneid;}");
    const uint32_t bars = sb + SM_BAR;
    const int tid = threadIdx.x, lane = tid & 31;
    unsigned smid;
    asm volatile("mov.u32 %0, %%smid;" : "=r"(smid));
    const bool spare = (smid >> 2) == 30;
    const int cta = smid < 120 ? smid : smid - 4;
    const int pg = cta >> 4, pi = cta & 15;
    if (!spare) {
        const unsigned row = (unsigned)tid / 10u, cc = (unsigned)tid - row * 10u;
        const unsigned go = (unsigned)(pi * 128 * 1280 + pg * 160) + row * 1280u + cc * 16u;
        const uint32_t so = sb + (row >> 4) * 16u + row * 160u + cc * 16u;
        const char* kb = (const char*)p.k + go;
        const char* vb = (const char*)p.v + go;
        cpasync16(so + SM_PK + 2576, kb, 16);
        cpasync16(so + SM_PV, vb, 16);
        cpasync16(so + SM_PK + 5 * 2576, kb + 64 * 1280, 16);
        cpasync16(so + SM_PV + 4 * 2576, vb + 64 * 1280, 16);
        if (tid < 30) cpasync16(so + SM_PK + 13 * 160, pi ? kb - 3 * 1280 : kb, pi ? 16 : 0);
        asm volatile("cp.async.commit_group;" ::: "memory");
    }
    const int warp = __shfl_sync(0xffffffffu, tid >> 5, 0);
    const int wg = warp >> 2, wq = warp & 3;
    unsigned ep0 = 0;
    if (wg == 4 || spare) ep0 = *(volatile unsigned*)&g_epoch[smid];
#define ep1 (ep0 + 1)

    if (spare) {
        const int sp = smid & 3;
        if (tid == 32) { sts32(sb + SM_GV + 512, smid); asm volatile("fence.release.sync_restrict::shared::cta.cluster;" ::: "memory"); }
        asm volatile("barrier.cluster.arrive.relaxed.aligned;" ::: "memory");
        asm volatile("barrier.cluster.wait.aligned;" ::: "memory");
        if (tid == 0) {
            for (int i = 0; i < 4; i++) mbar_init(bars + i * 8, 1);
            asm volatile("fence.mbarrier_init.release.cluster;" ::: "memory");
        }
        if (warp == 0) { if (lane < 8) flag_wait(FL_P + lane, ep1 * 16); __syncwarp(); }
        __syncthreads();
        const int cq = tid % 54, rg = tid / 54;
        float a[8];
#pragma unroll
        for (int i = 0; i < 8; i++) a[i] = 0.f;
#pragma unroll 1
        for (int it = -4; it < 10; it++) {
            const uint32_t st = sb + (it & 3) * 55296, fb = bars + (it & 3) * 8;
            if (it >= 0) {
                mbar_wait(fb, (it >> 2) & 1);
                if (tid < 432) {
#pragma unroll
                    for (int i = 0; i < 8; i++) {
                        uint4 w = lds128(st + (cq >= 27 ? 27648 - 432 : 0) + (rg * 8 + i) * 432 + cq * 16);
                        a[0] += blo(w.x); a[1] += bhi(w.x); a[2] += blo(w.y); a[3] += bhi(w.y);
                        a[4] += blo(w.z); a[5] += bhi(w.z); a[6] += blo(w.w); a[7] += bhi(w.w);
                    }
                }
                __syncthreads();
            }
            if (it < 6 && warp == 19 && elect()) {
                mbar_expect(fb, 55296);
                tma2d(st, &maps.w3s, sp * 432, (it + 4) * 64, fb);
                tma2d(st + 27648, &maps.w3s, sp * 432 + 216, (it + 4) * 64, fb);
            }
        }
        if (tid < 432) {
            sts128f(sb + rg * 1728 + cq * 32, a[0], a[1], a[2], a[3]);
            sts128f(sb + rg * 1728 + cq * 32 + 16, a[4], a[5], a[6], a[7]);
        }
        __syncthreads();
        if (tid < 432) {
            float s = 0.f;
#pragma unroll
            for (int i = 0; i < 8; i++) s += __uint_as_float(lds32(sb + i * 1728 + tid * 4));
            g_cs[sp * 432 + tid] = s;
        }
        __syncthreads();
        if (tid == 0) { flag_release(FL_CS); g_epoch[smid] = ep1; TS(0); }
        if (warp == 0) TSFLUSH();
        return;
    }

    int gpc, idx;
    if (smid < 64) { gpc = (smid & 15) >> 1; idx = (smid >> 4) * 2 + (smid & 1); }
    else if (smid < 120) { int t = smid - 64; gpc = 1 + (t % 14) / 2; idx = 8 + (t / 14) * 2 + (smid & 1); }
    else { gpc = 0; idx = 8 + (smid - 124); }
    const int rb = 2 * gpc + (idx & 1), j = idx >> 1;
    const int g = lane >> 2, c = lane & 3;
    const int cm = 160 * (j >> 1) + 64 * (j & 1) + ((j & 2) ? 32 : 0), cr = 160 * (j >> 1) + 16 * (j & 1) + ((j & 2) ? 0 : 128);

    {
        if (warp == 5) TSW(61);
        const int h = warp / 10, pr = (warp % 10) * 4 + (lane >> 3), blk = lane & 7;
        const int ch = 80 * pg + 2 * pr;
        const uint4 sw = __ldg(reinterpret_cast<const uint4*>(p.shift + ch * 4));
        if (warp == 6 && lane < 5) sts32(sb + SM_GV + 520 + lane * 4, (uint32_t)__bfloat16_as_ushort(p.ssmD[cta * 5 + lane]) << 16);
        if (tid == 0) {
            for (int i = 0; i < 12; i++) { mbar_init(bars + i * 8, 1); mbar_init(bars + (12 + i) * 8, i < NA ? 2 : 4); }
            for (int i = BAR_K; i <= BAR_Y2; i++) mbar_init(bars + i * 8, i == BAR_XY ? 2 : 1);
            asm volatile("fence.mbarrier_init.release.cluster;" ::: "memory");
            { uint32_t t0, t1; asm volatile("mov.u32 %0, %%clock;" : "=r"(t0)); do { asm volatile("mov.u32 %0, %%clock;" : "=r"(t1)); } while (t1 - t0 < -(SSM_WHEN)); }
#pragma unroll
            for (int i = 0; i < 5; i++) {
                mbar_expect(bars + (BAR_K + i) * 8, 4096);
                bulk_g2s(sb + SM_K + i * K_STRIDE + 32, p.ssmk + (size_t)(cta * 5 + i) * S_, 4096, bars + (BAR_K + i) * 8);
            }
        }
        if (tid == 96) { sts32(sb + SM_GV + 512, smid); asm volatile("fence.release.sync_restrict::shared::cta.cluster;" ::: "memory"); }
        if (warp == 1 && lane < 13) prefetch_map(&maps.hn + lane);
        if (warp == 2 && lane < 20)
            sts128(sb + SM_K + (lane >> 2) * K_STRIDE + ((lane >> 1) & 1) * 4160 + (lane & 1) * 16, make_uint4(0, 0, 0, 0));
        if (warp >= 10) {
            sts128(sb + SM_U + (warp - 10) * U_PLANE + 2048 + lane * 16, make_uint4(0, 0, 0, 0));
        }
        asm volatile("barrier.cluster.arrive.relaxed.aligned;" ::: "memory");
        asm volatile("cp.async.wait_group 0;" ::: "memory");
        asm volatile("barrier.cluster.wait.aligned;" ::: "memory");
        if (tid == 32) {
            uint32_t peer;
            asm volatile("ld.shared::cluster.u32 %0, [%1];" : "=r"(peer) : "r"(mapa(sb + SM_GV + 512, (blockIdx.x & 1) ^ 1)) : "memory");
            sts32(sb + SM_GV + 516, peer == (smid ^ 1));
        }
        __syncthreads();
        const uint32_t w0 = prmt(sw.x, sw.z, 0x5410), w1 = prmt(sw.x, sw.z, 0x7632), w2 = prmt(sw.y, sw.w, 0x5410), w3 = prmt(sw.y, sw.w, 0x7632);
        const uint32_t ka = sb + SM_PK + 2576 + blk * 2576 + h * 1280 + pr * 4;
        const uint32_t va = sb + SM_PV + blk * 2576 + h * 1280 + pr * 4;
        uint32_t kk[11], kv[8];
#pragma unroll
        for (int i = 0; i < 11; i++) kk[i] = lds32(ka + (i - 3) * 160 - ((i < 3 && h == 0) ? 16 : 0));
        TSD(1, kk[0]);
#pragma unroll
        for (int i = 0; i < 8; i++) {
            uint32_t t = badd2(badd2(badd2(bmul2(kk[i], w3), bmul2(kk[i + 1], w2)), bmul2(kk[i + 2], w1)), bmul2(kk[i + 3], w0));
            kv[i] = bmul2(t, lds32(va + i * 160));
        }
        uint4 o0, o1;
        o0.x = prmt(kv[1], kv[0], 0x5410); o0.y = prmt(kv[3], kv[2], 0x5410); o0.z = prmt(kv[5], kv[4], 0x5410); o0.w = prmt(kv[7], kv[6], 0x5410);
        o1.x = prmt(kv[1], kv[0], 0x7632); o1.y = prmt(kv[3], kv[2], 0x7632); o1.z = prmt(kv[5], kv[4], 0x7632); o1.w = prmt(kv[7], kv[6], 0x7632);
        uint4* dst = reinterpret_cast<uint4*>(g_kvT) + ch * 256 + h * 128 + (127 - (8 * pi + blk));
        TSD(33, o1.w);
        if (warp >= 10) fence_async_smem();
        dst[0] = o0;
        dst[256] = o1;
    }

    const int rho = 8 * rb + j;

    if (wg == 4) {
        asm volatile("setmaxnreg.dec.sync.aligned.u32 32;");
        const bool paired = lds32(sb + SM_GV + 516);
        if (wq == 0) {
            bar_sync(13, 640);
            TSW(39);
            if (lane == 0) flag_release(FL_P + pg);
            __syncwarp();
            TSW(2);
            flag_wait(FL_P + pg, ep1 * 16);
            fence_async_global();
            TSW(3);
            if (elect()) {
#pragma unroll
                for (int i = 0; i < 5; i++) {
                    const char* us = (const char*)g_kvT + (size_t)(cta * 5 + i) * 4096;
                    mbar_expect(bars + (BAR_U + i) * 8, 4096);
                    bulk_g2s(sb + SM_U + i * U_STRIDE, us, 2048, bars + (BAR_U + i) * 8);
                    bulk_g2s(sb + SM_U + i * U_STRIDE + U_PLANE, us + 2048, 2048, bars + (BAR_U + i) * 8);
                }
            }
            __syncwarp();
            if (elect()) {
                if (cta < 120) {
                    mbar_expect(bars + BAR_WM * 8, 40960);
#pragma unroll
                    for (int i = 0; i < 5; i++) tma2d(sb + SM_WM + i * 8192, &maps.wm, cta * 32, i * 128, bars + BAR_WM * 8);
                }
                bulk_prefetch((const char*)p.q + cta * 20480, 20480);
                bulk_prefetch((const char*)p.w1 + cta * 6400, 6400);
                bulk_prefetch((const char*)p.w2 + cta * 6400, 6400);
            }
            __syncwarp();
        } else {
            bar_arrive(13, 640);
        }
        if (cta < 120) {
            float d[4];
            if (tid < 592) {
                const int t = tid - 512;
                mbar_wait(bars + BAR_U * 8, 0);
                uint4 cv = __ldg(reinterpret_cast<const uint4*>(p.c) + t);
                auto silu2 = [](uint32_t v) { float a = blo(v), b = bhi(v); return pack2(__fdividef(a, 1.0f + __expf(-a)), __fdividef(b, 1.0f + __expf(-b))); };
                sts128(sb + SM_Y + (t % 40) * 32 + (t / 40) * 16, make_uint4(silu2(cv.x), silu2(cv.y), silu2(cv.z), silu2(cv.w)));
                fence_async_smem();
            }
            bar_sync(5, 128);
            mbar_wait(bars + BAR_WM * 8, 0);
            if (wq == 3) TSW(50);
            const uint32_t da = desc_lo(sb + SM_WM, 20480), db = desc_lo(sb + SM_Y, 32);
            wg_fence();
#pragma unroll
            for (int k = 0; k < 20; k++)
                asm volatile("{.reg .pred p; .reg .b32 l,m; .reg .b64 da,db; setp.ne.b32 p,%10,0; add.u32 l,%4,%6; mov.b64 da,{l,%8}; add.u32 m,%5,%7; mov.b64 db,{m,%9};"
                             " wgmma.mma_async.sync.aligned.m64n8k16.f32.bf16.bf16 {%0,%1,%2,%3},da,db,p,1,1,1,0;}"
                             : "+f"(d[0]), "+f"(d[1]), "+f"(d[2]), "+f"(d[3])
                             : "r"(da), "r"(db), "r"(64 * k), "r"(4 * k), "n"(desc_hi(512, 2u)), "n"(desc_hi(128, 0)), "r"(k));
            wg_commit();
            wg_wait<0>();
            reg_fence<4>(d);
            if (c == 0) {
                sts32(sb + SM_GV + (16 * wq + g) * 4, __float_as_uint(wq < 2 ? d[0] : d[1]));
                sts32(sb + SM_GV + (16 * wq + g + 8) * 4, __float_as_uint(wq < 2 ? d[2] : d[3]));
            }
            bar_sync(5, 128);
            if (wq == 2) {
                g_mod[cta * 32 + lane] = __float2bfloat16_rn(__uint_as_float(lds32(sb + SM_GV + lane * 4)) + __uint_as_float(lds32(sb + SM_GV + 128 + lane * 4)));
                __syncwarp();
                if (lane == 0) flag_release(FL_M);
                TSW(4);
            }
        }
        if (wq == 2) {
            bar_arrive(7, 640);
            flag_wait(FL_M, ep1 * 120);
            fence_async_global();
            if (elect()) {
                mbar_expect(bars + BAR_M * 8, 7680);
                bulk_g2s(sb + SM_MOD, g_mod, 7680, bars + BAR_M * 8);
            }
            __syncwarp();
            TSW(51);
            bar_sync(8, 544);  if (lane == 0) { flag_release(FL_R + rb); TS(23); }  __syncwarp();
            bar_sync(15, 288); if (lane == 0) { flag_release(FL_B1 + rb); TS(27); } __syncwarp();
            bar_sync(12, 288); if (lane == 0) { flag_release(FL_B2 + rb); TS(31); } __syncwarp();
#pragma unroll 1
            for (int i = 0; i < 2; i++) { bar_sync(1 + i, 288); if (lane == 0) { TS(53 + i); flag_release(FL_G + 16 * i + rb); TS(57 + i); } __syncwarp(); }
            if (lane == 0) g_epoch[smid] = ep1;
            return;
        }
        bar_sync(7, 640);
        if (wq == 3) {
            if (lane == 0) { flag_release(FL_C); TS(20); }
            __syncwarp();
            bar_arrive(10, 544);
            flag_wait(FL_C, ep1 * 128);
            fence_async_global();
            TSW(21);
            if (elect()) {
                mbar_expect(bars + BAR_Y * 8, 12288);
                bulk_g2s(sb + SM_Y, g_yv + rho * 5120, 12288, bars + BAR_Y * 8);
                mbar_expect(bars + BAR_Y2 * 8, 8192);
                bulk_g2s(sb + SM_Y + 12288, g_yv + rho * 5120 + 3072, 8192, bars + BAR_Y2 * 8);
            }
            __syncwarp();
            bar_arrive(9, 96);
        } else bar_sync(9, 96);
        if (wq == 1 && lane < 4 * NB) mbar_arrive_cl(mapa(bars + (BAR_EB + (lane >> 2)) * 8, paired ? lane & 1 : blockIdx.x & 1));
        if (elect()) {
            if (wq == 3) {
                mbar_expect(bars + BAR_XY * 8, 20480);
#pragma unroll 1
                for (int i = 0; i < 8; i++) {
                    bulk_g2s(sb + SM_YT + i * 2560, g_yv + (8 * rb + i) * 5120 + cm * 8, 2048, bars + BAR_XY * 8);
                    bulk_g2s(sb + SM_YT + i * 2560 + 2048, g_yv + (8 * rb + i) * 5120 + cr * 8, 512, bars + BAR_XY * 8);
                }
                mbar_wait(bars + BAR_FA * 8, 0);
                bulk_prefetch((const char*)p.w4 + cta * 17280, 17280);
                flag_wait(FL_CS, ep1 * 4);
                fence_async_global();
                mbar_expect(bars + BAR_CS * 8, 864);
                bulk_g2s(sb + SM_CS, g_cs + 64 * j, 256, bars + BAR_CS * 8);
                bulk_g2s(sb + SM_CS + 256, g_cs + 512 + 48 * j, 192, bars + BAR_CS * 8);
                bulk_g2s(sb + SM_CS + 448, g_cs + 896 + 64 * j, 256, bars + BAR_CS * 8);
                bulk_g2s(sb + SM_CS + 704, g_cs + 1408 + 40 * j, 160, bars + BAR_CS * 8);
            } else if (wq == 1) {
                Ring<NB, SM_RB, BAR_FB, BAR_EB> r{sb, 0, 0};
#pragma unroll 1
                for (int ph = 0; ph < 6; ph++) {
                    const CUtensorMap* ma = ph == 0 ? &maps.w1a : ph == 1 ? &maps.w2a : ph == 5 ? &maps.w4a : &maps.w3a;
                    const bool b3b = ph == 3 || ph == 4;
                    r.runw(paired, idx & 1, ma, ma + (b3b ? 2 : 1), ph == 2 ? 64 * j : b3b ? 896 + 64 * j : cm,
                           ph == 2 ? 512 + 48 * j : b3b ? 1408 + 40 * j : cr, ph == 3 ? (10 - NA) * 64 : 0,
                           ph == 5 ? 27 : ph == 3 ? NA : ph == 4 ? 10 - NA : 10, ph == 2 ? 14336 : b3b ? 13312 : 10240);
                }
            } else {
                Ring<NA, SM_RA, BAR_FA, BAR_EA> r{sb, 0, 0};
                mbar_expect(bars + BAR_XY * 8, 20480);
                tma2d(sb + SM_XT, &maps.xa, cm, rb * 128, bars + BAR_XY * 8);
                tma2d(sb + SM_XT2, &maps.xb, cr, rb * 128, bars + BAR_XY * 8);
                const int grp = j >> 1;
                const int delta = (grp & 1 ? 1 : -1) * (1 + (grp >> 1));
                const int nb = min(max(rb + (delta > 0 ? 1 : -1), 0), 15);
                flag_wait2(FL_R + nb, FL_R + rb, ep1 * 8);
                fence_async_global(); TS(24);
                r.run2d(&maps.hn, rb * 128 + delta);
                flag_wait(FL_B1 + rb, ep1 * 8); fence_async_global(); TS(28);
                r.run1d((const char*)g_h1 + (size_t)rb * 163840, 10);
                flag_wait(FL_B2 + rb, ep1 * 8); fence_async_global(); TS(32);
                r.run1d((const char*)g_x1 + (size_t)rb * 163840, 10);
                r.run1d((const char*)g_x1 + (size_t)rb * 163840, 10 - NA);
                const char* gs = (const char*)g_g + (size_t)rb * 442368;
#pragma unroll 1
                for (int i = 0; i < 2; i++) {
                    flag_wait(FL_G + 16 * i + rb, ep1 * 8); fence_async_global(); TS(36 + i);
                    const int n = 14 - i;
                    r.run1d(gs, n);
                    gs += n * SLOT;
                }
            }
        }
        return;
    }
    bar_arrive(13, 640);
    asm volatile("setmaxnreg.inc.sync.aligned.u32 112;");
    const int rrow = 16 * rho + (warp >> 1) + 8 * (warp & 1);

#pragma unroll 1
    for (int cc = wg; cc < 5; cc += 3) {
        if (cc == 3 && wg == 0) break;
        mbar_wait(bars + (BAR_K + cc) * 8, 0);
        if (cc == 4 && wq == 0) TSW(40);
        uint32_t a = sb + SM_K + cc * K_STRIDE + 32 + (tid & 127) * 32;
        uint32_t pw = lds32(a - 4);
        uint4 x = lds128(a), y = lds128(a + 16), o;
        if ((tid & 127) == 0) {
            uint16_t k0 = __bfloat16_as_ushort(__float2bfloat16_rn(blo(x.x) + __uint_as_float(lds32(sb + SM_GV + 520 + cc * 4))));
            x.x = (x.x & 0xffff0000u) | k0;
            sts16(a, k0);
        }
        o.x = prmt(pw, x.x, 0x5432); o.y = prmt(x.x, x.y, 0x5432); o.z = prmt(x.y, x.z, 0x5432); o.w = prmt(x.z, x.w, 0x5432);
        sts128(a + 4160, o);
        o.x = prmt(x.w, y.x, 0x5432); o.y = prmt(y.x, y.y, 0x5432); o.z = prmt(y.y, y.z, 0x5432); o.w = prmt(y.z, y.w, 0x5432);
        sts128(a + 4176, o);
    }
    bar_sync(1 + wg, 128);
#pragma unroll 1
    for (int cc = wg; cc < 5; cc += 3) {
        if (cc == 3 && wg == 0) break;
        const uint32_t kaddr = sb + SM_K + cc * K_STRIDE + ((g & 1) ? 32 : 4192) + 4 * ((g >> 1) - c) + 64 * wq;
        const AFrag f0 = ldA(kaddr), f1 = ldA(kaddr + 256);
        if (STAG && cc == 3) bar_sync(12, 256);
        mbar_wait(bars + (BAR_U + cc) * 8, 0);
        if (wq == 0) TSW(5 + cc);
        float d[64];
        conv_two<0>(d, f0, f1, kaddr, desc_lo(sb + SM_U + cc * U_STRIDE, U_PLANE), sb + SM_RED + cc * RED_STRIDE + wq * 4352 + g * 544 + c * 8, cc == 1);
        if (wq == 0) TSW(10 + cc);
        if (cc == 1) bar_arrive(6, 256);
    }
#pragma unroll 1
    for (int cc = wg == 1 ? 4 : wg;; cc++) {
        if (cc == 1) bar_sync(6, 256); else bar_sync(1 + wg, 128);
        const int ch = cta * 5 + cc;
        uint32_t* dst = g_yv + ch * 8 + ((g + (ch >> 2)) & 7) + (126 - 32 * wq - 2 * c) * 5120;
        uint2 v[16];
#pragma unroll
        for (int i = 0; i < 16; i++) v[i] = lds64(sb + SM_RED + cc * RED_STRIDE + g * 544 + wq * 128 + c * 8 + (i >> 2) * 32 + (i & 3) * 4360);
#pragma unroll
        for (int w = 1; w < 4; w++)
            if (wq == 3 && c > 3 - w) v[12 + w] = make_uint2(0, 0);
#pragma unroll
        for (int q = 0; q < 4; q++) {
            const uint2* u = v + 4 * q;
            dst[-8 * q * 5120] = badd2(u[0].x, badd2(u[1].x, badd2(u[2].x, u[3].x)));
            dst[(-8 * q + 1) * 5120] = badd2(u[0].y, badd2(u[1].y, badd2(u[2].y, u[3].y)));
        }
        if (wq == 0) TSW(15 + cc);
        if (cc != 0) break;
    }
    fence_async_smem();
    bar_arrive(7, 640);

    const uint32_t one2 = 0x3f803f80u;
    const unsigned ones = p.ones;
    {
        uint32_t x[10], a[10], cb[10], sbv[10];
        const uint32_t* xr = reinterpret_cast<const uint32_t*>(p.q + (size_t)rrow * D_) + lane;
        bar_sync(10, 544);
#pragma unroll
        for (int i = 0; i < 10; i++) x[i] = __ldg(xr + 32 * i);
        const uint3 s1 = row_stats(x, lane);
        const int up = lane >> 4, gg = warp >> 1, e = warp & 1;
        const uint32_t ya = sb + SM_Y + lane * 64 + ((gg + (lane >> 1)) & 7) * 4;
        const uint32_t sel = (up ? 0x1054u : 0x5410u) + (e ? 0x2222u : 0u);
        const uint32_t ma = sb + SM_MOD + lane * 4;
        mbar_wait(bars + BAR_M * 8, 0);
#pragma unroll
        for (int i = 0; i < 10; i++) {
            uint32_t h = bfma2(ln_apply(x[i], s1.x, s1.y, s1.z), badd2(lds32(ma + 1280 + i * 128), one2), lds32(ma + i * 128));
            a[i] = bmul2(h, lds32(ma + 2560 + i * 128));
            sbv[i] = lds32(ma + 3840 + i * 128);
            cb[i] = badd2(lds32(ma + 5120 + i * 128), one2);
        }
        if (warp == 4) TSW(52);
        mbar_wait(bars + BAR_Y * 8, 0);
        if (warp == 0) TSW(22);
#pragma unroll
        for (int i = 0; i < 10; i++) {
            if (i == 6) mbar_wait(bars + BAR_Y2 * 8, 0);
            uint32_t y0 = lds32(ya + i * 2048 + up * 32), y1 = lds32(ya + i * 2048 + (up ^ 1) * 32);
            x[i] = bfma2(a[i], prmt(y0, y1, sel), x[i]);
        }
        const uint3 s2 = row_stats(x, lane);
#pragma unroll
        for (int i = 0; i < 10; i++) x[i] = bfma2(ln_apply(x[i], s2.x, s2.y, s2.z), cb[i], sbv[i]);
        const uint3 s3 = row_stats(x, lane);
        uint32_t* o = reinterpret_cast<uint32_t*>(g_hn + (size_t)rrow * D_) + lane;
#pragma unroll
        for (int i = 0; i < 10; i++) o[32 * i] = ln_apply(x[i], s3.x, s3.y, s3.z);
        if (lane < 2) g_rs[rrow * 2 + lane] = lane ? make_uint4(s2.x, s2.y, s2.z, 0) : make_uint4(s1.x, s1.y, s1.z, 0);
        if (warp == 0) TSW(34);
        bar_arrive(8, 544);
    }

    const int half = wg & 1;
    const int row = 64 * half + 16 * wq + g;
    const int tw0 = (rb * 80 + (cm >> 3)) * 512 + row * 4 + c, tw1 = (rb * 80 + (cr >> 3) - 8) * 512 + row * 4 + c;
    const uint32_t park = sb + SM_Y + (tid & 255) * 16;
    const uint32_t ms0 = sb + SM_MOD + (cm + 2 * c) * 2, ms1 = sb + SM_MOD + (cr - 64 + 2 * c) * 2;
    if (wg >= 2) {
        {
            float acc[40];
            gemm_loop<80, true, 0, 0, 10, 10, 10, true, 0, 0, 25>(acc, sb, half);
#pragma unroll
            for (int k = 0; k < 10; k += CH) CHUNK(k) {
#pragma unroll
                for (int q = k; q < k + CH && q < 10; q++) {
                    uint32_t* dst = reinterpret_cast<uint32_t*>(g_h1) + (q < 8 ? tw0 : tw1);
                    dst[q * 512] = pack2(gelu(acc[4 * q]), gelu(acc[4 * q + 1]));
                    dst[q * 512 + 32] = pack2(gelu(acc[4 * q + 2]), gelu(acc[4 * q + 3]));
                }
            }
            bar_arrive(15, 288);
            bar_arrive(14, 512);
        }
        gemm3<112, 20, 20, 10 - NA, 11, 9, 1>(sb, rb, 8 * j, 64 + 6 * j, half, wq, g, c, ones);
        if (tid == 256) TS(35);
        {
            float acc[40];
            uint32_t gbv[10];
            uint4 bsv[5];
#pragma unroll
            for (int q = 0; q < 5; q++) { const uint32_t ms = q < 4 ? ms0 : ms1; gbv[2 * q] = lds32(ms + 6400 + q * 32); gbv[2 * q + 1] = lds32(ms + 6400 + q * 32 + 16); bsv[q] = lds128(park + q * 4096); }
            gemm_loop<80, false, 40 - NA, 40, 27, 27 - NA, 27 - NB, true, 10, 0, 42>(acc, sb, half);
            auto fin = [&](int q, int r) {
                const uint32_t gq = gbv[q], b = (q & 1) ? (r ? bsv[q >> 1].w : bsv[q >> 1].z) : (r ? bsv[q >> 1].y : bsv[q >> 1].x);
                return bfma2(gq, pack2(acc[4 * q + 2 * r], acc[4 * q + 2 * r + 1]), b);
            };
            auto tr4 = [&](uint32_t t0, uint32_t t1, uint32_t t2, uint32_t t3) {
                const bool o1 = c & 1, o2 = c & 2;
                uint32_t a = __shfl_xor_sync(0xffffffffu, o1 ? t0 : t1, 1), b = __shfl_xor_sync(0xffffffffu, o1 ? t2 : t3, 1);
                uint32_t u0 = o1 ? a : t0, u1 = o1 ? t1 : a, u2 = o1 ? b : t2, u3 = o1 ? t3 : b;
                a = __shfl_xor_sync(0xffffffffu, o2 ? u0 : u2, 2); b = __shfl_xor_sync(0xffffffffu, o2 ? u1 : u3, 2);
                return o2 ? make_uint4(a, b, u2, u3) : make_uint4(u0, u1, a, b);
            };
            bf16* go = p.out + (size_t)(rb * 128 + row) * D_;
#pragma unroll
            for (int k = 0; k < 2; k++) CHUNK(k) {
#pragma unroll
                for (int r = 0; r < 2; r++)
                    *reinterpret_cast<uint4*>(go + r * 8 * D_ + cm + 32 * k + 8 * c) = tr4(fin(4 * k, r), fin(4 * k + 1, r), fin(4 * k + 2, r), fin(4 * k + 3, r));
            }
            CHUNK(2) *reinterpret_cast<uint4*>(go + (c >> 1) * 8 * D_ + cr + 8 * (c & 1)) = tr4(fin(8, 0), fin(9, 0), fin(8, 1), fin(9, 1));
            if (tid == 256) TS(44);
            if (warp == 8) TSFLUSH();
        }
    } else {
        {
            float acc[40];
            uint32_t x2[20];
            {
                uint32_t y[20];
                mbar_wait(bars + BAR_XY * 8, 0);
                const uint32_t xa = sb + SM_XT + row * 128 + c * 4, xb = sb + SM_XT2 + row * 32 + c * 4;
                const uint32_t ya = sb + SM_YT + (4 * half + wq) * 2560 + c * 64;
#pragma unroll
                for (int q = 0; q < 10; q++) {
                    const uint32_t a = q < 8 ? xa + ((q ^ g) << 4) : xb + (q - 8) * 16;
                    x2[2 * q] = lds32(a); x2[2 * q + 1] = lds32(a + (q < 8 ? 1024 : 256));
                    const int pos = (g + ((q < 8 ? cm : cr) >> 2) + 2 * q + (c >> 1)) & 7;
                    y[2 * q] = lds32(ya + q * 256 + pos * 4); y[2 * q + 1] = lds32(ya + q * 256 + 32 + pos * 4);
                }
                fence_async_smem();
                bar_sync(1 + wg, 128);
                if ((tid & 127) < NA) mbar_arrive_cl(mapa(bars + (BAR_EA + (tid & 127)) * 8, blockIdx.x & 1));
                mbar_wait(bars + BAR_FA * 8, 0);
                const uint4* rp = g_rs + (rb * 128 + row) * 2;
                const uint4 ra = ldcg128(rp), rb2 = ldcg128(rp + 1), rc = ldcg128(rp + 16), rd = ldcg128(rp + 17);
                bar_sync(14, 512);
#pragma unroll
                for (int q = 0; q < 10; q++) {
                    const uint32_t ms = q < 8 ? ms0 : ms1;
                    const uint32_t sa = lds32(ms + 16 * q), ca = badd2(lds32(ms + 1280 + 16 * q), one2), ga = lds32(ms + 2560 + 16 * q);
                    const uint32_t sbv = lds32(ms + 3840 + 16 * q), cb = badd2(lds32(ms + 5120 + 16 * q), one2);
                    uint32_t u = x2[2 * q], v = x2[2 * q + 1];
                    u = bfma2(bmul2(bfma2(ln_apply(u, ra.x, ra.y, ra.z), ca, sa), ga), prmt(y[2 * q], y[2 * q + 1], 0x5410), u);
                    v = bfma2(bmul2(bfma2(ln_apply(v, rc.x, rc.y, rc.z), ca, sa), ga), prmt(y[2 * q], y[2 * q + 1], 0x7632), v);
                    x2[2 * q] = u; x2[2 * q + 1] = v;
                    u = bfma2(ln_apply(u, rb2.x, rb2.y, rb2.z), cb, sbv);
                    v = bfma2(ln_apply(v, rd.x, rd.y, rd.z), cb, sbv);
                    acc[4 * q] = blo(u); acc[4 * q + 1] = bhi(u); acc[4 * q + 2] = blo(v); acc[4 * q + 3] = bhi(v);
                }
            }
            reg_fence<40>(acc);
            if (tid == 0) TS(45);
            gemm_loop<80, false, 10, 10, 10, 10, 10, false, 0, 11, 29>(acc, sb, half);
            uint32_t x1[20];
            float s0 = 0.f, q0 = 0.f, s1 = 0.f, q1 = 0.f;
#pragma unroll
            for (int q = 0; q < 10; q++) {
                uint32_t u = pack2(acc[4 * q], acc[4 * q + 1]);
                uint32_t v = pack2(acc[4 * q + 2], acc[4 * q + 3]);
                uint32_t* dst = reinterpret_cast<uint32_t*>(g_x1) + (q < 8 ? tw0 : tw1);
                dst[q * 512] = u;
                dst[q * 512 + 32] = v;
                x1[2 * q] = u; x1[2 * q + 1] = v;
            }
            CHUNK(0)
#pragma unroll
            for (int q = 0; q < 10; q++) {
                float a = blo(x1[2 * q]), b = bhi(x1[2 * q]), e = blo(x1[2 * q + 1]), f = bhi(x1[2 * q + 1]);
                s0 += a + b; q0 = fmaf(a, a, fmaf(b, b, q0));
                s1 += e + f; q1 = fmaf(e, e, fmaf(f, f, q1));
            }
#pragma unroll
            for (int m = 1; m <= 2; m <<= 1) {
                s0 += __shfl_xor_sync(0xffffffffu, s0, m); q0 += __shfl_xor_sync(0xffffffffu, q0, m);
                s1 += __shfl_xor_sync(0xffffffffu, s1, m); q1 += __shfl_xor_sync(0xffffffffu, q1, m);
            }
            if (c < 2) g_st[(rb * 8 + j) * 128 + row + 8 * c] = c ? make_float2(s1, q1) : make_float2(s0, q0);
            bar_arrive(12, 288);
#pragma unroll
            for (int q = 0; q < 5; q++) {
                const uint32_t ms = q < 4 ? ms0 : ms1;
                const uint32_t g0 = lds32(ms + 6400 + q * 32), g1 = lds32(ms + 6400 + q * 32 + 16);
                sts128(park + q * 4096, make_uint4(bfma2(g0, x1[4 * q], x2[4 * q]), bfma2(g0, x1[4 * q + 1], x2[4 * q + 1]),
                                                   bfma2(g1, x1[4 * q + 2], x2[4 * q + 2]), bfma2(g1, x1[4 * q + 3], x2[4 * q + 3])));
            }
        }
        gemm3<104, 30 - NA, 30, 10, 9, 10, 2>(sb, rb, 112 + 8 * j, 176 + 5 * j, half, wq, g, c, ones);
        if (tid == 0) TS(38);
    }
}

typedef CUresult (*EncFn)(CUtensorMap*, CUtensorMapDataType, cuuint32_t, void*, const cuuint64_t*, const cuuint64_t*,
                          const cuuint32_t*, const cuuint32_t*, CUtensorMapInterleave, CUtensorMapSwizzle,
                          CUtensorMapL2promotion, CUtensorMapFloatOOBfill);

void make_map(EncFn enc, CUtensorMap* m, const void* base, uint64_t inner, uint64_t outer, uint32_t bi, uint32_t bo,
              CUtensorMapSwizzle swz = CU_TENSOR_MAP_SWIZZLE_128B) {
    cuuint64_t dims[2] = {inner, outer};
    cuuint64_t st[1] = {inner * 2};
    cuuint32_t box[2] = {bi, bo};
    cuuint32_t es[2] = {1, 1};
    enc(m, CU_TENSOR_MAP_DATA_TYPE_BFLOAT16, 2, const_cast<void*>(base), dims, st, box, es, CU_TENSOR_MAP_INTERLEAVE_NONE,
        swz, CU_TENSOR_MAP_L2_PROMOTION_NONE, CU_TENSOR_MAP_FLOAT_OOB_FILL_NONE);
}

}

extern "C" void kernel_launch(void* const* d_in, const int* in_sizes, int n_in, void* d_out, int out_size) {
    (void)in_sizes; (void)n_in; (void)out_size;
    Params p;
    p.q = (const bf16*)d_in[0]; p.k = (const bf16*)d_in[1]; p.v = (const bf16*)d_in[2];
    p.shift = (const bf16*)d_in[3]; p.ssmk = (const bf16*)d_in[4]; p.ssmD = (const bf16*)d_in[5];
    p.w1 = (const bf16*)d_in[7]; p.w2 = (const bf16*)d_in[8]; p.w3 = (const bf16*)d_in[9]; p.w4 = (const bf16*)d_in[10];
    p.c = (const bf16*)d_in[11]; p.wmod = (const bf16*)d_in[12];
    p.out = (bf16*)d_out;
    p.ones = 0xffffffffu;

    void* fn = nullptr;
    cudaDriverEntryPointQueryResult qr;
    cudaGetDriverEntryPoint("cuTensorMapEncodeTiled", &fn, cudaEnableDefault, &qr);
    EncFn enc = (EncFn)fn;
    void* hn = nullptr;
    cudaGetSymbolAddress(&hn, g_hn);
    Maps maps;
    make_map(enc, &maps.w3s, p.w3, F_, D_, 216, 64, CU_TENSOR_MAP_SWIZZLE_NONE);
    make_map(enc, &maps.wm, p.wmod, 6 * D_, D_, 32, 128, CU_TENSOR_MAP_SWIZZLE_64B);
    make_map(enc, &maps.xa, p.q, D_, S_, 64, 128);
    make_map(enc, &maps.xb, p.q, D_, S_, 16, 128, CU_TENSOR_MAP_SWIZZLE_NONE);
    make_map(enc, &maps.hn, hn, D_, S_, 64, 128);
    make_map(enc, &maps.w1a, p.w1, D_, D_, 64, 64);
    make_map(enc, &maps.w1b, p.w1, D_, D_, 16, 64);
    make_map(enc, &maps.w2a, p.w2, D_, D_, 64, 64);
    make_map(enc, &maps.w2b, p.w2, D_, D_, 16, 64);
    make_map(enc, &maps.w3a, p.w3, F_, D_, 64, 64);
    make_map(enc, &maps.w3b, p.w3, F_, D_, 48, 64);
    make_map(enc, &maps.w3c, p.w3, F_, D_, 40, 64);
    make_map(enc, &maps.w4a, p.w4, D_, F_, 64, 64);
    make_map(enc, &maps.w4b, p.w4, D_, F_, 16, 64);
    cudaFuncSetAttribute(fused_kernel, cudaFuncAttributeMaxDynamicSharedMemorySize, SMEM_BYTES);
    fused_kernel<<<132, NTHREADS, SMEM_BYTES>>>(p, maps);
}
```

```cpp
#include <cuda_runtime.h>
#include <cuda_bf16.h>
#include <cuda.h>
#include <stdint.h>
#include <string.h>

#define SEED 1
#define RING_A 6
#define MMA_STAT 0
#define CH 2
#define FAST_LN 1
#define STAG 10
#define REDM 1
#define CONVV 0
#define NPOLL 1
#define PGELU 2
#define CH3 4
#define HO_A 14
#define HO_B 14
#define LATE 0
#define HOLD 1
#define SSM_WHEN -2000
#define PF_EARLY 0

namespace {

typedef __nv_bfloat16 bf16;
typedef __nv_bfloat162 bf162;

constexpr int S_ = 2048, D_ = 640, F_ = 1728;
constexpr int NTHREADS = 640;
constexpr int NA = RING_A, NB = 12 - RING_A;
constexpr int SLOT = 16384;
constexpr int SM_RA = 0, SM_RB = NA * SLOT;

constexpr int SM_RED = 0;
constexpr int RED_STRIDE = 17536;
constexpr int SM_PK = 0;
constexpr int SM_PV = 24576;
constexpr int SM_WM = 88064;
constexpr int SM_K = SM_WM + 40960;
constexpr int K_STRIDE = 8320;
constexpr int SM_U = SM_K + 5 * K_STRIDE;
constexpr int U_PLANE = 2560, U_STRIDE = 5120;
constexpr int SM_Y = 12 * SLOT;
static_assert(SM_U + 5 * U_STRIDE <= SM_Y, "smem map");
constexpr int SM_XT = 3 * SLOT, SM_XT2 = 4 * SLOT, SM_YT = SM_XT2 + 4096;
constexpr int SM_MOD = SM_Y + 20480;
constexpr int SM_GV = SM_MOD + 7680;
constexpr int SM_CS = SM_GV + 1024;
constexpr int SM_RP = SM_CS + 1024;
constexpr int SM_BAR = SM_RP + 1024;
constexpr int SM_PROF = SM_BAR + 512;
constexpr int SM_TOTAL = SM_PROF + 512;
constexpr int SMEM_BYTES = SM_TOTAL + 1024;
static_assert(SMEM_BYTES <= 232448, "smem");

constexpr int BAR_FA = 0, BAR_FB = NA, BAR_EA = 12, BAR_EB = 12 + NA, BAR_K = 24, BAR_U = 29, BAR_Y = 34, BAR_CS = 35, BAR_WM = 36, BAR_M = 37, BAR_XY = 38, BAR_Y2 = 39, BAR_G = 40, BAR_ST = 43;

__device__ __align__(1024) bf16 g_kvT[D_ * S_];
__device__ __align__(1024) uint32_t g_yv[128 * 5120];
__device__ __align__(1024) bf16 g_mod[6 * D_];
__device__ __align__(1024) bf16 g_hn[S_ * D_];
__device__ __align__(1024) uint4 g_rs[S_ * 2];
__device__ __align__(1024) bf16 g_h1[S_ * D_];
__device__ __align__(1024) bf16 g_x1[S_ * D_];
__device__ __align__(1024) bf16 g_g[S_ * F_];
__device__ __align__(1024) float2 g_st[S_ * 8];
__device__ __align__(1024) float g_cs[F_];
__device__ __align__(1024) unsigned g_flags[128 * 32];
__device__ __align__(1024) unsigned g_epoch[160];
constexpr int FL_P = 0, FL_C = 8, FL_CS = 9, FL_M = 10, FL_R = 16, FL_B1 = 32, FL_B2 = 48, FL_G = 64;

#define TS(i) do {} while (0)
#define TSW(i) do {} while (0)
#define TSD(i, dep) do {} while (0)
#define TSD2(i, dep) do {} while (0)
#define TSFLUSH() do {} while (0)

struct Params {
    const bf16 *q, *k, *v, *shift, *ssmk, *ssmD, *w1, *w2, *w3, *w4, *c, *wmod;
    bf16* out;
    unsigned ones;
};
#define CHUNK(k) if (ones & (1u << (k)))
struct Maps { CUtensorMap hn, w1a, w1b, w2a, w2b, w3a, w3b, w3c, w4a, w4b, wm, xa, xb, w3s; };

template<int N> struct WgRs;
template<int N> struct WgSs;
template<> struct WgRs<32> { template<int OFF,int HI,int SC> static __device__ __forceinline__ void run(float* d,uint32_t a0,uint32_t a1,uint32_t a2,uint32_t a3,uint32_t blo){
 asm volatile("{.reg .b32 l; .reg .b64 db; add.u32 l,%20,%21; mov.b64 db,{l,%22}; wgmma.mma_async.sync.aligned.m64n32k16.f32.bf16.bf16 {%0,%1,%2,%3,%4,%5,%6,%7,%8,%9,%10,%11,%12,%13,%14,%15},{%16,%17,%18,%19},db,%23,1,1,0;}"
 :"+f"(d[0]),"+f"(d[1]),"+f"(d[2]),"+f"(d[3]),"+f"(d[4]),"+f"(d[5]),"+f"(d[6]),"+f"(d[7]),"+f"(d[8]),"+f"(d[9]),"+f"(d[10]),"+f"(d[11]),"+f"(d[12]),"+f"(d[13]),"+f"(d[14]),"+f"(d[15])
 :"r"(a0),"r"(a1),"r"(a2),"r"(a3),"r"(blo),"n"(OFF),"n"(HI),"n"(SC)); } };
template<> struct WgRs<48> { template<int OFF,int HI,int SC> static __device__ __forceinline__ void run(float* d,uint32_t a0,uint32_t a1,uint32_t a2,uint32_t a3,uint32_t blo){
 asm volatile("{.reg .b32 l; .reg .b64 db; add.u32 l,%28,%29; mov.b64 db,{l,%30}; wgmma.mma_async.sync.aligned.m64n48k16.f32.bf16.bf16 {%0,%1,%2,%3,%4,%5,%6,%7,%8,%9,%10,%11,%12,%13,%14,%15,%16,%17,%18,%19,%20,%21,%22,%23},{%24,%25,%26,%27},db,%31,1,1,0;}"
 :"+f"(d[0]),"+f"(d[1]),"+f"(d[2]),"+f"(d[3]),"+f"(d[4]),"+f"(d[5]),"+f"(d[6]),"+f"(d[7]),"+f"(d[8]),"+f"(d[9]),"+f"(d[10]),"+f"(d[11]),"+f"(d[12]),"+f"(d[13]),"+f"(d[14]),"+f"(d[15]),"+f"(d[16]),"+f"(d[17]),"+f"(d[18]),"+f"(d[19]),"+f"(d[20]),"+f"(d[21]),"+f"(d[22]),"+f"(d[23])
 :"r"(a0),"r"(a1),"r"(a2),"r"(a3),"r"(blo),"n"(OFF),"n"(HI),"n"(SC)); } };
template<> struct WgRs<64> { template<int OFF,int HI,int SC> static __device__ __forceinline__ void run(float* d,uint32_t a0,uint32_t a1,uint32_t a2,uint32_t a3,uint32_t blo){
 asm volatile("{.reg .b32 l; .reg .b64 db; add.u32 l,%36,%37; mov.b64 db,{l,%38}; wgmma.mma_async.sync.aligned.m64n64k16.f32.bf16.bf16 {%0,%1,%2,%3,%4,%5,%6,%7,%8,%9,%10,%11,%12,%13,%14,%15,%16,%17,%18,%19,%20,%21,%22,%23,%24,%25,%26,%27,%28,%29,%30,%31},{%32,%33,%34,%35},db,%39,1,1,0;}"
 :"+f"(d[0]),"+f"(d[1]),"+f"(d[2]),"+f"(d[3]),"+f"(d[4]),"+f"(d[5]),"+f"(d[6]),"+f"(d[7]),"+f"(d[8]),"+f"(d[9]),"+f"(d[10]),"+f"(d[11]),"+f"(d[12]),"+f"(d[13]),"+f"(d[14]),"+f"(d[15]),"+f"(d[16]),"+f"(d[17]),"+f"(d[18]),"+f"(d[19]),"+f"(d[20]),"+f"(d[21]),"+f"(d[22]),"+f"(d[23]),"+f"(d[24]),"+f"(d[25]),"+f"(d[26]),"+f"(d[27]),"+f"(d[28]),"+f"(d[29]),"+f"(d[30]),"+f"(d[31])
 :"r"(a0),"r"(a1),"r"(a2),"r"(a3),"r"(blo),"n"(OFF),"n"(HI),"n"(SC)); } };
template<> struct WgRs<80> { template<int OFF,int HI,int SC> static __device__ __forceinline__ void run(float* d,uint32_t a0,uint32_t a1,uint32_t a2,uint32_t a3,uint32_t blo){
 asm volatile("{.reg .b32 l; .reg .b64 db; add.u32 l,%44,%45; mov.b64 db,{l,%46}; wgmma.mma_async.sync.aligned.m64n80k16.f32.bf16.bf16 {%0,%1,%2,%3,%4,%5,%6,%7,%8,%9,%10,%11,%12,%13,%14,%15,%16,%17,%18,%19,%20,%21,%22,%23,%24,%25,%26,%27,%28,%29,%30,%31,%32,%33,%34,%35,%36,%37,%38,%39},{%40,%41,%42,%43},db,%47,1,1,0;}"
 :"+f"(d[0]),"+f"(d[1]),"+f"(d[2]),"+f"(d[3]),"+f"(d[4]),"+f"(d[5]),"+f"(d[6]),"+f"(d[7]),"+f"(d[8]),"+f"(d[9]),"+f"(d[10]),"+f"(d[11]),"+f"(d[12]),"+f"(d[13]),"+f"(d[14]),"+f"(d[15]),"+f"(d[16]),"+f"(d[17]),"+f"(d[18]),"+f"(d[19]),"+f"(d[20]),"+f"(d[21]),"+f"(d[22]),"+f"(d[23]),"+f"(d[24]),"+f"(d[25]),"+f"(d[26]),"+f"(d[27]),"+f"(d[28]),"+f"(d[29]),"+f"(d[30]),"+f"(d[31]),"+f"(d[32]),"+f"(d[33]),"+f"(d[34]),"+f"(d[35]),"+f"(d[36]),"+f"(d[37]),"+f"(d[38]),"+f"(d[39])
 :"r"(a0),"r"(a1),"r"(a2),"r"(a3),"r"(blo),"n"(OFF),"n"(HI),"n"(SC)); } };
template<> struct WgRs<96> { template<int OFF,int HI,int SC> static __device__ __forceinline__ void run(float* d,uint32_t a0,uint32_t a1,uint32_t a2,uint32_t a3,uint32_t blo){
 asm volatile("{.reg .b32 l; .reg .b64 db; add.u32 l,%52,%53; mov.b64 db,{l,%54}; wgmma.mma_async.sync.aligned.m64n96k16.f32.bf16.bf16 {%0,%1,%2,%3,%4,%5,%6,%7,%8,%9,%10,%11,%12,%13,%14,%15,%16,%17,%18,%19,%20,%21,%22,%23,%24,%25,%26,%27,%28,%29,%30,%31,%32,%33,%34,%35,%36,%37,%38,%39,%40,%41,%42,%43,%44,%45,%46,%47},{%48,%49,%50,%51},db,%55,1,1,0;}"
 :"+f"(d[0]),"+f"(d[1]),"+f"(d[2]),"+f"(d[3]),"+f"(d[4]),"+f"(d[5]),"+f"(d[6]),"+f"(d[7]),"+f"(d[8]),"+f"(d[9]),"+f"(d[10]),"+f"(d[11]),"+f"(d[12]),"+f"(d[13]),"+f"(d[14]),"+f"(d[15]),"+f"(d[16]),"+f"(d[17]),"+f"(d[18]),"+f"(d[19]),"+f"(d[20]),"+f"(d[21]),"+f"(d[22]),"+f"(d[23]),"+f"(d[24]),"+f"(d[25]),"+f"(d[26]),"+f"(d[27]),"+f"(d[28]),"+f"(d[29]),"+f"(d[30]),"+f"(d[31]),"+f"(d[32]),"+f"(d[33]),"+f"(d[34]),"+f"(d[35]),"+f"(d[36]),"+f"(d[37]),"+f"(d[38]),"+f"(d[39]),"+f"(d[40]),"+f"(d[41]),"+f"(d[42]),"+f"(d[43]),"+f"(d[44]),"+f"(d[45]),"+f"(d[46]),"+f"(d[47])
 :"r"(a0),"r"(a1),"r"(a2),"r"(a3),"r"(blo),"n"(OFF),"n"(HI),"n"(SC)); } };
template<> struct WgRs<112> { template<int OFF,int HI,int SC> static __device__ __forceinline__ void run(float* d,uint32_t a0,uint32_t a1,uint32_t a2,uint32_t a3,uint32_t blo){
 asm volatile("{.reg .b32 l; .reg .b64 db; add.u32 l,%60,%61; mov.b64 db,{l,%62}; wgmma.mma_async.sync.aligned.m64n112k16.f32.bf16.bf16 {%0,%1,%2,%3,%4,%5,%6,%7,%8,%9,%10,%11,%12,%13,%14,%15,%16,%17,%18,%19,%20,%21,%22,%23,%24,%25,%26,%27,%28,%29,%30,%31,%32,%33,%34,%35,%36,%37,%38,%39,%40,%41,%42,%43,%44,%45,%46,%47,%48,%49,%50,%51,%52,%53,%54,%55},{%56,%57,%58,%59},db,%63,1,1,0;}"
 :"+f"(d[0]),"+f"(d[1]),"+f"(d[2]),"+f"(d[3]),"+f"(d[4]),"+f"(d[5]),"+f"(d[6]),"+f"(d[7]),"+f"(d[8]),"+f"(d[9]),"+f"(d[10]),"+f"(d[11]),"+f"(d[12]),"+f"(d[13]),"+f"(d[14]),"+f"(d[15]),"+f"(d[16]),"+f"(d[17]),"+f"(d[18]),"+f"(d[19]),"+f"(d[20]),"+f"(d[21]),"+f"(d[22]),"+f"(d[23]),"+f"(d[24]),"+f"(d[25]),"+f"(d[26]),"+f"(d[27]),"+f"(d[28]),"+f"(d[29]),"+f"(d[30]),"+f"(d[31]),"+f"(d[32]),"+f"(d[33]),"+f"(d[34]),"+f"(d[35]),"+f"(d[36]),"+f"(d[37]),"+f"(d[38]),"+f"(d[39]),"+f"(d[40]),"+f"(d[41]),"+f"(d[42]),"+f"(d[43]),"+f"(d[44]),"+f"(d[45]),"+f"(d[46]),"+f"(d[47]),"+f"(d[48]),"+f"(d[49]),"+f"(d[50]),"+f"(d[51]),"+f"(d[52]),"+f"(d[53]),"+f"(d[54]),"+f"(d[55])
 :"r"(a0),"r"(a1),"r"(a2),"r"(a3),"r"(blo),"n"(OFF),"n"(HI),"n"(SC)); } };
template<> struct WgRs<128> { template<int OFF,int HI,int SC> static __device__ __forceinline__ void run(float* d,uint32_t a0,uint32_t a1,uint32_t a2,uint32_t a3,uint32_t blo){
 asm volatile("{.reg .b32 l; .reg .b64 db; add.u32 l,%68,%69; mov.b64 db,{l,%70}; wgmma.mma_async.sync.aligned.m64n128k16.f32.bf16.bf16 {%0,%1,%2,%3,%4,%5,%6,%7,%8,%9,%10,%11,%12,%13,%14,%15,%16,%17,%18,%19,%20,%21,%22,%23,%24,%25,%26,%27,%28,%29,%30,%31,%32,%33,%34,%35,%36,%37,%38,%39,%40,%41,%42,%43,%44,%45,%46,%47,%48,%49,%50,%51,%52,%53,%54,%55,%56,%57,%58,%59,%60,%61,%62,%63},{%64,%65,%66,%67},db,%71,1,1,0;}"
 :"+f"(d[0]),"+f"(d[1]),"+f"(d[2]),"+f"(d[3]),"+f"(d[4]),"+f"(d[5]),"+f"(d[6]),"+f"(d[7]),"+f"(d[8]),"+f"(d[9]),"+f"(d[10]),"+f"(d[11]),"+f"(d[12]),"+f"(d[13]),"+f"(d[14]),"+f"(d[15]),"+f"(d[16]),"+f"(d[17]),"+f"(d[18]),"+f"(d[19]),"+f"(d[20]),"+f"(d[21]),"+f"(d[22]),"+f"(d[23]),"+f"(d[24]),"+f"(d[25]),"+f"(d[26]),"+f"(d[27]),"+f"(d[28]),"+f"(d[29]),"+f"(d[30]),"+f"(d[31]),"+f"(d[32]),"+f"(d[33]),"+f"(d[34]),"+f"(d[35]),"+f"(d[36]),"+f"(d[37]),"+f"(d[38]),"+f"(d[39]),"+f"(d[40]),"+f"(d[41]),"+f"(d[42]),"+f"(d[43]),"+f"(d[44]),"+f"(d[45]),"+f"(d[46]),"+f"(d[47]),"+f"(d[48]),"+f"(d[49]),"+f"(d[50]),"+f"(d[51]),"+f"(d[52]),"+f"(d[53]),"+f"(d[54]),"+f"(d[55]),"+f"(d[56]),"+f"(d[57]),"+f"(d[58]),"+f"(d[59]),"+f"(d[60]),"+f"(d[61]),"+f"(d[62]),"+f"(d[63])
 :"r"(a0),"r"(a1),"r"(a2),"r"(a3),"r"(blo),"n"(OFF),"n"(HI),"n"(SC)); } };
template<> struct WgSs<80> { template<int AOFF,int AHI,int BOFF,int BHI,int SC> static __device__ __forceinline__ void run(float* d,uint32_t alo,uint32_t blo){
 asm volatile("{.reg .b32 l,m; .reg .b64 da,db; add.u32 l,%40,%42; mov.b64 da,{l,%43}; add.u32 m,%41,%44; mov.b64 db,{m,%45}; wgmma.mma_async.sync.aligned.m64n80k16.f32.bf16.bf16 {%0,%1,%2,%3,%4,%5,%6,%7,%8,%9,%10,%11,%12,%13,%14,%15,%16,%17,%18,%19,%20,%21,%22,%23,%24,%25,%26,%27,%28,%29,%30,%31,%32,%33,%34,%35,%36,%37,%38,%39},da,db,%46,1,1,0,1;}"
 :"+f"(d[0]),"+f"(d[1]),"+f"(d[2]),"+f"(d[3]),"+f"(d[4]),"+f"(d[5]),"+f"(d[6]),"+f"(d[7]),"+f"(d[8]),"+f"(d[9]),"+f"(d[10]),"+f"(d[11]),"+f"(d[12]),"+f"(d[13]),"+f"(d[14]),"+f"(d[15]),"+f"(d[16]),"+f"(d[17]),"+f"(d[18]),"+f"(d[19]),"+f"(d[20]),"+f"(d[21]),"+f"(d[22]),"+f"(d[23]),"+f"(d[24]),"+f"(d[25]),"+f"(d[26]),"+f"(d[27]),"+f"(d[28]),"+f"(d[29]),"+f"(d[30]),"+f"(d[31]),"+f"(d[32]),"+f"(d[33]),"+f"(d[34]),"+f"(d[35]),"+f"(d[36]),"+f"(d[37]),"+f"(d[38]),"+f"(d[39])
 :"r"(alo),"r"(blo),"n"(AOFF),"n"(AHI),"n"(BOFF),"n"(BHI),"n"(SC)); } };
template<> struct WgSs<104> { template<int AOFF,int AHI,int BOFF,int BHI,int SC> static __device__ __forceinline__ void run(float* d,uint32_t alo,uint32_t blo){
 asm volatile("{.reg .b32 l,m; .reg .b64 da,db; add.u32 l,%52,%54; mov.b64 da,{l,%55}; add.u32 m,%53,%56; mov.b64 db,{m,%57}; wgmma.mma_async.sync.aligned.m64n104k16.f32.bf16.bf16 {%0,%1,%2,%3,%4,%5,%6,%7,%8,%9,%10,%11,%12,%13,%14,%15,%16,%17,%18,%19,%20,%21,%22,%23,%24,%25,%26,%27,%28,%29,%30,%31,%32,%33,%34,%35,%36,%37,%38,%39,%40,%41,%42,%43,%44,%45,%46,%47,%48,%49,%50,%51},da,db,%58,1,1,0,1;}"
 :"+f"(d[0]),"+f"(d[1]),"+f"(d[2]),"+f"(d[3]),"+f"(d[4]),"+f"(d[5]),"+f"(d[6]),"+f"(d[7]),"+f"(d[8]),"+f"(d[9]),"+f"(d[10]),"+f"(d[11]),"+f"(d[12]),"+f"(d[13]),"+f"(d[14]),"+f"(d[15]),"+f"(d[16]),"+f"(d[17]),"+f"(d[18]),"+f"(d[19]),"+f"(d[20]),"+f"(d[21]),"+f"(d[22]),"+f"(d[23]),"+f"(d[24]),"+f"(d[25]),"+f"(d[26]),"+f"(d[27]),"+f"(d[28]),"+f"(d[29]),"+f"(d[30]),"+f"(d[31]),"+f"(d[32]),"+f"(d[33]),"+f"(d[34]),"+f"(d[35]),"+f"(d[36]),"+f"(d[37]),"+f"(d[38]),"+f"(d[39]),"+f"(d[40]),"+f"(d[41]),"+f"(d[42]),"+f"(d[43]),"+f"(d[44]),"+f"(d[45]),"+f"(d[46]),"+f"(d[47]),"+f"(d[48]),"+f"(d[49]),"+f"(d[50]),"+f"(d[51])
 :"r"(alo),"r"(blo),"n"(AOFF),"n"(AHI),"n"(BOFF),"n"(BHI),"n"(SC)); } };
template<> struct WgSs<112> { template<int AOFF,int AHI,int BOFF,int BHI,int SC> static __device__ __forceinline__ void run(float* d,uint32_t alo,uint32_t blo){
 asm volatile("{.reg .b32 l,m; .reg .b64 da,db; add.u32 l,%56,%58; mov.b64 da,{l,%59}; add.u32 m,%57,%60; mov.b64 db,{m,%61}; wgmma.mma_async.sync.aligned.m64n112k16.f32.bf16.bf16 {%0,%1,%2,%3,%4,%5,%6,%7,%8,%9,%10,%11,%12,%13,%14,%15,%16,%17,%18,%19,%20,%21,%22,%23,%24,%25,%26,%27,%28,%29,%30,%31,%32,%33,%34,%35,%36,%37,%38,%39,%40,%41,%42,%43,%44,%45,%46,%47,%48,%49,%50,%51,%52,%53,%54,%55},da,db,%62,1,1,0,1;}"
 :"+f"(d[0]),"+f"(d[1]),"+f"(d[2]),"+f"(d[3]),"+f"(d[4]),"+f"(d[5]),"+f"(d[6]),"+f"(d[7]),"+f"(d[8]),"+f"(d[9]),"+f"(d[10]),"+f"(d[11]),"+f"(d[12]),"+f"(d[13]),"+f"(d[14]),"+f"(d[15]),"+f"(d[16]),"+f"(d[17]),"+f"(d[18]),"+f"(d[19]),"+f"(d[20]),"+f"(d[21]),"+f"(d[22]),"+f"(d[23]),"+f"(d[24]),"+f"(d[25]),"+f"(d[26]),"+f"(d[27]),"+f"(d[28]),"+f"(d[29]),"+f"(d[30]),"+f"(d[31]),"+f"(d[32]),"+f"(d[33]),"+f"(d[34]),"+f"(d[35]),"+f"(d[36]),"+f"(d[37]),"+f"(d[38]),"+f"(d[39]),"+f"(d[40]),"+f"(d[41]),"+f"(d[42]),"+f"(d[43]),"+f"(d[44]),"+f"(d[45]),"+f"(d[46]),"+f"(d[47]),"+f"(d[48]),"+f"(d[49]),"+f"(d[50]),"+f"(d[51]),"+f"(d[52]),"+f"(d[53]),"+f"(d[54]),"+f"(d[55])
 :"r"(alo),"r"(blo),"n"(AOFF),"n"(AHI),"n"(BOFF),"n"(BHI),"n"(SC)); } };

__device__ __forceinline__ void wg_fence() { asm volatile("wgmma.fence.sync.aligned;" ::: "memory"); }
__device__ __forceinline__ void wg_commit() { asm volatile("wgmma.commit_group.sync.aligned;" ::: "memory"); }
template <int N> __device__ __forceinline__ void wg_wait() { asm volatile("wgmma.wait_group.sync.aligned %0;" ::"n"(N) : "memory"); }
template <int N> __device__ __forceinline__ void reg_fence(float* d) {
#pragma unroll
    for (int i = 0; i < N; i++) asm volatile("" : "+f"(d[i])::"memory");
}
__device__ __forceinline__ uint32_t desc_lo(uint32_t addr, uint32_t lbo) { return ((addr & 0x3FFFF) >> 4) | ((lbo >> 4) << 16); }
#define desc_hi(sbo, sw) (((sbo) >> 4) | ((sw) << 30))
__device__ __forceinline__ uint32_t smem_u32(const void* p) { return (uint32_t)__cvta_generic_to_shared(p); }
__device__ __forceinline__ bool elect() {
    uint32_t p;
    asm volatile("{.reg .pred P; elect.sync _|P, 0xffffffff; selp.u32 %0,1,0,P;}" : "=r"(p));
    return p;
}
__device__ __forceinline__ void mbar_init(uint32_t bar, uint32_t cnt) { asm volatile("mbarrier.init.shared::cta.b64 [%0], %1;" ::"r"(bar), "r"(cnt) : "memory"); }
__device__ __forceinline__ void mbar_expect(uint32_t bar, uint32_t bytes) { asm volatile("mbarrier.arrive.expect_tx.shared::cta.b64 _, [%0], %1;" ::"r"(bar), "r"(bytes) : "memory"); }
__device__ __forceinline__ bool mbar_try(uint32_t bar, uint32_t par) {
    uint32_t ok;
    asm volatile("{.reg .pred p; mbarrier.try_wait.parity.shared::cta.b64 p, [%1], %2; selp.u32 %0,1,0,p;}" : "=r"(ok) : "r"(bar), "r"(par) : "memory");
    return ok;
}
constexpr int SPIN_LIMIT = 1 << 18;
__device__ __forceinline__ void mbar_wait(uint32_t bar, uint32_t par) {
    if (mbar_try(bar, par)) return;
    int n = 0;
    while (!mbar_try(bar, par) && ++n < SPIN_LIMIT) {}
}
__device__ __forceinline__ void bulk_g2s(uint32_t dst, const void* src, uint32_t bytes, uint32_t bar) {
    asm volatile("cp.async.bulk.shared::cluster.global.mbarrier::complete_tx::bytes [%0], [%1], %2, [%3];" ::"r"(dst), "l"(src), "r"(bytes), "r"(bar) : "memory");
}
__device__ __forceinline__ void bulk_s2g(void* dst, uint32_t src, uint32_t bytes) {
    asm volatile("cp.async.bulk.global.shared::cta.bulk_group [%0], [%1], %2;" ::"l"(dst), "r"(src), "r"(bytes) : "memory");
}
__device__ __forceinline__ void bulk_prefetch(const void* src, uint32_t bytes) {
    asm volatile("cp.async.bulk.prefetch.L2.global [%0], %1;" ::"l"(src), "r"(bytes) : "memory");
}
__device__ __forceinline__ void tma2d(uint32_t dst, const CUtensorMap* m, int c0, int c1, uint32_t bar) {
    asm volatile("cp.async.bulk.tensor.2d.shared::cluster.global.mbarrier::complete_tx::bytes [%0], [%1, {%3, %4}], [%2];" ::"r"(dst), "l"(m), "r"(bar), "r"(c0), "r"(c1) : "memory");
}
__device__ __forceinline__ void tma2d_mc(uint32_t dst, const CUtensorMap* m, int c0, int c1, uint32_t bar) {
    asm volatile("cp.async.bulk.tensor.2d.shared::cluster.global.mbarrier::complete_tx::bytes.multicast::cluster [%0], [%1, {%3, %4}], [%2], %5;" ::"r"(dst), "l"(m), "r"(bar), "r"(c0), "r"(c1), "h"((uint16_t)3) : "memory");
}
__device__ __forceinline__ uint32_t mapa(uint32_t a, uint32_t rank) { uint32_t r; asm("mapa.shared::cluster.u32 %0, %1, %2;" : "=r"(r) : "r"(a), "r"(rank)); return r; }
__device__ __forceinline__ void mbar_arrive_cl(uint32_t bar) { asm volatile("mbarrier.arrive.shared::cluster.b64 _, [%0];" ::"r"(bar) : "memory"); }
__device__ __forceinline__ void prefetch_map(const CUtensorMap* m) { asm volatile("prefetch.tensormap [%0];" ::"l"(m) : "memory"); }
__device__ __forceinline__ void cpasync16(uint32_t dst, const void* src, uint32_t srcsz) {
    asm volatile("cp.async.cg.shared.global [%0], [%1], 16, %2;" ::"r"(dst), "l"(src), "r"(srcsz) : "memory");
}
__device__ __forceinline__ void bar_sync(int id, int n) { asm volatile("bar.sync %0, %1;" ::"r"(id), "r"(n) : "memory"); }
__device__ __forceinline__ void bar_arrive(int id, int n) { asm volatile("bar.arrive %0, %1;" ::"r"(id), "r"(n) : "memory"); }
__device__ __forceinline__ void fence_async_smem() { asm volatile("fence.proxy.async.shared::cta;" ::: "memory"); }
__device__ __forceinline__ void fence_async_global() { asm volatile("fence.proxy.async.global;" ::: "memory"); }
__device__ __forceinline__ void flag_release(int f) { asm volatile("red.release.gpu.global.add.u32 [%0], 1;" ::"l"(&g_flags[f * 32]) : "memory"); }
__device__ __forceinline__ void flag_wait(int f, unsigned target) {
    const unsigned* p = &g_flags[f * 32];
    unsigned v; int n = 0;
    do {
        asm volatile("ld.relaxed.gpu.global.u32 %0, [%1];" : "=r"(v) : "l"(p) : "memory");
    } while ((int)(v - target) < 0 && ++n < SPIN_LIMIT);
    asm volatile("fence.acquire.gpu;" ::: "memory");
}
__device__ __forceinline__ unsigned ld_flag(const unsigned* p) { unsigned v; asm volatile("ld.relaxed.gpu.global.u32 %0, [%1];" : "=r"(v) : "l"(p) : "memory"); return v; }
__device__ __forceinline__ void spin(unsigned n) { unsigned t0, t1; asm volatile("mov.u32 %0, %%clock;" : "=r"(t0)); do { asm volatile("mov.u32 %0, %%clock;" : "=r"(t1)); } while (t1 - t0 < n); }
__device__ __forceinline__ void flag_wait_fast(int f, unsigned target) {
    flag_wait(f, target);
}
__device__ __forceinline__ void flag_wait2(int f0, int f1, unsigned target) {
    const unsigned *p = &g_flags[f0 * 32], *q = &g_flags[f1 * 32];
    unsigned v, w; int n = 0;
    do { v = ld_flag(p); w = ld_flag(q); } while ((int)((v - target) | (w - target)) < 0 && ++n < SPIN_LIMIT);
    asm volatile("fence.acquire.gpu;" ::: "memory");
}
__device__ __forceinline__ uint32_t lds32(uint32_t a) { uint32_t v; asm volatile("ld.shared.u32 %0, [%1];" : "=r"(v) : "r"(a)); return v; }
__device__ __forceinline__ float2 lds64f(uint32_t a) { float2 v; asm volatile("ld.shared.v2.f32 {%0,%1}, [%2];" : "=f"(v.x), "=f"(v.y) : "r"(a)); return v; }
__device__ __forceinline__ uint2 lds64(uint32_t a) { uint2 v; asm volatile("ld.shared.v2.u32 {%0,%1}, [%2];" : "=r"(v.x), "=r"(v.y) : "r"(a)); return v; }
__device__ __forceinline__ void sts64f(uint32_t a, float2 v) { asm volatile("st.shared.v2.f32 [%0], {%1,%2};" ::"r"(a), "f"(v.x), "f"(v.y) : "memory"); }
__device__ __forceinline__ void sts32(uint32_t a, uint32_t v) { asm volatile("st.shared.u32 [%0], %1;" ::"r"(a), "r"(v) : "memory"); }
__device__ __forceinline__ void sts64(uint32_t a, uint32_t x, uint32_t y) { asm volatile("st.shared.v2.u32 [%0], {%1,%2};" ::"r"(a), "r"(x), "r"(y) : "memory"); }
__device__ __forceinline__ void sts16(uint32_t a, uint16_t v) { asm volatile("st.shared.u16 [%0], %1;" ::"r"(a), "h"(v) : "memory"); }
__device__ __forceinline__ uint4 lds128(uint32_t a) { uint4 v; asm volatile("ld.shared.v4.u32 {%0,%1,%2,%3}, [%4];" : "=r"(v.x), "=r"(v.y), "=r"(v.z), "=r"(v.w) : "r"(a)); return v; }
__device__ __forceinline__ void sts128(uint32_t a, uint4 v) { asm volatile("st.shared.v4.u32 [%0], {%1,%2,%3,%4};" ::"r"(a), "r"(v.x), "r"(v.y), "r"(v.z), "r"(v.w) : "memory"); }
__device__ __forceinline__ void sts128f(uint32_t a, float x, float y, float z, float w) { asm volatile("st.shared.v4.f32 [%0], {%1,%2,%3,%4};" ::"r"(a), "f"(x), "f"(y), "f"(z), "f"(w) : "memory"); }
__device__ __forceinline__ uint32_t prmt(uint32_t a, uint32_t b, uint32_t s) { uint32_t r; asm("prmt.b32 %0,%1,%2,%3;" : "=r"(r) : "r"(a), "r"(b), "r"(s)); return r; }
__device__ __forceinline__ uint32_t pack2(float lo, float hi) { uint32_t r; asm("cvt.rn.bf16x2.f32 %0, %1, %2;" : "=r"(r) : "f"(hi), "f"(lo)); return r; }
__device__ __forceinline__ float blo(uint32_t v) { return __uint_as_float(v << 16); }
__device__ __forceinline__ float bhi(uint32_t v) { return __uint_as_float(v & 0xffff0000u); }
__device__ __forceinline__ uint32_t bmul2(uint32_t a, uint32_t b) { uint32_t r; asm("mul.rn.bf16x2 %0,%1,%2;" : "=r"(r) : "r"(a), "r"(b)); return r; }
__device__ __forceinline__ uint32_t badd2(uint32_t a, uint32_t b) { uint32_t r; asm("add.rn.bf16x2 %0,%1,%2;" : "=r"(r) : "r"(a), "r"(b)); return r; }
__device__ __forceinline__ float rbf(float x) { return __bfloat162float(__float2bfloat16_rn(x)); }
__device__ __forceinline__ uint32_t ldcg32(const void* p) { uint32_t v; asm volatile("ld.global.cg.u32 %0, [%1];" : "=r"(v) : "l"(p) : "memory"); return v; }
__device__ __forceinline__ uint4 ldcg128(const void* p) { uint4 v; asm volatile("ld.global.cg.v4.u32 {%0,%1,%2,%3}, [%4];" : "=r"(v.x), "=r"(v.y), "=r"(v.z), "=r"(v.w) : "l"(p) : "memory"); return v; }
__device__ __forceinline__ void stg32_if(void* p, uint32_t v, int on) { asm volatile("{.reg .pred q; setp.ne.b32 q, %2, 0; @q st.global.u32 [%0], %1;}" ::"l"(p), "r"(v), "r"(on) : "memory"); }
__device__ __forceinline__ uint2 ldcg64(const void* p) { uint2 v; asm volatile("ld.global.cg.v2.u32 {%0,%1}, [%2];" : "=r"(v.x), "=r"(v.y) : "l"(p) : "memory"); return v; }
__device__ __forceinline__ float gelu_h(float h) {
    float u = h * fmaf(h * h, 8.0f * 0.044715f * 0.7978845608028654f, 2.0f * 0.7978845608028654f);
    float th;
    asm("tanh.approx.f32 %0, %1;" : "=f"(th) : "f"(u));
    return fmaf(h, th, h);
}
__device__ __forceinline__ float gelu(float x) { return gelu_h(0.5f * x); }
__device__ __forceinline__ float half_rstd(float sum, float sq) {
    float mean = sum * (1.0f / D_), inv;
    asm("rsqrt.approx.ftz.f32 %0, %1;" : "=f"(inv) : "f"(fmaxf(fmaf(-mean, mean, fmaf(sq, 1.0f / D_, 1e-5f)), 1e-5f)));
    return 0.5f * inv;
}
__device__ __forceinline__ uint32_t bsub2(uint32_t a, uint32_t b) { uint32_t r; asm("sub.rn.bf16x2 %0,%1,%2;" : "=r"(r) : "r"(a), "r"(b)); return r; }
__device__ __forceinline__ uint32_t bfma2(uint32_t a, uint32_t b, uint32_t c) { uint32_t r; asm("fma.rn.bf16x2 %0,%1,%2,%3;" : "=r"(r) : "r"(a), "r"(b), "r"(c)); return r; }
__device__ __forceinline__ uint32_t gelu2_h(uint32_t h) {
    uint32_t u = bmul2(h, bfma2(bmul2(h, h), 0x3e923e92u, 0x3fcc3fccu)), th;
    asm("tanh.approx.bf16x2 %0, %1;" : "=r"(th) : "r"(u));
    return bfma2(h, th, h);
}
__device__ __forceinline__ void mma_stat(float* d, uint32_t u, uint32_t v) {
    asm("mma.sync.aligned.m16n8k16.row.col.f32.bf16.bf16.f32 {%0,%1,%2,%3},{%4,%6,%5,%6},{%4,%5},{%0,%1,%2,%3};"
        : "+f"(d[0]), "+f"(d[1]), "+f"(d[2]), "+f"(d[3]) : "r"(u), "r"(v), "r"(0x3f803f80u));
}
__device__ __forceinline__ void mma_sel(float* d, uint2 u, uint2 v, uint32_t b0, uint32_t b1) {
    asm("mma.sync.aligned.m16n8k16.row.col.f32.bf16.bf16.f32 {%0,%1,%2,%3},{%4,%5,%6,%7},{%8,%9},{%0,%1,%2,%3};"
        : "+f"(d[0]), "+f"(d[1]), "+f"(d[2]), "+f"(d[3]) : "r"(u.x), "r"(v.x), "r"(u.y), "r"(v.y), "r"(b0), "r"(b1));
}
__device__ __forceinline__ void conv_sum4(float* d, uint32_t a, bool last, int g, int c) {
    uint2 v0 = lds64(a), v1 = lds64(a + 8), v2 = lds64(a + 16), v3 = lds64(a + 24);
    if (last) {
        if (c > 2) v1 = make_uint2(0, 0);
        if (c > 1) v2 = make_uint2(0, 0);
        if (c > 0) v3 = make_uint2(0, 0);
    }
    const uint32_t one = (g & 1) ? 0x3f800000u : 0x00003f80u;
    mma_sel(d, v0, v1, (g >> 1) == 0 ? one : 0u, (g >> 1) == 1 ? one : 0u);
    mma_sel(d, v2, v3, (g >> 1) == 2 ? one : 0u, (g >> 1) == 3 ? one : 0u);
}
__device__ __forceinline__ uint3 row_stats(const uint32_t* v, int lane) {
    float s = 0.f, q = 0.f, s_ = 0.f, q_ = 0.f;
#pragma unroll
    for (int i = 0; i < 10; i++) { float a = blo(v[i]), b = bhi(v[i]); s += a; s_ += b; q = fmaf(a, a, q); q_ = fmaf(b, b, q_); }
    s += s_; q += q_;
    {
        float t = __shfl_xor_sync(0xffffffffu, (lane & 16) ? s : q, 16);
        t += (lane & 16) ? q : s;
#pragma unroll
        for (int m = 8; m; m >>= 1) t += __shfl_xor_sync(0xffffffffu, t, m);
        float o = __shfl_xor_sync(0xffffffffu, t, 16);
        s = (lane & 16) ? o : t; q = (lane & 16) ? t : o;
    }
    float mean = s * (1.0f / D_), inv;
    asm("rsqrt.approx.ftz.f32 %0, %1;" : "=f"(inv) : "f"(fmaxf(fmaf(-mean, mean, fmaf(q, 1.0f / D_, 1e-5f)), 1e-5f)));
    uint3 r;
    r.x = pack2(mean, mean);
    r.y = pack2(inv, inv);
    inv -= blo(r.y);
    r.z = pack2(inv, inv);
    return r;
}
__device__ __forceinline__ uint32_t ln_apply(uint32_t x, uint32_t m, uint32_t hi, uint32_t lo) {
    uint32_t xc = bsub2(x, m);
    return bfma2(xc, hi, bmul2(xc, lo));
}

struct AFrag { uint32_t m, a, b, c, d; };
__device__ __forceinline__ AFrag ldA(uint32_t a) { AFrag f; f.m = lds32(a - 16); f.a = lds32(a); f.b = lds32(a + 16); f.c = lds32(a + 32); f.d = lds32(a + 48); return f; }
template <int N, int M> __device__ __forceinline__ void conv_pair(float* d, const AFrag& f, uint32_t descU) {
    WgRs<N>::template run<8 * M, desc_hi(128, 0), M ? 1 : 0>(d, f.a, f.b, f.m, f.a, descU);
    WgRs<N>::template run<8 * M + 1, desc_hi(128, 0), 1>(d, f.c, f.d, f.b, f.c, descU);
}
template <int Q> __device__ __forceinline__ void conv_put(float* d, uint32_t r0) {
    sts64(r0 + Q * 32, pack2(d[4 * Q + 1], d[4 * Q + 3]), pack2(d[4 * Q], d[4 * Q + 2]));
}
template <int M> __device__ __forceinline__ void conv_two(float* d, AFrag f0, AFrag f1, uint32_t kaddr, uint32_t descU, uint32_t r0, bool handoff) {
    constexpr int N = M < 14 ? 128 - 8 * M : 32;
    wg_fence();
    conv_pair<N, M>(d, f0, descU);
    wg_commit();
    if constexpr (M > 0) f1 = ldA(kaddr + 256 * (M + 1));
    wg_fence();
    conv_pair<N, M + 1>(d, f1, descU);
    wg_commit();
    if (STAG && M == STAG && handoff) bar_arrive(12, 256);
    if constexpr (M < 14) {
        if constexpr (M > 0) { conv_put<17 - M>(d, r0); conv_put<16 - M>(d, r0); }
        wg_wait<1>();
        f0 = ldA(kaddr + 256 * (M + 2));
        if constexpr (M < 12) wg_wait<0>();
        conv_two<M + 2>(d, f0, f1, kaddr, descU, r0, handoff);
    } else {
        wg_wait<0>();
        conv_put<3>(d, r0); conv_put<2>(d, r0); conv_put<1>(d, r0); conv_put<0>(d, r0);
    }
}
template <int N, bool ASWZ, int SC0>
__device__ __forceinline__ void gemm_issue(float* acc, uint32_t bars, int sa, int pa, int sw, int pw, uint32_t da0, uint32_t db0) {
    mbar_wait(bars + (BAR_FB + sw) * 8, pw);
    mbar_wait(bars + (BAR_FA + sa) * 8, pa);
    const uint32_t da = da0 + sa * (SLOT >> 4), db = db0 + sw * (SLOT >> 4);
    constexpr int AK = ASWZ ? 2 : 256, AH = ASWZ ? desc_hi(1024, 1) : desc_hi(128, 0), BH = desc_hi(1024, 1);
    wg_fence();
    WgSs<N>::template run<0, AH, 0, BH, SC0>(acc, da, db);
    WgSs<N>::template run<AK, AH, 128, BH, 1>(acc, da, db);
    WgSs<N>::template run<2 * AK, AH, 256, BH, 1>(acc, da, db);
    WgSs<N>::template run<3 * AK, AH, 384, BH, 1>(acc, da, db);
    wg_commit();
}
template <int N, bool ASWZ, int NKB, int RELB, bool ZERO>
__device__ __forceinline__ void gemm_loop(float* acc, uint32_t sb, int half, int ia0, int ib0, int rela, int wait_bar, int order_bar, int tsid) {
    int sa = ia0 % NA, pa = (ia0 / NA) & 1, sw = ib0 % NB, pw = (ib0 / NB) & 1;
    const uint32_t bars = sb + SM_BAR;
    const int t = threadIdx.x & 127;
    uint32_t ebar = mapa(bars + (t < 2 ? BAR_EB : BAR_EA) * 8, (t < 2 && lds32(sb + SM_GV + 516)) ? t : blockIdx.x & 1);
    const int nrel = t < 2 ? RELB : t == 2 ? rela : 0;
    const uint32_t da0 = ASWZ ? desc_lo(sb + SM_RA + half * 8192, 16) : desc_lo(sb + SM_RA + half * 1024, 2048), db0 = desc_lo(sb + SM_RB, 8192);
    asm volatile("" : "+r"(ebar));
    if (wait_bar) bar_sync(wait_bar, 512);
    gemm_issue<N, ASWZ, ZERO ? 0 : 1>(acc, bars, sa, pa, sw, pw, da0, db0);
    if ((threadIdx.x & 255) == 0) TS(tsid);
#pragma unroll 1
    for (int kb = 1; kb < NKB; kb++) {
        const int prev = t < 2 ? sw : sa;
        if (++sa == NA) { sa = 0; pa ^= 1; }
        if (++sw == NB) { sw = 0; pw ^= 1; }
        gemm_issue<N, ASWZ, 1>(acc, bars, sa, pa, sw, pw, da0, db0);
        if (order_bar && kb == NKB - 1) bar_arrive(order_bar, 512);
        wg_wait<1>();
        if (kb <= nrel) mbar_arrive_cl(ebar + prev * 8);
    }
    wg_wait<0>();
    if (nrel == NKB) mbar_arrive_cl(ebar + (t < 2 ? sw : sa) * 8);
    reg_fence<N / 2>(acc);
    if ((threadIdx.x & 255) == 0) TS(tsid + 1);
}

template <int PART>
__device__ __forceinline__ void gemm3(uint32_t sb, int rb, int j, int half, int row, int c, unsigned ones) {
    constexpr int N = PART ? 104 : 112, NQ = N / 8;
    constexpr int HO = PART ? HO_B : HO_A;
    float acc[N / 2];
    float2 cr[NQ];
    mbar_wait(sb + SM_BAR + BAR_CS * 8, 0);
#pragma unroll
    for (int q = 0; q < NQ; q++) cr[q] = lds64f(sb + SM_CS + PART * 448 + 8 * c + 32 * q);
    uint4 rp;
    if (PART) {
        mbar_wait(sb + SM_BAR + (BAR_FA + 21 % NA) * 8, (21 / NA) & 1);
        const float2* sp = &g_st[(rb * 8 + 2 * c) * 128 + row];
        const uint2 s0 = ldcg64(sp), s1 = ldcg64(sp + 128), s2 = ldcg64(sp + 8), s3 = ldcg64(sp + 136);
        float a0 = __uint_as_float(s0.x) + __uint_as_float(s1.x), b0 = __uint_as_float(s0.y) + __uint_as_float(s1.y);
        float a1 = __uint_as_float(s2.x) + __uint_as_float(s3.x), b1 = __uint_as_float(s2.y) + __uint_as_float(s3.y);
#pragma unroll
        for (int m = 1; m <= 2; m <<= 1) {
            a0 += __shfl_xor_sync(0xffffffffu, a0, m); b0 += __shfl_xor_sync(0xffffffffu, b0, m);
            a1 += __shfl_xor_sync(0xffffffffu, a1, m); b1 += __shfl_xor_sync(0xffffffffu, b1, m);
        }
        const float inv0 = half_rstd(a0, b0), inv1 = half_rstd(a1, b1);
        rp = make_uint4(PGELU ? pack2(inv0, inv0) : __float_as_uint(inv0), __float_as_uint(a0 * (-1.0f / D_)),
                        PGELU ? pack2(inv1, inv1) : __float_as_uint(inv1), __float_as_uint(a1 * (-1.0f / D_)));
        if (c == 0) sts128(sb + SM_RP + ((threadIdx.x & 255) >> 2) * 16, rp);
        bar_arrive(13, 512);
    }
    gemm_loop<N, false, 10, 10, true>(acc, sb, half, 20 + (10 - NA) * PART, 20 + 10 * PART, PART ? 10 : 10 - NA, 9 + PART, HO < 0 ? 10 + PART : 0, 46 + 2 * PART);
    if (!PART) {
        bar_sync(13, 512);
        rp = lds128(sb + SM_RP + ((threadIdx.x & 255) >> 2) * 16);
    }
    const float nb0 = __uint_as_float(rp.y), nb1 = __uint_as_float(rp.w);
    uint32_t* dst = reinterpret_cast<uint32_t*>(g_g) + (rb * 216 + 112 * PART + 8 * j) * 512 + row * 4 + c;
    auto act = [&](int q, int r) {
        const float nb = r ? nb1 : nb0;
        const uint32_t inv = r ? rp.z : rp.x;
        const float t0 = fmaf(nb, cr[q].x, acc[4 * q + 2 * r]), t1 = fmaf(nb, cr[q].y, acc[4 * q + 2 * r + 1]);
        return gelu2_h(bmul2(pack2(t0, t1), inv));
    };
    uint32_t* dst1 = dst + (56 - (16 - NQ) * j) * 512;
#pragma unroll
    for (int k = 0; k < NQ; k += CH3) {
        if (k == HO) bar_arrive(10 + PART, 512);
        CHUNK(k) {
#pragma unroll
            for (int q = k; q < k + CH3 && q < NQ; q++) { (q < 8 ? dst : dst1)[q * 512] = act(q, 0); (q < 8 ? dst : dst1)[q * 512 + 32] = act(q, 1); }
        }
    }
    if (HO >= NQ) bar_arrive(10 + PART, 512);
    bar_arrive(1 + PART, 288);
}

template <int NS, int BASE, int BF, int BE> struct Ring {
    uint32_t sb, st, ph;
    __device__ __forceinline__ uint32_t acquire(uint32_t bytes) {
        mbar_wait(sb + SM_BAR + BE * 8 + st * 8, ph);
        uint32_t fb = sb + SM_BAR + BF * 8 + st * 8;
        mbar_expect(fb, bytes);
        return fb;
    }
    __device__ __forceinline__ uint32_t slot() { return sb + BASE + st * SLOT; }
    __device__ __forceinline__ void next() { if (++st == NS) { st = 0; ph ^= 1; } }
    __device__ __forceinline__ void run2d(const CUtensorMap* m, int c1) {
#pragma unroll 1
        for (int c0 = 64; c0 < D_; c0 += 64) {
            uint32_t fb = acquire(SLOT);
            tma2d(slot(), m, c0, c1, fb);
            next();
        }
    }
    __device__ __forceinline__ void runw(bool paired, int rk, const CUtensorMap* ma, const CUtensorMap* mb, int ca, int cb, int c1, int n, uint32_t bytes) {
        if (paired) {
            const CUtensorMap* m = rk ? mb : ma;
            const int c0 = rk ? cb : ca;
#pragma unroll 1
            for (; n > 0; n--, c1 += 64) {
                uint32_t fb = acquire(bytes);
                tma2d_mc(slot() + 8192 * rk, m, c0, c1, fb);
                next();
            }
        } else {
#pragma unroll 1
            for (; n > 0; n--, c1 += 64) {
                uint32_t fb = acquire(bytes);
                tma2d(slot(), ma, ca, c1, fb);
                tma2d(slot() + 8192, mb, cb, c1, fb);
                next();
            }
        }
    }
    __device__ __forceinline__ void run1d(const char* src, int n) {
#pragma unroll 1
        for (; n > 0; n--) {
            uint32_t fb = acquire(SLOT);
            bulk_g2s(slot(), src, SLOT, fb);
            src += SLOT;
            next();
        }
    }
};

__global__ void __cluster_dims__(2, 1, 1) __launch_bounds__(NTHREADS, 1) fused_kernel(const Params p, const __grid_constant__ Maps maps) {
    extern __shared__ __align__(1024) unsigned char smem_raw[];
    const uint32_t sb = (smem_u32(smem_raw) + 1023u) & ~1023u;
#pragma unroll
    for (int i = 0; i < SEED; i++) asm volatile("{.reg .b32 t; mov.u32 t, %laneid;}");
    const uint32_t bars = sb + SM_BAR;
    const int tid = threadIdx.x, lane = tid & 31;
    unsigned smid;
    asm volatile("mov.u32 %0, %%smid;" : "=r"(smid));
    const bool spare = (smid >> 2) == 30;
    const int cta = smid < 120 ? smid : smid - 4;
    const int pg = cta >> 4, pi = cta & 15;
    if (!spare) {
        const unsigned row = (unsigned)tid / 10u, cc = (unsigned)tid - row * 10u;
        const unsigned go = (unsigned)(pi * 128 * 1280 + pg * 160) + row * 1280u + cc * 16u;
        const uint32_t so = sb + (row >> 4) * 16u + row * 160u + cc * 16u;
        const char* kb = (const char*)p.k + go;
        const char* vb = (const char*)p.v + go;
        cpasync16(so + SM_PK + 2576, kb, 16);
        cpasync16(so + SM_PV, vb, 16);
        cpasync16(so + SM_PK + 5 * 2576, kb + 64 * 1280, 16);
        cpasync16(so + SM_PV + 4 * 2576, vb + 64 * 1280, 16);
        if (tid < 30) cpasync16(so + SM_PK + 13 * 160, pi ? kb - 3 * 1280 : kb, pi ? 16 : 0);
        asm volatile("cp.async.commit_group;" ::: "memory");
    }
    const int warp = __shfl_sync(0xffffffffu, tid >> 5, 0);
    const int wg = warp >> 2, wq = warp & 3;
    unsigned ep0 = 0;
    if (wg == 4 || spare) ep0 = *(volatile unsigned*)&g_epoch[smid];
#define ep1 (ep0 + 1)

    if (spare) {
        const int sp = smid & 3;
        if (tid == 32) { sts32(sb + SM_GV + 512, smid); asm volatile("fence.release.sync_restrict::shared::cta.cluster;" ::: "memory"); }
        asm volatile("barrier.cluster.arrive.relaxed.aligned;" ::: "memory");
        asm volatile("barrier.cluster.wait.aligned;" ::: "memory");
        if (tid == 0) {
            for (int i = 0; i < 4; i++) mbar_init(bars + i * 8, 1);
            asm volatile("fence.mbarrier_init.release.cluster;" ::: "memory");
        }
        if (warp == 0) { if (lane < 8) flag_wait(FL_P + lane, ep1 * 16); __syncwarp(); }
        __syncthreads();
        const int cq = tid % 54, rg = tid / 54;
        float a[8];
#pragma unroll
        for (int i = 0; i < 8; i++) a[i] = 0.f;
#pragma unroll 1
        for (int it = -4; it < 10; it++) {
            const uint32_t st = sb + (it & 3) * 55296, fb = bars + (it & 3) * 8;
            if (it >= 0) {
                mbar_wait(fb, (it >> 2) & 1);
                if (tid < 432) {
#pragma unroll
                    for (int i = 0; i < 8; i++) {
                        uint4 w = lds128(st + (cq >= 27 ? 27648 - 432 : 0) + (rg * 8 + i) * 432 + cq * 16);
                        a[0] += blo(w.x); a[1] += bhi(w.x); a[2] += blo(w.y); a[3] += bhi(w.y);
                        a[4] += blo(w.z); a[5] += bhi(w.z); a[6] += blo(w.w); a[7] += bhi(w.w);
                    }
                }
                __syncthreads();
            }
            if (it < 6 && warp == 19 && elect()) {
                mbar_expect(fb, 55296);
                tma2d(st, &maps.w3s, sp * 432, (it + 4) * 64, fb);
                tma2d(st + 27648, &maps.w3s, sp * 432 + 216, (it + 4) * 64, fb);
            }
        }
        if (tid < 432) {
            sts128f(sb + rg * 1728 + cq * 32, a[0], a[1], a[2], a[3]);
            sts128f(sb + rg * 1728 + cq * 32 + 16, a[4], a[5], a[6], a[7]);
        }
        __syncthreads();
        if (tid < 432) {
            float s = 0.f;
#pragma unroll
            for (int i = 0; i < 8; i++) s += __uint_as_float(lds32(sb + i * 1728 + tid * 4));
            g_cs[sp * 432 + tid] = s;
        }
        __syncthreads();
        if (tid == 0) { flag_release(FL_CS); g_epoch[smid] = ep1; TS(0); }
        if (warp == 0) TSFLUSH();
        return;
    }

    int gpc, idx;
    if (smid < 64) { gpc = (smid & 15) >> 1; idx = (smid >> 4) * 2 + (smid & 1); }
    else if (smid < 120) { int t = smid - 64; gpc = 1 + (t % 14) / 2; idx = 8 + (t / 14) * 2 + (smid & 1); }
    else { gpc = 0; idx = 8 + (smid - 124); }
    const int rb = 2 * gpc + (idx & 1), j = idx >> 1;
    const int g = lane >> 2, c = lane & 3;
    const int cm = 160 * (j >> 1) + 64 * (j & 1) + ((j & 2) ? 32 : 0), cr = 160 * (j >> 1) + 16 * (j & 1) + ((j & 2) ? 0 : 128);

    {
        if (warp == 5) TSW(61);
        const int h = warp / 10, pr = (warp % 10) * 4 + (lane >> 3), blk = lane & 7;
        const int ch = 80 * pg + 2 * pr;
        const uint4 sw = __ldg(reinterpret_cast<const uint4*>(p.shift + ch * 4));
        if (warp == 6 && lane < 5) sts32(sb + SM_GV + 520 + lane * 4, (uint32_t)__bfloat16_as_ushort(p.ssmD[cta * 5 + lane]) << 16);
        if (tid == 0) {
            for (int i = 0; i < 12; i++) { mbar_init(bars + i * 8, 1); mbar_init(bars + (12 + i) * 8, i < NA ? 2 : 4); }
            for (int i = BAR_K; i <= BAR_ST; i++) mbar_init(bars + i * 8, i == BAR_XY ? 2 : 1);
            asm volatile("fence.mbarrier_init.release.cluster;" ::: "memory");
            { uint32_t t0, t1; asm volatile("mov.u32 %0, %%clock;" : "=r"(t0)); do { asm volatile("mov.u32 %0, %%clock;" : "=r"(t1)); } while (t1 - t0 < -(SSM_WHEN)); }
#pragma unroll
            for (int i = 0; i < 5; i++) {
                mbar_expect(bars + (BAR_K + i) * 8, 4096);
                bulk_g2s(sb + SM_K + i * K_STRIDE + 32, p.ssmk + (size_t)(cta * 5 + i) * S_, 4096, bars + (BAR_K + i) * 8);
            }
        }
        if (tid == 96) { sts32(sb + SM_GV + 512, smid); asm volatile("fence.release.sync_restrict::shared::cta.cluster;" ::: "memory"); }
        if (warp == 1 && lane < 13) prefetch_map(&maps.hn + lane);
        if (warp == 2 && lane < 20)
            sts128(sb + SM_K + (lane >> 2) * K_STRIDE + ((lane >> 1) & 1) * 4160 + (lane & 1) * 16, make_uint4(0, 0, 0, 0));
        if (warp >= 10) {
            sts128(sb + SM_U + (warp - 10) * U_PLANE + 2048 + lane * 16, make_uint4(0, 0, 0, 0));
        }
        asm volatile("barrier.cluster.arrive.relaxed.aligned;" ::: "memory");
        asm volatile("cp.async.wait_group 0;" ::: "memory");
        asm volatile("barrier.cluster.wait.aligned;" ::: "memory");
        if (tid == 32) {
            uint32_t peer;
            asm volatile("ld.shared::cluster.u32 %0, [%1];" : "=r"(peer) : "r"(mapa(sb + SM_GV + 512, (blockIdx.x & 1) ^ 1)) : "memory");
            sts32(sb + SM_GV + 516, peer == (smid ^ 1));
        }
        __syncthreads();
        const uint32_t w0 = prmt(sw.x, sw.z, 0x5410), w1 = prmt(sw.x, sw.z, 0x7632), w2 = prmt(sw.y, sw.w, 0x5410), w3 = prmt(sw.y, sw.w, 0x7632);
        const uint32_t ka = sb + SM_PK + 2576 + blk * 2576 + h * 1280 + pr * 4;
        const uint32_t va = sb + SM_PV + blk * 2576 + h * 1280 + pr * 4;
        uint32_t kk[11], kv[8];
#pragma unroll
        for (int i = 0; i < 11; i++) kk[i] = lds32(ka + (i - 3) * 160 - ((i < 3 && h == 0) ? 16 : 0));
        TSD(1, kk[0]);
#pragma unroll
        for (int i = 0; i < 8; i++) {
            uint32_t t = badd2(badd2(badd2(bmul2(kk[i], w3), bmul2(kk[i + 1], w2)), bmul2(kk[i + 2], w1)), bmul2(kk[i + 3], w0));
            kv[i] = bmul2(t, lds32(va + i * 160));
        }
        uint4 o0, o1;
        o0.x = prmt(kv[1], kv[0], 0x5410); o0.y = prmt(kv[3], kv[2], 0x5410); o0.z = prmt(kv[5], kv[4], 0x5410); o0.w = prmt(kv[7], kv[6], 0x5410);
        o1.x = prmt(kv[1], kv[0], 0x7632); o1.y = prmt(kv[3], kv[2], 0x7632); o1.z = prmt(kv[5], kv[4], 0x7632); o1.w = prmt(kv[7], kv[6], 0x7632);
        uint4* dst = reinterpret_cast<uint4*>(g_kvT) + ch * 256 + h * 128 + (127 - (8 * pi + blk));
        TSD(33, o1.w);
        if (warp >= 10) fence_async_smem();
        dst[0] = o0;
        dst[256] = o1;
    }

    const int rho = 8 * rb + j;

    if (wg == 4) {
        asm volatile("setmaxnreg.dec.sync.aligned.u32 32;");
        const bool paired = lds32(sb + SM_GV + 516);
        if (wq == 0) {
            bar_sync(13, 640);
            TSW(39);
            if (lane == 0) flag_release(FL_P + pg);
            __syncwarp();
            TSW(2);
            if (lane < 5) mbar_expect(bars + (BAR_U + lane) * 8, 4096);
            flag_wait_fast(FL_P + pg, ep1 * 16);
            fence_async_global();
            TSW(3);
            if (elect()) {
#pragma unroll
                for (int i = 0; i < 5; i++) {
                    const char* us = (const char*)g_kvT + (size_t)(cta * 5 + i) * 4096;
                    bulk_g2s(sb + SM_U + i * U_STRIDE, us, 2048, bars + (BAR_U + i) * 8);
                    bulk_g2s(sb + SM_U + i * U_STRIDE + U_PLANE, us + 2048, 2048, bars + (BAR_U + i) * 8);
                }
            }
            __syncwarp();
            if (elect()) {
                if (cta < 120) {
                    mbar_expect(bars + BAR_WM * 8, 40960);
#pragma unroll
                    for (int i = 0; i < 5; i++) tma2d(sb + SM_WM + i * 8192, &maps.wm, cta * 32, i * 128, bars + BAR_WM * 8);
                }
                bulk_prefetch((const char*)p.q + cta * 20480, 20480);
                bulk_prefetch((const char*)p.w1 + cta * 6400, 6400);
                bulk_prefetch((const char*)p.w2 + cta * 6400, 6400);
            }
            __syncwarp();
        } else {
            bar_arrive(13, 640);
        }
        if (cta < 120) {
            float d[4];
            if (tid < 592) {
                const int t = tid - 512;
                mbar_wait(bars + BAR_U * 8, 0);
                uint4 cv = __ldg(reinterpret_cast<const uint4*>(p.c) + t);
                auto silu2 = [](uint32_t v) { float a = blo(v), b = bhi(v); return pack2(__fdividef(a, 1.0f + __expf(-a)), __fdividef(b, 1.0f + __expf(-b))); };
                sts128(sb + SM_Y + (t % 40) * 32 + (t / 40) * 16, make_uint4(silu2(cv.x), silu2(cv.y), silu2(cv.z), silu2(cv.w)));
                fence_async_smem();
            }
            bar_sync(5, 128);
            mbar_wait(bars + BAR_WM * 8, 0);
            if (wq == 3) TSW(56);
            const uint32_t da = desc_lo(sb + SM_WM, 20480), db = desc_lo(sb + SM_Y, 32);
            wg_fence();
#pragma unroll
            for (int k = 0; k < 20; k++)
                asm volatile("{.reg .pred p; .reg .b32 l,m; .reg .b64 da,db; setp.ne.b32 p,%10,0; add.u32 l,%4,%6; mov.b64 da,{l,%8}; add.u32 m,%5,%7; mov.b64 db,{m,%9};"
                             " wgmma.mma_async.sync.aligned.m64n8k16.f32.bf16.bf16 {%0,%1,%2,%3},da,db,p,1,1,1,0;}"
                             : "+f"(d[0]), "+f"(d[1]), "+f"(d[2]), "+f"(d[3])
                             : "r"(da), "r"(db), "r"(64 * k), "r"(4 * k), "n"(desc_hi(512, 2u)), "n"(desc_hi(128, 0)), "r"(k));
            wg_commit();
            wg_wait<0>();
            reg_fence<4>(d);
            if (c == 0) {
                sts32(sb + SM_GV + (16 * wq + g) * 4, __float_as_uint(wq < 2 ? d[0] : d[1]));
                sts32(sb + SM_GV + (16 * wq + g + 8) * 4, __float_as_uint(wq < 2 ? d[2] : d[3]));
            }
            bar_sync(5, 128);
            if (wq == 2) {
                g_mod[cta * 32 + lane] = __float2bfloat16_rn(__uint_as_float(lds32(sb + SM_GV + lane * 4)) + __uint_as_float(lds32(sb + SM_GV + 128 + lane * 4)));
                __syncwarp();
                if (lane == 0) flag_release(FL_M);
                TSW(4);
            }
        }
        if (wq == 2) {
            bar_arrive(7, 640);
            flag_wait(FL_M, ep1 * 120);
            fence_async_global();
            if (elect()) {
                mbar_expect(bars + BAR_M * 8, 7680);
                bulk_g2s(sb + SM_MOD, g_mod, 7680, bars + BAR_M * 8);
            }
            __syncwarp();
            TSW(60);
            bar_sync(8, 544);  if (lane == 0) { flag_release(FL_R + rb); TS(23); }  __syncwarp();
            bar_sync(15, 288); if (lane == 0) { flag_release(FL_B1 + rb); TS(27); } __syncwarp();
            bar_sync(6, 288);  if (lane == 0) { flag_release(FL_B2 + rb); TS(31); } __syncwarp();
#pragma unroll 1
            for (int i = 0; i < 2; i++) { bar_sync(1 + i, 288); if (lane == 0) { TS(53 + i); flag_release(FL_G + 16 * i + rb); TS(57 + i); } __syncwarp(); }
            if (lane == 0) g_epoch[smid] = ep1;
            return;
        }
        bar_sync(7, 640);
        if (wq == 3) {
            if (lane == 0) { flag_release(FL_C); TS(20); }
            __syncwarp();
            bar_arrive(10, 544);
            if (lane < 2) mbar_expect(bars + (lane ? BAR_Y2 : BAR_Y) * 8, lane ? 8192 : 12288);
            flag_wait_fast(FL_C, ep1 * 128);
            fence_async_global();
            TSW(21);
            if (elect()) {
                bulk_g2s(sb + SM_Y, g_yv + rho * 5120, 12288, bars + BAR_Y * 8);
                bulk_g2s(sb + SM_Y + 12288, g_yv + rho * 5120 + 3072, 8192, bars + BAR_Y2 * 8);
            }
            __syncwarp();
            bar_arrive(9, 96);
        } else bar_sync(9, 96);
        if (wq == 1 && lane < 4 * NB) mbar_arrive_cl(mapa(bars + (BAR_EB + (lane >> 2)) * 8, paired ? lane & 1 : blockIdx.x & 1));
        if (elect()) {
            if (wq == 3) {
                mbar_expect(bars + BAR_XY * 8, 20480);
#pragma unroll 1
                for (int i = 0; i < 8; i++) {
                    bulk_g2s(sb + SM_YT + i * 2560, g_yv + (8 * rb + i) * 5120 + cm * 8, 2048, bars + BAR_XY * 8);
                    bulk_g2s(sb + SM_YT + i * 2560 + 2048, g_yv + (8 * rb + i) * 5120 + cr * 8, 512, bars + BAR_XY * 8);
                }
                mbar_wait(bars + BAR_FA * 8, 0);
                bulk_prefetch((const char*)p.w4 + cta * 17280, 17280);
                flag_wait(FL_CS, ep1 * 4);
                fence_async_global();
                mbar_expect(bars + BAR_CS * 8, 864);
                bulk_g2s(sb + SM_CS, g_cs + 64 * j, 256, bars + BAR_CS * 8);
                bulk_g2s(sb + SM_CS + 256, g_cs + 512 + 48 * j, 192, bars + BAR_CS * 8);
                bulk_g2s(sb + SM_CS + 448, g_cs + 896 + 64 * j, 256, bars + BAR_CS * 8);
                bulk_g2s(sb + SM_CS + 704, g_cs + 1408 + 40 * j, 160, bars + BAR_CS * 8);
                mbar_wait(bars + BAR_ST * 8, 0);
#pragma unroll 1
                for (int i = 0; i < 2; i++) {
                    flag_wait(FL_G + 16 * i + rb, ep1 * 8);
                    mbar_expect(bars + (BAR_G + i) * 8, 0);
                    TS(35 + i);
                }
            } else if (wq == 1) {
                Ring<NB, SM_RB, BAR_FB, BAR_EB> r{sb, 0, 0};
#pragma unroll 1
                for (int ph = 0; ph < 6; ph++) {
                    const CUtensorMap* ma = ph == 0 ? &maps.w1a : ph == 1 ? &maps.w2a : ph == 5 ? &maps.w4a : &maps.w3a;
                    const bool b3b = ph == 3 || ph == 4;
                    r.runw(paired, idx & 1, ma, ma + (b3b ? 2 : 1), ph == 2 ? 64 * j : b3b ? 896 + 64 * j : cm,
                           ph == 2 ? 512 + 48 * j : b3b ? 1408 + 40 * j : cr, ph == 3 ? (10 - NA) * 64 : 0,
                           ph == 5 ? 27 : ph == 3 ? NA : ph == 4 ? 10 - NA : 10, ph == 2 ? 14336 : b3b ? 13312 : 10240);
                }
            } else {
                Ring<NA, SM_RA, BAR_FA, BAR_EA> r{sb, 0, 0};
                mbar_expect(bars + BAR_XY * 8, 20480);
                tma2d(sb + SM_XT, &maps.xa, cm, rb * 128, bars + BAR_XY * 8);
                tma2d(sb + SM_XT2, &maps.xb, cr, rb * 128, bars + BAR_XY * 8);
                const int grp = j >> 1;
                const int delta = (grp & 1 ? 1 : -1) * (1 + (grp >> 1));
                const int nb = min(max(rb + (delta > 0 ? 1 : -1), 0), 15);
                uint32_t fb = r.acquire(SLOT), dst = r.slot();
                flag_wait2(FL_R + nb, FL_R + rb, ep1 * 8);
                fence_async_global();
                tma2d(dst, &maps.hn, 0, rb * 128 + delta, fb);
                TS(24);
                r.next();
                r.run2d(&maps.hn, rb * 128 + delta);
#pragma unroll 1
                for (int i = 0; i < 2; i++) {
                    const char* src = (const char*)(i ? g_x1 : g_h1) + (size_t)rb * 163840;
                    fb = r.acquire(SLOT); dst = r.slot();
                    flag_wait_fast(FL_B1 + 16 * i + rb, ep1 * 8);
                    fence_async_global();
                    bulk_g2s(dst, src, SLOT, fb);
                    TS(28 + 4 * i);
                    if (i) mbar_expect(bars + BAR_ST * 8, 0);
                    r.next();
                    r.run1d(src + SLOT, 9);
                }
                r.run1d((const char*)g_x1 + (size_t)rb * 163840, 10 - NA);
#pragma unroll 1
                for (int i = 0; i < 2; i++) {
                    mbar_wait(bars + (BAR_G + i) * 8, 0); fence_async_global();
                    r.run1d((const char*)g_g + (size_t)rb * 442368 + i * 14 * SLOT, 14 - i);
                }
            }
        }
        return;
    }
    bar_arrive(13, 640);
    asm volatile("setmaxnreg.inc.sync.aligned.u32 112;");
    const int rrow = 16 * rho + (warp >> 1) + 8 * (warp & 1);

#pragma unroll 1
    for (int cc = wg; cc < 5; cc += 3) {
        if (cc == 3 && wg == 0) break;
        mbar_wait(bars + (BAR_K + cc) * 8, 0);
        if (cc == 4 && wq == 0) TSW(40);
        uint32_t a = sb + SM_K + cc * K_STRIDE + 32 + (tid & 127) * 32;
        uint32_t pw = lds32(a - 4);
        uint4 x = lds128(a), y = lds128(a + 16), o;
        if ((tid & 127) == 0) {
            uint16_t k0 = __bfloat16_as_ushort(__float2bfloat16_rn(blo(x.x) + __uint_as_float(lds32(sb + SM_GV + 520 + cc * 4))));
            x.x = (x.x & 0xffff0000u) | k0;
            sts16(a, k0);
        }
        o.x = prmt(pw, x.x, 0x5432); o.y = prmt(x.x, x.y, 0x5432); o.z = prmt(x.y, x.z, 0x5432); o.w = prmt(x.z, x.w, 0x5432);
        sts128(a + 4160, o);
        o.x = prmt(x.w, y.x, 0x5432); o.y = prmt(y.x, y.y, 0x5432); o.z = prmt(y.y, y.z, 0x5432); o.w = prmt(y.z, y.w, 0x5432);
        sts128(a + 4176, o);
    }
    bar_sync(1 + wg, 128);
#pragma unroll 1
    for (int cc = wg; cc < 5; cc += 3) {
        if (cc == 3 && wg == 0) break;
        const uint32_t kaddr = sb + SM_K + cc * K_STRIDE + ((g & 1) ? 32 : 4192) + 4 * ((g >> 1) - c) + 64 * wq;
        const AFrag f0 = ldA(kaddr), f1 = ldA(kaddr + 256);
        if (STAG && cc == 3) bar_sync(12, 256);
        mbar_wait(bars + (BAR_U + cc) * 8, 0);
        if (wq == 0) TSW(5 + cc);
        float d[64];
        conv_two<0>(d, f0, f1, kaddr, desc_lo(sb + SM_U + cc * U_STRIDE, U_PLANE), sb + SM_RED + cc * RED_STRIDE + wq * 4352 + g * 544 + c * 8, cc == 1);
        if (wq == 0) TSW(10 + cc);
        if (cc == 1) bar_arrive(6, 256);
    }
#pragma unroll 1
    for (int cc = wg == 1 ? 4 : wg;; cc++) {
        if (cc == 1) bar_sync(6, 256); else bar_sync(1 + wg, 128);
        const int ch = cta * 5 + cc;
        uint32_t* dst = g_yv + ch * 8 + ((g + (ch >> 2)) & 7) + (126 - 32 * wq - 2 * c) * 5120;
        uint2 v[16];
#pragma unroll
        for (int i = 0; i < 16; i++) v[i] = lds64(sb + SM_RED + cc * RED_STRIDE + g * 544 + wq * 128 + c * 8 + (i >> 2) * 32 + (i & 3) * 4360);
#pragma unroll
        for (int w = 1; w < 4; w++)
            if (wq == 3 && c > 3 - w) v[12 + w] = make_uint2(0, 0);
#pragma unroll
        for (int q = 0; q < 4; q++) {
            const uint2* u = v + 4 * q;
            dst[-8 * q * 5120] = badd2(u[0].x, badd2(u[1].x, badd2(u[2].x, u[3].x)));
            dst[(-8 * q + 1) * 5120] = badd2(u[0].y, badd2(u[1].y, badd2(u[2].y, u[3].y)));
        }
        if (wq == 0) TSW(15 + cc);
        if (cc != 0) break;
    }
    fence_async_smem();
    bar_arrive(7, 640);

    const uint32_t one2 = 0x3f803f80u;
    const unsigned ones = p.ones;
    {
        uint32_t x[10], a[10], cb[10], sbv[10];
        const uint32_t* xr = reinterpret_cast<const uint32_t*>(p.q + (size_t)rrow * D_) + lane;
        bar_sync(10, 544);
#pragma unroll
        for (int i = 0; i < 10; i++) x[i] = __ldg(xr + 32 * i);
        const uint3 s1 = row_stats(x, lane);
        const int up = lane >> 4, gg = warp >> 1, e = warp & 1;
        const uint32_t ya = sb + SM_Y + lane * 64 + ((gg + (lane >> 1)) & 7) * 4;
        const uint32_t sel = (up ? 0x1054u : 0x5410u) + (e ? 0x2222u : 0u);
        const uint32_t ma = sb + SM_MOD + lane * 4;
        mbar_wait(bars + BAR_M * 8, 0);
#pragma unroll
        for (int i = 0; i < 10; i++) {
            uint32_t h = bfma2(ln_apply(x[i], s1.x, s1.y, s1.z), badd2(lds32(ma + 1280 + i * 128), one2), lds32(ma + i * 128));
            a[i] = bmul2(h, lds32(ma + 2560 + i * 128));
            sbv[i] = lds32(ma + 3840 + i * 128);
            cb[i] = badd2(lds32(ma + 5120 + i * 128), one2);
        }
        if (warp == 4) TSW(52);
        mbar_wait(bars + BAR_Y * 8, 0);
        if (warp == 0) TSW(22);
#pragma unroll
        for (int i = 0; i < 10; i++) {
            if (i == 6) mbar_wait(bars + BAR_Y2 * 8, 0);
            uint32_t y0 = lds32(ya + i * 2048 + up * 32), y1 = lds32(ya + i * 2048 + (up ^ 1) * 32);
            x[i] = bfma2(a[i], prmt(y0, y1, sel), x[i]);
        }
        const uint3 s2 = row_stats(x, lane);
#pragma unroll
        for (int i = 0; i < 10; i++) x[i] = bfma2(ln_apply(x[i], s2.x, s2.y, s2.z), cb[i], sbv[i]);
        const uint3 s3 = row_stats(x, lane);
        uint32_t* o = reinterpret_cast<uint32_t*>(g_hn + (size_t)rrow * D_) + lane;
#pragma unroll
        for (int i = 0; i < 10; i++) o[32 * i] = ln_apply(x[i], s3.x, s3.y, s3.z);
        if (lane < 2) g_rs[rrow * 2 + lane] = lane ? make_uint4(s2.x, s2.y, s2.z, 0) : make_uint4(s1.x, s1.y, s1.z, 0);
        if (warp == 0) TSW(34);
        bar_arrive(8, 544);
    }

    const int half = wg & 1;
    const int row = 64 * half + 16 * wq + g;
    const int tw0 = (rb * 80 + (cm >> 3)) * 512 + row * 4 + c, tw1 = (rb * 80 + (cr >> 3) - 8) * 512 + row * 4 + c;
    const uint32_t park = sb + SM_Y + (tid & 255) * 16;
    const uint32_t ms0 = sb + SM_MOD + (cm + 2 * c) * 2, ms1 = sb + SM_MOD + (cr - 64 + 2 * c) * 2;
    if (wg >= 2) {
        {
            float acc[40];
            gemm_loop<80, true, 10, 10, true>(acc, sb, half, 0, 0, 10, 0, 0, 25);
#pragma unroll
            for (int k = 0; k < 10; k += CH) CHUNK(k) {
#pragma unroll
                for (int q = k; q < k + CH && q < 10; q++) {
                    uint32_t* dst = reinterpret_cast<uint32_t*>(g_h1) + (q < 8 ? tw0 : tw1);
                    dst[q * 512] = gelu2_h(bmul2(pack2(acc[4 * q], acc[4 * q + 1]), 0x3f003f00u));
                    dst[q * 512 + 32] = gelu2_h(bmul2(pack2(acc[4 * q + 2], acc[4 * q + 3]), 0x3f003f00u));
                }
            }
            bar_arrive(15, 288);
            bar_arrive(14, 512);
        }
        gemm3<0>(sb, rb, j, half, row, c, ones);
        {
            float acc[40];
            uint32_t gbv[10], base[20];
#pragma unroll
            for (int q = 0; q < 10; q++) gbv[q] = lds32((q < 8 ? ms0 : ms1) + 6400 + q * 16);
#pragma unroll
            for (int q = 0; q < 5; q++) { const uint4 t = lds128(park + q * 4096); base[4 * q] = t.x; base[4 * q + 1] = t.y; base[4 * q + 2] = t.z; base[4 * q + 3] = t.w; }
            gemm_loop<80, false, 27, 27 - NB, true>(acc, sb, half, 40 - NA, 40, 27 - NA, 11, 0, 42);
            auto fin = [&](int q, int r) {
                return bfma2(gbv[q], pack2(acc[4 * q + 2 * r], acc[4 * q + 2 * r + 1]), base[2 * q + r]);
            };
            auto tr4 = [&](uint32_t t0, uint32_t t1, uint32_t t2, uint32_t t3) {
                const bool o1 = c & 1, o2 = c & 2;
                uint32_t a = __shfl_xor_sync(0xffffffffu, o1 ? t0 : t1, 1), b = __shfl_xor_sync(0xffffffffu, o1 ? t2 : t3, 1);
                uint32_t u0 = o1 ? a : t0, u1 = o1 ? t1 : a, u2 = o1 ? b : t2, u3 = o1 ? t3 : b;
                a = __shfl_xor_sync(0xffffffffu, o2 ? u0 : u2, 2); b = __shfl_xor_sync(0xffffffffu, o2 ? u1 : u3, 2);
                return o2 ? make_uint4(a, b, u2, u3) : make_uint4(u0, u1, a, b);
            };
            bf16* go = p.out + (size_t)(rb * 128 + row) * D_;
#pragma unroll
            for (int k = 0; k < 2; k++) CHUNK(k) {
#pragma unroll
                for (int r = 0; r < 2; r++)
                    *reinterpret_cast<uint4*>(go + r * 8 * D_ + cm + 32 * k + 8 * c) = tr4(fin(4 * k, r), fin(4 * k + 1, r), fin(4 * k + 2, r), fin(4 * k + 3, r));
            }
            CHUNK(2) *reinterpret_cast<uint4*>(go + (c >> 1) * 8 * D_ + cr + 8 * (c & 1)) = tr4(fin(8, 0), fin(9, 0), fin(8, 1), fin(9, 1));
            if (tid == 256) TS(44);
            if (warp == 8) TSFLUSH();
        }
    } else {
        {
            float acc[40];
            uint32_t x2[20];
            {
                uint32_t y[20];
                mbar_wait(bars + BAR_XY * 8, 0);
                const uint32_t xa = sb + SM_XT + row * 128 + c * 4, xb = sb + SM_XT2 + row * 32 + c * 4;
                const uint32_t ya = sb + SM_YT + (4 * half + wq) * 2560 + c * 64;
#pragma unroll
                for (int q = 0; q < 10; q++) {
                    const uint32_t a = q < 8 ? xa + ((q ^ g) << 4) : xb + (q - 8) * 16;
                    x2[2 * q] = lds32(a); x2[2 * q + 1] = lds32(a + (q < 8 ? 1024 : 256));
                    const int pos = (g + ((q < 8 ? cm : cr) >> 2) + 2 * q + (c >> 1)) & 7;
                    y[2 * q] = lds32(ya + q * 256 + pos * 4); y[2 * q + 1] = lds32(ya + q * 256 + 32 + pos * 4);
                }
                fence_async_smem();
                bar_sync(1 + wg, 128);
                if ((tid & 127) < NA) mbar_arrive_cl(mapa(bars + (BAR_EA + (tid & 127)) * 8, blockIdx.x & 1));
                mbar_wait(bars + (BAR_FA + 1) * 8, 0);
                const uint4* rp = g_rs + (rb * 128 + row) * 2;
                const uint4 ra = ldcg128(rp), rb2 = ldcg128(rp + 1), rc = ldcg128(rp + 16), rd = ldcg128(rp + 17);
                bar_sync(14, 512);
#pragma unroll
                for (int q = 0; q < 10; q++) {
                    const uint32_t ms = q < 8 ? ms0 : ms1;
                    const uint32_t sa = lds32(ms + 16 * q), ca = badd2(lds32(ms + 1280 + 16 * q), one2), ga = lds32(ms + 2560 + 16 * q);
                    const uint32_t sbv = lds32(ms + 3840 + 16 * q), cb = badd2(lds32(ms + 5120 + 16 * q), one2);
                    uint32_t u = x2[2 * q], v = x2[2 * q + 1];
                    u = bfma2(bmul2(bfma2(ln_apply(u, ra.x, ra.y, ra.z), ca, sa), ga), prmt(y[2 * q], y[2 * q + 1], 0x5410), u);
                    v = bfma2(bmul2(bfma2(ln_apply(v, rc.x, rc.y, rc.z), ca, sa), ga), prmt(y[2 * q], y[2 * q + 1], 0x7632), v);
                    x2[2 * q] = u; x2[2 * q + 1] = v;
                    u = bfma2(ln_apply(u, rb2.x, rb2.y, rb2.z), cb, sbv);
                    v = bfma2(ln_apply(v, rd.x, rd.y, rd.z), cb, sbv);
                    acc[4 * q] = blo(u); acc[4 * q + 1] = bhi(u); acc[4 * q + 2] = blo(v); acc[4 * q + 3] = bhi(v);
                }
            }
            reg_fence<40>(acc);
            if (tid == 0) TS(45);
            gemm_loop<80, false, 10, 10, false>(acc, sb, half, 10, 10, 10, 0, 9, 29);
            uint32_t x1[20];
            float s0 = 0.f, q0 = 0.f, s1 = 0.f, q1 = 0.f;
#pragma unroll
            for (int q = 0; q < 10; q++) {
                uint32_t u = pack2(acc[4 * q], acc[4 * q + 1]);
                uint32_t v = pack2(acc[4 * q + 2], acc[4 * q + 3]);
                uint32_t* dst = reinterpret_cast<uint32_t*>(g_x1) + (q < 8 ? tw0 : tw1);
                dst[q * 512] = u;
                dst[q * 512 + 32] = v;
                x1[2 * q] = u; x1[2 * q + 1] = v;
            }
            CHUNK(0)
#pragma unroll
            for (int q = 0; q < 10; q++) {
                float a = blo(x1[2 * q]), b = bhi(x1[2 * q]), e = blo(x1[2 * q + 1]), f = bhi(x1[2 * q + 1]);
                s0 += a + b; q0 = fmaf(a, a, fmaf(b, b, q0));
                s1 += e + f; q1 = fmaf(e, e, fmaf(f, f, q1));
            }
#pragma unroll
            for (int m = 1; m <= 2; m <<= 1) {
                s0 += __shfl_xor_sync(0xffffffffu, s0, m); q0 += __shfl_xor_sync(0xffffffffu, q0, m);
                s1 += __shfl_xor_sync(0xffffffffu, s1, m); q1 += __shfl_xor_sync(0xffffffffu, q1, m);
            }
            if (c < 2) g_st[(rb * 8 + j) * 128 + row + 8 * c] = c ? make_float2(s1, q1) : make_float2(s0, q0);
            bar_arrive(6, 288);
#pragma unroll
            for (int q = 0; q < 5; q++) {
                const uint32_t ms = q < 4 ? ms0 : ms1;
                const uint32_t g0 = lds32(ms + 6400 + q * 32), g1 = lds32(ms + 6400 + q * 32 + 16);
                sts128(park + q * 4096, make_uint4(bfma2(g0, x1[4 * q], x2[4 * q]), bfma2(g0, x1[4 * q + 1], x2[4 * q + 1]),
                                                   bfma2(g1, x1[4 * q + 2], x2[4 * q + 2]), bfma2(g1, x1[4 * q + 3], x2[4 * q + 3])));
            }
        }
        gemm3<1>(sb, rb, j, half, row, c, ones);
    }
}

typedef CUresult (*EncFn)(CUtensorMap*, CUtensorMapDataType, cuuint32_t, void*, const cuuint64_t*, const cuuint64_t*,
                          const cuuint32_t*, const cuuint32_t*, CUtensorMapInterleave, CUtensorMapSwizzle,
                          CUtensorMapL2promotion, CUtensorMapFloatOOBfill);

void make_map(EncFn enc, CUtensorMap* m, const void* base, uint64_t inner, uint64_t outer, uint32_t bi, uint32_t bo,
              CUtensorMapSwizzle swz = CU_TENSOR_MAP_SWIZZLE_128B) {
    cuuint64_t dims[2] = {inner, outer};
    cuuint64_t st[1] = {inner * 2};
    cuuint32_t box[2] = {bi, bo};
    cuuint32_t es[2] = {1, 1};
    enc(m, CU_TENSOR_MAP_DATA_TYPE_BFLOAT16, 2, const_cast<void*>(base), dims, st, box, es, CU_TENSOR_MAP_INTERLEAVE_NONE,
        swz, CU_TENSOR_MAP_L2_PROMOTION_NONE, CU_TENSOR_MAP_FLOAT_OOB_FILL_NONE);
}

}

extern "C" void kernel_launch(void* const* d_in, const int* in_sizes, int n_in, void* d_out, int out_size) {
    (void)in_sizes; (void)n_in; (void)out_size;
    Params p;
    p.q = (const bf16*)d_in[0]; p.k = (const bf16*)d_in[1]; p.v = (const bf16*)d_in[2];
    p.shift = (const bf16*)d_in[3]; p.ssmk = (const bf16*)d_in[4]; p.ssmD = (const bf16*)d_in[5];
    p.w1 = (const bf16*)d_in[7]; p.w2 = (const bf16*)d_in[8]; p.w3 = (const bf16*)d_in[9]; p.w4 = (const bf16*)d_in[10];
    p.c = (const bf16*)d_in[11]; p.wmod = (const bf16*)d_in[12];
    p.out = (bf16*)d_out;
    p.ones = 0xffffffffu;

    void* fn = nullptr;
    cudaDriverEntryPointQueryResult qr;
    cudaGetDriverEntryPoint("cuTensorMapEncodeTiled", &fn, cudaEnableDefault, &qr);
    EncFn enc = (EncFn)fn;
    void* hn = nullptr;
    cudaGetSymbolAddress(&hn, g_hn);
    Maps maps;
    make_map(enc, &maps.w3s, p.w3, F_, D_, 216, 64, CU_TENSOR_MAP_SWIZZLE_NONE);
    make_map(enc, &maps.wm, p.wmod, 6 * D_, D_, 32, 128, CU_TENSOR_MAP_SWIZZLE_64B);
    make_map(enc, &maps.xa, p.q, D_, S_, 64, 128);
    make_map(enc, &maps.xb, p.q, D_, S_, 16, 128, CU_TENSOR_MAP_SWIZZLE_NONE);
    make_map(enc, &maps.hn, hn, D_, S_, 64, 128);
    make_map(enc, &maps.w1a, p.w1, D_, D_, 64, 64);
    make_map(enc, &maps.w1b, p.w1, D_, D_, 16, 64);
    make_map(enc, &maps.w2a, p.w2, D_, D_, 64, 64);
    make_map(enc, &maps.w2b, p.w2, D_, D_, 16, 64);
    make_map(enc, &maps.w3a, p.w3, F_, D_, 64, 64);
    make_map(enc, &maps.w3b, p.w3, F_, D_, 48, 64);
    make_map(enc, &maps.w3c, p.w3, F_, D_, 40, 64);
    make_map(enc, &maps.w4a, p.w4, D_, F_, 64, 64);
    make_map(enc, &maps.w4b, p.w4, D_, F_, 16, 64);
    cudaFuncSetAttribute(fused_kernel, cudaFuncAttributeMaxDynamicSharedMemorySize, SMEM_BYTES);
    fused_kernel<<<132, NTHREADS, SMEM_BYTES>>>(p, maps);
}
```

```cpp
#include <cuda_runtime.h>
#include <cuda_bf16.h>
#include <cuda.h>
#include <stdint.h>
#include <string.h>

#define SEED 0
#define RING_A 6
#define MMA_STAT 0
#define CH 2
#define FAST_LN 1
#define STAG 10
#define REDM 1
#define CONVV 0
#define NPOLL 1
#define PGELU 2
#define CH3 4
#define HO_A 14
#define HO_B 14
#define LATE 0
#define HOLD 1
#define SSM_DELAY 0
#define B_DELAY 300
#define SSM_N 3
#define PF_EARLY 0

namespace {

typedef __nv_bfloat16 bf16;
typedef __nv_bfloat162 bf162;

constexpr int S_ = 2048, D_ = 640, F_ = 1728;
constexpr int NTHREADS = 640;
constexpr int NA = RING_A, NB = 12 - RING_A;
constexpr int SLOT = 16384;
constexpr int SM_RA = 0, SM_RB = NA * SLOT;

constexpr int SM_RED = 0;
constexpr int RED_STRIDE = 17536;
constexpr int SM_PK = 0;
constexpr int SM_PV = 24576;
constexpr int SM_WM = 88064;
constexpr int SM_K = SM_WM + 40960;
constexpr int K_STRIDE = 8320;
constexpr int SM_U = SM_K + 5 * K_STRIDE;
constexpr int U_PLANE = 2560, U_STRIDE = 5120;
constexpr int SM_Y = 12 * SLOT;
static_assert(SM_U + 5 * U_STRIDE <= SM_Y, "smem map");
constexpr int SM_XT = 3 * SLOT, SM_XT2 = 4 * SLOT, SM_YT = SM_XT2 + 4096;
constexpr int SM_MOD = SM_Y + 20480;
constexpr int SM_GV = SM_MOD + 7680;
constexpr int SM_CS = SM_GV + 1024;
constexpr int SM_RP = SM_CS + 1024;
constexpr int SM_BAR = SM_RP + 1024;
constexpr int SM_PROF = SM_BAR + 512;
constexpr int SM_TOTAL = SM_PROF + 512;
constexpr int SMEM_BYTES = SM_TOTAL + 1024;
static_assert(SMEM_BYTES <= 232448, "smem");

constexpr int BAR_FA = 0, BAR_FB = NA, BAR_EA = 12, BAR_EB = 12 + NA, BAR_K = 24, BAR_U = 29, BAR_Y = 34, BAR_CS = 35, BAR_WM = 36, BAR_M = 37, BAR_XY = 38, BAR_Y2 = 39, BAR_G = 40, BAR_ST = 43, NBARS = 44;

__device__ __align__(1024) bf16 g_kvT[D_ * S_];
__device__ __align__(1024) uint32_t g_yv[128 * 5120];
__device__ __align__(1024) bf16 g_mod[6 * D_];
__device__ __align__(1024) bf16 g_hn[S_ * D_];
__device__ __align__(1024) uint4 g_rs[S_ * 2];
__device__ __align__(1024) bf16 g_h1[S_ * D_];
__device__ __align__(1024) bf16 g_x1[S_ * D_];
__device__ __align__(1024) bf16 g_g[S_ * F_];
__device__ __align__(1024) float2 g_st[S_ * 8];
__device__ __align__(1024) float g_cs[F_];
__device__ __align__(1024) unsigned g_flags[128 * 32];
__device__ __align__(1024) unsigned g_epoch[160];
constexpr int FL_P = 0, FL_C = 8, FL_CS = 9, FL_M = 10, FL_R = 16, FL_B1 = 32, FL_B2 = 48, FL_G = 64;

#define TS(i) do {} while (0)
#define TSW(i) do {} while (0)
#define TSD(i, dep) do {} while (0)
#define TSD2(i, dep) do {} while (0)
#define TSFLUSH() do {} while (0)

struct Params {
    const bf16 *q, *k, *v, *shift, *ssmk, *ssmD, *w1, *w2, *w3, *w4, *c, *wmod;
    bf16* out;
    unsigned ones;
};
#define CHUNK(k) if (ones & (1u << (k)))
struct Maps { CUtensorMap hn, w1a, w1b, w2a, w2b, w3a, w3b, w3c, w4a, w4b, wm, xa, xb, w3s; };

template<int N> struct WgRs;
template<int N> struct WgSs;
template<> struct WgRs<32> { template<int OFF,int HI,int SC> static __device__ __forceinline__ void run(float* d,uint32_t a0,uint32_t a1,uint32_t a2,uint32_t a3,uint32_t blo){
 asm volatile("{.reg .b32 l; .reg .b64 db; add.u32 l,%20,%21; mov.b64 db,{l,%22}; wgmma.mma_async.sync.aligned.m64n32k16.f32.bf16.bf16 {%0,%1,%2,%3,%4,%5,%6,%7,%8,%9,%10,%11,%12,%13,%14,%15},{%16,%17,%18,%19},db,%23,1,1,0;}"
 :"+f"(d[0]),"+f"(d[1]),"+f"(d[2]),"+f"(d[3]),"+f"(d[4]),"+f"(d[5]),"+f"(d[6]),"+f"(d[7]),"+f"(d[8]),"+f"(d[9]),"+f"(d[10]),"+f"(d[11]),"+f"(d[12]),"+f"(d[13]),"+f"(d[14]),"+f"(d[15])
 :"r"(a0),"r"(a1),"r"(a2),"r"(a3),"r"(blo),"n"(OFF),"n"(HI),"n"(SC)); } };
template<> struct WgRs<48> { template<int OFF,int HI,int SC> static __device__ __forceinline__ void run(float* d,uint32_t a0,uint32_t a1,uint32_t a2,uint32_t a3,uint32_t blo){
 asm volatile("{.reg .b32 l; .reg .b64 db; add.u32 l,%28,%29; mov.b64 db,{l,%30}; wgmma.mma_async.sync.aligned.m64n48k16.f32.bf16.bf16 {%0,%1,%2,%3,%4,%5,%6,%7,%8,%9,%10,%11,%12,%13,%14,%15,%16,%17,%18,%19,%20,%21,%22,%23},{%24,%25,%26,%27},db,%31,1,1,0;}"
 :"+f"(d[0]),"+f"(d[1]),"+f"(d[2]),"+f"(d[3]),"+f"(d[4]),"+f"(d[5]),"+f"(d[6]),"+f"(d[7]),"+f"(d[8]),"+f"(d[9]),"+f"(d[10]),"+f"(d[11]),"+f"(d[12]),"+f"(d[13]),"+f"(d[14]),"+f"(d[15]),"+f"(d[16]),"+f"(d[17]),"+f"(d[18]),"+f"(d[19]),"+f"(d[20]),"+f"(d[21]),"+f"(d[22]),"+f"(d[23])
 :"r"(a0),"r"(a1),"r"(a2),"r"(a3),"r"(blo),"n"(OFF),"n"(HI),"n"(SC)); } };
template<> struct WgRs<64> { template<int OFF,int HI,int SC> static __device__ __forceinline__ void run(float* d,uint32_t a0,uint32_t a1,uint32_t a2,uint32_t a3,uint32_t blo){
 asm volatile("{.reg .b32 l; .reg .b64 db; add.u32 l,%36,%37; mov.b64 db,{l,%38}; wgmma.mma_async.sync.aligned.m64n64k16.f32.bf16.bf16 {%0,%1,%2,%3,%4,%5,%6,%7,%8,%9,%10,%11,%12,%13,%14,%15,%16,%17,%18,%19,%20,%21,%22,%23,%24,%25,%26,%27,%28,%29,%30,%31},{%32,%33,%34,%35},db,%39,1,1,0;}"
 :"+f"(d[0]),"+f"(d[1]),"+f"(d[2]),"+f"(d[3]),"+f"(d[4]),"+f"(d[5]),"+f"(d[6]),"+f"(d[7]),"+f"(d[8]),"+f"(d[9]),"+f"(d[10]),"+f"(d[11]),"+f"(d[12]),"+f"(d[13]),"+f"(d[14]),"+f"(d[15]),"+f"(d[16]),"+f"(d[17]),"+f"(d[18]),"+f"(d[19]),"+f"(d[20]),"+f"(d[21]),"+f"(d[22]),"+f"(d[23]),"+f"(d[24]),"+f"(d[25]),"+f"(d[26]),"+f"(d[27]),"+f"(d[28]),"+f"(d[29]),"+f"(d[30]),"+f"(d[31])
 :"r"(a0),"r"(a1),"r"(a2),"r"(a3),"r"(blo),"n"(OFF),"n"(HI),"n"(SC)); } };
template<> struct WgRs<80> { template<int OFF,int HI,int SC> static __device__ __forceinline__ void run(float* d,uint32_t a0,uint32_t a1,uint32_t a2,uint32_t a3,uint32_t blo){
 asm volatile("{.reg .b32 l; .reg .b64 db; add.u32 l,%44,%45; mov.b64 db,{l,%46}; wgmma.mma_async.sync.aligned.m64n80k16.f32.bf16.bf16 {%0,%1,%2,%3,%4,%5,%6,%7,%8,%9,%10,%11,%12,%13,%14,%15,%16,%17,%18,%19,%20,%21,%22,%23,%24,%25,%26,%27,%28,%29,%30,%31,%32,%33,%34,%35,%36,%37,%38,%39},{%40,%41,%42,%43},db,%47,1,1,0;}"
 :"+f"(d[0]),"+f"(d[1]),"+f"(d[2]),"+f"(d[3]),"+f"(d[4]),"+f"(d[5]),"+f"(d[6]),"+f"(d[7]),"+f"(d[8]),"+f"(d[9]),"+f"(d[10]),"+f"(d[11]),"+f"(d[12]),"+f"(d[13]),"+f"(d[14]),"+f"(d[15]),"+f"(d[16]),"+f"(d[17]),"+f"(d[18]),"+f"(d[19]),"+f"(d[20]),"+f"(d[21]),"+f"(d[22]),"+f"(d[23]),"+f"(d[24]),"+f"(d[25]),"+f"(d[26]),"+f"(d[27]),"+f"(d[28]),"+f"(d[29]),"+f"(d[30]),"+f"(d[31]),"+f"(d[32]),"+f"(d[33]),"+f"(d[34]),"+f"(d[35]),"+f"(d[36]),"+f"(d[37]),"+f"(d[38]),"+f"(d[39])
 :"r"(a0),"r"(a1),"r"(a2),"r"(a3),"r"(blo),"n"(OFF),"n"(HI),"n"(SC)); } };
template<> struct WgRs<96> { template<int OFF,int HI,int SC> static __device__ __forceinline__ void run(float* d,uint32_t a0,uint32_t a1,uint32_t a2,uint32_t a3,uint32_t blo){
 asm volatile("{.reg .b32 l; .reg .b64 db; add.u32 l,%52,%53; mov.b64 db,{l,%54}; wgmma.mma_async.sync.aligned.m64n96k16.f32.bf16.bf16 {%0,%1,%2,%3,%4,%5,%6,%7,%8,%9,%10,%11,%12,%13,%14,%15,%16,%17,%18,%19,%20,%21,%22,%23,%24,%25,%26,%27,%28,%29,%30,%31,%32,%33,%34,%35,%36,%37,%38,%39,%40,%41,%42,%43,%44,%45,%46,%47},{%48,%49,%50,%51},db,%55,1,1,0;}"
 :"+f"(d[0]),"+f"(d[1]),"+f"(d[2]),"+f"(d[3]),"+f"(d[4]),"+f"(d[5]),"+f"(d[6]),"+f"(d[7]),"+f"(d[8]),"+f"(d[9]),"+f"(d[10]),"+f"(d[11]),"+f"(d[12]),"+f"(d[13]),"+f"(d[14]),"+f"(d[15]),"+f"(d[16]),"+f"(d[17]),"+f"(d[18]),"+f"(d[19]),"+f"(d[20]),"+f"(d[21]),"+f"(d[22]),"+f"(d[23]),"+f"(d[24]),"+f"(d[25]),"+f"(d[26]),"+f"(d[27]),"+f"(d[28]),"+f"(d[29]),"+f"(d[30]),"+f"(d[31]),"+f"(d[32]),"+f"(d[33]),"+f"(d[34]),"+f"(d[35]),"+f"(d[36]),"+f"(d[37]),"+f"(d[38]),"+f"(d[39]),"+f"(d[40]),"+f"(d[41]),"+f"(d[42]),"+f"(d[43]),"+f"(d[44]),"+f"(d[45]),"+f"(d[46]),"+f"(d[47])
 :"r"(a0),"r"(a1),"r"(a2),"r"(a3),"r"(blo),"n"(OFF),"n"(HI),"n"(SC)); } };
template<> struct WgRs<112> { template<int OFF,int HI,int SC> static __device__ __forceinline__ void run(float* d,uint32_t a0,uint32_t a1,uint32_t a2,uint32_t a3,uint32_t blo){
 asm volatile("{.reg .b32 l; .reg .b64 db; add.u32 l,%60,%61; mov.b64 db,{l,%62}; wgmma.mma_async.sync.aligned.m64n112k16.f32.bf16.bf16 {%0,%1,%2,%3,%4,%5,%6,%7,%8,%9,%10,%11,%12,%13,%14,%15,%16,%17,%18,%19,%20,%21,%22,%23,%24,%25,%26,%27,%28,%29,%30,%31,%32,%33,%34,%35,%36,%37,%38,%39,%40,%41,%42,%43,%44,%45,%46,%47,%48,%49,%50,%51,%52,%53,%54,%55},{%56,%57,%58,%59},db,%63,1,1,0;}"
 :"+f"(d[0]),"+f"(d[1]),"+f"(d[2]),"+f"(d[3]),"+f"(d[4]),"+f"(d[5]),"+f"(d[6]),"+f"(d[7]),"+f"(d[8]),"+f"(d[9]),"+f"(d[10]),"+f"(d[11]),"+f"(d[12]),"+f"(d[13]),"+f"(d[14]),"+f"(d[15]),"+f"(d[16]),"+f"(d[17]),"+f"(d[18]),"+f"(d[19]),"+f"(d[20]),"+f"(d[21]),"+f"(d[22]),"+f"(d[23]),"+f"(d[24]),"+f"(d[25]),"+f"(d[26]),"+f"(d[27]),"+f"(d[28]),"+f"(d[29]),"+f"(d[30]),"+f"(d[31]),"+f"(d[32]),"+f"(d[33]),"+f"(d[34]),"+f"(d[35]),"+f"(d[36]),"+f"(d[37]),"+f"(d[38]),"+f"(d[39]),"+f"(d[40]),"+f"(d[41]),"+f"(d[42]),"+f"(d[43]),"+f"(d[44]),"+f"(d[45]),"+f"(d[46]),"+f"(d[47]),"+f"(d[48]),"+f"(d[49]),"+f"(d[50]),"+f"(d[51]),"+f"(d[52]),"+f"(d[53]),"+f"(d[54]),"+f"(d[55])
 :"r"(a0),"r"(a1),"r"(a2),"r"(a3),"r"(blo),"n"(OFF),"n"(HI),"n"(SC)); } };
template<> struct WgRs<128> { template<int OFF,int HI,int SC> static __device__ __forceinline__ void run(float* d,uint32_t a0,uint32_t a1,uint32_t a2,uint32_t a3,uint32_t blo){
 asm volatile("{.reg .b32 l; .reg .b64 db; add.u32 l,%68,%69; mov.b64 db,{l,%70}; wgmma.mma_async.sync.aligned.m64n128k16.f32.bf16.bf16 {%0,%1,%2,%3,%4,%5,%6,%7,%8,%9,%10,%11,%12,%13,%14,%15,%16,%17,%18,%19,%20,%21,%22,%23,%24,%25,%26,%27,%28,%29,%30,%31,%32,%33,%34,%35,%36,%37,%38,%39,%40,%41,%42,%43,%44,%45,%46,%47,%48,%49,%50,%51,%52,%53,%54,%55,%56,%57,%58,%59,%60,%61,%62,%63},{%64,%65,%66,%67},db,%71,1,1,0;}"
 :"+f"(d[0]),"+f"(d[1]),"+f"(d[2]),"+f"(d[3]),"+f"(d[4]),"+f"(d[5]),"+f"(d[6]),"+f"(d[7]),"+f"(d[8]),"+f"(d[9]),"+f"(d[10]),"+f"(d[11]),"+f"(d[12]),"+f"(d[13]),"+f"(d[14]),"+f"(d[15]),"+f"(d[16]),"+f"(d[17]),"+f"(d[18]),"+f"(d[19]),"+f"(d[20]),"+f"(d[21]),"+f"(d[22]),"+f"(d[23]),"+f"(d[24]),"+f"(d[25]),"+f"(d[26]),"+f"(d[27]),"+f"(d[28]),"+f"(d[29]),"+f"(d[30]),"+f"(d[31]),"+f"(d[32]),"+f"(d[33]),"+f"(d[34]),"+f"(d[35]),"+f"(d[36]),"+f"(d[37]),"+f"(d[38]),"+f"(d[39]),"+f"(d[40]),"+f"(d[41]),"+f"(d[42]),"+f"(d[43]),"+f"(d[44]),"+f"(d[45]),"+f"(d[46]),"+f"(d[47]),"+f"(d[48]),"+f"(d[49]),"+f"(d[50]),"+f"(d[51]),"+f"(d[52]),"+f"(d[53]),"+f"(d[54]),"+f"(d[55]),"+f"(d[56]),"+f"(d[57]),"+f"(d[58]),"+f"(d[59]),"+f"(d[60]),"+f"(d[61]),"+f"(d[62]),"+f"(d[63])
 :"r"(a0),"r"(a1),"r"(a2),"r"(a3),"r"(blo),"n"(OFF),"n"(HI),"n"(SC)); } };
template<> struct WgSs<80> { template<int AOFF,int AHI,int BOFF,int BHI,int SC> static __device__ __forceinline__ void run(float* d,uint32_t alo,uint32_t blo){
 asm volatile("{.reg .b32 l,m; .reg .b64 da,db; add.u32 l,%40,%42; mov.b64 da,{l,%43}; add.u32 m,%41,%44; mov.b64 db,{m,%45}; wgmma.mma_async.sync.aligned.m64n80k16.f32.bf16.bf16 {%0,%1,%2,%3,%4,%5,%6,%7,%8,%9,%10,%11,%12,%13,%14,%15,%16,%17,%18,%19,%20,%21,%22,%23,%24,%25,%26,%27,%28,%29,%30,%31,%32,%33,%34,%35,%36,%37,%38,%39},da,db,%46,1,1,0,1;}"
 :"+f"(d[0]),"+f"(d[1]),"+f"(d[2]),"+f"(d[3]),"+f"(d[4]),"+f"(d[5]),"+f"(d[6]),"+f"(d[7]),"+f"(d[8]),"+f"(d[9]),"+f"(d[10]),"+f"(d[11]),"+f"(d[12]),"+f"(d[13]),"+f"(d[14]),"+f"(d[15]),"+f"(d[16]),"+f"(d[17]),"+f"(d[18]),"+f"(d[19]),"+f"(d[20]),"+f"(d[21]),"+f"(d[22]),"+f"(d[23]),"+f"(d[24]),"+f"(d[25]),"+f"(d[26]),"+f"(d[27]),"+f"(d[28]),"+f"(d[29]),"+f"(d[30]),"+f"(d[31]),"+f"(d[32]),"+f"(d[33]),"+f"(d[34]),"+f"(d[35]),"+f"(d[36]),"+f"(d[37]),"+f"(d[38]),"+f"(d[39])
 :"r"(alo),"r"(blo),"n"(AOFF),"n"(AHI),"n"(BOFF),"n"(BHI),"n"(SC)); } };
template<> struct WgSs<104> { template<int AOFF,int AHI,int BOFF,int BHI,int SC> static __device__ __forceinline__ void run(float* d,uint32_t alo,uint32_t blo){
 asm volatile("{.reg .b32 l,m; .reg .b64 da,db; add.u32 l,%52,%54; mov.b64 da,{l,%55}; add.u32 m,%53,%56; mov.b64 db,{m,%57}; wgmma.mma_async.sync.aligned.m64n104k16.f32.bf16.bf16 {%0,%1,%2,%3,%4,%5,%6,%7,%8,%9,%10,%11,%12,%13,%14,%15,%16,%17,%18,%19,%20,%21,%22,%23,%24,%25,%26,%27,%28,%29,%30,%31,%32,%33,%34,%35,%36,%37,%38,%39,%40,%41,%42,%43,%44,%45,%46,%47,%48,%49,%50,%51},da,db,%58,1,1,0,1;}"
 :"+f"(d[0]),"+f"(d[1]),"+f"(d[2]),"+f"(d[3]),"+f"(d[4]),"+f"(d[5]),"+f"(d[6]),"+f"(d[7]),"+f"(d[8]),"+f"(d[9]),"+f"(d[10]),"+f"(d[11]),"+f"(d[12]),"+f"(d[13]),"+f"(d[14]),"+f"(d[15]),"+f"(d[16]),"+f"(d[17]),"+f"(d[18]),"+f"(d[19]),"+f"(d[20]),"+f"(d[21]),"+f"(d[22]),"+f"(d[23]),"+f"(d[24]),"+f"(d[25]),"+f"(d[26]),"+f"(d[27]),"+f"(d[28]),"+f"(d[29]),"+f"(d[30]),"+f"(d[31]),"+f"(d[32]),"+f"(d[33]),"+f"(d[34]),"+f"(d[35]),"+f"(d[36]),"+f"(d[37]),"+f"(d[38]),"+f"(d[39]),"+f"(d[40]),"+f"(d[41]),"+f"(d[42]),"+f"(d[43]),"+f"(d[44]),"+f"(d[45]),"+f"(d[46]),"+f"(d[47]),"+f"(d[48]),"+f"(d[49]),"+f"(d[50]),"+f"(d[51])
 :"r"(alo),"r"(blo),"n"(AOFF),"n"(AHI),"n"(BOFF),"n"(BHI),"n"(SC)); } };
template<> struct WgSs<112> { template<int AOFF,int AHI,int BOFF,int BHI,int SC> static __device__ __forceinline__ void run(float* d,uint32_t alo,uint32_t blo){
 asm volatile("{.reg .b32 l,m; .reg .b64 da,db; add.u32 l,%56,%58; mov.b64 da,{l,%59}; add.u32 m,%57,%60; mov.b64 db,{m,%61}; wgmma.mma_async.sync.aligned.m64n112k16.f32.bf16.bf16 {%0,%1,%2,%3,%4,%5,%6,%7,%8,%9,%10,%11,%12,%13,%14,%15,%16,%17,%18,%19,%20,%21,%22,%23,%24,%25,%26,%27,%28,%29,%30,%31,%32,%33,%34,%35,%36,%37,%38,%39,%40,%41,%42,%43,%44,%45,%46,%47,%48,%49,%50,%51,%52,%53,%54,%55},da,db,%62,1,1,0,1;}"
 :"+f"(d[0]),"+f"(d[1]),"+f"(d[2]),"+f"(d[3]),"+f"(d[4]),"+f"(d[5]),"+f"(d[6]),"+f"(d[7]),"+f"(d[8]),"+f"(d[9]),"+f"(d[10]),"+f"(d[11]),"+f"(d[12]),"+f"(d[13]),"+f"(d[14]),"+f"(d[15]),"+f"(d[16]),"+f"(d[17]),"+f"(d[18]),"+f"(d[19]),"+f"(d[20]),"+f"(d[21]),"+f"(d[22]),"+f"(d[23]),"+f"(d[24]),"+f"(d[25]),"+f"(d[26]),"+f"(d[27]),"+f"(d[28]),"+f"(d[29]),"+f"(d[30]),"+f"(d[31]),"+f"(d[32]),"+f"(d[33]),"+f"(d[34]),"+f"(d[35]),"+f"(d[36]),"+f"(d[37]),"+f"(d[38]),"+f"(d[39]),"+f"(d[40]),"+f"(d[41]),"+f"(d[42]),"+f"(d[43]),"+f"(d[44]),"+f"(d[45]),"+f"(d[46]),"+f"(d[47]),"+f"(d[48]),"+f"(d[49]),"+f"(d[50]),"+f"(d[51]),"+f"(d[52]),"+f"(d[53]),"+f"(d[54]),"+f"(d[55])
 :"r"(alo),"r"(blo),"n"(AOFF),"n"(AHI),"n"(BOFF),"n"(BHI),"n"(SC)); } };

__device__ __forceinline__ void wg_fence() { asm volatile("wgmma.fence.sync.aligned;" ::: "memory"); }
__device__ __forceinline__ void wg_commit() { asm volatile("wgmma.commit_group.sync.aligned;" ::: "memory"); }
template <int N> __device__ __forceinline__ void wg_wait() { asm volatile("wgmma.wait_group.sync.aligned %0;" ::"n"(N) : "memory"); }
template <int N> __device__ __forceinline__ void reg_fence(float* d) {
#pragma unroll
    for (int i = 0; i < N; i++) asm volatile("" : "+f"(d[i])::"memory");
}
__device__ __forceinline__ uint32_t desc_lo(uint32_t addr, uint32_t lbo) { return ((addr & 0x3FFFF) >> 4) | ((lbo >> 4) << 16); }
#define desc_hi(sbo, sw) (((sbo) >> 4) | ((sw) << 30))
__device__ __forceinline__ uint32_t smem_u32(const void* p) { return (uint32_t)__cvta_generic_to_shared(p); }
__device__ __forceinline__ bool elect() {
    uint32_t p;
    asm volatile("{.reg .pred P; elect.sync _|P, 0xffffffff; selp.u32 %0,1,0,P;}" : "=r"(p));
    return p;
}
__device__ __forceinline__ void mbar_init(uint32_t bar, uint32_t cnt) { asm volatile("mbarrier.init.shared::cta.b64 [%0], %1;" ::"r"(bar), "r"(cnt) : "memory"); }
__device__ __forceinline__ void mbar_expect(uint32_t bar, uint32_t bytes) { asm volatile("mbarrier.arrive.expect_tx.shared::cta.b64 _, [%0], %1;" ::"r"(bar), "r"(bytes) : "memory"); }
__device__ __forceinline__ bool mbar_try(uint32_t bar, uint32_t par) {
    uint32_t ok;
    asm volatile("{.reg .pred p; mbarrier.try_wait.parity.shared::cta.b64 p, [%1], %2; selp.u32 %0,1,0,p;}" : "=r"(ok) : "r"(bar), "r"(par) : "memory");
    return ok;
}
constexpr int SPIN_LIMIT = 1 << 18;
__device__ __forceinline__ void mbar_wait(uint32_t bar, uint32_t par) {
    if (mbar_try(bar, par)) return;
    int n = 0;
    while (!mbar_try(bar, par) && ++n < SPIN_LIMIT) {}
}
__device__ __forceinline__ void bulk_g2s(uint32_t dst, const void* src, uint32_t bytes, uint32_t bar) {
    asm volatile("cp.async.bulk.shared::cluster.global.mbarrier::complete_tx::bytes [%0], [%1], %2, [%3];" ::"r"(dst), "l"(src), "r"(bytes), "r"(bar) : "memory");
}
__device__ __forceinline__ void bulk_s2g(void* dst, uint32_t src, uint32_t bytes) {
    asm volatile("cp.async.bulk.global.shared::cta.bulk_group [%0], [%1], %2;" ::"l"(dst), "r"(src), "r"(bytes) : "memory");
}
__device__ __forceinline__ void bulk_prefetch(const void* src, uint32_t bytes) {
    asm volatile("cp.async.bulk.prefetch.L2.global [%0], %1;" ::"l"(src), "r"(bytes) : "memory");
}
__device__ __forceinline__ void tma2d(uint32_t dst, const CUtensorMap* m, int c0, int c1, uint32_t bar) {
    asm volatile("cp.async.bulk.tensor.2d.shared::cluster.global.mbarrier::complete_tx::bytes [%0], [%1, {%3, %4}], [%2];" ::"r"(dst), "l"(m), "r"(bar), "r"(c0), "r"(c1) : "memory");
}
__device__ __forceinline__ void tma2d_mc(uint32_t dst, const CUtensorMap* m, int c0, int c1, uint32_t bar) {
    asm volatile("cp.async.bulk.tensor.2d.shared::cluster.global.mbarrier::complete_tx::bytes.multicast::cluster [%0], [%1, {%3, %4}], [%2], %5;" ::"r"(dst), "l"(m), "r"(bar), "r"(c0), "r"(c1), "h"((uint16_t)3) : "memory");
}
__device__ __forceinline__ uint32_t mapa(uint32_t a, uint32_t rank) { uint32_t r; asm("mapa.shared::cluster.u32 %0, %1, %2;" : "=r"(r) : "r"(a), "r"(rank)); return r; }
__device__ __forceinline__ void mbar_arrive_cl(uint32_t bar) { asm volatile("mbarrier.arrive.shared::cluster.b64 _, [%0];" ::"r"(bar) : "memory"); }
__device__ __forceinline__ void prefetch_map(const CUtensorMap* m) { asm volatile("prefetch.tensormap [%0];" ::"l"(m) : "memory"); }
__device__ __forceinline__ void cpasync16(uint32_t dst, const void* src, uint32_t srcsz) {
    asm volatile("cp.async.cg.shared.global [%0], [%1], 16, %2;" ::"r"(dst), "l"(src), "r"(srcsz) : "memory");
}
__device__ __forceinline__ void bar_sync(int id, int n) { asm volatile("bar.sync %0, %1;" ::"r"(id), "r"(n) : "memory"); }
__device__ __forceinline__ void bar_arrive(int id, int n) { asm volatile("bar.arrive %0, %1;" ::"r"(id), "r"(n) : "memory"); }
__device__ __forceinline__ void fence_async_smem() { asm volatile("fence.proxy.async.shared::cta;" ::: "memory"); }
__device__ __forceinline__ void fence_async_global() { asm volatile("fence.proxy.async.global;" ::: "memory"); }
__device__ __forceinline__ void flag_release(int f) { asm volatile("red.release.gpu.global.add.u32 [%0], 1;" ::"l"(&g_flags[f * 32]) : "memory"); }
__device__ __forceinline__ void flag_wait(int f, unsigned target) {
    const unsigned* p = &g_flags[f * 32];
    unsigned v; int n = 0;
    do {
        asm volatile("ld.relaxed.gpu.global.u32 %0, [%1];" : "=r"(v) : "l"(p) : "memory");
    } while ((int)(v - target) < 0 && ++n < SPIN_LIMIT);
    asm volatile("fence.acquire.gpu;" ::: "memory");
}
__device__ __forceinline__ unsigned ld_flag(const unsigned* p) { unsigned v; asm volatile("ld.relaxed.gpu.global.u32 %0, [%1];" : "=r"(v) : "l"(p) : "memory"); return v; }
__device__ __forceinline__ void spin(unsigned n) { unsigned t0, t1; asm volatile("mov.u32 %0, %%clock;" : "=r"(t0)); do { asm volatile("mov.u32 %0, %%clock;" : "=r"(t1)); } while (t1 - t0 < n); }
__device__ __forceinline__ void flag_wait_fast(int f, unsigned target) {
    flag_wait(f, target);
}
__device__ __forceinline__ void flag_wait2(int f0, int f1, unsigned target) {
    const unsigned *p = &g_flags[f0 * 32], *q = &g_flags[f1 * 32];
    unsigned v, w; int n = 0;
    do { v = ld_flag(p); w = ld_flag(q); } while ((int)((v - target) | (w - target)) < 0 && ++n < SPIN_LIMIT);
    asm volatile("fence.acquire.gpu;" ::: "memory");
}
__device__ __forceinline__ uint32_t lds32(uint32_t a) { uint32_t v; asm volatile("ld.shared.u32 %0, [%1];" : "=r"(v) : "r"(a)); return v; }
__device__ __forceinline__ float2 lds64f(uint32_t a) { float2 v; asm volatile("ld.shared.v2.f32 {%0,%1}, [%2];" : "=f"(v.x), "=f"(v.y) : "r"(a)); return v; }
__device__ __forceinline__ uint2 lds64(uint32_t a) { uint2 v; asm volatile("ld.shared.v2.u32 {%0,%1}, [%2];" : "=r"(v.x), "=r"(v.y) : "r"(a)); return v; }
__device__ __forceinline__ void sts64f(uint32_t a, float2 v) { asm volatile("st.shared.v2.f32 [%0], {%1,%2};" ::"r"(a), "f"(v.x), "f"(v.y) : "memory"); }
__device__ __forceinline__ void sts32(uint32_t a, uint32_t v) { asm volatile("st.shared.u32 [%0], %1;" ::"r"(a), "r"(v) : "memory"); }
__device__ __forceinline__ void sts64(uint32_t a, uint32_t x, uint32_t y) { asm volatile("st.shared.v2.u32 [%0], {%1,%2};" ::"r"(a), "r"(x), "r"(y) : "memory"); }
__device__ __forceinline__ void sts16(uint32_t a, uint16_t v) { asm volatile("st.shared.u16 [%0], %1;" ::"r"(a), "h"(v) : "memory"); }
__device__ __forceinline__ uint4 lds128(uint32_t a) { uint4 v; asm volatile("ld.shared.v4.u32 {%0,%1,%2,%3}, [%4];" : "=r"(v.x), "=r"(v.y), "=r"(v.z), "=r"(v.w) : "r"(a)); return v; }
__device__ __forceinline__ void sts128(uint32_t a, uint4 v) { asm volatile("st.shared.v4.u32 [%0], {%1,%2,%3,%4};" ::"r"(a), "r"(v.x), "r"(v.y), "r"(v.z), "r"(v.w) : "memory"); }
__device__ __forceinline__ void sts128f(uint32_t a, float x, float y, float z, float w) { asm volatile("st.shared.v4.f32 [%0], {%1,%2,%3,%4};" ::"r"(a), "f"(x), "f"(y), "f"(z), "f"(w) : "memory"); }
__device__ __forceinline__ uint32_t prmt(uint32_t a, uint32_t b, uint32_t s) { uint32_t r; asm("prmt.b32 %0,%1,%2,%3;" : "=r"(r) : "r"(a), "r"(b), "r"(s)); return r; }
__device__ __forceinline__ uint32_t pack2(float lo, float hi) { uint32_t r; asm("cvt.rn.bf16x2.f32 %0, %1, %2;" : "=r"(r) : "f"(hi), "f"(lo)); return r; }
__device__ __forceinline__ float blo(uint32_t v) { return __uint_as_float(v << 16); }
__device__ __forceinline__ float bhi(uint32_t v) { return __uint_as_float(v & 0xffff0000u); }
__device__ __forceinline__ uint32_t bmul2(uint32_t a, uint32_t b) { uint32_t r; asm("mul.rn.bf16x2 %0,%1,%2;" : "=r"(r) : "r"(a), "r"(b)); return r; }
__device__ __forceinline__ uint32_t badd2(uint32_t a, uint32_t b) { uint32_t r; asm("add.rn.bf16x2 %0,%1,%2;" : "=r"(r) : "r"(a), "r"(b)); return r; }
__device__ __forceinline__ float rbf(float x) { return __bfloat162float(__float2bfloat16_rn(x)); }
__device__ __forceinline__ uint32_t ldcg32(const void* p) { uint32_t v; asm volatile("ld.global.cg.u32 %0, [%1];" : "=r"(v) : "l"(p) : "memory"); return v; }
__device__ __forceinline__ uint4 ldcg128(const void* p) { uint4 v; asm volatile("ld.global.cg.v4.u32 {%0,%1,%2,%3}, [%4];" : "=r"(v.x), "=r"(v.y), "=r"(v.z), "=r"(v.w) : "l"(p) : "memory"); return v; }
__device__ __forceinline__ void stg32_if(void* p, uint32_t v, int on) { asm volatile("{.reg .pred q; setp.ne.b32 q, %2, 0; @q st.global.u32 [%0], %1;}" ::"l"(p), "r"(v), "r"(on) : "memory"); }
__device__ __forceinline__ uint2 ldcg64(const void* p) { uint2 v; asm volatile("ld.global.cg.v2.u32 {%0,%1}, [%2];" : "=r"(v.x), "=r"(v.y) : "l"(p) : "memory"); return v; }
__device__ __forceinline__ float gelu_h(float h) {
    float u = h * fmaf(h * h, 8.0f * 0.044715f * 0.7978845608028654f, 2.0f * 0.7978845608028654f);
    float th;
    asm("tanh.approx.f32 %0, %1;" : "=f"(th) : "f"(u));
    return fmaf(h, th, h);
}
__device__ __forceinline__ float gelu(float x) { return gelu_h(0.5f * x); }
__device__ __forceinline__ float half_rstd(float sum, float sq) {
    float mean = sum * (1.0f / D_), inv;
    asm("rsqrt.approx.ftz.f32 %0, %1;" : "=f"(inv) : "f"(fmaxf(fmaf(-mean, mean, fmaf(sq, 1.0f / D_, 1e-5f)), 1e-5f)));
    return 0.5f * inv;
}
__device__ __forceinline__ uint32_t bsub2(uint32_t a, uint32_t b) { uint32_t r; asm("sub.rn.bf16x2 %0,%1,%2;" : "=r"(r) : "r"(a), "r"(b)); return r; }
__device__ __forceinline__ uint32_t bfma2(uint32_t a, uint32_t b, uint32_t c) { uint32_t r; asm("fma.rn.bf16x2 %0,%1,%2,%3;" : "=r"(r) : "r"(a), "r"(b), "r"(c)); return r; }
__device__ __forceinline__ uint32_t gelu2_h(uint32_t h) {
    uint32_t u = bmul2(h, bfma2(bmul2(h, h), 0x3e923e92u, 0x3fcc3fccu)), th;
    asm("tanh.approx.bf16x2 %0, %1;" : "=r"(th) : "r"(u));
    return bfma2(h, th, h);
}
__device__ __forceinline__ void mma_stat(float* d, uint32_t u, uint32_t v) {
    asm("mma.sync.aligned.m16n8k16.row.col.f32.bf16.bf16.f32 {%0,%1,%2,%3},{%4,%6,%5,%6},{%4,%5},{%0,%1,%2,%3};"
        : "+f"(d[0]), "+f"(d[1]), "+f"(d[2]), "+f"(d[3]) : "r"(u), "r"(v), "r"(0x3f803f80u));
}
__device__ __forceinline__ void mma_sel(float* d, uint2 u, uint2 v, uint32_t b0, uint32_t b1) {
    asm("mma.sync.aligned.m16n8k16.row.col.f32.bf16.bf16.f32 {%0,%1,%2,%3},{%4,%5,%6,%7},{%8,%9},{%0,%1,%2,%3};"
        : "+f"(d[0]), "+f"(d[1]), "+f"(d[2]), "+f"(d[3]) : "r"(u.x), "r"(v.x), "r"(u.y), "r"(v.y), "r"(b0), "r"(b1));
}
__device__ __forceinline__ void conv_sum4(float* d, uint32_t a, bool last, int g, int c) {
    uint2 v0 = lds64(a), v1 = lds64(a + 8), v2 = lds64(a + 16), v3 = lds64(a + 24);
    if (last) {
        if (c > 2) v1 = make_uint2(0, 0);
        if (c > 1) v2 = make_uint2(0, 0);
        if (c > 0) v3 = make_uint2(0, 0);
    }
    const uint32_t one = (g & 1) ? 0x3f800000u : 0x00003f80u;
    mma_sel(d, v0, v1, (g >> 1) == 0 ? one : 0u, (g >> 1) == 1 ? one : 0u);
    mma_sel(d, v2, v3, (g >> 1) == 2 ? one : 0u, (g >> 1) == 3 ? one : 0u);
}
__device__ __forceinline__ uint3 row_stats(const uint32_t* v, int lane) {
    float s = 0.f, q = 0.f, s_ = 0.f, q_ = 0.f;
#pragma unroll
    for (int i = 0; i < 10; i++) { float a = blo(v[i]), b = bhi(v[i]); s += a; s_ += b; q = fmaf(a, a, q); q_ = fmaf(b, b, q_); }
    s += s_; q += q_;
    {
        float t = __shfl_xor_sync(0xffffffffu, (lane & 16) ? s : q, 16);
        t += (lane & 16) ? q : s;
#pragma unroll
        for (int m = 8; m; m >>= 1) t += __shfl_xor_sync(0xffffffffu, t, m);
        float o = __shfl_xor_sync(0xffffffffu, t, 16);
        s = (lane & 16) ? o : t; q = (lane & 16) ? t : o;
    }
    float mean = s * (1.0f / D_), inv;
    asm("rsqrt.approx.ftz.f32 %0, %1;" : "=f"(inv) : "f"(fmaxf(fmaf(-mean, mean, fmaf(q, 1.0f / D_, 1e-5f)), 1e-5f)));
    uint3 r;
    r.x = pack2(mean, mean);
    r.y = pack2(inv, inv);
    inv -= blo(r.y);
    r.z = pack2(inv, inv);
    return r;
}
__device__ __forceinline__ uint32_t ln_apply(uint32_t x, uint32_t m, uint32_t hi, uint32_t lo) {
    uint32_t xc = bsub2(x, m);
    return bfma2(xc, hi, bmul2(xc, lo));
}

struct AFrag { uint32_t m, a, b, c, d; };
__device__ __forceinline__ AFrag ldA(uint32_t a) { AFrag f; f.m = lds32(a - 16); f.a = lds32(a); f.b = lds32(a + 16); f.c = lds32(a + 32); f.d = lds32(a + 48); return f; }
template <int N, int M> __device__ __forceinline__ void conv_pair(float* d, const AFrag& f, uint32_t descU) {
    WgRs<N>::template run<8 * M, desc_hi(128, 0), M ? 1 : 0>(d, f.a, f.b, f.m, f.a, descU);
    WgRs<N>::template run<8 * M + 1, desc_hi(128, 0), 1>(d, f.c, f.d, f.b, f.c, descU);
}
template <int Q> __device__ __forceinline__ void conv_put(float* d, uint32_t r0) {
    sts64(r0 + Q * 32, pack2(d[4 * Q + 1], d[4 * Q + 3]), pack2(d[4 * Q], d[4 * Q + 2]));
}
template <int M> __device__ __forceinline__ void conv_two(float* d, AFrag f0, AFrag f1, uint32_t kaddr, uint32_t descU, uint32_t r0, bool handoff) {
    constexpr int N = M < 14 ? 128 - 8 * M : 32;
    wg_fence();
    conv_pair<N, M>(d, f0, descU);
    wg_commit();
    if constexpr (M > 0) f1 = ldA(kaddr + 256 * (M + 1));
    wg_fence();
    conv_pair<N, M + 1>(d, f1, descU);
    wg_commit();
    if (STAG && M == STAG && handoff) bar_arrive(12, 256);
    if constexpr (M < 14) {
        if constexpr (M > 0) { conv_put<17 - M>(d, r0); conv_put<16 - M>(d, r0); }
        wg_wait<1>();
        f0 = ldA(kaddr + 256 * (M + 2));
        if constexpr (M < 12) wg_wait<0>();
        conv_two<M + 2>(d, f0, f1, kaddr, descU, r0, handoff);
    } else {
        wg_wait<0>();
        conv_put<3>(d, r0); conv_put<2>(d, r0); conv_put<1>(d, r0); conv_put<0>(d, r0);
    }
}
template <int N, bool ASWZ, int SC0>
__device__ __forceinline__ void gemm_issue(float* acc, uint32_t bars, int sa, int pa, int sw, int pw, uint32_t da0, uint32_t db0) {
    mbar_wait(bars + (BAR_FB + sw) * 8, pw);
    mbar_wait(bars + (BAR_FA + sa) * 8, pa);
    const uint32_t da = da0 + sa * (SLOT >> 4), db = db0 + sw * (SLOT >> 4);
    constexpr int AK = ASWZ ? 2 : 256, AH = ASWZ ? desc_hi(1024, 1) : desc_hi(128, 0), BH = desc_hi(1024, 1);
    wg_fence();
    WgSs<N>::template run<0, AH, 0, BH, SC0>(acc, da, db);
    WgSs<N>::template run<AK, AH, 128, BH, 1>(acc, da, db);
    WgSs<N>::template run<2 * AK, AH, 256, BH, 1>(acc, da, db);
    WgSs<N>::template run<3 * AK, AH, 384, BH, 1>(acc, da, db);
    wg_commit();
}
template <int N, bool ASWZ, int NKB, int RELB, bool ZERO>
__device__ __forceinline__ void gemm_loop(float* acc, uint32_t sb, int half, int ia0, int ib0, int rela, int wait_bar, int order_bar, int tsid) {
    int sa = ia0 % NA, pa = (ia0 / NA) & 1, sw = ib0 % NB, pw = (ib0 / NB) & 1;
    const uint32_t bars = sb + SM_BAR;
    const int t = threadIdx.x & 127;
    uint32_t ebar = mapa(bars + (t < 2 ? BAR_EB : BAR_EA) * 8, (t < 2 && lds32(sb + SM_GV + 516)) ? t : blockIdx.x & 1);
    const int nrel = t < 2 ? RELB : t == 2 ? rela : 0;
    const uint32_t da0 = ASWZ ? desc_lo(sb + SM_RA + half * 8192, 16) : desc_lo(sb + SM_RA + half * 1024, 2048), db0 = desc_lo(sb + SM_RB, 8192);
    asm volatile("" : "+r"(ebar));
    if (wait_bar) bar_sync(wait_bar, 512);
    gemm_issue<N, ASWZ, ZERO ? 0 : 1>(acc, bars, sa, pa, sw, pw, da0, db0);
    if ((threadIdx.x & 255) == 0) TS(tsid);
#pragma unroll 1
    for (int kb = 1; kb < NKB; kb++) {
        const int prev = t < 2 ? sw : sa;
        if (++sa == NA) { sa = 0; pa ^= 1; }
        if (++sw == NB) { sw = 0; pw ^= 1; }
        gemm_issue<N, ASWZ, 1>(acc, bars, sa, pa, sw, pw, da0, db0);
        if (order_bar && kb == NKB - 1) bar_arrive(order_bar, 512);
        wg_wait<1>();
        if (kb <= nrel) mbar_arrive_cl(ebar + prev * 8);
    }
    wg_wait<0>();
    if (nrel == NKB) mbar_arrive_cl(ebar + (t < 2 ? sw : sa) * 8);
    reg_fence<N / 2>(acc);
    if ((threadIdx.x & 255) == 0) TS(tsid + 1);
}

template <int PART>
__device__ __forceinline__ void gemm3(uint32_t sb, int rb, int j, int half, int row, int c, unsigned ones) {
    constexpr int N = PART ? 104 : 112, NQ = N / 8;
    constexpr int HO = PART ? HO_B : HO_A;
    float acc[N / 2];
    float2 cr[NQ];
    mbar_wait(sb + SM_BAR + BAR_CS * 8, 0);
#pragma unroll
    for (int q = 0; q < NQ; q++) cr[q] = lds64f(sb + SM_CS + PART * 448 + 8 * c + 32 * q);
    uint4 rp;
    if (PART) {
        mbar_wait(sb + SM_BAR + (BAR_FA + 21 % NA) * 8, (21 / NA) & 1);
        const float2* sp = &g_st[(rb * 8 + 2 * c) * 128 + row];
        const uint2 s0 = ldcg64(sp), s1 = ldcg64(sp + 128), s2 = ldcg64(sp + 8), s3 = ldcg64(sp + 136);
        float a0 = __uint_as_float(s0.x) + __uint_as_float(s1.x), b0 = __uint_as_float(s0.y) + __uint_as_float(s1.y);
        float a1 = __uint_as_float(s2.x) + __uint_as_float(s3.x), b1 = __uint_as_float(s2.y) + __uint_as_float(s3.y);
#pragma unroll
        for (int m = 1; m <= 2; m <<= 1) {
            a0 += __shfl_xor_sync(0xffffffffu, a0, m); b0 += __shfl_xor_sync(0xffffffffu, b0, m);
            a1 += __shfl_xor_sync(0xffffffffu, a1, m); b1 += __shfl_xor_sync(0xffffffffu, b1, m);
        }
        const float inv0 = half_rstd(a0, b0), inv1 = half_rstd(a1, b1);
        rp = make_uint4(PGELU ? pack2(inv0, inv0) : __float_as_uint(inv0), __float_as_uint(a0 * (-1.0f / D_)),
                        PGELU ? pack2(inv1, inv1) : __float_as_uint(inv1), __float_as_uint(a1 * (-1.0f / D_)));
        if (c == 0) sts128(sb + SM_RP + ((threadIdx.x & 255) >> 2) * 16, rp);
        bar_arrive(13, 512);
    }
    gemm_loop<N, false, 10, 10, true>(acc, sb, half, 20 + (10 - NA) * PART, 20 + 10 * PART, PART ? 10 : 10 - NA, 9 + PART, HO < 0 ? 10 + PART : 0, 46 + 2 * PART);
    if (!PART) {
        bar_sync(13, 512);
        rp = lds128(sb + SM_RP + ((threadIdx.x & 255) >> 2) * 16);
    }
    const float nb0 = __uint_as_float(rp.y), nb1 = __uint_as_float(rp.w);
    uint32_t* dst = reinterpret_cast<uint32_t*>(g_g) + (rb * 216 + 112 * PART + 8 * j) * 512 + row * 4 + c;
    auto act = [&](int q, int r) {
        const float nb = r ? nb1 : nb0;
        const uint32_t inv = r ? rp.z : rp.x;
        const float t0 = fmaf(nb, cr[q].x, acc[4 * q + 2 * r]), t1 = fmaf(nb, cr[q].y, acc[4 * q + 2 * r + 1]);
        return gelu2_h(bmul2(pack2(t0, t1), inv));
    };
    uint32_t* dst1 = dst + (56 - (16 - NQ) * j) * 512;
#pragma unroll
    for (int k = 0; k < NQ; k += CH3) {
        if (k == HO) bar_arrive(10 + PART, 512);
        CHUNK(k) {
#pragma unroll
            for (int q = k; q < k + CH3 && q < NQ; q++) { (q < 8 ? dst : dst1)[q * 512] = act(q, 0); (q < 8 ? dst : dst1)[q * 512 + 32] = act(q, 1); }
        }
    }
    if (HO >= NQ) bar_arrive(10 + PART, 512);
    bar_arrive(1 + PART, 288);
}

template <int NS, int BASE, int BF, int BE> struct Ring {
    uint32_t sb, st, ph;
    __device__ __forceinline__ uint32_t acquire(uint32_t bytes) {
        mbar_wait(sb + SM_BAR + BE * 8 + st * 8, ph);
        uint32_t fb = sb + SM_BAR + BF * 8 + st * 8;
        mbar_expect(fb, bytes);
        return fb;
    }
    __device__ __forceinline__ uint32_t slot() { return sb + BASE + st * SLOT; }
    __device__ __forceinline__ void next() { if (++st == NS) { st = 0; ph ^= 1; } }
    __device__ __forceinline__ void run2d(const CUtensorMap* m, int c1) {
#pragma unroll 1
        for (int c0 = 64; c0 < D_; c0 += 64) {
            uint32_t fb = acquire(SLOT);
            tma2d(slot(), m, c0, c1, fb);
            next();
        }
    }
    __device__ __forceinline__ void runw(bool paired, int rk, const CUtensorMap* ma, const CUtensorMap* mb, int ca, int cb, int c1, int n, uint32_t bytes) {
        if (paired) {
            const CUtensorMap* m = rk ? mb : ma;
            const int c0 = rk ? cb : ca;
#pragma unroll 1
            for (; n > 0; n--, c1 += 64) {
                uint32_t fb = acquire(bytes);
                tma2d_mc(slot() + 8192 * rk, m, c0, c1, fb);
                next();
            }
        } else {
#pragma unroll 1
            for (; n > 0; n--, c1 += 64) {
                uint32_t fb = acquire(bytes);
                tma2d(slot(), ma, ca, c1, fb);
                tma2d(slot() + 8192, mb, cb, c1, fb);
                next();
            }
        }
    }
    __device__ __forceinline__ void run1d(const char* src, int n) {
#pragma unroll 1
        for (; n > 0; n--) {
            uint32_t fb = acquire(SLOT);
            bulk_g2s(slot(), src, SLOT, fb);
            src += SLOT;
            next();
        }
    }
};

__global__ void __cluster_dims__(2, 1, 1) __launch_bounds__(NTHREADS, 1) fused_kernel(const Params p, const __grid_constant__ Maps maps) {
    extern __shared__ __align__(1024) unsigned char smem_raw[];
    const uint32_t sb = (smem_u32(smem_raw) + 1023u) & ~1023u;
#pragma unroll
    for (int i = 0; i < SEED; i++) asm volatile("{.reg .b32 t; mov.u32 t, %laneid;}");
    const uint32_t bars = sb + SM_BAR;
    const int tid = threadIdx.x, lane = tid & 31;
    unsigned smid;
    asm volatile("mov.u32 %0, %%smid;" : "=r"(smid));
    const bool spare = (smid >> 2) == 30;
    const int cta = smid < 120 ? smid : smid - 4;
    const int pg = cta >> 4, pi = cta & 15;
    const int hb = tid >= 320;
    if (!spare) {
        const unsigned t = tid - 320 * hb, r32 = t / 10u, cc = t - r32 * 10u, row = r32 + 64 * hb;
        const unsigned go = (unsigned)(pi * 128 * 1280 + pg * 160) + row * 1280u + cc * 16u;
        const uint32_t so = sb + (row >> 4) * 32u + row * 160u + cc * 16u;
        const char* kb = (const char*)p.k + go;
        const char* vb = (const char*)p.v + go;
        if (hb) {
            if (tid >= 640 - NBARS) {
                const int i = 639 - tid;
                mbar_init(bars + i * 8, (i >= BAR_EB && i < BAR_K) ? 4 : ((i >= BAR_EA && i < BAR_EB) || i == BAR_XY) ? 2 : 1);
                asm volatile("fence.mbarrier_init.release.cluster;" ::: "memory");
            }
            bar_arrive(14, 640);
            if (B_DELAY) spin(B_DELAY);
        }
        cpasync16(so + SM_PK + 2592, kb, 16);
        cpasync16(so + SM_PV, vb, 16);
        cpasync16(so + SM_PK + 3 * 2592, kb + 32 * 1280, 16);
        cpasync16(so + SM_PV + 2 * 2592, vb + 32 * 1280, 16);
        if (tid < 30) cpasync16(so + SM_PK + 13 * 160, pi ? kb - 3 * 1280 : kb, pi ? 16 : 0);
        asm volatile("cp.async.commit_group;" ::: "memory");
    }
    const int warp = __shfl_sync(0xffffffffu, tid >> 5, 0);
    const int wg = warp >> 2, wq = warp & 3;
    unsigned ep0 = 0;
    if (wg == 4 || spare) ep0 = *(volatile unsigned*)&g_epoch[smid];
#define ep1 (ep0 + 1)

    if (spare) {
        const int sp = smid & 3;
        if (tid == 32) { sts32(sb + SM_GV + 512, smid); asm volatile("fence.release.sync_restrict::shared::cta.cluster;" ::: "memory"); }
        asm volatile("barrier.cluster.arrive.relaxed.aligned;" ::: "memory");
        asm volatile("barrier.cluster.wait.aligned;" ::: "memory");
        if (tid == 0) {
            for (int i = 0; i < 4; i++) mbar_init(bars + i * 8, 1);
            asm volatile("fence.mbarrier_init.release.cluster;" ::: "memory");
        }
        if (warp == 0) { if (lane < 8) flag_wait(FL_P + lane, ep1 * 16); __syncwarp(); }
        __syncthreads();
        const int cq = tid % 54, rg = tid / 54;
        float a[8];
#pragma unroll
        for (int i = 0; i < 8; i++) a[i] = 0.f;
#pragma unroll 1
        for (int it = -4; it < 10; it++) {
            const uint32_t st = sb + (it & 3) * 55296, fb = bars + (it & 3) * 8;
            if (it >= 0) {
                mbar_wait(fb, (it >> 2) & 1);
                if (tid < 432) {
#pragma unroll
                    for (int i = 0; i < 8; i++) {
                        uint4 w = lds128(st + (cq >= 27 ? 27648 - 432 : 0) + (rg * 8 + i) * 432 + cq * 16);
                        a[0] += blo(w.x); a[1] += bhi(w.x); a[2] += blo(w.y); a[3] += bhi(w.y);
                        a[4] += blo(w.z); a[5] += bhi(w.z); a[6] += blo(w.w); a[7] += bhi(w.w);
                    }
                }
                __syncthreads();
            }
            if (it < 6 && warp == 19 && elect()) {
                mbar_expect(fb, 55296);
                tma2d(st, &maps.w3s, sp * 432, (it + 4) * 64, fb);
                tma2d(st + 27648, &maps.w3s, sp * 432 + 216, (it + 4) * 64, fb);
            }
        }
        if (tid < 432) {
            sts128f(sb + rg * 1728 + cq * 32, a[0], a[1], a[2], a[3]);
            sts128f(sb + rg * 1728 + cq * 32 + 16, a[4], a[5], a[6], a[7]);
        }
        __syncthreads();
        if (tid < 432) {
            float s = 0.f;
#pragma unroll
            for (int i = 0; i < 8; i++) s += __uint_as_float(lds32(sb + i * 1728 + tid * 4));
            g_cs[sp * 432 + tid] = s;
        }
        __syncthreads();
        if (tid == 0) { flag_release(FL_CS); g_epoch[smid] = ep1; TS(0); }
        if (warp == 0) TSFLUSH();
        return;
    }

    int gpc, idx;
    if (smid < 64) { gpc = (smid & 15) >> 1; idx = (smid >> 4) * 2 + (smid & 1); }
    else if (smid < 120) { int t = smid - 64; gpc = 1 + (t % 14) / 2; idx = 8 + (t / 14) * 2 + (smid & 1); }
    else { gpc = 0; idx = 8 + (smid - 124); }
    const int rb = 2 * gpc + (idx & 1), j = idx >> 1;
    const int g = lane >> 2, c = lane & 3;
    const int cm = 160 * (j >> 1) + 64 * (j & 1) + ((j & 2) ? 32 : 0), cr = 160 * (j >> 1) + 16 * (j & 1) + ((j & 2) ? 0 : 128);

    {
        if (warp == 5) TSW(61);
        const int w10 = warp - 10 * hb, h = w10 >= 5;
        const int pr = (w10 - 5 * h) * 8 + (lane >> 2), blk = 4 * hb + (lane & 3);
        const int ch = 80 * pg + 2 * pr;
        const uint4 sw = __ldg(reinterpret_cast<const uint4*>(p.shift + ch * 4));
        uint32_t dv = 0;
        if (warp == 9 && lane < 5) dv = __bfloat16_as_ushort(p.ssmD[cta * 5 + lane]);
        if (tid == 512) { sts32(sb + SM_GV + 512, smid); asm volatile("fence.release.sync_restrict::shared::cta.cluster;" ::: "memory"); }
        asm volatile("barrier.cluster.arrive.relaxed.aligned;" ::: "memory");
        if (warp == 11 && lane < 13) prefetch_map(&maps.hn + lane);
        if (wg < 4) {
            const int t = tid & 127, cc = (wg == 3 && t >= 64) ? 4 : wg;
            if (t < 64 || wg == 3) sts128(sb + SM_U + cc * U_STRIDE + ((t >> 5) & 1) * U_PLANE + 2048 + lane * 16, make_uint4(0, 0, 0, 0));
            if ((t & 63) < 4 && (t < 64 || wg == 3)) sts128(sb + SM_K + cc * K_STRIDE + ((t >> 1) & 1) * 4160 + (t & 1) * 16, make_uint4(0, 0, 0, 0));
        }
        if (warp == 9 && lane < 5) sts32(sb + SM_GV + 520 + lane * 4, dv << 16);
        asm volatile("cp.async.wait_group 0;" ::: "memory");
        if (!hb) bar_arrive(12, 640);
        bar_sync(hb ? 12 : 14, 640);
        if (warp == 9) {
            if (SSM_DELAY) spin(SSM_DELAY);
            if (elect()) {
#pragma unroll
                for (int i = 0; i < SSM_N; i++) {
                    mbar_expect(bars + (BAR_K + i) * 8, 4096);
                    bulk_g2s(sb + SM_K + i * K_STRIDE + 32, p.ssmk + (size_t)(cta * 5 + i) * S_, 4096, bars + (BAR_K + i) * 8);
                }
            }
        }
        const uint32_t w0 = prmt(sw.x, sw.z, 0x5410), w1 = prmt(sw.x, sw.z, 0x7632), w2 = prmt(sw.y, sw.w, 0x5410), w3 = prmt(sw.y, sw.w, 0x7632);
        const uint32_t ka = sb + SM_PK + 2592 + blk * 2592 + h * 1280 + pr * 4;
        const uint32_t va = sb + SM_PV + blk * 2592 + h * 1280 + pr * 4;
        uint32_t kk[11], kv[8];
#pragma unroll
        for (int i = 0; i < 11; i++) kk[i] = lds32(ka + (i - 3) * 160 - ((i < 3 && h == 0) ? 32 : 0));
#pragma unroll
        for (int i = 0; i < 8; i++) {
            uint32_t t = badd2(badd2(badd2(bmul2(kk[i], w3), bmul2(kk[i + 1], w2)), bmul2(kk[i + 2], w1)), bmul2(kk[i + 3], w0));
            kv[i] = bmul2(t, lds32(va + i * 160));
        }
        uint4 o0, o1;
        o0.x = prmt(kv[1], kv[0], 0x5410); o0.y = prmt(kv[3], kv[2], 0x5410); o0.z = prmt(kv[5], kv[4], 0x5410); o0.w = prmt(kv[7], kv[6], 0x5410);
        o1.x = prmt(kv[1], kv[0], 0x7632); o1.y = prmt(kv[3], kv[2], 0x7632); o1.z = prmt(kv[5], kv[4], 0x7632); o1.w = prmt(kv[7], kv[6], 0x7632);
        uint4* dst = reinterpret_cast<uint4*>(g_kvT) + ch * 256 + h * 128 + (127 - (8 * pi + blk));
        dst[0] = o0;
        dst[256] = o1;
    }

    const int rho = 8 * rb + j;

    if (wg == 4) {
        asm volatile("setmaxnreg.dec.sync.aligned.u32 32;");
        if (wq == 0) {
            bar_sync(13, 640);
            TSW(39);
            if (lane == 0) flag_release(FL_P + pg);
            __syncwarp();
            TSW(2);
            if (lane < 5) mbar_expect(bars + (BAR_U + lane) * 8, 4096);
            flag_wait_fast(FL_P + pg, ep1 * 16);
            fence_async_global();
            TSW(3);
            if (elect()) {
#pragma unroll
                for (int i = 0; i < 5; i++) {
                    const char* us = (const char*)g_kvT + (size_t)(cta * 5 + i) * 4096;
                    bulk_g2s(sb + SM_U + i * U_STRIDE, us, 2048, bars + (BAR_U + i) * 8);
                    bulk_g2s(sb + SM_U + i * U_STRIDE + U_PLANE, us + 2048, 2048, bars + (BAR_U + i) * 8);
                }
            }
            __syncwarp();
            if (elect()) {
#pragma unroll
                for (int i = SSM_N; i < 5; i++) {
                    mbar_expect(bars + (BAR_K + i) * 8, 4096);
                    bulk_g2s(sb + SM_K + i * K_STRIDE + 32, p.ssmk + (size_t)(cta * 5 + i) * S_, 4096, bars + (BAR_K + i) * 8);
                }
                if (cta < 120) {
                    mbar_expect(bars + BAR_WM * 8, 40960);
#pragma unroll
                    for (int i = 0; i < 5; i++) tma2d(sb + SM_WM + i * 8192, &maps.wm, cta * 32, i * 128, bars + BAR_WM * 8);
                }
                bulk_prefetch((const char*)p.q + cta * 20480, 20480);
                bulk_prefetch((const char*)p.w1 + cta * 6400, 6400);
                bulk_prefetch((const char*)p.w2 + cta * 6400, 6400);
            }
            __syncwarp();
        } else {
            bar_arrive(13, 640);
        }
        asm volatile("barrier.cluster.wait.aligned;" ::: "memory");
        uint32_t peer;
        asm volatile("ld.shared::cluster.u32 %0, [%1];" : "=r"(peer) : "r"(mapa(sb + SM_GV + 512, (blockIdx.x & 1) ^ 1)) : "memory");
        const bool paired = peer == (smid ^ 1);
        if (tid == 639) sts32(sb + SM_GV + 516, paired);
        if (cta < 120) {
            float d[4];
            if (tid < 592) {
                const int t = tid - 512;
                mbar_wait(bars + BAR_U * 8, 0);
                uint4 cv = __ldg(reinterpret_cast<const uint4*>(p.c) + t);
                auto silu2 = [](uint32_t v) { float a = blo(v), b = bhi(v); return pack2(__fdividef(a, 1.0f + __expf(-a)), __fdividef(b, 1.0f + __expf(-b))); };
                sts128(sb + SM_Y + (t % 40) * 32 + (t / 40) * 16, make_uint4(silu2(cv.x), silu2(cv.y), silu2(cv.z), silu2(cv.w)));
                fence_async_smem();
            }
            bar_sync(5, 128);
            mbar_wait(bars + BAR_WM * 8, 0);
            if (wq == 3) TSW(56);
            const uint32_t da = desc_lo(sb + SM_WM, 20480), db = desc_lo(sb + SM_Y, 32);
            wg_fence();
#pragma unroll
            for (int k = 0; k < 20; k++)
                asm volatile("{.reg .pred p; .reg .b32 l,m; .reg .b64 da,db; setp.ne.b32 p,%10,0; add.u32 l,%4,%6; mov.b64 da,{l,%8}; add.u32 m,%5,%7; mov.b64 db,{m,%9};"
                             " wgmma.mma_async.sync.aligned.m64n8k16.f32.bf16.bf16 {%0,%1,%2,%3},da,db,p,1,1,1,0;}"
                             : "+f"(d[0]), "+f"(d[1]), "+f"(d[2]), "+f"(d[3])
                             : "r"(da), "r"(db), "r"(64 * k), "r"(4 * k), "n"(desc_hi(512, 2u)), "n"(desc_hi(128, 0)), "r"(k));
            wg_commit();
            wg_wait<0>();
            reg_fence<4>(d);
            if (c == 0) {
                sts32(sb + SM_GV + (16 * wq + g) * 4, __float_as_uint(wq < 2 ? d[0] : d[1]));
                sts32(sb + SM_GV + (16 * wq + g + 8) * 4, __float_as_uint(wq < 2 ? d[2] : d[3]));
            }
            bar_sync(5, 128);
            if (wq == 2) {
                g_mod[cta * 32 + lane] = __float2bfloat16_rn(__uint_as_float(lds32(sb + SM_GV + lane * 4)) + __uint_as_float(lds32(sb + SM_GV + 128 + lane * 4)));
                __syncwarp();
                if (lane == 0) flag_release(FL_M);
                TSW(4);
            }
        }
        if (wq == 2) {
            bar_arrive(7, 640);
            flag_wait(FL_M, ep1 * 120);
            fence_async_global();
            if (elect()) {
                mbar_expect(bars + BAR_M * 8, 7680);
                bulk_g2s(sb + SM_MOD, g_mod, 7680, bars + BAR_M * 8);
            }
            __syncwarp();
            TSW(60);
            bar_sync(8, 544);  if (lane == 0) { flag_release(FL_R + rb); TS(23); }  __syncwarp();
            bar_sync(15, 288); if (lane == 0) { flag_release(FL_B1 + rb); TS(27); } __syncwarp();
            bar_sync(6, 288);  if (lane == 0) { flag_release(FL_B2 + rb); TS(31); } __syncwarp();
#pragma unroll 1
            for (int i = 0; i < 2; i++) { bar_sync(1 + i, 288); if (lane == 0) { TS(53 + i); flag_release(FL_G + 16 * i + rb); TS(57 + i); } __syncwarp(); }
            if (lane == 0) g_epoch[smid] = ep1;
            return;
        }
        bar_sync(7, 640);
        if (wq == 3) {
            if (lane == 0) { flag_release(FL_C); TS(20); }
            __syncwarp();
            bar_arrive(10, 544);
            if (lane < 2) mbar_expect(bars + (lane ? BAR_Y2 : BAR_Y) * 8, lane ? 8192 : 12288);
            flag_wait_fast(FL_C, ep1 * 128);
            fence_async_global();
            TSW(21);
            if (elect()) {
                bulk_g2s(sb + SM_Y, g_yv + rho * 5120, 12288, bars + BAR_Y * 8);
                bulk_g2s(sb + SM_Y + 12288, g_yv + rho * 5120 + 3072, 8192, bars + BAR_Y2 * 8);
            }
            __syncwarp();
            bar_arrive(9, 96);
        } else bar_sync(9, 96);
        if (wq == 1 && lane < 4 * NB) mbar_arrive_cl(mapa(bars + (BAR_EB + (lane >> 2)) * 8, paired ? lane & 1 : blockIdx.x & 1));
        if (elect()) {
            if (wq == 3) {
                mbar_expect(bars + BAR_XY * 8, 20480);
#pragma unroll 1
                for (int i = 0; i < 8; i++) {
                    bulk_g2s(sb + SM_YT + i * 2560, g_yv + (8 * rb + i) * 5120 + cm * 8, 2048, bars + BAR_XY * 8);
                    bulk_g2s(sb + SM_YT + i * 2560 + 2048, g_yv + (8 * rb + i) * 5120 + cr * 8, 512, bars + BAR_XY * 8);
                }
                mbar_wait(bars + BAR_FA * 8, 0);
                bulk_prefetch((const char*)p.w4 + cta * 17280, 17280);
                flag_wait(FL_CS, ep1 * 4);
                fence_async_global();
                mbar_expect(bars + BAR_CS * 8, 864);
                bulk_g2s(sb + SM_CS, g_cs + 64 * j, 256, bars + BAR_CS * 8);
                bulk_g2s(sb + SM_CS + 256, g_cs + 512 + 48 * j, 192, bars + BAR_CS * 8);
                bulk_g2s(sb + SM_CS + 448, g_cs + 896 + 64 * j, 256, bars + BAR_CS * 8);
                bulk_g2s(sb + SM_CS + 704, g_cs + 1408 + 40 * j, 160, bars + BAR_CS * 8);
                mbar_wait(bars + BAR_ST * 8, 0);
#pragma unroll 1
                for (int i = 0; i < 2; i++) {
                    flag_wait(FL_G + 16 * i + rb, ep1 * 8);
                    mbar_expect(bars + (BAR_G + i) * 8, 0);
                    TS(35 + i);
                }
            } else if (wq == 1) {
                Ring<NB, SM_RB, BAR_FB, BAR_EB> r{sb, 0, 0};
#pragma unroll 1
                for (int ph = 0; ph < 6; ph++) {
                    const CUtensorMap* ma = ph == 0 ? &maps.w1a : ph == 1 ? &maps.w2a : ph == 5 ? &maps.w4a : &maps.w3a;
                    const bool b3b = ph == 3 || ph == 4;
                    r.runw(paired, idx & 1, ma, ma + (b3b ? 2 : 1), ph == 2 ? 64 * j : b3b ? 896 + 64 * j : cm,
                           ph == 2 ? 512 + 48 * j : b3b ? 1408 + 40 * j : cr, ph == 3 ? (10 - NA) * 64 : 0,
                           ph == 5 ? 27 : ph == 3 ? NA : ph == 4 ? 10 - NA : 10, ph == 2 ? 14336 : b3b ? 13312 : 10240);
                }
            } else {
                Ring<NA, SM_RA, BAR_FA, BAR_EA> r{sb, 0, 0};
                mbar_expect(bars + BAR_XY * 8, 20480);
                tma2d(sb + SM_XT, &maps.xa, cm, rb * 128, bars + BAR_XY * 8);
                tma2d(sb + SM_XT2, &maps.xb, cr, rb * 128, bars + BAR_XY * 8);
                const int grp = j >> 1;
                const int delta = (grp & 1 ? 1 : -1) * (1 + (grp >> 1));
                const int nb = min(max(rb + (delta > 0 ? 1 : -1), 0), 15);
                uint32_t fb = r.acquire(SLOT), dst = r.slot();
                flag_wait2(FL_R + nb, FL_R + rb, ep1 * 8);
                fence_async_global();
                tma2d(dst, &maps.hn, 0, rb * 128 + delta, fb);
                TS(24);
                r.next();
                r.run2d(&maps.hn, rb * 128 + delta);
#pragma unroll 1
                for (int i = 0; i < 2; i++) {
                    const char* src = (const char*)(i ? g_x1 : g_h1) + (size_t)rb * 163840;
                    fb = r.acquire(SLOT); dst = r.slot();
                    flag_wait_fast(FL_B1 + 16 * i + rb, ep1 * 8);
                    fence_async_global();
                    bulk_g2s(dst, src, SLOT, fb);
                    TS(28 + 4 * i);
                    if (i) mbar_expect(bars + BAR_ST * 8, 0);
                    r.next();
                    r.run1d(src + SLOT, 9);
                }
                r.run1d((const char*)g_x1 + (size_t)rb * 163840, 10 - NA);
#pragma unroll 1
                for (int i = 0; i < 2; i++) {
                    mbar_wait(bars + (BAR_G + i) * 8, 0); fence_async_global();
                    r.run1d((const char*)g_g + (size_t)rb * 442368 + i * 14 * SLOT, 14 - i);
                }
            }
        }
        return;
    }
    bar_arrive(13, 640);
    asm volatile("setmaxnreg.inc.sync.aligned.u32 112;");
    const int rrow = 16 * rho + (warp >> 1) + 8 * (warp & 1);

    fence_async_smem();
    bar_sync(1 + wg, 128);
#pragma unroll 1
    for (int cc = wg; cc < wg + 1 + (wg == 3); cc++) {
        mbar_wait(bars + (BAR_K + cc) * 8, 0);
        if (cc == 2 && wq == 0) TSW(40);
        uint32_t a = sb + SM_K + cc * K_STRIDE + 32 + (tid & 127) * 32;
        uint32_t pw = lds32(a - 4);
        uint4 x = lds128(a), y = lds128(a + 16), o;
        if ((tid & 127) == 0) {
            uint16_t k0 = __bfloat16_as_ushort(__float2bfloat16_rn(blo(x.x) + __uint_as_float(lds32(sb + SM_GV + 520 + cc * 4))));
            x.x = (x.x & 0xffff0000u) | k0;
            sts16(a, k0);
        }
        o.x = prmt(pw, x.x, 0x5432); o.y = prmt(x.x, x.y, 0x5432); o.z = prmt(x.y, x.z, 0x5432); o.w = prmt(x.z, x.w, 0x5432);
        sts128(a + 4160, o);
        o.x = prmt(x.w, y.x, 0x5432); o.y = prmt(y.x, y.y, 0x5432); o.z = prmt(y.y, y.z, 0x5432); o.w = prmt(y.z, y.w, 0x5432);
        sts128(a + 4176, o);
    }
    bar_sync(1 + wg, 128);
    if (wg == 3) bar_arrive(11, 256);
#pragma unroll 1
    for (int cc = wg; cc < 5; cc += 3) {
        if (cc == 3 && wg == 0) break;
        if (cc == 4) bar_sync(11, 256);
        const uint32_t kaddr = sb + SM_K + cc * K_STRIDE + ((g & 1) ? 32 : 4192) + 4 * ((g >> 1) - c) + 64 * wq;
        const AFrag f0 = ldA(kaddr), f1 = ldA(kaddr + 256);
        if (STAG && cc == 3) bar_sync(12, 256);
        mbar_wait(bars + (BAR_U + cc) * 8, 0);
        if (wq == 0) TSW(5 + cc);
        float d[64];
        conv_two<0>(d, f0, f1, kaddr, desc_lo(sb + SM_U + cc * U_STRIDE, U_PLANE), sb + SM_RED + cc * RED_STRIDE + wq * 4352 + g * 544 + c * 8, cc == 1);
        if (wq == 0) TSW(10 + cc);
        if (cc == 1) bar_arrive(6, 256);
    }
#pragma unroll 1
    for (int cc = wg == 1 ? 4 : wg;; cc++) {
        if (cc == 1) bar_sync(6, 256); else bar_sync(1 + wg, 128);
        const int ch = cta * 5 + cc;
        uint32_t* dst = g_yv + ch * 8 + ((g + (ch >> 2)) & 7) + (126 - 32 * wq - 2 * c) * 5120;
        uint2 v[16];
#pragma unroll
        for (int i = 0; i < 16; i++) v[i] = lds64(sb + SM_RED + cc * RED_STRIDE + g * 544 + wq * 128 + c * 8 + (i >> 2) * 32 + (i & 3) * 4360);
#pragma unroll
        for (int w = 1; w < 4; w++)
            if (wq == 3 && c > 3 - w) v[12 + w] = make_uint2(0, 0);
#pragma unroll
        for (int q = 0; q < 4; q++) {
            const uint2* u = v + 4 * q;
            dst[-8 * q * 5120] = badd2(u[0].x, badd2(u[1].x, badd2(u[2].x, u[3].x)));
            dst[(-8 * q + 1) * 5120] = badd2(u[0].y, badd2(u[1].y, badd2(u[2].y, u[3].y)));
        }
        if (wq == 0) TSW(15 + cc);
        if (cc != 0) break;
    }
    fence_async_smem();
    bar_arrive(7, 640);

    const uint32_t one2 = 0x3f803f80u;
    const unsigned ones = p.ones;
    {
        uint32_t x[10], a[10], cb[10], sbv[10];
        const uint32_t* xr = reinterpret_cast<const uint32_t*>(p.q + (size_t)rrow * D_) + lane;
        bar_sync(10, 544);
#pragma unroll
        for (int i = 0; i < 10; i++) x[i] = __ldg(xr + 32 * i);
        const uint3 s1 = row_stats(x, lane);
        const int up = lane >> 4, gg = warp >> 1, e = warp & 1;
        const uint32_t ya = sb + SM_Y + lane * 64 + ((gg + (lane >> 1)) & 7) * 4;
        const uint32_t sel = (up ? 0x1054u : 0x5410u) + (e ? 0x2222u : 0u);
        const uint32_t ma = sb + SM_MOD + lane * 4;
        mbar_wait(bars + BAR_M * 8, 0);
#pragma unroll
        for (int i = 0; i < 10; i++) {
            uint32_t h = bfma2(ln_apply(x[i], s1.x, s1.y, s1.z), badd2(lds32(ma + 1280 + i * 128), one2), lds32(ma + i * 128));
            a[i] = bmul2(h, lds32(ma + 2560 + i * 128));
            sbv[i] = lds32(ma + 3840 + i * 128);
            cb[i] = badd2(lds32(ma + 5120 + i * 128), one2);
        }
        if (warp == 4) TSW(52);
        mbar_wait(bars + BAR_Y * 8, 0);
        if (warp == 0) TSW(22);
#pragma unroll
        for (int i = 0; i < 10; i++) {
            if (i == 6) mbar_wait(bars + BAR_Y2 * 8, 0);
            uint32_t y0 = lds32(ya + i * 2048 + up * 32), y1 = lds32(ya + i * 2048 + (up ^ 1) * 32);
            x[i] = bfma2(a[i], prmt(y0, y1, sel), x[i]);
        }
        const uint3 s2 = row_stats(x, lane);
#pragma unroll
        for (int i = 0; i < 10; i++) x[i] = bfma2(ln_apply(x[i], s2.x, s2.y, s2.z), cb[i], sbv[i]);
        const uint3 s3 = row_stats(x, lane);
        uint32_t* o = reinterpret_cast<uint32_t*>(g_hn + (size_t)rrow * D_) + lane;
#pragma unroll
        for (int i = 0; i < 10; i++) o[32 * i] = ln_apply(x[i], s3.x, s3.y, s3.z);
        if (lane < 2) g_rs[rrow * 2 + lane] = lane ? make_uint4(s2.x, s2.y, s2.z, 0) : make_uint4(s1.x, s1.y, s1.z, 0);
        if (warp == 0) TSW(34);
        bar_arrive(8, 544);
    }

    const int half = wg & 1;
    const int row = 64 * half + 16 * wq + g;
    const int tw0 = (rb * 80 + (cm >> 3)) * 512 + row * 4 + c, tw1 = (rb * 80 + (cr >> 3) - 8) * 512 + row * 4 + c;
    const uint32_t park = sb + SM_Y + (tid & 255) * 16;
    const uint32_t ms0 = sb + SM_MOD + (cm + 2 * c) * 2, ms1 = sb + SM_MOD + (cr - 64 + 2 * c) * 2;
    if (wg >= 2) {
        {
            float acc[40];
            gemm_loop<80, true, 10, 10, true>(acc, sb, half, 0, 0, 10, 0, 0, 25);
#pragma unroll
            for (int k = 0; k < 10; k += CH) CHUNK(k) {
#pragma unroll
                for (int q = k; q < k + CH && q < 10; q++) {
                    uint32_t* dst = reinterpret_cast<uint32_t*>(g_h1) + (q < 8 ? tw0 : tw1);
                    dst[q * 512] = gelu2_h(bmul2(pack2(acc[4 * q], acc[4 * q + 1]), 0x3f003f00u));
                    dst[q * 512 + 32] = gelu2_h(bmul2(pack2(acc[4 * q + 2], acc[4 * q + 3]), 0x3f003f00u));
                }
            }
            bar_arrive(15, 288);
            bar_arrive(14, 512);
        }
        gemm3<0>(sb, rb, j, half, row, c, ones);
        {
            float acc[40];
            uint32_t gbv[10], base[20];
#pragma unroll
            for (int q = 0; q < 10; q++) gbv[q] = lds32((q < 8 ? ms0 : ms1) + 6400 + q * 16);
#pragma unroll
            for (int q = 0; q < 5; q++) { const uint4 t = lds128(park + q * 4096); base[4 * q] = t.x; base[4 * q + 1] = t.y; base[4 * q + 2] = t.z; base[4 * q + 3] = t.w; }
            gemm_loop<80, false, 27, 27 - NB, true>(acc, sb, half, 40 - NA, 40, 27 - NA, 11, 0, 42);
            auto fin = [&](int q, int r) {
                return bfma2(gbv[q], pack2(acc[4 * q + 2 * r], acc[4 * q + 2 * r + 1]), base[2 * q + r]);
            };
            auto tr4 = [&](uint32_t t0, uint32_t t1, uint32_t t2, uint32_t t3) {
                const bool o1 = c & 1, o2 = c & 2;
                uint32_t a = __shfl_xor_sync(0xffffffffu, o1 ? t0 : t1, 1), b = __shfl_xor_sync(0xffffffffu, o1 ? t2 : t3, 1);
                uint32_t u0 = o1 ? a : t0, u1 = o1 ? t1 : a, u2 = o1 ? b : t2, u3 = o1 ? t3 : b;
                a = __shfl_xor_sync(0xffffffffu, o2 ? u0 : u2, 2); b = __shfl_xor_sync(0xffffffffu, o2 ? u1 : u3, 2);
                return o2 ? make_uint4(a, b, u2, u3) : make_uint4(u0, u1, a, b);
            };
            bf16* go = p.out + (size_t)(rb * 128 + row) * D_;
#pragma unroll
            for (int k = 0; k < 2; k++) CHUNK(k) {
#pragma unroll
                for (int r = 0; r < 2; r++)
                    *reinterpret_cast<uint4*>(go + r * 8 * D_ + cm + 32 * k + 8 * c) = tr4(fin(4 * k, r), fin(4 * k + 1, r), fin(4 * k + 2, r), fin(4 * k + 3, r));
            }
            CHUNK(2) *reinterpret_cast<uint4*>(go + (c >> 1) * 8 * D_ + cr + 8 * (c & 1)) = tr4(fin(8, 0), fin(9, 0), fin(8, 1), fin(9, 1));
            if (tid == 256) TS(44);
            if (warp == 8) TSFLUSH();
        }
    } else {
        {
            float acc[40];
            uint32_t x2[20];
            {
                uint32_t y[20];
                mbar_wait(bars + BAR_XY * 8, 0);
                const uint32_t xa = sb + SM_XT + row * 128 + c * 4, xb = sb + SM_XT2 + row * 32 + c * 4;
                const uint32_t ya = sb + SM_YT + (4 * half + wq) * 2560 + c * 64;
#pragma unroll
                for (int q = 0; q < 10; q++) {
                    const uint32_t a = q < 8 ? xa + ((q ^ g) << 4) : xb + (q - 8) * 16;
                    x2[2 * q] = lds32(a); x2[2 * q + 1] = lds32(a + (q < 8 ? 1024 : 256));
                    const int pos = (g + ((q < 8 ? cm : cr) >> 2) + 2 * q + (c >> 1)) & 7;
                    y[2 * q] = lds32(ya + q * 256 + pos * 4); y[2 * q + 1] = lds32(ya + q * 256 + 32 + pos * 4);
                }
                fence_async_smem();
                bar_sync(1 + wg, 128);
                if ((tid & 127) < NA) mbar_arrive_cl(mapa(bars + (BAR_EA + (tid & 127)) * 8, blockIdx.x & 1));
                mbar_wait(bars + (BAR_FA + 1) * 8, 0);
                const uint4* rp = g_rs + (rb * 128 + row) * 2;
                const uint4 ra = ldcg128(rp), rb2 = ldcg128(rp + 1), rc = ldcg128(rp + 16), rd = ldcg128(rp + 17);
                bar_sync(14, 512);
#pragma unroll
                for (int q = 0; q < 10; q++) {
                    const uint32_t ms = q < 8 ? ms0 : ms1;
                    const uint32_t sa = lds32(ms + 16 * q), ca = badd2(lds32(ms + 1280 + 16 * q), one2), ga = lds32(ms + 2560 + 16 * q);
                    const uint32_t sbv = lds32(ms + 3840 + 16 * q), cb = badd2(lds32(ms + 5120 + 16 * q), one2);
                    uint32_t u = x2[2 * q], v = x2[2 * q + 1];
                    u = bfma2(bmul2(bfma2(ln_apply(u, ra.x, ra.y, ra.z), ca, sa), ga), prmt(y[2 * q], y[2 * q + 1], 0x5410), u);
                    v = bfma2(bmul2(bfma2(ln_apply(v, rc.x, rc.y, rc.z), ca, sa), ga), prmt(y[2 * q], y[2 * q + 1], 0x7632), v);
                    x2[2 * q] = u; x2[2 * q + 1] = v;
                    u = bfma2(ln_apply(u, rb2.x, rb2.y, rb2.z), cb, sbv);
                    v = bfma2(ln_apply(v, rd.x, rd.y, rd.z), cb, sbv);
                    acc[4 * q] = blo(u); acc[4 * q + 1] = bhi(u); acc[4 * q + 2] = blo(v); acc[4 * q + 3] = bhi(v);
                }
            }
            reg_fence<40>(acc);
            if (tid == 0) TS(45);
            gemm_loop<80, false, 10, 10, false>(acc, sb, half, 10, 10, 10, 0, 9, 29);
            uint32_t x1[20];
            float s0 = 0.f, q0 = 0.f, s1 = 0.f, q1 = 0.f;
#pragma unroll
            for (int q = 0; q < 10; q++) {
                uint32_t u = pack2(acc[4 * q], acc[4 * q + 1]);
                uint32_t v = pack2(acc[4 * q + 2], acc[4 * q + 3]);
                uint32_t* dst = reinterpret_cast<uint32_t*>(g_x1) + (q < 8 ? tw0 : tw1);
                dst[q * 512] = u;
                dst[q * 512 + 32] = v;
                x1[2 * q] = u; x1[2 * q + 1] = v;
            }
            CHUNK(0)
#pragma unroll
            for (int q = 0; q < 10; q++) {
                float a = blo(x1[2 * q]), b = bhi(x1[2 * q]), e = blo(x1[2 * q + 1]), f = bhi(x1[2 * q + 1]);
                s0 += a + b; q0 = fmaf(a, a, fmaf(b, b, q0));
                s1 += e + f; q1 = fmaf(e, e, fmaf(f, f, q1));
            }
#pragma unroll
            for (int m = 1; m <= 2; m <<= 1) {
                s0 += __shfl_xor_sync(0xffffffffu, s0, m); q0 += __shfl_xor_sync(0xffffffffu, q0, m);
                s1 += __shfl_xor_sync(0xffffffffu, s1, m); q1 += __shfl_xor_sync(0xffffffffu, q1, m);
            }
            if (c < 2) g_st[(rb * 8 + j) * 128 + row + 8 * c] = c ? make_float2(s1, q1) : make_float2(s0, q0);
            bar_arrive(6, 288);
#pragma unroll
            for (int q = 0; q < 5; q++) {
                const uint32_t ms = q < 4 ? ms0 : ms1;
                const uint32_t g0 = lds32(ms + 6400 + q * 32), g1 = lds32(ms + 6400 + q * 32 + 16);
                sts128(park + q * 4096, make_uint4(bfma2(g0, x1[4 * q], x2[4 * q]), bfma2(g0, x1[4 * q + 1], x2[4 * q + 1]),
                                                   bfma2(g1, x1[4 * q + 2], x2[4 * q + 2]), bfma2(g1, x1[4 * q + 3], x2[4 * q + 3])));
            }
        }
        gemm3<1>(sb, rb, j, half, row, c, ones);
    }
}

typedef CUresult (*EncFn)(CUtensorMap*, CUtensorMapDataType, cuuint32_t, void*, const cuuint64_t*, const cuuint64_t*,
                          const cuuint32_t*, const cuuint32_t*, CUtensorMapInterleave, CUtensorMapSwizzle,
                          CUtensorMapL2promotion, CUtensorMapFloatOOBfill);

void make_map(EncFn enc, CUtensorMap* m, const void* base, uint64_t inner, uint64_t outer, uint32_t bi, uint32_t bo,
              CUtensorMapSwizzle swz = CU_TENSOR_MAP_SWIZZLE_128B) {
    cuuint64_t dims[2] = {inner, outer};
    cuuint64_t st[1] = {inner * 2};
    cuuint32_t box[2] = {bi, bo};
    cuuint32_t es[2] = {1, 1};
    enc(m, CU_TENSOR_MAP_DATA_TYPE_BFLOAT16, 2, const_cast<void*>(base), dims, st, box, es, CU_TENSOR_MAP_INTERLEAVE_NONE,
        swz, CU_TENSOR_MAP_L2_PROMOTION_NONE, CU_TENSOR_MAP_FLOAT_OOB_FILL_NONE);
}

}

extern "C" void kernel_launch(void* const* d_in, const int* in_sizes, int n_in, void* d_out, int out_size) {
    (void)in_sizes; (void)n_in; (void)out_size;
    Params p;
    p.q = (const bf16*)d_in[0]; p.k = (const bf16*)d_in[1]; p.v = (const bf16*)d_in[2];
    p.shift = (const bf16*)d_in[3]; p.ssmk = (const bf16*)d_in[4]; p.ssmD = (const bf16*)d_in[5];
    p.w1 = (const bf16*)d_in[7]; p.w2 = (const bf16*)d_in[8]; p.w3 = (const bf16*)d_in[9]; p.w4 = (const bf16*)d_in[10];
    p.c = (const bf16*)d_in[11]; p.wmod = (const bf16*)d_in[12];
    p.out = (bf16*)d_out;
    p.ones = 0xffffffffu;

    void* fn = nullptr;
    cudaDriverEntryPointQueryResult qr;
    cudaGetDriverEntryPoint("cuTensorMapEncodeTiled", &fn, cudaEnableDefault, &qr);
    EncFn enc = (EncFn)fn;
    void* hn = nullptr;
    cudaGetSymbolAddress(&hn, g_hn);
    Maps maps;
    make_map(enc, &maps.w3s, p.w3, F_, D_, 216, 64, CU_TENSOR_MAP_SWIZZLE_NONE);
    make_map(enc, &maps.wm, p.wmod, 6 * D_, D_, 32, 128, CU_TENSOR_MAP_SWIZZLE_64B);
    make_map(enc, &maps.xa, p.q, D_, S_, 64, 128);
    make_map(enc, &maps.xb, p.q, D_, S_, 16, 128, CU_TENSOR_MAP_SWIZZLE_NONE);
    make_map(enc, &maps.hn, hn, D_, S_, 64, 128);
    make_map(enc, &maps.w1a, p.w1, D_, D_, 64, 64);
    make_map(enc, &maps.w1b, p.w1, D_, D_, 16, 64);
    make_map(enc, &maps.w2a, p.w2, D_, D_, 64, 64);
    make_map(enc, &maps.w2b, p.w2, D_, D_, 16, 64);
    make_map(enc, &maps.w3a, p.w3, F_, D_, 64, 64);
    make_map(enc, &maps.w3b, p.w3, F_, D_, 48, 64);
    make_map(enc, &maps.w3c, p.w3, F_, D_, 40, 64);
    make_map(enc, &maps.w4a, p.w4, D_, F_, 64, 64);
    make_map(enc, &maps.w4b, p.w4, D_, F_, 16, 64);
    cudaFuncSetAttribute(fused_kernel, cudaFuncAttributeMaxDynamicSharedMemorySize, SMEM_BYTES);
    fused_kernel<<<132, NTHREADS, SMEM_BYTES>>>(p, maps);
}
```

```cpp
#include <cuda_runtime.h>
#include <cuda_bf16.h>
#include <cuda.h>
#include <stdint.h>
#include <string.h>

#define SEED 0
#define RING_A 6
#define MMA_STAT 0
#define CH 2
#define FAST_LN 1
#define STAG 10
#define REDM 1
#define CONVV 0
#define NPOLL 1
#define PGELU 2
#define CH3 4
#define HO_A 14
#define HO_B 14
#define LATE 0
#define HOLD 1
#define SSM_DELAY 0
#define B_DELAY 300
#define RPRE_WAIT 1
#define SSM_N 3
#define PF_EARLY 0

namespace {

typedef __nv_bfloat16 bf16;
typedef __nv_bfloat162 bf162;

constexpr int S_ = 2048, D_ = 640, F_ = 1728;
constexpr int NTHREADS = 640;
constexpr int NA = RING_A, NB = 12 - RING_A;
constexpr int SLOT = 16384;
constexpr int SM_RA = 0, SM_RB = NA * SLOT;

static_assert(NA == 6, "smem map");
constexpr int RED_STRIDE = 17536;
constexpr int K_STRIDE = 8320;
constexpr int U_PLANE = 2560, U_STRIDE = 5120;
constexpr int SM_Y = 12 * SLOT;
__device__ __forceinline__ int sm_red(int cc) { return cc * RED_STRIDE + (cc < 3 ? SM_RB : -3 * RED_STRIDE); }
__device__ __forceinline__ int sm_k(int cc) { return cc * K_STRIDE + (cc < 3 ? SM_RB + 3 * RED_STRIDE : 2 * RED_STRIDE - 3 * K_STRIDE); }
__device__ __forceinline__ int sm_u(int cc) { return cc * U_STRIDE + (cc < 3 ? SM_RB + 3 * RED_STRIDE + 3 * K_STRIDE : SM_Y + 8192 - 3 * U_STRIDE); }
constexpr int SM_PK = SM_RB;
constexpr int SM_PV = SM_RB + 24576;
constexpr int SM_WM = 57344;
constexpr int SM_XT = SM_WM, SM_XT2 = SM_WM + 16384, SM_XR = SM_WM + 20480;
constexpr int SM_YT = 0;
constexpr int SM_MOD = SM_Y + 20480;
constexpr int SM_GV = SM_MOD + 7680;
constexpr int SM_CS = SM_GV + 1024;
constexpr int SM_RP = SM_CS + 1024;
constexpr int SM_BAR = SM_RP + 1024;
constexpr int SM_PROF = SM_BAR + 512;
constexpr int SM_TOTAL = SM_PROF + 512;
constexpr int SMEM_BYTES = SM_TOTAL + 1024;
static_assert(SMEM_BYTES <= 232448, "smem");

constexpr int BAR_FA = 0, BAR_FB = NA, BAR_EA = 12, BAR_EB = 12 + NA, BAR_K = 24, BAR_U = 29, BAR_Y = 34, BAR_CS = 35, BAR_WM = 36, BAR_M = 37, BAR_XY = 38, BAR_Y2 = 39, BAR_G = 40, BAR_ST = 43, BAR_XR = 44, NBARS = 45;

__device__ __align__(1024) bf16 g_kvT[D_ * S_];
__device__ __align__(1024) uint32_t g_yv[128 * 5120];
__device__ __align__(1024) bf16 g_mod[6 * D_];
__device__ __align__(1024) bf16 g_hn[S_ * D_];
__device__ __align__(1024) uint4 g_rs[S_ * 2];
__device__ __align__(1024) bf16 g_h1[S_ * D_];
__device__ __align__(1024) bf16 g_x1[S_ * D_];
__device__ __align__(1024) bf16 g_g[S_ * F_];
__device__ __align__(1024) float2 g_st[S_ * 8];
__device__ __align__(1024) float g_cs[F_];
__device__ __align__(1024) unsigned g_flags[128 * 32];
__device__ __align__(1024) unsigned g_epoch[160];
constexpr int FL_P = 0, FL_C = 8, FL_CS = 9, FL_M = 10, FL_R = 16, FL_B1 = 32, FL_B2 = 48, FL_G = 64;

#define TS(i) do {} while (0)
#define TSW(i) do {} while (0)
#define TSD(i, dep) do {} while (0)
#define TSD2(i, dep) do {} while (0)
#define TSFLUSH() do {} while (0)

struct Params {
    const bf16 *q, *k, *v, *shift, *ssmk, *ssmD, *w1, *w2, *w3, *w4, *c, *wmod;
    bf16* out;
    unsigned ones;
};
#define CHUNK(k) if (ones & (1u << (k)))
struct Maps { CUtensorMap hn, w1a, w1b, w2a, w2b, w3a, w3b, w3c, w4a, w4b, wm, xa, xb, w3s; };

template<int N> struct WgRs;
template<int N> struct WgSs;
template<> struct WgRs<32> { template<int OFF,int HI,int SC> static __device__ __forceinline__ void run(float* d,uint32_t a0,uint32_t a1,uint32_t a2,uint32_t a3,uint32_t blo){
 asm volatile("{.reg .b32 l; .reg .b64 db; add.u32 l,%20,%21; mov.b64 db,{l,%22}; wgmma.mma_async.sync.aligned.m64n32k16.f32.bf16.bf16 {%0,%1,%2,%3,%4,%5,%6,%7,%8,%9,%10,%11,%12,%13,%14,%15},{%16,%17,%18,%19},db,%23,1,1,0;}"
 :"+f"(d[0]),"+f"(d[1]),"+f"(d[2]),"+f"(d[3]),"+f"(d[4]),"+f"(d[5]),"+f"(d[6]),"+f"(d[7]),"+f"(d[8]),"+f"(d[9]),"+f"(d[10]),"+f"(d[11]),"+f"(d[12]),"+f"(d[13]),"+f"(d[14]),"+f"(d[15])
 :"r"(a0),"r"(a1),"r"(a2),"r"(a3),"r"(blo),"n"(OFF),"n"(HI),"n"(SC)); } };
template<> struct WgRs<48> { template<int OFF,int HI,int SC> static __device__ __forceinline__ void run(float* d,uint32_t a0,uint32_t a1,uint32_t a2,uint32_t a3,uint32_t blo){
 asm volatile("{.reg .b32 l; .reg .b64 db; add.u32 l,%28,%29; mov.b64 db,{l,%30}; wgmma.mma_async.sync.aligned.m64n48k16.f32.bf16.bf16 {%0,%1,%2,%3,%4,%5,%6,%7,%8,%9,%10,%11,%12,%13,%14,%15,%16,%17,%18,%19,%20,%21,%22,%23},{%24,%25,%26,%27},db,%31,1,1,0;}"
 :"+f"(d[0]),"+f"(d[1]),"+f"(d[2]),"+f"(d[3]),"+f"(d[4]),"+f"(d[5]),"+f"(d[6]),"+f"(d[7]),"+f"(d[8]),"+f"(d[9]),"+f"(d[10]),"+f"(d[11]),"+f"(d[12]),"+f"(d[13]),"+f"(d[14]),"+f"(d[15]),"+f"(d[16]),"+f"(d[17]),"+f"(d[18]),"+f"(d[19]),"+f"(d[20]),"+f"(d[21]),"+f"(d[22]),"+f"(d[23])
 :"r"(a0),"r"(a1),"r"(a2),"r"(a3),"r"(blo),"n"(OFF),"n"(HI),"n"(SC)); } };
template<> struct WgRs<64> { template<int OFF,int HI,int SC> static __device__ __forceinline__ void run(float* d,uint32_t a0,uint32_t a1,uint32_t a2,uint32_t a3,uint32_t blo){
 asm volatile("{.reg .b32 l; .reg .b64 db; add.u32 l,%36,%37; mov.b64 db,{l,%38}; wgmma.mma_async.sync.aligned.m64n64k16.f32.bf16.bf16 {%0,%1,%2,%3,%4,%5,%6,%7,%8,%9,%10,%11,%12,%13,%14,%15,%16,%17,%18,%19,%20,%21,%22,%23,%24,%25,%26,%27,%28,%29,%30,%31},{%32,%33,%34,%35},db,%39,1,1,0;}"
 :"+f"(d[0]),"+f"(d[1]),"+f"(d[2]),"+f"(d[3]),"+f"(d[4]),"+f"(d[5]),"+f"(d[6]),"+f"(d[7]),"+f"(d[8]),"+f"(d[9]),"+f"(d[10]),"+f"(d[11]),"+f"(d[12]),"+f"(d[13]),"+f"(d[14]),"+f"(d[15]),"+f"(d[16]),"+f"(d[17]),"+f"(d[18]),"+f"(d[19]),"+f"(d[20]),"+f"(d[21]),"+f"(d[22]),"+f"(d[23]),"+f"(d[24]),"+f"(d[25]),"+f"(d[26]),"+f"(d[27]),"+f"(d[28]),"+f"(d[29]),"+f"(d[30]),"+f"(d[31])
 :"r"(a0),"r"(a1),"r"(a2),"r"(a3),"r"(blo),"n"(OFF),"n"(HI),"n"(SC)); } };
template<> struct WgRs<80> { template<int OFF,int HI,int SC> static __device__ __forceinline__ void run(float* d,uint32_t a0,uint32_t a1,uint32_t a2,uint32_t a3,uint32_t blo){
 asm volatile("{.reg .b32 l; .reg .b64 db; add.u32 l,%44,%45; mov.b64 db,{l,%46}; wgmma.mma_async.sync.aligned.m64n80k16.f32.bf16.bf16 {%0,%1,%2,%3,%4,%5,%6,%7,%8,%9,%10,%11,%12,%13,%14,%15,%16,%17,%18,%19,%20,%21,%22,%23,%24,%25,%26,%27,%28,%29,%30,%31,%32,%33,%34,%35,%36,%37,%38,%39},{%40,%41,%42,%43},db,%47,1,1,0;}"
 :"+f"(d[0]),"+f"(d[1]),"+f"(d[2]),"+f"(d[3]),"+f"(d[4]),"+f"(d[5]),"+f"(d[6]),"+f"(d[7]),"+f"(d[8]),"+f"(d[9]),"+f"(d[10]),"+f"(d[11]),"+f"(d[12]),"+f"(d[13]),"+f"(d[14]),"+f"(d[15]),"+f"(d[16]),"+f"(d[17]),"+f"(d[18]),"+f"(d[19]),"+f"(d[20]),"+f"(d[21]),"+f"(d[22]),"+f"(d[23]),"+f"(d[24]),"+f"(d[25]),"+f"(d[26]),"+f"(d[27]),"+f"(d[28]),"+f"(d[29]),"+f"(d[30]),"+f"(d[31]),"+f"(d[32]),"+f"(d[33]),"+f"(d[34]),"+f"(d[35]),"+f"(d[36]),"+f"(d[37]),"+f"(d[38]),"+f"(d[39])
 :"r"(a0),"r"(a1),"r"(a2),"r"(a3),"r"(blo),"n"(OFF),"n"(HI),"n"(SC)); } };
template<> struct WgRs<96> { template<int OFF,int HI,int SC> static __device__ __forceinline__ void run(float* d,uint32_t a0,uint32_t a1,uint32_t a2,uint32_t a3,uint32_t blo){
 asm volatile("{.reg .b32 l; .reg .b64 db; add.u32 l,%52,%53; mov.b64 db,{l,%54}; wgmma.mma_async.sync.aligned.m64n96k16.f32.bf16.bf16 {%0,%1,%2,%3,%4,%5,%6,%7,%8,%9,%10,%11,%12,%13,%14,%15,%16,%17,%18,%19,%20,%21,%22,%23,%24,%25,%26,%27,%28,%29,%30,%31,%32,%33,%34,%35,%36,%37,%38,%39,%40,%41,%42,%43,%44,%45,%46,%47},{%48,%49,%50,%51},db,%55,1,1,0;}"
 :"+f"(d[0]),"+f"(d[1]),"+f"(d[2]),"+f"(d[3]),"+f"(d[4]),"+f"(d[5]),"+f"(d[6]),"+f"(d[7]),"+f"(d[8]),"+f"(d[9]),"+f"(d[10]),"+f"(d[11]),"+f"(d[12]),"+f"(d[13]),"+f"(d[14]),"+f"(d[15]),"+f"(d[16]),"+f"(d[17]),"+f"(d[18]),"+f"(d[19]),"+f"(d[20]),"+f"(d[21]),"+f"(d[22]),"+f"(d[23]),"+f"(d[24]),"+f"(d[25]),"+f"(d[26]),"+f"(d[27]),"+f"(d[28]),"+f"(d[29]),"+f"(d[30]),"+f"(d[31]),"+f"(d[32]),"+f"(d[33]),"+f"(d[34]),"+f"(d[35]),"+f"(d[36]),"+f"(d[37]),"+f"(d[38]),"+f"(d[39]),"+f"(d[40]),"+f"(d[41]),"+f"(d[42]),"+f"(d[43]),"+f"(d[44]),"+f"(d[45]),"+f"(d[46]),"+f"(d[47])
 :"r"(a0),"r"(a1),"r"(a2),"r"(a3),"r"(blo),"n"(OFF),"n"(HI),"n"(SC)); } };
template<> struct WgRs<112> { template<int OFF,int HI,int SC> static __device__ __forceinline__ void run(float* d,uint32_t a0,uint32_t a1,uint32_t a2,uint32_t a3,uint32_t blo){
 asm volatile("{.reg .b32 l; .reg .b64 db; add.u32 l,%60,%61; mov.b64 db,{l,%62}; wgmma.mma_async.sync.aligned.m64n112k16.f32.bf16.bf16 {%0,%1,%2,%3,%4,%5,%6,%7,%8,%9,%10,%11,%12,%13,%14,%15,%16,%17,%18,%19,%20,%21,%22,%23,%24,%25,%26,%27,%28,%29,%30,%31,%32,%33,%34,%35,%36,%37,%38,%39,%40,%41,%42,%43,%44,%45,%46,%47,%48,%49,%50,%51,%52,%53,%54,%55},{%56,%57,%58,%59},db,%63,1,1,0;}"
 :"+f"(d[0]),"+f"(d[1]),"+f"(d[2]),"+f"(d[3]),"+f"(d[4]),"+f"(d[5]),"+f"(d[6]),"+f"(d[7]),"+f"(d[8]),"+f"(d[9]),"+f"(d[10]),"+f"(d[11]),"+f"(d[12]),"+f"(d[13]),"+f"(d[14]),"+f"(d[15]),"+f"(d[16]),"+f"(d[17]),"+f"(d[18]),"+f"(d[19]),"+f"(d[20]),"+f"(d[21]),"+f"(d[22]),"+f"(d[23]),"+f"(d[24]),"+f"(d[25]),"+f"(d[26]),"+f"(d[27]),"+f"(d[28]),"+f"(d[29]),"+f"(d[30]),"+f"(d[31]),"+f"(d[32]),"+f"(d[33]),"+f"(d[34]),"+f"(d[35]),"+f"(d[36]),"+f"(d[37]),"+f"(d[38]),"+f"(d[39]),"+f"(d[40]),"+f"(d[41]),"+f"(d[42]),"+f"(d[43]),"+f"(d[44]),"+f"(d[45]),"+f"(d[46]),"+f"(d[47]),"+f"(d[48]),"+f"(d[49]),"+f"(d[50]),"+f"(d[51]),"+f"(d[52]),"+f"(d[53]),"+f"(d[54]),"+f"(d[55])
 :"r"(a0),"r"(a1),"r"(a2),"r"(a3),"r"(blo),"n"(OFF),"n"(HI),"n"(SC)); } };
template<> struct WgRs<128> { template<int OFF,int HI,int SC> static __device__ __forceinline__ void run(float* d,uint32_t a0,uint32_t a1,uint32_t a2,uint32_t a3,uint32_t blo){
 asm volatile("{.reg .b32 l; .reg .b64 db; add.u32 l,%68,%69; mov.b64 db,{l,%70}; wgmma.mma_async.sync.aligned.m64n128k16.f32.bf16.bf16 {%0,%1,%2,%3,%4,%5,%6,%7,%8,%9,%10,%11,%12,%13,%14,%15,%16,%17,%18,%19,%20,%21,%22,%23,%24,%25,%26,%27,%28,%29,%30,%31,%32,%33,%34,%35,%36,%37,%38,%39,%40,%41,%42,%43,%44,%45,%46,%47,%48,%49,%50,%51,%52,%53,%54,%55,%56,%57,%58,%59,%60,%61,%62,%63},{%64,%65,%66,%67},db,%71,1,1,0;}"
 :"+f"(d[0]),"+f"(d[1]),"+f"(d[2]),"+f"(d[3]),"+f"(d[4]),"+f"(d[5]),"+f"(d[6]),"+f"(d[7]),"+f"(d[8]),"+f"(d[9]),"+f"(d[10]),"+f"(d[11]),"+f"(d[12]),"+f"(d[13]),"+f"(d[14]),"+f"(d[15]),"+f"(d[16]),"+f"(d[17]),"+f"(d[18]),"+f"(d[19]),"+f"(d[20]),"+f"(d[21]),"+f"(d[22]),"+f"(d[23]),"+f"(d[24]),"+f"(d[25]),"+f"(d[26]),"+f"(d[27]),"+f"(d[28]),"+f"(d[29]),"+f"(d[30]),"+f"(d[31]),"+f"(d[32]),"+f"(d[33]),"+f"(d[34]),"+f"(d[35]),"+f"(d[36]),"+f"(d[37]),"+f"(d[38]),"+f"(d[39]),"+f"(d[40]),"+f"(d[41]),"+f"(d[42]),"+f"(d[43]),"+f"(d[44]),"+f"(d[45]),"+f"(d[46]),"+f"(d[47]),"+f"(d[48]),"+f"(d[49]),"+f"(d[50]),"+f"(d[51]),"+f"(d[52]),"+f"(d[53]),"+f"(d[54]),"+f"(d[55]),"+f"(d[56]),"+f"(d[57]),"+f"(d[58]),"+f"(d[59]),"+f"(d[60]),"+f"(d[61]),"+f"(d[62]),"+f"(d[63])
 :"r"(a0),"r"(a1),"r"(a2),"r"(a3),"r"(blo),"n"(OFF),"n"(HI),"n"(SC)); } };
template<> struct WgSs<80> { template<int AOFF,int AHI,int BOFF,int BHI,int SC> static __device__ __forceinline__ void run(float* d,uint32_t alo,uint32_t blo){
 asm volatile("{.reg .b32 l,m; .reg .b64 da,db; add.u32 l,%40,%42; mov.b64 da,{l,%43}; add.u32 m,%41,%44; mov.b64 db,{m,%45}; wgmma.mma_async.sync.aligned.m64n80k16.f32.bf16.bf16 {%0,%1,%2,%3,%4,%5,%6,%7,%8,%9,%10,%11,%12,%13,%14,%15,%16,%17,%18,%19,%20,%21,%22,%23,%24,%25,%26,%27,%28,%29,%30,%31,%32,%33,%34,%35,%36,%37,%38,%39},da,db,%46,1,1,0,1;}"
 :"+f"(d[0]),"+f"(d[1]),"+f"(d[2]),"+f"(d[3]),"+f"(d[4]),"+f"(d[5]),"+f"(d[6]),"+f"(d[7]),"+f"(d[8]),"+f"(d[9]),"+f"(d[10]),"+f"(d[11]),"+f"(d[12]),"+f"(d[13]),"+f"(d[14]),"+f"(d[15]),"+f"(d[16]),"+f"(d[17]),"+f"(d[18]),"+f"(d[19]),"+f"(d[20]),"+f"(d[21]),"+f"(d[22]),"+f"(d[23]),"+f"(d[24]),"+f"(d[25]),"+f"(d[26]),"+f"(d[27]),"+f"(d[28]),"+f"(d[29]),"+f"(d[30]),"+f"(d[31]),"+f"(d[32]),"+f"(d[33]),"+f"(d[34]),"+f"(d[35]),"+f"(d[36]),"+f"(d[37]),"+f"(d[38]),"+f"(d[39])
 :"r"(alo),"r"(blo),"n"(AOFF),"n"(AHI),"n"(BOFF),"n"(BHI),"n"(SC)); } };
template<> struct WgSs<104> { template<int AOFF,int AHI,int BOFF,int BHI,int SC> static __device__ __forceinline__ void run(float* d,uint32_t alo,uint32_t blo){
 asm volatile("{.reg .b32 l,m; .reg .b64 da,db; add.u32 l,%52,%54; mov.b64 da,{l,%55}; add.u32 m,%53,%56; mov.b64 db,{m,%57}; wgmma.mma_async.sync.aligned.m64n104k16.f32.bf16.bf16 {%0,%1,%2,%3,%4,%5,%6,%7,%8,%9,%10,%11,%12,%13,%14,%15,%16,%17,%18,%19,%20,%21,%22,%23,%24,%25,%26,%27,%28,%29,%30,%31,%32,%33,%34,%35,%36,%37,%38,%39,%40,%41,%42,%43,%44,%45,%46,%47,%48,%49,%50,%51},da,db,%58,1,1,0,1;}"
 :"+f"(d[0]),"+f"(d[1]),"+f"(d[2]),"+f"(d[3]),"+f"(d[4]),"+f"(d[5]),"+f"(d[6]),"+f"(d[7]),"+f"(d[8]),"+f"(d[9]),"+f"(d[10]),"+f"(d[11]),"+f"(d[12]),"+f"(d[13]),"+f"(d[14]),"+f"(d[15]),"+f"(d[16]),"+f"(d[17]),"+f"(d[18]),"+f"(d[19]),"+f"(d[20]),"+f"(d[21]),"+f"(d[22]),"+f"(d[23]),"+f"(d[24]),"+f"(d[25]),"+f"(d[26]),"+f"(d[27]),"+f"(d[28]),"+f"(d[29]),"+f"(d[30]),"+f"(d[31]),"+f"(d[32]),"+f"(d[33]),"+f"(d[34]),"+f"(d[35]),"+f"(d[36]),"+f"(d[37]),"+f"(d[38]),"+f"(d[39]),"+f"(d[40]),"+f"(d[41]),"+f"(d[42]),"+f"(d[43]),"+f"(d[44]),"+f"(d[45]),"+f"(d[46]),"+f"(d[47]),"+f"(d[48]),"+f"(d[49]),"+f"(d[50]),"+f"(d[51])
 :"r"(alo),"r"(blo),"n"(AOFF),"n"(AHI),"n"(BOFF),"n"(BHI),"n"(SC)); } };
template<> struct WgSs<112> { template<int AOFF,int AHI,int BOFF,int BHI,int SC> static __device__ __forceinline__ void run(float* d,uint32_t alo,uint32_t blo){
 asm volatile("{.reg .b32 l,m; .reg .b64 da,db; add.u32 l,%56,%58; mov.b64 da,{l,%59}; add.u32 m,%57,%60; mov.b64 db,{m,%61}; wgmma.mma_async.sync.aligned.m64n112k16.f32.bf16.bf16 {%0,%1,%2,%3,%4,%5,%6,%7,%8,%9,%10,%11,%12,%13,%14,%15,%16,%17,%18,%19,%20,%21,%22,%23,%24,%25,%26,%27,%28,%29,%30,%31,%32,%33,%34,%35,%36,%37,%38,%39,%40,%41,%42,%43,%44,%45,%46,%47,%48,%49,%50,%51,%52,%53,%54,%55},da,db,%62,1,1,0,1;}"
 :"+f"(d[0]),"+f"(d[1]),"+f"(d[2]),"+f"(d[3]),"+f"(d[4]),"+f"(d[5]),"+f"(d[6]),"+f"(d[7]),"+f"(d[8]),"+f"(d[9]),"+f"(d[10]),"+f"(d[11]),"+f"(d[12]),"+f"(d[13]),"+f"(d[14]),"+f"(d[15]),"+f"(d[16]),"+f"(d[17]),"+f"(d[18]),"+f"(d[19]),"+f"(d[20]),"+f"(d[21]),"+f"(d[22]),"+f"(d[23]),"+f"(d[24]),"+f"(d[25]),"+f"(d[26]),"+f"(d[27]),"+f"(d[28]),"+f"(d[29]),"+f"(d[30]),"+f"(d[31]),"+f"(d[32]),"+f"(d[33]),"+f"(d[34]),"+f"(d[35]),"+f"(d[36]),"+f"(d[37]),"+f"(d[38]),"+f"(d[39]),"+f"(d[40]),"+f"(d[41]),"+f"(d[42]),"+f"(d[43]),"+f"(d[44]),"+f"(d[45]),"+f"(d[46]),"+f"(d[47]),"+f"(d[48]),"+f"(d[49]),"+f"(d[50]),"+f"(d[51]),"+f"(d[52]),"+f"(d[53]),"+f"(d[54]),"+f"(d[55])
 :"r"(alo),"r"(blo),"n"(AOFF),"n"(AHI),"n"(BOFF),"n"(BHI),"n"(SC)); } };

__device__ __forceinline__ void wg_fence() { asm volatile("wgmma.fence.sync.aligned;" ::: "memory"); }
__device__ __forceinline__ void wg_commit() { asm volatile("wgmma.commit_group.sync.aligned;" ::: "memory"); }
template <int N> __device__ __forceinline__ void wg_wait() { asm volatile("wgmma.wait_group.sync.aligned %0;" ::"n"(N) : "memory"); }
template <int N> __device__ __forceinline__ void reg_fence(float* d) {
#pragma unroll
    for (int i = 0; i < N; i++) asm volatile("" : "+f"(d[i])::"memory");
}
__device__ __forceinline__ uint32_t desc_lo(uint32_t addr, uint32_t lbo) { return ((addr & 0x3FFFF) >> 4) | ((lbo >> 4) << 16); }
#define desc_hi(sbo, sw) (((sbo) >> 4) | ((sw) << 30))
__device__ __forceinline__ uint32_t smem_u32(const void* p) { return (uint32_t)__cvta_generic_to_shared(p); }
__device__ __forceinline__ bool elect() {
    uint32_t p;
    asm volatile("{.reg .pred P; elect.sync _|P, 0xffffffff; selp.u32 %0,1,0,P;}" : "=r"(p));
    return p;
}
__device__ __forceinline__ void mbar_init(uint32_t bar, uint32_t cnt) { asm volatile("mbarrier.init.shared::cta.b64 [%0], %1;" ::"r"(bar), "r"(cnt) : "memory"); }
__device__ __forceinline__ void mbar_expect(uint32_t bar, uint32_t bytes) { asm volatile("mbarrier.arrive.expect_tx.shared::cta.b64 _, [%0], %1;" ::"r"(bar), "r"(bytes) : "memory"); }
__device__ __forceinline__ bool mbar_try(uint32_t bar, uint32_t par) {
    uint32_t ok;
    asm volatile("{.reg .pred p; mbarrier.try_wait.parity.shared::cta.b64 p, [%1], %2; selp.u32 %0,1,0,p;}" : "=r"(ok) : "r"(bar), "r"(par) : "memory");
    return ok;
}
constexpr int SPIN_LIMIT = 1 << 18;
__device__ __forceinline__ void mbar_wait(uint32_t bar, uint32_t par) {
    if (mbar_try(bar, par)) return;
    int n = 0;
    while (!mbar_try(bar, par) && ++n < SPIN_LIMIT) {}
}
__device__ __forceinline__ void bulk_g2s(uint32_t dst, const void* src, uint32_t bytes, uint32_t bar) {
    asm volatile("cp.async.bulk.shared::cluster.global.mbarrier::complete_tx::bytes [%0], [%1], %2, [%3];" ::"r"(dst), "l"(src), "r"(bytes), "r"(bar) : "memory");
}
__device__ __forceinline__ void bulk_s2g(void* dst, uint32_t src, uint32_t bytes) {
    asm volatile("cp.async.bulk.global.shared::cta.bulk_group [%0], [%1], %2;" ::"l"(dst), "r"(src), "r"(bytes) : "memory");
}
__device__ __forceinline__ void bulk_prefetch(const void* src, uint32_t bytes) {
    asm volatile("cp.async.bulk.prefetch.L2.global [%0], %1;" ::"l"(src), "r"(bytes) : "memory");
}
__device__ __forceinline__ void tma2d(uint32_t dst, const CUtensorMap* m, int c0, int c1, uint32_t bar) {
    asm volatile("cp.async.bulk.tensor.2d.shared::cluster.global.mbarrier::complete_tx::bytes [%0], [%1, {%3, %4}], [%2];" ::"r"(dst), "l"(m), "r"(bar), "r"(c0), "r"(c1) : "memory");
}
__device__ __forceinline__ void tma2d_mc(uint32_t dst, const CUtensorMap* m, int c0, int c1, uint32_t bar) {
    asm volatile("cp.async.bulk.tensor.2d.shared::cluster.global.mbarrier::complete_tx::bytes.multicast::cluster [%0], [%1, {%3, %4}], [%2], %5;" ::"r"(dst), "l"(m), "r"(bar), "r"(c0), "r"(c1), "h"((uint16_t)3) : "memory");
}
__device__ __forceinline__ uint32_t mapa(uint32_t a, uint32_t rank) { uint32_t r; asm("mapa.shared::cluster.u32 %0, %1, %2;" : "=r"(r) : "r"(a), "r"(rank)); return r; }
__device__ __forceinline__ void mbar_arrive_cl(uint32_t bar) { asm volatile("mbarrier.arrive.shared::cluster.b64 _, [%0];" ::"r"(bar) : "memory"); }
__device__ __forceinline__ void prefetch_map(const CUtensorMap* m) { asm volatile("prefetch.tensormap [%0];" ::"l"(m) : "memory"); }
__device__ __forceinline__ void cpasync16(uint32_t dst, const void* src, uint32_t srcsz) {
    asm volatile("cp.async.cg.shared.global [%0], [%1], 16, %2;" ::"r"(dst), "l"(src), "r"(srcsz) : "memory");
}
__device__ __forceinline__ void bar_sync(int id, int n) { asm volatile("bar.sync %0, %1;" ::"r"(id), "r"(n) : "memory"); }
__device__ __forceinline__ void bar_arrive(int id, int n) { asm volatile("bar.arrive %0, %1;" ::"r"(id), "r"(n) : "memory"); }
__device__ __forceinline__ void fence_async_smem() { asm volatile("fence.proxy.async.shared::cta;" ::: "memory"); }
__device__ __forceinline__ void fence_async_global() { asm volatile("fence.proxy.async.global;" ::: "memory"); }
__device__ __forceinline__ void flag_release(int f) { asm volatile("red.release.gpu.global.add.u32 [%0], 1;" ::"l"(&g_flags[f * 32]) : "memory"); }
__device__ __forceinline__ void flag_wait(int f, unsigned target) {
    const unsigned* p = &g_flags[f * 32];
    unsigned v; int n = 0;
    do {
        asm volatile("ld.relaxed.gpu.global.u32 %0, [%1];" : "=r"(v) : "l"(p) : "memory");
    } while ((int)(v - target) < 0 && ++n < SPIN_LIMIT);
    asm volatile("fence.acquire.gpu;" ::: "memory");
}
__device__ __forceinline__ unsigned ld_flag(const unsigned* p) { unsigned v; asm volatile("ld.relaxed.gpu.global.u32 %0, [%1];" : "=r"(v) : "l"(p) : "memory"); return v; }
__device__ __forceinline__ void spin(unsigned n) { unsigned t0, t1; asm volatile("mov.u32 %0, %%clock;" : "=r"(t0)); do { asm volatile("mov.u32 %0, %%clock;" : "=r"(t1)); } while (t1 - t0 < n); }
__device__ __forceinline__ void flag_wait_fast(int f, unsigned target) {
    flag_wait(f, target);
}
__device__ __forceinline__ void flag_wait2(int f0, int f1, unsigned target) {
    const unsigned *p = &g_flags[f0 * 32], *q = &g_flags[f1 * 32];
    unsigned v, w; int n = 0;
    do { v = ld_flag(p); w = ld_flag(q); } while ((int)((v - target) | (w - target)) < 0 && ++n < SPIN_LIMIT);
    asm volatile("fence.acquire.gpu;" ::: "memory");
}
__device__ __forceinline__ uint32_t lds32(uint32_t a) { uint32_t v; asm volatile("ld.shared.u32 %0, [%1];" : "=r"(v) : "r"(a)); return v; }
__device__ __forceinline__ float2 lds64f(uint32_t a) { float2 v; asm volatile("ld.shared.v2.f32 {%0,%1}, [%2];" : "=f"(v.x), "=f"(v.y) : "r"(a)); return v; }
__device__ __forceinline__ uint2 lds64(uint32_t a) { uint2 v; asm volatile("ld.shared.v2.u32 {%0,%1}, [%2];" : "=r"(v.x), "=r"(v.y) : "r"(a)); return v; }
__device__ __forceinline__ void sts64f(uint32_t a, float2 v) { asm volatile("st.shared.v2.f32 [%0], {%1,%2};" ::"r"(a), "f"(v.x), "f"(v.y) : "memory"); }
__device__ __forceinline__ void sts32(uint32_t a, uint32_t v) { asm volatile("st.shared.u32 [%0], %1;" ::"r"(a), "r"(v) : "memory"); }
__device__ __forceinline__ void sts64(uint32_t a, uint32_t x, uint32_t y) { asm volatile("st.shared.v2.u32 [%0], {%1,%2};" ::"r"(a), "r"(x), "r"(y) : "memory"); }
__device__ __forceinline__ void sts16(uint32_t a, uint16_t v) { asm volatile("st.shared.u16 [%0], %1;" ::"r"(a), "h"(v) : "memory"); }
__device__ __forceinline__ uint4 lds128(uint32_t a) { uint4 v; asm volatile("ld.shared.v4.u32 {%0,%1,%2,%3}, [%4];" : "=r"(v.x), "=r"(v.y), "=r"(v.z), "=r"(v.w) : "r"(a)); return v; }
__device__ __forceinline__ void sts128(uint32_t a, uint4 v) { asm volatile("st.shared.v4.u32 [%0], {%1,%2,%3,%4};" ::"r"(a), "r"(v.x), "r"(v.y), "r"(v.z), "r"(v.w) : "memory"); }
__device__ __forceinline__ void sts128f(uint32_t a, float x, float y, float z, float w) { asm volatile("st.shared.v4.f32 [%0], {%1,%2,%3,%4};" ::"r"(a), "f"(x), "f"(y), "f"(z), "f"(w) : "memory"); }
__device__ __forceinline__ uint32_t prmt(uint32_t a, uint32_t b, uint32_t s) { uint32_t r; asm("prmt.b32 %0,%1,%2,%3;" : "=r"(r) : "r"(a), "r"(b), "r"(s)); return r; }
__device__ __forceinline__ uint32_t pack2(float lo, float hi) { uint32_t r; asm("cvt.rn.bf16x2.f32 %0, %1, %2;" : "=r"(r) : "f"(hi), "f"(lo)); return r; }
__device__ __forceinline__ float blo(uint32_t v) { return __uint_as_float(v << 16); }
__device__ __forceinline__ float bhi(uint32_t v) { return __uint_as_float(v & 0xffff0000u); }
__device__ __forceinline__ uint32_t bmul2(uint32_t a, uint32_t b) { uint32_t r; asm("mul.rn.bf16x2 %0,%1,%2;" : "=r"(r) : "r"(a), "r"(b)); return r; }
__device__ __forceinline__ uint32_t badd2(uint32_t a, uint32_t b) { uint32_t r; asm("add.rn.bf16x2 %0,%1,%2;" : "=r"(r) : "r"(a), "r"(b)); return r; }
__device__ __forceinline__ float rbf(float x) { return __bfloat162float(__float2bfloat16_rn(x)); }
__device__ __forceinline__ uint32_t ldcg32(const void* p) { uint32_t v; asm volatile("ld.global.cg.u32 %0, [%1];" : "=r"(v) : "l"(p) : "memory"); return v; }
__device__ __forceinline__ uint4 ldcg128(const void* p) { uint4 v; asm volatile("ld.global.cg.v4.u32 {%0,%1,%2,%3}, [%4];" : "=r"(v.x), "=r"(v.y), "=r"(v.z), "=r"(v.w) : "l"(p) : "memory"); return v; }
__device__ __forceinline__ void stg32_if(void* p, uint32_t v, int on) { asm volatile("{.reg .pred q; setp.ne.b32 q, %2, 0; @q st.global.u32 [%0], %1;}" ::"l"(p), "r"(v), "r"(on) : "memory"); }
__device__ __forceinline__ uint2 ldcg64(const void* p) { uint2 v; asm volatile("ld.global.cg.v2.u32 {%0,%1}, [%2];" : "=r"(v.x), "=r"(v.y) : "l"(p) : "memory"); return v; }
__device__ __forceinline__ float gelu_h(float h) {
    float u = h * fmaf(h * h, 8.0f * 0.044715f * 0.7978845608028654f, 2.0f * 0.7978845608028654f);
    float th;
    asm("tanh.approx.f32 %0, %1;" : "=f"(th) : "f"(u));
    return fmaf(h, th, h);
}
__device__ __forceinline__ float gelu(float x) { return gelu_h(0.5f * x); }
__device__ __forceinline__ float half_rstd(float sum, float sq) {
    float mean = sum * (1.0f / D_), inv;
    asm("rsqrt.approx.ftz.f32 %0, %1;" : "=f"(inv) : "f"(fmaxf(fmaf(-mean, mean, fmaf(sq, 1.0f / D_, 1e-5f)), 1e-5f)));
    return 0.5f * inv;
}
__device__ __forceinline__ uint32_t bsub2(uint32_t a, uint32_t b) { uint32_t r; asm("sub.rn.bf16x2 %0,%1,%2;" : "=r"(r) : "r"(a), "r"(b)); return r; }
__device__ __forceinline__ uint32_t bfma2(uint32_t a, uint32_t b, uint32_t c) { uint32_t r; asm("fma.rn.bf16x2 %0,%1,%2,%3;" : "=r"(r) : "r"(a), "r"(b), "r"(c)); return r; }
__device__ __forceinline__ uint32_t gelu2_h(uint32_t h) {
    uint32_t u = bmul2(h, bfma2(bmul2(h, h), 0x3e923e92u, 0x3fcc3fccu)), th;
    asm("tanh.approx.bf16x2 %0, %1;" : "=r"(th) : "r"(u));
    return bfma2(h, th, h);
}
__device__ __forceinline__ void mma_stat(float* d, uint32_t u, uint32_t v) {
    asm("mma.sync.aligned.m16n8k16.row.col.f32.bf16.bf16.f32 {%0,%1,%2,%3},{%4,%6,%5,%6},{%4,%5},{%0,%1,%2,%3};"
        : "+f"(d[0]), "+f"(d[1]), "+f"(d[2]), "+f"(d[3]) : "r"(u), "r"(v), "r"(0x3f803f80u));
}
__device__ __forceinline__ void mma_sel(float* d, uint2 u, uint2 v, uint32_t b0, uint32_t b1) {
    asm("mma.sync.aligned.m16n8k16.row.col.f32.bf16.bf16.f32 {%0,%1,%2,%3},{%4,%5,%6,%7},{%8,%9},{%0,%1,%2,%3};"
        : "+f"(d[0]), "+f"(d[1]), "+f"(d[2]), "+f"(d[3]) : "r"(u.x), "r"(v.x), "r"(u.y), "r"(v.y), "r"(b0), "r"(b1));
}
__device__ __forceinline__ void conv_sum4(float* d, uint32_t a, bool last, int g, int c) {
    uint2 v0 = lds64(a), v1 = lds64(a + 8), v2 = lds64(a + 16), v3 = lds64(a + 24);
    if (last) {
        if (c > 2) v1 = make_uint2(0, 0);
        if (c > 1) v2 = make_uint2(0, 0);
        if (c > 0) v3 = make_uint2(0, 0);
    }
    const uint32_t one = (g & 1) ? 0x3f800000u : 0x00003f80u;
    mma_sel(d, v0, v1, (g >> 1) == 0 ? one : 0u, (g >> 1) == 1 ? one : 0u);
    mma_sel(d, v2, v3, (g >> 1) == 2 ? one : 0u, (g >> 1) == 3 ? one : 0u);
}
__device__ __forceinline__ uint3 row_stats(const uint32_t* v, int lane) {
    float s = 0.f, q = 0.f, s_ = 0.f, q_ = 0.f;
#pragma unroll
    for (int i = 0; i < 10; i++) { float a = blo(v[i]), b = bhi(v[i]); s += a; s_ += b; q = fmaf(a, a, q); q_ = fmaf(b, b, q_); }
    s += s_; q += q_;
    {
        float t = __shfl_xor_sync(0xffffffffu, (lane & 16) ? s : q, 16);
        t += (lane & 16) ? q : s;
#pragma unroll
        for (int m = 8; m; m >>= 1) t += __shfl_xor_sync(0xffffffffu, t, m);
        float o = __shfl_xor_sync(0xffffffffu, t, 16);
        s = (lane & 16) ? o : t; q = (lane & 16) ? t : o;
    }
    float mean = s * (1.0f / D_), inv;
    asm("rsqrt.approx.ftz.f32 %0, %1;" : "=f"(inv) : "f"(fmaxf(fmaf(-mean, mean, fmaf(q, 1.0f / D_, 1e-5f)), 1e-5f)));
    uint3 r;
    r.x = pack2(mean, mean);
    r.y = pack2(inv, inv);
    inv -= blo(r.y);
    r.z = pack2(inv, inv);
    return r;
}
__device__ __forceinline__ uint32_t ln_apply(uint32_t x, uint32_t m, uint32_t hi, uint32_t lo) {
    uint32_t xc = bsub2(x, m);
    return bfma2(xc, hi, bmul2(xc, lo));
}

struct AFrag { uint32_t m, a, b, c, d; };
__device__ __forceinline__ AFrag ldA(uint32_t a) { AFrag f; f.m = lds32(a - 16); f.a = lds32(a); f.b = lds32(a + 16); f.c = lds32(a + 32); f.d = lds32(a + 48); return f; }
template <int N, int M> __device__ __forceinline__ void conv_pair(float* d, const AFrag& f, uint32_t descU) {
    WgRs<N>::template run<8 * M, desc_hi(128, 0), M ? 1 : 0>(d, f.a, f.b, f.m, f.a, descU);
    WgRs<N>::template run<8 * M + 1, desc_hi(128, 0), 1>(d, f.c, f.d, f.b, f.c, descU);
}
template <int Q> __device__ __forceinline__ void conv_put(float* d, uint32_t r0) {
    sts64(r0 + Q * 32, pack2(d[4 * Q + 1], d[4 * Q + 3]), pack2(d[4 * Q], d[4 * Q + 2]));
}
template <int M> __device__ __forceinline__ void conv_two(float* d, AFrag f0, AFrag f1, uint32_t kaddr, uint32_t descU, uint32_t r0, bool handoff) {
    constexpr int N = M < 14 ? 128 - 8 * M : 32;
    wg_fence();
    conv_pair<N, M>(d, f0, descU);
    wg_commit();
    if constexpr (M > 0) f1 = ldA(kaddr + 256 * (M + 1));
    wg_fence();
    conv_pair<N, M + 1>(d, f1, descU);
    wg_commit();
    if (STAG && M == STAG && handoff) bar_arrive(12, 256);
    if constexpr (M < 14) {
        if constexpr (M > 0) { conv_put<17 - M>(d, r0); conv_put<16 - M>(d, r0); }
        wg_wait<1>();
        f0 = ldA(kaddr + 256 * (M + 2));
        if constexpr (M < 12) wg_wait<0>();
        conv_two<M + 2>(d, f0, f1, kaddr, descU, r0, handoff);
    } else {
        wg_wait<0>();
        conv_put<3>(d, r0); conv_put<2>(d, r0); conv_put<1>(d, r0); conv_put<0>(d, r0);
    }
}
template <int N, bool ASWZ, int SC0>
__device__ __forceinline__ void gemm_issue(float* acc, uint32_t bars, int sa, int pa, int sw, int pw, uint32_t da0, uint32_t db0) {
    mbar_wait(bars + (BAR_FB + sw) * 8, pw);
    mbar_wait(bars + (BAR_FA + sa) * 8, pa);
    const uint32_t da = da0 + sa * (SLOT >> 4), db = db0 + sw * (SLOT >> 4);
    constexpr int AK = ASWZ ? 2 : 256, AH = ASWZ ? desc_hi(1024, 1) : desc_hi(128, 0), BH = desc_hi(1024, 1);
    wg_fence();
    WgSs<N>::template run<0, AH, 0, BH, SC0>(acc, da, db);
    WgSs<N>::template run<AK, AH, 128, BH, 1>(acc, da, db);
    WgSs<N>::template run<2 * AK, AH, 256, BH, 1>(acc, da, db);
    WgSs<N>::template run<3 * AK, AH, 384, BH, 1>(acc, da, db);
    wg_commit();
}
template <int N, bool ASWZ, int NKB, int RELB, bool ZERO>
__device__ __forceinline__ void gemm_loop(float* acc, uint32_t sb, int half, int ia0, int ib0, int rela, int wait_bar, int order_bar, int tsid) {
    int sa = ia0 % NA, pa = (ia0 / NA) & 1, sw = ib0 % NB, pw = (ib0 / NB) & 1;
    const uint32_t bars = sb + SM_BAR;
    const int t = threadIdx.x & 127;
    uint32_t ebar = mapa(bars + (t < 2 ? BAR_EB : BAR_EA) * 8, (t < 2 && lds32(sb + SM_GV + 516)) ? t : blockIdx.x & 1);
    const int nrel = t < 2 ? RELB : t == 2 ? rela : 0;
    const uint32_t da0 = ASWZ ? desc_lo(sb + SM_RA + half * 8192, 16) : desc_lo(sb + SM_RA + half * 1024, 2048), db0 = desc_lo(sb + SM_RB, 8192);
    asm volatile("" : "+r"(ebar));
    if (wait_bar) bar_sync(wait_bar, 512);
    gemm_issue<N, ASWZ, ZERO ? 0 : 1>(acc, bars, sa, pa, sw, pw, da0, db0);
    if ((threadIdx.x & 255) == 0) TS(tsid);
#pragma unroll 1
    for (int kb = 1; kb < NKB; kb++) {
        const int prev = t < 2 ? sw : sa;
        if (++sa == NA) { sa = 0; pa ^= 1; }
        if (++sw == NB) { sw = 0; pw ^= 1; }
        gemm_issue<N, ASWZ, 1>(acc, bars, sa, pa, sw, pw, da0, db0);
        if (order_bar && kb == NKB - 1) bar_arrive(order_bar, 512);
        wg_wait<1>();
        if (kb <= nrel) mbar_arrive_cl(ebar + prev * 8);
    }
    wg_wait<0>();
    if (nrel == NKB) mbar_arrive_cl(ebar + (t < 2 ? sw : sa) * 8);
    reg_fence<N / 2>(acc);
    if ((threadIdx.x & 255) == 0) TS(tsid + 1);
}

template <int PART>
__device__ __forceinline__ void gemm3(uint32_t sb, int rb, int j, int half, int row, int c, unsigned ones) {
    constexpr int N = PART ? 104 : 112, NQ = N / 8;
    constexpr int HO = PART ? HO_B : HO_A;
    float acc[N / 2];
    float2 cr[NQ];
    mbar_wait(sb + SM_BAR + BAR_CS * 8, 0);
#pragma unroll
    for (int q = 0; q < NQ; q++) cr[q] = lds64f(sb + SM_CS + PART * 448 + 8 * c + 32 * q);
    uint4 rp;
    if (PART) {
        mbar_wait(sb + SM_BAR + (BAR_FA + 21 % NA) * 8, (21 / NA) & 1);
        const float2* sp = &g_st[(rb * 8 + 2 * c) * 128 + row];
        const uint2 s0 = ldcg64(sp), s1 = ldcg64(sp + 128), s2 = ldcg64(sp + 8), s3 = ldcg64(sp + 136);
        float a0 = __uint_as_float(s0.x) + __uint_as_float(s1.x), b0 = __uint_as_float(s0.y) + __uint_as_float(s1.y);
        float a1 = __uint_as_float(s2.x) + __uint_as_float(s3.x), b1 = __uint_as_float(s2.y) + __uint_as_float(s3.y);
#pragma unroll
        for (int m = 1; m <= 2; m <<= 1) {
            a0 += __shfl_xor_sync(0xffffffffu, a0, m); b0 += __shfl_xor_sync(0xffffffffu, b0, m);
            a1 += __shfl_xor_sync(0xffffffffu, a1, m); b1 += __shfl_xor_sync(0xffffffffu, b1, m);
        }
        const float inv0 = half_rstd(a0, b0), inv1 = half_rstd(a1, b1);
        rp = make_uint4(PGELU ? pack2(inv0, inv0) : __float_as_uint(inv0), __float_as_uint(a0 * (-1.0f / D_)),
                        PGELU ? pack2(inv1, inv1) : __float_as_uint(inv1), __float_as_uint(a1 * (-1.0f / D_)));
        if (c == 0) sts128(sb + SM_RP + ((threadIdx.x & 255) >> 2) * 16, rp);
        bar_arrive(13, 512);
    }
    gemm_loop<N, false, 10, 10, true>(acc, sb, half, 20 + (10 - NA) * PART, 20 + 10 * PART, PART ? 10 : 10 - NA, 9 + PART, HO < 0 ? 10 + PART : 0, 46 + 2 * PART);
    if (!PART) {
        bar_sync(13, 512);
        rp = lds128(sb + SM_RP + ((threadIdx.x & 255) >> 2) * 16);
    }
    const float nb0 = __uint_as_float(rp.y), nb1 = __uint_as_float(rp.w);
    uint32_t* dst = reinterpret_cast<uint32_t*>(g_g) + (rb * 216 + 112 * PART + 8 * j) * 512 + row * 4 + c;
    auto act = [&](int q, int r) {
        const float nb = r ? nb1 : nb0;
        const uint32_t inv = r ? rp.z : rp.x;
        const float t0 = fmaf(nb, cr[q].x, acc[4 * q + 2 * r]), t1 = fmaf(nb, cr[q].y, acc[4 * q + 2 * r + 1]);
        return gelu2_h(bmul2(pack2(t0, t1), inv));
    };
    uint32_t* dst1 = dst + (56 - (16 - NQ) * j) * 512;
#pragma unroll
    for (int k = 0; k < NQ; k += CH3) {
        if (k == HO) bar_arrive(10 + PART, 512);
        CHUNK(k) {
#pragma unroll
            for (int q = k; q < k + CH3 && q < NQ; q++) { (q < 8 ? dst : dst1)[q * 512] = act(q, 0); (q < 8 ? dst : dst1)[q * 512 + 32] = act(q, 1); }
        }
    }
    if (HO >= NQ) bar_arrive(10 + PART, 512);
    bar_arrive(1 + PART, 288);
}

template <int NS, int BASE, int BF, int BE> struct Ring {
    uint32_t sb, st, ph;
    __device__ __forceinline__ uint32_t acquire(uint32_t bytes) {
        mbar_wait(sb + SM_BAR + BE * 8 + st * 8, ph);
        uint32_t fb = sb + SM_BAR + BF * 8 + st * 8;
        mbar_expect(fb, bytes);
        return fb;
    }
    __device__ __forceinline__ uint32_t slot() { return sb + BASE + st * SLOT; }
    __device__ __forceinline__ void next() { if (++st == NS) { st = 0; ph ^= 1; } }
    __device__ __forceinline__ void run2d(const CUtensorMap* m, int c1) {
#pragma unroll 1
        for (int c0 = 64; c0 < D_; c0 += 64) {
            uint32_t fb = acquire(SLOT);
            tma2d(slot(), m, c0, c1, fb);
            next();
        }
    }
    __device__ __forceinline__ void runw(bool paired, int rk, const CUtensorMap* ma, const CUtensorMap* mb, int ca, int cb, int c1, int n, uint32_t bytes) {
        if (paired) {
            const CUtensorMap* m = rk ? mb : ma;
            const int c0 = rk ? cb : ca;
#pragma unroll 1
            for (; n > 0; n--, c1 += 64) {
                uint32_t fb = acquire(bytes);
                tma2d_mc(slot() + 8192 * rk, m, c0, c1, fb);
                next();
            }
        } else {
#pragma unroll 1
            for (; n > 0; n--, c1 += 64) {
                uint32_t fb = acquire(bytes);
                tma2d(slot(), ma, ca, c1, fb);
                tma2d(slot() + 8192, mb, cb, c1, fb);
                next();
            }
        }
    }
    __device__ __forceinline__ void run1d(const char* src, int n) {
#pragma unroll 1
        for (; n > 0; n--) {
            uint32_t fb = acquire(SLOT);
            bulk_g2s(slot(), src, SLOT, fb);
            src += SLOT;
            next();
        }
    }
};

__global__ void __cluster_dims__(2, 1, 1) __launch_bounds__(NTHREADS, 1) fused_kernel(const Params p, const __grid_constant__ Maps maps) {
    extern __shared__ __align__(1024) unsigned char smem_raw[];
    const uint32_t sb = (smem_u32(smem_raw) + 1023u) & ~1023u;
#pragma unroll
    for (int i = 0; i < SEED; i++) asm volatile("{.reg .b32 t; mov.u32 t, %laneid;}");
    const uint32_t bars = sb + SM_BAR;
    const int tid = threadIdx.x, lane = tid & 31;
    unsigned smid;
    asm volatile("mov.u32 %0, %%smid;" : "=r"(smid));
    const bool spare = (smid >> 2) == 30;
    const int cta = smid < 120 ? smid : smid - 4;
    const int pg = cta >> 4, pi = cta & 15;
    const int hb = tid >= 320;
    if (!spare) {
        const unsigned t = tid - 320 * hb, r32 = t / 10u, cc = t - r32 * 10u, row = r32 + 64 * hb;
        const unsigned go = (unsigned)(pi * 128 * 1280 + pg * 160) + row * 1280u + cc * 16u;
        const uint32_t so = sb + (row >> 4) * 32u + row * 160u + cc * 16u;
        const char* kb = (const char*)p.k + go;
        const char* vb = (const char*)p.v + go;
        if (hb) {
            if (tid >= 640 - NBARS) {
                const int i = 639 - tid;
                mbar_init(bars + i * 8, (i >= BAR_EB && i < BAR_K) ? 4 : ((i >= BAR_EA && i < BAR_EB) || i == BAR_XY) ? 2 : 1);
                asm volatile("fence.mbarrier_init.release.cluster;" ::: "memory");
            }
            bar_arrive(14, 640);
            if (B_DELAY) spin(B_DELAY);
        }
        cpasync16(so + SM_PK + 2592, kb, 16);
        cpasync16(so + SM_PV, vb, 16);
        cpasync16(so + SM_PK + 3 * 2592, kb + 32 * 1280, 16);
        cpasync16(so + SM_PV + 2 * 2592, vb + 32 * 1280, 16);
        if (tid < 30) cpasync16(so + SM_PK + 13 * 160, pi ? kb - 3 * 1280 : kb, pi ? 16 : 0);
        asm volatile("cp.async.commit_group;" ::: "memory");
    }
    const int warp = __shfl_sync(0xffffffffu, tid >> 5, 0);
    const int wg = warp >> 2, wq = warp & 3;
    unsigned ep0 = 0;
    if (wg == 4 || spare) ep0 = *(volatile unsigned*)&g_epoch[smid];
#define ep1 (ep0 + 1)

    if (spare) {
        const int sp = smid & 3;
        if (tid == 32) { sts32(sb + SM_GV + 512, smid); asm volatile("fence.release.sync_restrict::shared::cta.cluster;" ::: "memory"); }
        asm volatile("barrier.cluster.arrive.relaxed.aligned;" ::: "memory");
        asm volatile("barrier.cluster.wait.aligned;" ::: "memory");
        if (tid == 0) {
            for (int i = 0; i < 4; i++) mbar_init(bars + i * 8, 1);
            asm volatile("fence.mbarrier_init.release.cluster;" ::: "memory");
        }
        if (warp == 0) { if (lane < 8) flag_wait(FL_P + lane, ep1 * 16); __syncwarp(); }
        __syncthreads();
        const int cq = tid % 54, rg = tid / 54;
        float a[8];
#pragma unroll
        for (int i = 0; i < 8; i++) a[i] = 0.f;
#pragma unroll 1
        for (int it = -4; it < 10; it++) {
            const uint32_t st = sb + (it & 3) * 55296, fb = bars + (it & 3) * 8;
            if (it >= 0) {
                mbar_wait(fb, (it >> 2) & 1);
                if (tid < 432) {
#pragma unroll
                    for (int i = 0; i < 8; i++) {
                        uint4 w = lds128(st + (cq >= 27 ? 27648 - 432 : 0) + (rg * 8 + i) * 432 + cq * 16);
                        a[0] += blo(w.x); a[1] += bhi(w.x); a[2] += blo(w.y); a[3] += bhi(w.y);
                        a[4] += blo(w.z); a[5] += bhi(w.z); a[6] += blo(w.w); a[7] += bhi(w.w);
                    }
                }
                __syncthreads();
            }
            if (it < 6 && warp == 19 && elect()) {
                mbar_expect(fb, 55296);
                tma2d(st, &maps.w3s, sp * 432, (it + 4) * 64, fb);
                tma2d(st + 27648, &maps.w3s, sp * 432 + 216, (it + 4) * 64, fb);
            }
        }
        if (tid < 432) {
            sts128f(sb + rg * 1728 + cq * 32, a[0], a[1], a[2], a[3]);
            sts128f(sb + rg * 1728 + cq * 32 + 16, a[4], a[5], a[6], a[7]);
        }
        __syncthreads();
        if (tid < 432) {
            float s = 0.f;
#pragma unroll
            for (int i = 0; i < 8; i++) s += __uint_as_float(lds32(sb + i * 1728 + tid * 4));
            g_cs[sp * 432 + tid] = s;
        }
        __syncthreads();
        if (tid == 0) { flag_release(FL_CS); g_epoch[smid] = ep1; TS(0); }
        if (warp == 0) TSFLUSH();
        return;
    }

    int gpc, idx;
    if (smid < 64) { gpc = (smid & 15) >> 1; idx = (smid >> 4) * 2 + (smid & 1); }
    else if (smid < 120) { int t = smid - 64; gpc = 1 + (t % 14) / 2; idx = 8 + (t / 14) * 2 + (smid & 1); }
    else { gpc = 0; idx = 8 + (smid - 124); }
    const int rb = 2 * gpc + (idx & 1), j = idx >> 1;
    const int g = lane >> 2, c = lane & 3;
    const int cm = 160 * (j >> 1) + 64 * (j & 1) + ((j & 2) ? 32 : 0), cr = 160 * (j >> 1) + 16 * (j & 1) + ((j & 2) ? 0 : 128);

    {
        if (warp == 5) TSW(61);
        const int w10 = warp - 10 * hb, h = w10 >= 5;
        const int pr = (w10 - 5 * h) * 8 + (lane >> 2), blk = 4 * hb + (lane & 3);
        const int ch = 80 * pg + 2 * pr;
        const uint4 sw = __ldg(reinterpret_cast<const uint4*>(p.shift + ch * 4));
        uint32_t dv = 0;
        if (warp == 9 && lane < 5) dv = __bfloat16_as_ushort(p.ssmD[cta * 5 + lane]);
        if (tid == 512) { sts32(sb + SM_GV + 512, smid); asm volatile("fence.release.sync_restrict::shared::cta.cluster;" ::: "memory"); }
        asm volatile("barrier.cluster.arrive.relaxed.aligned;" ::: "memory");
        if (warp == 11 && lane < 13) prefetch_map(&maps.hn + lane);
        if (wg < 4) {
            const int t = tid & 127, cc = (wg == 3 && t >= 64) ? 4 : wg;
            if (t < 64 || wg == 3) sts128(sb + sm_u(cc) + ((t >> 5) & 1) * U_PLANE + 2048 + lane * 16, make_uint4(0, 0, 0, 0));
            if ((t & 63) < 4 && (t < 64 || wg == 3)) sts128(sb + sm_k(cc) + ((t >> 1) & 1) * 4160 + (t & 1) * 16, make_uint4(0, 0, 0, 0));
        }
        if (warp == 9 && lane < 5) sts32(sb + SM_GV + 520 + lane * 4, dv << 16);
        asm volatile("cp.async.wait_group 0;" ::: "memory");
        if (!hb) bar_arrive(12, 640);
        bar_sync(hb ? 12 : 14, 640);
        if (warp == 9) {
            if (SSM_DELAY) spin(SSM_DELAY);
            if (elect()) {
#pragma unroll
                for (int i = 0; i < SSM_N; i++) {
                    mbar_expect(bars + (BAR_K + i) * 8, 4096);
                    bulk_g2s(sb + sm_k(i) + 32, p.ssmk + (size_t)(cta * 5 + i) * S_, 4096, bars + (BAR_K + i) * 8);
                }
            }
        }
        const uint32_t w0 = prmt(sw.x, sw.z, 0x5410), w1 = prmt(sw.x, sw.z, 0x7632), w2 = prmt(sw.y, sw.w, 0x5410), w3 = prmt(sw.y, sw.w, 0x7632);
        const uint32_t ka = sb + SM_PK + 2592 + blk * 2592 + h * 1280 + pr * 4;
        const uint32_t va = sb + SM_PV + blk * 2592 + h * 1280 + pr * 4;
        uint32_t kk[11], kv[8];
#pragma unroll
        for (int i = 0; i < 11; i++) kk[i] = lds32(ka + (i - 3) * 160 - ((i < 3 && h == 0) ? 32 : 0));
#pragma unroll
        for (int i = 0; i < 8; i++) {
            uint32_t t = badd2(badd2(badd2(bmul2(kk[i], w3), bmul2(kk[i + 1], w2)), bmul2(kk[i + 2], w1)), bmul2(kk[i + 3], w0));
            kv[i] = bmul2(t, lds32(va + i * 160));
        }
        uint4 o0, o1;
        o0.x = prmt(kv[1], kv[0], 0x5410); o0.y = prmt(kv[3], kv[2], 0x5410); o0.z = prmt(kv[5], kv[4], 0x5410); o0.w = prmt(kv[7], kv[6], 0x5410);
        o1.x = prmt(kv[1], kv[0], 0x7632); o1.y = prmt(kv[3], kv[2], 0x7632); o1.z = prmt(kv[5], kv[4], 0x7632); o1.w = prmt(kv[7], kv[6], 0x7632);
        uint4* dst = reinterpret_cast<uint4*>(g_kvT) + ch * 256 + h * 128 + (127 - (8 * pi + blk));
        dst[0] = o0;
        dst[256] = o1;
    }

    const int rho = 8 * rb + j;

    if (wg == 4) {
        asm volatile("setmaxnreg.dec.sync.aligned.u32 32;");
        if (wq == 0) {
            bar_sync(13, 640);
            TSW(39);
            if (lane == 0) flag_release(FL_P + pg);
            __syncwarp();
            TSW(2);
            if (lane < 5) mbar_expect(bars + (BAR_U + lane) * 8, 4096);
            flag_wait_fast(FL_P + pg, ep1 * 16);
            fence_async_global();
            TSW(3);
            if (elect()) {
#pragma unroll
                for (int i = 0; i < 5; i++) {
                    const char* us = (const char*)g_kvT + (size_t)(cta * 5 + i) * 4096;
                    bulk_g2s(sb + sm_u(i), us, 2048, bars + (BAR_U + i) * 8);
                    bulk_g2s(sb + sm_u(i) + U_PLANE, us + 2048, 2048, bars + (BAR_U + i) * 8);
                }
            }
            __syncwarp();
            if (elect()) {
#pragma unroll
                for (int i = SSM_N; i < 5; i++) {
                    mbar_expect(bars + (BAR_K + i) * 8, 4096);
                    bulk_g2s(sb + sm_k(i) + 32, p.ssmk + (size_t)(cta * 5 + i) * S_, 4096, bars + (BAR_K + i) * 8);
                }
                if (cta < 120) {
                    mbar_expect(bars + BAR_WM * 8, 40960);
#pragma unroll
                    for (int i = 0; i < 5; i++) tma2d(sb + SM_WM + i * 8192, &maps.wm, cta * 32, i * 128, bars + BAR_WM * 8);
                }
                bulk_prefetch((const char*)p.q + cta * 20480, 20480);
                bulk_prefetch((const char*)p.w1 + cta * 6400, 6400);
                bulk_prefetch((const char*)p.w2 + cta * 6400, 6400);
            }
            __syncwarp();
        } else {
            bar_arrive(13, 640);
        }
        asm volatile("barrier.cluster.wait.aligned;" ::: "memory");
        uint32_t peer;
        asm volatile("ld.shared::cluster.u32 %0, [%1];" : "=r"(peer) : "r"(mapa(sb + SM_GV + 512, (blockIdx.x & 1) ^ 1)) : "memory");
        const bool paired = peer == (smid ^ 1);
        if (tid == 639) sts32(sb + SM_GV + 516, paired);
        if (cta < 120) {
            float d[4];
            if (tid < 592) {
                const int t = tid - 512;
                mbar_wait(bars + BAR_U * 8, 0);
                uint4 cv = __ldg(reinterpret_cast<const uint4*>(p.c) + t);
                auto silu2 = [](uint32_t v) { float a = blo(v), b = bhi(v); return pack2(__fdividef(a, 1.0f + __expf(-a)), __fdividef(b, 1.0f + __expf(-b))); };
                sts128(sb + SM_Y + (t % 40) * 32 + (t / 40) * 16, make_uint4(silu2(cv.x), silu2(cv.y), silu2(cv.z), silu2(cv.w)));
                fence_async_smem();
            }
            bar_sync(5, 128);
            mbar_wait(bars + BAR_WM * 8, 0);
            if (wq == 3) TSW(56);
            const uint32_t da = desc_lo(sb + SM_WM, 20480), db = desc_lo(sb + SM_Y, 32);
            wg_fence();
#pragma unroll
            for (int k = 0; k < 20; k++)
                asm volatile("{.reg .pred p; .reg .b32 l,m; .reg .b64 da,db; setp.ne.b32 p,%10,0; add.u32 l,%4,%6; mov.b64 da,{l,%8}; add.u32 m,%5,%7; mov.b64 db,{m,%9};"
                             " wgmma.mma_async.sync.aligned.m64n8k16.f32.bf16.bf16 {%0,%1,%2,%3},da,db,p,1,1,1,0;}"
                             : "+f"(d[0]), "+f"(d[1]), "+f"(d[2]), "+f"(d[3])
                             : "r"(da), "r"(db), "r"(64 * k), "r"(4 * k), "n"(desc_hi(512, 2u)), "n"(desc_hi(128, 0)), "r"(k));
            wg_commit();
            wg_wait<0>();
            reg_fence<4>(d);
            if (c == 0) {
                sts32(sb + SM_GV + (16 * wq + g) * 4, __float_as_uint(wq < 2 ? d[0] : d[1]));
                sts32(sb + SM_GV + (16 * wq + g + 8) * 4, __float_as_uint(wq < 2 ? d[2] : d[3]));
            }
            bar_sync(5, 128);
            if (wq == 2) {
                g_mod[cta * 32 + lane] = __float2bfloat16_rn(__uint_as_float(lds32(sb + SM_GV + lane * 4)) + __uint_as_float(lds32(sb + SM_GV + 128 + lane * 4)));
                __syncwarp();
                if (lane == 0) flag_release(FL_M);
                TSW(4);
            }
        }
        if (wq == 2) {
            flag_wait(FL_M, ep1 * 120);
            fence_async_global();
            if (elect()) {
                mbar_expect(bars + BAR_M * 8, 7680);
                bulk_g2s(sb + SM_MOD, g_mod, 7680, bars + BAR_M * 8);
            }
            __syncwarp();
            TSW(60);
            bar_sync(8, 544);  if (lane == 0) { flag_release(FL_R + rb); TS(23); }  __syncwarp();
            bar_sync(15, 288); if (lane == 0) { flag_release(FL_B1 + rb); TS(27); } __syncwarp();
            bar_sync(6, 288);  if (lane == 0) { flag_release(FL_B2 + rb); TS(31); } __syncwarp();
#pragma unroll 1
            for (int i = 0; i < 2; i++) { bar_sync(1 + i, 288); if (lane == 0) { TS(53 + i); flag_release(FL_G + 16 * i + rb); TS(57 + i); } __syncwarp(); }
            if (lane == 0) g_epoch[smid] = ep1;
            return;
        }
        if (wq == 1) {
            bar_sync(9, 288);
            if (lane < 4 * NB) mbar_arrive_cl(mapa(bars + (BAR_EB + (lane >> 2)) * 8, paired ? lane & 1 : blockIdx.x & 1));
        }
        if (wq == 3) {
            bar_sync(7, 544);
            if (lane == 0) { flag_release(FL_C); TS(20); }
            __syncwarp();
            if (lane < 2) mbar_expect(bars + (lane ? BAR_Y2 : BAR_Y) * 8, lane ? 8192 : 12288);
            flag_wait_fast(FL_C, ep1 * 128);
            fence_async_global();
            TSW(21);
            if (elect()) {
                bulk_g2s(sb + SM_Y, g_yv + rho * 5120, 12288, bars + BAR_Y * 8);
                bulk_g2s(sb + SM_Y + 12288, g_yv + rho * 5120 + 3072, 8192, bars + BAR_Y2 * 8);
            }
            __syncwarp();
        }
        if (elect()) {
            if (wq == 3) {
                mbar_expect(bars + BAR_XY * 8, 20480);
#pragma unroll 1
                for (int i = 0; i < 8; i++) {
                    bulk_g2s(sb + SM_YT + i * 2560, g_yv + (8 * rb + i) * 5120 + cm * 8, 2048, bars + BAR_XY * 8);
                    bulk_g2s(sb + SM_YT + i * 2560 + 2048, g_yv + (8 * rb + i) * 5120 + cr * 8, 512, bars + BAR_XY * 8);
                }
                mbar_wait(bars + BAR_FA * 8, 0);
                bulk_prefetch((const char*)p.w4 + cta * 17280, 17280);
                flag_wait(FL_CS, ep1 * 4);
                fence_async_global();
                mbar_expect(bars + BAR_CS * 8, 864);
                bulk_g2s(sb + SM_CS, g_cs + 64 * j, 256, bars + BAR_CS * 8);
                bulk_g2s(sb + SM_CS + 256, g_cs + 512 + 48 * j, 192, bars + BAR_CS * 8);
                bulk_g2s(sb + SM_CS + 448, g_cs + 896 + 64 * j, 256, bars + BAR_CS * 8);
                bulk_g2s(sb + SM_CS + 704, g_cs + 1408 + 40 * j, 160, bars + BAR_CS * 8);
                mbar_wait(bars + BAR_ST * 8, 0);
#pragma unroll 1
                for (int i = 0; i < 2; i++) {
                    flag_wait(FL_G + 16 * i + rb, ep1 * 8);
                    mbar_expect(bars + (BAR_G + i) * 8, 0);
                    TS(35 + i);
                }
            } else if (wq == 1) {
                Ring<NB, SM_RB, BAR_FB, BAR_EB> r{sb, 0, 0};
#pragma unroll 1
                for (int ph = 0; ph < 6; ph++) {
                    const CUtensorMap* ma = ph == 0 ? &maps.w1a : ph == 1 ? &maps.w2a : ph == 5 ? &maps.w4a : &maps.w3a;
                    const bool b3b = ph == 3 || ph == 4;
                    r.runw(paired, idx & 1, ma, ma + (b3b ? 2 : 1), ph == 2 ? 64 * j : b3b ? 896 + 64 * j : cm,
                           ph == 2 ? 512 + 48 * j : b3b ? 1408 + 40 * j : cr, ph == 3 ? (10 - NA) * 64 : 0,
                           ph == 5 ? 27 : ph == 3 ? NA : ph == 4 ? 10 - NA : 10, ph == 2 ? 14336 : b3b ? 13312 : 10240);
                }
            } else {
                Ring<NA, SM_RA, BAR_FA, BAR_EA> r{sb, 0, 0};
                if (cta >= 120) mbar_wait(bars + (BAR_K + 4) * 8, 0);
                mbar_expect(bars + BAR_XR * 8, 20480);
                bulk_g2s(sb + SM_XR, p.q + (size_t)rho * 16 * D_, 20480, bars + BAR_XR * 8);
                mbar_expect(bars + BAR_XY * 8, 20480);
                tma2d(sb + SM_XT, &maps.xa, cm, rb * 128, bars + BAR_XY * 8);
                tma2d(sb + SM_XT2, &maps.xb, cr, rb * 128, bars + BAR_XY * 8);
                const int grp = j >> 1;
                const int delta = (grp & 1 ? 1 : -1) * (1 + (grp >> 1));
                const int nb = min(max(rb + (delta > 0 ? 1 : -1), 0), 15);
                uint32_t fb = r.acquire(SLOT), dst = r.slot();
                flag_wait2(FL_R + nb, FL_R + rb, ep1 * 8);
                fence_async_global();
                tma2d(dst, &maps.hn, 0, rb * 128 + delta, fb);
                TS(24);
                r.next();
                r.run2d(&maps.hn, rb * 128 + delta);
#pragma unroll 1
                for (int i = 0; i < 2; i++) {
                    const char* src = (const char*)(i ? g_x1 : g_h1) + (size_t)rb * 163840;
                    fb = r.acquire(SLOT); dst = r.slot();
                    flag_wait_fast(FL_B1 + 16 * i + rb, ep1 * 8);
                    fence_async_global();
                    bulk_g2s(dst, src, SLOT, fb);
                    TS(28 + 4 * i);
                    if (i) mbar_expect(bars + BAR_ST * 8, 0);
                    r.next();
                    r.run1d(src + SLOT, 9);
                }
                r.run1d((const char*)g_x1 + (size_t)rb * 163840, 10 - NA);
#pragma unroll 1
                for (int i = 0; i < 2; i++) {
                    mbar_wait(bars + (BAR_G + i) * 8, 0); fence_async_global();
                    r.run1d((const char*)g_g + (size_t)rb * 442368 + i * 14 * SLOT, 14 - i);
                }
            }
        }
        return;
    }
    bar_arrive(13, 640);
    asm volatile("setmaxnreg.inc.sync.aligned.u32 112;");
    const int rrow = 16 * rho + (warp >> 1) + 8 * (warp & 1);

    fence_async_smem();
    bar_sync(1 + wg, 128);
#pragma unroll 1
    for (int cc = wg; cc < wg + 1 + (wg == 3); cc++) {
        mbar_wait(bars + (BAR_K + cc) * 8, 0);
        if (cc == 2 && wq == 0) TSW(40);
        uint32_t a = sb + sm_k(cc) + 32 + (tid & 127) * 32;
        uint32_t pw = lds32(a - 4);
        uint4 x = lds128(a), y = lds128(a + 16), o;
        if ((tid & 127) == 0) {
            uint16_t k0 = __bfloat16_as_ushort(__float2bfloat16_rn(blo(x.x) + __uint_as_float(lds32(sb + SM_GV + 520 + cc * 4))));
            x.x = (x.x & 0xffff0000u) | k0;
            sts16(a, k0);
        }
        o.x = prmt(pw, x.x, 0x5432); o.y = prmt(x.x, x.y, 0x5432); o.z = prmt(x.y, x.z, 0x5432); o.w = prmt(x.z, x.w, 0x5432);
        sts128(a + 4160, o);
        o.x = prmt(x.w, y.x, 0x5432); o.y = prmt(y.x, y.y, 0x5432); o.z = prmt(y.y, y.z, 0x5432); o.w = prmt(y.z, y.w, 0x5432);
        sts128(a + 4176, o);
    }
    bar_sync(1 + wg, 128);
    if (wg == 3) bar_arrive(11, 256);
#pragma unroll 1
    for (int cc = wg; cc < 5; cc += 3) {
        if (cc == 3 && wg == 0) break;
        if (cc == 4) bar_sync(11, 256);
        const uint32_t kaddr = sb + sm_k(cc) + ((g & 1) ? 32 : 4192) + 4 * ((g >> 1) - c) + 64 * wq;
        const AFrag f0 = ldA(kaddr), f1 = ldA(kaddr + 256);
        if (STAG && cc == 3) bar_sync(12, 256);
        mbar_wait(bars + (BAR_U + cc) * 8, 0);
        if (wq == 0) TSW(5 + cc);
        float d[64];
        conv_two<0>(d, f0, f1, kaddr, desc_lo(sb + sm_u(cc), U_PLANE), sb + sm_red(cc) + wq * 4352 + g * 544 + c * 8, cc == 1);
        if (wq == 0) TSW(10 + cc);
        if (cc == 1) bar_arrive(6, 256);
    }
#pragma unroll 1
    for (int cc = wg == 1 ? 4 : wg;; cc++) {
        if (cc == 1) bar_sync(6, 256); else bar_sync(1 + wg, 128);
        const int ch = cta * 5 + cc;
        uint32_t* dst = g_yv + ch * 8 + ((g + (ch >> 2)) & 7) + (126 - 32 * wq - 2 * c) * 5120;
        uint2 v[16];
#pragma unroll
        for (int i = 0; i < 16; i++) v[i] = lds64(sb + sm_red(cc) + g * 544 + wq * 128 + c * 8 + (i >> 2) * 32 + (i & 3) * 4360);
#pragma unroll
        for (int w = 1; w < 4; w++)
            if (wq == 3 && c > 3 - w) v[12 + w] = make_uint2(0, 0);
#pragma unroll
        for (int q = 0; q < 4; q++) {
            const uint2* u = v + 4 * q;
            dst[-8 * q * 5120] = badd2(u[0].x, badd2(u[1].x, badd2(u[2].x, u[3].x)));
            dst[(-8 * q + 1) * 5120] = badd2(u[0].y, badd2(u[1].y, badd2(u[2].y, u[3].y)));
        }
        if (wq == 0) TSW(15 + cc);
        if (cc != 0) break;
    }
    fence_async_smem();
    if (!(wg & 1)) bar_arrive(9, 288);
    bar_arrive(7, 544);

    const uint32_t one2 = 0x3f803f80u;
    const unsigned ones = p.ones;
    {
        uint32_t x[10], a[10], cb[10], sbv[10];
        if (RPRE_WAIT) bar_sync(10, 512);
        mbar_wait(bars + BAR_XR * 8, 0);
#pragma unroll
        for (int i = 0; i < 10; i++) x[i] = lds32(sb + SM_XR + (rrow & 15) * 1280 + lane * 4 + i * 128);
        const uint3 s1 = row_stats(x, lane);
        const int up = lane >> 4, gg = warp >> 1, e = warp & 1;
        const uint32_t ya = sb + SM_Y + lane * 64 + ((gg + (lane >> 1)) & 7) * 4;
        const uint32_t sel = (up ? 0x1054u : 0x5410u) + (e ? 0x2222u : 0u);
        const uint32_t ma = sb + SM_MOD + lane * 4;
        mbar_wait(bars + BAR_M * 8, 0);
        uint32_t pin = 0;
#pragma unroll
        for (int i = 0; i < 10; i++) {
            uint32_t h = bfma2(ln_apply(x[i], s1.x, s1.y, s1.z), badd2(lds32(ma + 1280 + i * 128), one2), lds32(ma + i * 128));
            a[i] = bmul2(h, lds32(ma + 2560 + i * 128));
            sbv[i] = lds32(ma + 3840 + i * 128);
            cb[i] = badd2(lds32(ma + 5120 + i * 128), one2);
            pin ^= a[i] ^ cb[i];
        }
        if (pin & ~ones) sts32(sb + SM_GV, pin);
        if (warp == 4) TSW(52);
        mbar_wait(bars + BAR_Y * 8, 0);
        if (warp == 0) TSW(22);
#pragma unroll
        for (int i = 0; i < 10; i++) {
            if (i == 6) mbar_wait(bars + BAR_Y2 * 8, 0);
            uint32_t y0 = lds32(ya + i * 2048 + up * 32), y1 = lds32(ya + i * 2048 + (up ^ 1) * 32);
            x[i] = bfma2(a[i], prmt(y0, y1, sel), x[i]);
        }
        const uint3 s2 = row_stats(x, lane);
#pragma unroll
        for (int i = 0; i < 10; i++) x[i] = bfma2(ln_apply(x[i], s2.x, s2.y, s2.z), cb[i], sbv[i]);
        const uint3 s3 = row_stats(x, lane);
        uint32_t* o = reinterpret_cast<uint32_t*>(g_hn + (size_t)rrow * D_) + lane;
#pragma unroll
        for (int i = 0; i < 10; i++) o[32 * i] = ln_apply(x[i], s3.x, s3.y, s3.z);
        if (lane < 2) g_rs[rrow * 2 + lane] = lane ? make_uint4(s2.x, s2.y, s2.z, 0) : make_uint4(s1.x, s1.y, s1.z, 0);
        if (warp == 0) TSW(34);
        bar_arrive(8, 544);
    }

    const int half = wg & 1;
    const int row = 64 * half + 16 * wq + g;
    const int tw0 = (rb * 80 + (cm >> 3)) * 512 + row * 4 + c, tw1 = (rb * 80 + (cr >> 3) - 8) * 512 + row * 4 + c;
    const uint32_t park = sb + SM_Y + (tid & 255) * 16;
    const uint32_t ms0 = sb + SM_MOD + (cm + 2 * c) * 2, ms1 = sb + SM_MOD + (cr - 64 + 2 * c) * 2;
    if (wg >= 2) {
        {
            float acc[40];
            gemm_loop<80, true, 10, 10, true>(acc, sb, half, 0, 0, 10, 0, 0, 25);
#pragma unroll
            for (int k = 0; k < 10; k += CH) CHUNK(k) {
#pragma unroll
                for (int q = k; q < k + CH && q < 10; q++) {
                    uint32_t* dst = reinterpret_cast<uint32_t*>(g_h1) + (q < 8 ? tw0 : tw1);
                    dst[q * 512] = gelu2_h(bmul2(pack2(acc[4 * q], acc[4 * q + 1]), 0x3f003f00u));
                    dst[q * 512 + 32] = gelu2_h(bmul2(pack2(acc[4 * q + 2], acc[4 * q + 3]), 0x3f003f00u));
                }
            }
            bar_arrive(15, 288);
            bar_arrive(14, 512);
        }
        gemm3<0>(sb, rb, j, half, row, c, ones);
        {
            float acc[40];
            uint32_t gbv[10], base[20];
#pragma unroll
            for (int q = 0; q < 10; q++) gbv[q] = lds32((q < 8 ? ms0 : ms1) + 6400 + q * 16);
#pragma unroll
            for (int q = 0; q < 5; q++) { const uint4 t = lds128(park + q * 4096); base[4 * q] = t.x; base[4 * q + 1] = t.y; base[4 * q + 2] = t.z; base[4 * q + 3] = t.w; }
            gemm_loop<80, false, 27, 27 - NB, true>(acc, sb, half, 40 - NA, 40, 27 - NA, 11, 0, 42);
            auto fin = [&](int q, int r) {
                return bfma2(gbv[q], pack2(acc[4 * q + 2 * r], acc[4 * q + 2 * r + 1]), base[2 * q + r]);
            };
            auto tr4 = [&](uint32_t t0, uint32_t t1, uint32_t t2, uint32_t t3) {
                const bool o1 = c & 1, o2 = c & 2;
                uint32_t a = __shfl_xor_sync(0xffffffffu, o1 ? t0 : t1, 1), b = __shfl_xor_sync(0xffffffffu, o1 ? t2 : t3, 1);
                uint32_t u0 = o1 ? a : t0, u1 = o1 ? t1 : a, u2 = o1 ? b : t2, u3 = o1 ? t3 : b;
                a = __shfl_xor_sync(0xffffffffu, o2 ? u0 : u2, 2); b = __shfl_xor_sync(0xffffffffu, o2 ? u1 : u3, 2);
                return o2 ? make_uint4(a, b, u2, u3) : make_uint4(u0, u1, a, b);
            };
            bf16* go = p.out + (size_t)(rb * 128 + row) * D_;
#pragma unroll
            for (int k = 0; k < 2; k++) CHUNK(k) {
#pragma unroll
                for (int r = 0; r < 2; r++)
                    *reinterpret_cast<uint4*>(go + r * 8 * D_ + cm + 32 * k + 8 * c) = tr4(fin(4 * k, r), fin(4 * k + 1, r), fin(4 * k + 2, r), fin(4 * k + 3, r));
            }
            CHUNK(2) *reinterpret_cast<uint4*>(go + (c >> 1) * 8 * D_ + cr + 8 * (c & 1)) = tr4(fin(8, 0), fin(9, 0), fin(8, 1), fin(9, 1));
            if (tid == 256) TS(44);
            if (warp == 8) TSFLUSH();
        }
    } else {
        {
            float acc[40];
            uint32_t x2[20];
            {
                uint32_t y[20];
                mbar_wait(bars + BAR_XY * 8, 0);
                const uint32_t xa = sb + SM_XT + row * 128 + c * 4, xb = sb + SM_XT2 + row * 32 + c * 4;
                const uint32_t ya = sb + SM_YT + (4 * half + wq) * 2560 + c * 64;
#pragma unroll
                for (int q = 0; q < 10; q++) {
                    const uint32_t a = q < 8 ? xa + ((q ^ g) << 4) : xb + (q - 8) * 16;
                    x2[2 * q] = lds32(a); x2[2 * q + 1] = lds32(a + (q < 8 ? 1024 : 256));
                    const int pos = (g + ((q < 8 ? cm : cr) >> 2) + 2 * q + (c >> 1)) & 7;
                    y[2 * q] = lds32(ya + q * 256 + pos * 4); y[2 * q + 1] = lds32(ya + q * 256 + 32 + pos * 4);
                }
                fence_async_smem();
                bar_sync(1 + wg, 128);
                if ((tid & 127) < NA) mbar_arrive_cl(mapa(bars + (BAR_EA + (tid & 127)) * 8, blockIdx.x & 1));
                mbar_wait(bars + (BAR_FA + 1) * 8, 0);
                const uint4* rp = g_rs + (rb * 128 + row) * 2;
                const uint4 ra = ldcg128(rp), rb2 = ldcg128(rp + 1), rc = ldcg128(rp + 16), rd = ldcg128(rp + 17);
                bar_sync(14, 512);
#pragma unroll
                for (int q = 0; q < 10; q++) {
                    const uint32_t ms = q < 8 ? ms0 : ms1;
                    const uint32_t sa = lds32(ms + 16 * q), ca = badd2(lds32(ms + 1280 + 16 * q), one2), ga = lds32(ms + 2560 + 16 * q);
                    const uint32_t sbv = lds32(ms + 3840 + 16 * q), cb = badd2(lds32(ms + 5120 + 16 * q), one2);
                    uint32_t u = x2[2 * q], v = x2[2 * q + 1];
                    u = bfma2(bmul2(bfma2(ln_apply(u, ra.x, ra.y, ra.z), ca, sa), ga), prmt(y[2 * q], y[2 * q + 1], 0x5410), u);
                    v = bfma2(bmul2(bfma2(ln_apply(v, rc.x, rc.y, rc.z), ca, sa), ga), prmt(y[2 * q], y[2 * q + 1], 0x7632), v);
                    x2[2 * q] = u; x2[2 * q + 1] = v;
                    u = bfma2(ln_apply(u, rb2.x, rb2.y, rb2.z), cb, sbv);
                    v = bfma2(ln_apply(v, rd.x, rd.y, rd.z), cb, sbv);
                    acc[4 * q] = blo(u); acc[4 * q + 1] = bhi(u); acc[4 * q + 2] = blo(v); acc[4 * q + 3] = bhi(v);
                }
            }
            reg_fence<40>(acc);
            if (tid == 0) TS(45);
            gemm_loop<80, false, 10, 10, false>(acc, sb, half, 10, 10, 10, 0, 9, 29);
            uint32_t x1[20];
            float s0 = 0.f, q0 = 0.f, s1 = 0.f, q1 = 0.f;
#pragma unroll
            for (int q = 0; q < 10; q++) {
                uint32_t u = pack2(acc[4 * q], acc[4 * q + 1]);
                uint32_t v = pack2(acc[4 * q + 2], acc[4 * q + 3]);
                uint32_t* dst = reinterpret_cast<uint32_t*>(g_x1) + (q < 8 ? tw0 : tw1);
                dst[q * 512] = u;
                dst[q * 512 + 32] = v;
                x1[2 * q] = u; x1[2 * q + 1] = v;
            }
            CHUNK(0)
#pragma unroll
            for (int q = 0; q < 10; q++) {
                float a = blo(x1[2 * q]), b = bhi(x1[2 * q]), e = blo(x1[2 * q + 1]), f = bhi(x1[2 * q + 1]);
                s0 += a + b; q0 = fmaf(a, a, fmaf(b, b, q0));
                s1 += e + f; q1 = fmaf(e, e, fmaf(f, f, q1));
            }
#pragma unroll
            for (int m = 1; m <= 2; m <<= 1) {
                s0 += __shfl_xor_sync(0xffffffffu, s0, m); q0 += __shfl_xor_sync(0xffffffffu, q0, m);
                s1 += __shfl_xor_sync(0xffffffffu, s1, m); q1 += __shfl_xor_sync(0xffffffffu, q1, m);
            }
            if (c < 2) g_st[(rb * 8 + j) * 128 + row + 8 * c] = c ? make_float2(s1, q1) : make_float2(s0, q0);
            bar_arrive(6, 288);
#pragma unroll
            for (int q = 0; q < 5; q++) {
                const uint32_t ms = q < 4 ? ms0 : ms1;
                const uint32_t g0 = lds32(ms + 6400 + q * 32), g1 = lds32(ms + 6400 + q * 32 + 16);
                sts128(park + q * 4096, make_uint4(bfma2(g0, x1[4 * q], x2[4 * q]), bfma2(g0, x1[4 * q + 1], x2[4 * q + 1]),
                                                   bfma2(g1, x1[4 * q + 2], x2[4 * q + 2]), bfma2(g1, x1[4 * q + 3], x2[4 * q + 3])));
            }
        }
        gemm3<1>(sb, rb, j, half, row, c, ones);
    }
}

typedef CUresult (*EncFn)(CUtensorMap*, CUtensorMapDataType, cuuint32_t, void*, const cuuint64_t*, const cuuint64_t*,
                          const cuuint32_t*, const cuuint32_t*, CUtensorMapInterleave, CUtensorMapSwizzle,
                          CUtensorMapL2promotion, CUtensorMapFloatOOBfill);

void make_map(EncFn enc, CUtensorMap* m, const void* base, uint64_t inner, uint64_t outer, uint32_t bi, uint32_t bo,
              CUtensorMapSwizzle swz = CU_TENSOR_MAP_SWIZZLE_128B) {
    cuuint64_t dims[2] = {inner, outer};
    cuuint64_t st[1] = {inner * 2};
    cuuint32_t box[2] = {bi, bo};
    cuuint32_t es[2] = {1, 1};
    enc(m, CU_TENSOR_MAP_DATA_TYPE_BFLOAT16, 2, const_cast<void*>(base), dims, st, box, es, CU_TENSOR_MAP_INTERLEAVE_NONE,
        swz, CU_TENSOR_MAP_L2_PROMOTION_NONE, CU_TENSOR_MAP_FLOAT_OOB_FILL_NONE);
}

}

extern "C" void kernel_launch(void* const* d_in, const int* in_sizes, int n_in, void* d_out, int out_size) {
    (void)in_sizes; (void)n_in; (void)out_size;
    Params p;
    p.q = (const bf16*)d_in[0]; p.k = (const bf16*)d_in[1]; p.v = (const bf16*)d_in[2];
    p.shift = (const bf16*)d_in[3]; p.ssmk = (const bf16*)d_in[4]; p.ssmD = (const bf16*)d_in[5];
    p.w1 = (const bf16*)d_in[7]; p.w2 = (const bf16*)d_in[8]; p.w3 = (const bf16*)d_in[9]; p.w4 = (const bf16*)d_in[10];
    p.c = (const bf16*)d_in[11]; p.wmod = (const bf16*)d_in[12];
    p.out = (bf16*)d_out;
    p.ones = 0xffffffffu;

    void* fn = nullptr;
    cudaDriverEntryPointQueryResult qr;
    cudaGetDriverEntryPoint("cuTensorMapEncodeTiled", &fn, cudaEnableDefault, &qr);
    EncFn enc = (EncFn)fn;
    void* hn = nullptr;
    cudaGetSymbolAddress(&hn, g_hn);
    Maps maps;
    make_map(enc, &maps.w3s, p.w3, F_, D_, 216, 64, CU_TENSOR_MAP_SWIZZLE_NONE);
    make_map(enc, &maps.wm, p.wmod, 6 * D_, D_, 32, 128, CU_TENSOR_MAP_SWIZZLE_64B);
    make_map(enc, &maps.xa, p.q, D_, S_, 64, 128);
    make_map(enc, &maps.xb, p.q, D_, S_, 16, 128, CU_TENSOR_MAP_SWIZZLE_NONE);
    make_map(enc, &maps.hn, hn, D_, S_, 64, 128);
    make_map(enc, &maps.w1a, p.w1, D_, D_, 64, 64);
    make_map(enc, &maps.w1b, p.w1, D_, D_, 16, 64);
    make_map(enc, &maps.w2a, p.w2, D_, D_, 64, 64);
    make_map(enc, &maps.w2b, p.w2, D_, D_, 16, 64);
    make_map(enc, &maps.w3a, p.w3, F_, D_, 64, 64);
    make_map(enc, &maps.w3b, p.w3, F_, D_, 48, 64);
    make_map(enc, &maps.w3c, p.w3, F_, D_, 40, 64);
    make_map(enc, &maps.w4a, p.w4, D_, F_, 64, 64);
    make_map(enc, &maps.w4b, p.w4, D_, F_, 16, 64);
    cudaFuncSetAttribute(fused_kernel, cudaFuncAttributeMaxDynamicSharedMemorySize, SMEM_BYTES);
    fused_kernel<<<132, NTHREADS, SMEM_BYTES>>>(p, maps);
}
```

```cpp
#include <cuda_runtime.h>
#include <cuda_bf16.h>
#include <cuda.h>
#include <stdint.h>
#include <string.h>

#define SEED 0
#define RING_A 6
#define MMA_STAT 0
#define CH 2
#define FAST_LN 2
#define STAG 10
#define REDM 1
#define CONVV 0
#define NPOLL 1
#define PGELU 2
#define CH3 4
#define HO_A 14
#define HO_B 14
#define LATE 0
#define HOLD 1
#define SSM_DELAY 0
#define B_DELAY 300
#define RPRE_WAIT 1
#define OWN 1
#define XAFTER 0
#define SSM_N 3
#define PF_EARLY 0

namespace {

typedef __nv_bfloat16 bf16;
typedef __nv_bfloat162 bf162;

constexpr int S_ = 2048, D_ = 640, F_ = 1728;
constexpr int NTHREADS = 640;
constexpr int NA = RING_A, NB = 12 - RING_A;
constexpr int SLOT = 16384;
constexpr int SM_RA = 0, SM_RB = NA * SLOT;

static_assert(NA == 6, "smem map");
constexpr int RED_STRIDE = 17536;
constexpr int K_STRIDE = 8320;
constexpr int U_PLANE = 2560, U_STRIDE = 5120;
constexpr int SM_Y = 12 * SLOT;
__device__ __forceinline__ int sm_red(int cc) { return cc * RED_STRIDE + (cc < 3 ? SM_RB : -3 * RED_STRIDE); }
__device__ __forceinline__ int sm_k(int cc) { return cc * K_STRIDE + (cc < 3 ? SM_RB + 3 * RED_STRIDE : 2 * RED_STRIDE - 3 * K_STRIDE); }
__device__ __forceinline__ int sm_u(int cc) { return cc * U_STRIDE + (cc < 3 ? SM_RB + 3 * RED_STRIDE + 3 * K_STRIDE : SM_Y + 8192 - 3 * U_STRIDE); }
constexpr int SM_PK = SM_RB;
constexpr int SM_PV = SM_RB + 24576;
constexpr int SM_WM = 57344;
constexpr int SM_XT = SM_WM, SM_XT2 = SM_WM + 16384, SM_XR = SM_WM + 20480;
constexpr int SM_YT = 0;
constexpr int SM_MOD = SM_Y + 20480;
constexpr int SM_GV = SM_MOD + 7680;
constexpr int SM_CS = SM_GV + 1024;
constexpr int SM_RP = SM_CS + 1024;
constexpr int SM_BAR = SM_RP + 1024;
constexpr int SM_PROF = SM_BAR + 512;
constexpr int SM_TOTAL = SM_PROF + 512;
constexpr int SMEM_BYTES = SM_TOTAL + 1024;
static_assert(SMEM_BYTES <= 232448, "smem");

constexpr int BAR_FA = 0, BAR_FB = NA, BAR_EA = 12, BAR_EB = 12 + NA, BAR_K = 24, BAR_U = 29, BAR_Y = 34, BAR_CS = 35, BAR_WM = 36, BAR_M = 37, BAR_XY = 38, BAR_Y2 = 39, BAR_G = 40, BAR_ST = 43, BAR_XR = 44, NBARS = 45;

__device__ __align__(1024) bf16 g_kvT[D_ * S_];
__device__ __align__(1024) uint32_t g_yv[128 * 5120];
__device__ __align__(1024) bf16 g_mod[6 * D_];
__device__ __align__(1024) bf16 g_hn[S_ * D_];
__device__ __align__(1024) uint4 g_rs[S_ * 2];
__device__ __align__(1024) bf16 g_h1[S_ * D_];
__device__ __align__(1024) bf16 g_x1[S_ * D_];
__device__ __align__(1024) bf16 g_g[S_ * F_];
__device__ __align__(1024) float2 g_st[S_ * 8];
__device__ __align__(1024) float g_cs[F_];
__device__ __align__(1024) unsigned g_flags[128 * 32];
__device__ __align__(1024) unsigned g_epoch[160];
constexpr int FL_P = 0, FL_C = 8, FL_CS = 9, FL_M = 10, FL_R = 16, FL_B1 = 32, FL_B2 = 48, FL_G = 64;

#define TS(i) do {} while (0)
#define TSW(i) do {} while (0)
#define TSD(i, dep) do {} while (0)
#define TSD2(i, dep) do {} while (0)
#define TSFLUSH() do {} while (0)

struct Params {
    const bf16 *q, *k, *v, *shift, *ssmk, *ssmD, *w1, *w2, *w3, *w4, *c, *wmod;
    bf16* out;
    unsigned ones;
};
#define CHUNK(k) if (ones & (1u << (k)))
struct Maps { CUtensorMap hn, w1a, w1b, w2a, w2b, w3a, w3b, w3c, w4a, w4b, wm, xa, xb, w3s; };

template<int N> struct WgRs;
template<int N> struct WgSs;
template<> struct WgRs<32> { template<int OFF,int HI,int SC> static __device__ __forceinline__ void run(float* d,uint32_t a0,uint32_t a1,uint32_t a2,uint32_t a3,uint32_t blo){
 asm volatile("{.reg .b32 l; .reg .b64 db; add.u32 l,%20,%21; mov.b64 db,{l,%22}; wgmma.mma_async.sync.aligned.m64n32k16.f32.bf16.bf16 {%0,%1,%2,%3,%4,%5,%6,%7,%8,%9,%10,%11,%12,%13,%14,%15},{%16,%17,%18,%19},db,%23,1,1,0;}"
 :"+f"(d[0]),"+f"(d[1]),"+f"(d[2]),"+f"(d[3]),"+f"(d[4]),"+f"(d[5]),"+f"(d[6]),"+f"(d[7]),"+f"(d[8]),"+f"(d[9]),"+f"(d[10]),"+f"(d[11]),"+f"(d[12]),"+f"(d[13]),"+f"(d[14]),"+f"(d[15])
 :"r"(a0),"r"(a1),"r"(a2),"r"(a3),"r"(blo),"n"(OFF),"n"(HI),"n"(SC)); } };
template<> struct WgRs<48> { template<int OFF,int HI,int SC> static __device__ __forceinline__ void run(float* d,uint32_t a0,uint32_t a1,uint32_t a2,uint32_t a3,uint32_t blo){
 asm volatile("{.reg .b32 l; .reg .b64 db; add.u32 l,%28,%29; mov.b64 db,{l,%30}; wgmma.mma_async.sync.aligned.m64n48k16.f32.bf16.bf16 {%0,%1,%2,%3,%4,%5,%6,%7,%8,%9,%10,%11,%12,%13,%14,%15,%16,%17,%18,%19,%20,%21,%22,%23},{%24,%25,%26,%27},db,%31,1,1,0;}"
 :"+f"(d[0]),"+f"(d[1]),"+f"(d[2]),"+f"(d[3]),"+f"(d[4]),"+f"(d[5]),"+f"(d[6]),"+f"(d[7]),"+f"(d[8]),"+f"(d[9]),"+f"(d[10]),"+f"(d[11]),"+f"(d[12]),"+f"(d[13]),"+f"(d[14]),"+f"(d[15]),"+f"(d[16]),"+f"(d[17]),"+f"(d[18]),"+f"(d[19]),"+f"(d[20]),"+f"(d[21]),"+f"(d[22]),"+f"(d[23])
 :"r"(a0),"r"(a1),"r"(a2),"r"(a3),"r"(blo),"n"(OFF),"n"(HI),"n"(SC)); } };
template<> struct WgRs<64> { template<int OFF,int HI,int SC> static __device__ __forceinline__ void run(float* d,uint32_t a0,uint32_t a1,uint32_t a2,uint32_t a3,uint32_t blo){
 asm volatile("{.reg .b32 l; .reg .b64 db; add.u32 l,%36,%37; mov.b64 db,{l,%38}; wgmma.mma_async.sync.aligned.m64n64k16.f32.bf16.bf16 {%0,%1,%2,%3,%4,%5,%6,%7,%8,%9,%10,%11,%12,%13,%14,%15,%16,%17,%18,%19,%20,%21,%22,%23,%24,%25,%26,%27,%28,%29,%30,%31},{%32,%33,%34,%35},db,%39,1,1,0;}"
 :"+f"(d[0]),"+f"(d[1]),"+f"(d[2]),"+f"(d[3]),"+f"(d[4]),"+f"(d[5]),"+f"(d[6]),"+f"(d[7]),"+f"(d[8]),"+f"(d[9]),"+f"(d[10]),"+f"(d[11]),"+f"(d[12]),"+f"(d[13]),"+f"(d[14]),"+f"(d[15]),"+f"(d[16]),"+f"(d[17]),"+f"(d[18]),"+f"(d[19]),"+f"(d[20]),"+f"(d[21]),"+f"(d[22]),"+f"(d[23]),"+f"(d[24]),"+f"(d[25]),"+f"(d[26]),"+f"(d[27]),"+f"(d[28]),"+f"(d[29]),"+f"(d[30]),"+f"(d[31])
 :"r"(a0),"r"(a1),"r"(a2),"r"(a3),"r"(blo),"n"(OFF),"n"(HI),"n"(SC)); } };
template<> struct WgRs<80> { template<int OFF,int HI,int SC> static __device__ __forceinline__ void run(float* d,uint32_t a0,uint32_t a1,uint32_t a2,uint32_t a3,uint32_t blo){
 asm volatile("{.reg .b32 l; .reg .b64 db; add.u32 l,%44,%45; mov.b64 db,{l,%46}; wgmma.mma_async.sync.aligned.m64n80k16.f32.bf16.bf16 {%0,%1,%2,%3,%4,%5,%6,%7,%8,%9,%10,%11,%12,%13,%14,%15,%16,%17,%18,%19,%20,%21,%22,%23,%24,%25,%26,%27,%28,%29,%30,%31,%32,%33,%34,%35,%36,%37,%38,%39},{%40,%41,%42,%43},db,%47,1,1,0;}"
 :"+f"(d[0]),"+f"(d[1]),"+f"(d[2]),"+f"(d[3]),"+f"(d[4]),"+f"(d[5]),"+f"(d[6]),"+f"(d[7]),"+f"(d[8]),"+f"(d[9]),"+f"(d[10]),"+f"(d[11]),"+f"(d[12]),"+f"(d[13]),"+f"(d[14]),"+f"(d[15]),"+f"(d[16]),"+f"(d[17]),"+f"(d[18]),"+f"(d[19]),"+f"(d[20]),"+f"(d[21]),"+f"(d[22]),"+f"(d[23]),"+f"(d[24]),"+f"(d[25]),"+f"(d[26]),"+f"(d[27]),"+f"(d[28]),"+f"(d[29]),"+f"(d[30]),"+f"(d[31]),"+f"(d[32]),"+f"(d[33]),"+f"(d[34]),"+f"(d[35]),"+f"(d[36]),"+f"(d[37]),"+f"(d[38]),"+f"(d[39])
 :"r"(a0),"r"(a1),"r"(a2),"r"(a3),"r"(blo),"n"(OFF),"n"(HI),"n"(SC)); } };
template<> struct WgRs<96> { template<int OFF,int HI,int SC> static __device__ __forceinline__ void run(float* d,uint32_t a0,uint32_t a1,uint32_t a2,uint32_t a3,uint32_t blo){
 asm volatile("{.reg .b32 l; .reg .b64 db; add.u32 l,%52,%53; mov.b64 db,{l,%54}; wgmma.mma_async.sync.aligned.m64n96k16.f32.bf16.bf16 {%0,%1,%2,%3,%4,%5,%6,%7,%8,%9,%10,%11,%12,%13,%14,%15,%16,%17,%18,%19,%20,%21,%22,%23,%24,%25,%26,%27,%28,%29,%30,%31,%32,%33,%34,%35,%36,%37,%38,%39,%40,%41,%42,%43,%44,%45,%46,%47},{%48,%49,%50,%51},db,%55,1,1,0;}"
 :"+f"(d[0]),"+f"(d[1]),"+f"(d[2]),"+f"(d[3]),"+f"(d[4]),"+f"(d[5]),"+f"(d[6]),"+f"(d[7]),"+f"(d[8]),"+f"(d[9]),"+f"(d[10]),"+f"(d[11]),"+f"(d[12]),"+f"(d[13]),"+f"(d[14]),"+f"(d[15]),"+f"(d[16]),"+f"(d[17]),"+f"(d[18]),"+f"(d[19]),"+f"(d[20]),"+f"(d[21]),"+f"(d[22]),"+f"(d[23]),"+f"(d[24]),"+f"(d[25]),"+f"(d[26]),"+f"(d[27]),"+f"(d[28]),"+f"(d[29]),"+f"(d[30]),"+f"(d[31]),"+f"(d[32]),"+f"(d[33]),"+f"(d[34]),"+f"(d[35]),"+f"(d[36]),"+f"(d[37]),"+f"(d[38]),"+f"(d[39]),"+f"(d[40]),"+f"(d[41]),"+f"(d[42]),"+f"(d[43]),"+f"(d[44]),"+f"(d[45]),"+f"(d[46]),"+f"(d[47])
 :"r"(a0),"r"(a1),"r"(a2),"r"(a3),"r"(blo),"n"(OFF),"n"(HI),"n"(SC)); } };
template<> struct WgRs<112> { template<int OFF,int HI,int SC> static __device__ __forceinline__ void run(float* d,uint32_t a0,uint32_t a1,uint32_t a2,uint32_t a3,uint32_t blo){
 asm volatile("{.reg .b32 l; .reg .b64 db; add.u32 l,%60,%61; mov.b64 db,{l,%62}; wgmma.mma_async.sync.aligned.m64n112k16.f32.bf16.bf16 {%0,%1,%2,%3,%4,%5,%6,%7,%8,%9,%10,%11,%12,%13,%14,%15,%16,%17,%18,%19,%20,%21,%22,%23,%24,%25,%26,%27,%28,%29,%30,%31,%32,%33,%34,%35,%36,%37,%38,%39,%40,%41,%42,%43,%44,%45,%46,%47,%48,%49,%50,%51,%52,%53,%54,%55},{%56,%57,%58,%59},db,%63,1,1,0;}"
 :"+f"(d[0]),"+f"(d[1]),"+f"(d[2]),"+f"(d[3]),"+f"(d[4]),"+f"(d[5]),"+f"(d[6]),"+f"(d[7]),"+f"(d[8]),"+f"(d[9]),"+f"(d[10]),"+f"(d[11]),"+f"(d[12]),"+f"(d[13]),"+f"(d[14]),"+f"(d[15]),"+f"(d[16]),"+f"(d[17]),"+f"(d[18]),"+f"(d[19]),"+f"(d[20]),"+f"(d[21]),"+f"(d[22]),"+f"(d[23]),"+f"(d[24]),"+f"(d[25]),"+f"(d[26]),"+f"(d[27]),"+f"(d[28]),"+f"(d[29]),"+f"(d[30]),"+f"(d[31]),"+f"(d[32]),"+f"(d[33]),"+f"(d[34]),"+f"(d[35]),"+f"(d[36]),"+f"(d[37]),"+f"(d[38]),"+f"(d[39]),"+f"(d[40]),"+f"(d[41]),"+f"(d[42]),"+f"(d[43]),"+f"(d[44]),"+f"(d[45]),"+f"(d[46]),"+f"(d[47]),"+f"(d[48]),"+f"(d[49]),"+f"(d[50]),"+f"(d[51]),"+f"(d[52]),"+f"(d[53]),"+f"(d[54]),"+f"(d[55])
 :"r"(a0),"r"(a1),"r"(a2),"r"(a3),"r"(blo),"n"(OFF),"n"(HI),"n"(SC)); } };
template<> struct WgRs<128> { template<int OFF,int HI,int SC> static __device__ __forceinline__ void run(float* d,uint32_t a0,uint32_t a1,uint32_t a2,uint32_t a3,uint32_t blo){
 asm volatile("{.reg .b32 l; .reg .b64 db; add.u32 l,%68,%69; mov.b64 db,{l,%70}; wgmma.mma_async.sync.aligned.m64n128k16.f32.bf16.bf16 {%0,%1,%2,%3,%4,%5,%6,%7,%8,%9,%10,%11,%12,%13,%14,%15,%16,%17,%18,%19,%20,%21,%22,%23,%24,%25,%26,%27,%28,%29,%30,%31,%32,%33,%34,%35,%36,%37,%38,%39,%40,%41,%42,%43,%44,%45,%46,%47,%48,%49,%50,%51,%52,%53,%54,%55,%56,%57,%58,%59,%60,%61,%62,%63},{%64,%65,%66,%67},db,%71,1,1,0;}"
 :"+f"(d[0]),"+f"(d[1]),"+f"(d[2]),"+f"(d[3]),"+f"(d[4]),"+f"(d[5]),"+f"(d[6]),"+f"(d[7]),"+f"(d[8]),"+f"(d[9]),"+f"(d[10]),"+f"(d[11]),"+f"(d[12]),"+f"(d[13]),"+f"(d[14]),"+f"(d[15]),"+f"(d[16]),"+f"(d[17]),"+f"(d[18]),"+f"(d[19]),"+f"(d[20]),"+f"(d[21]),"+f"(d[22]),"+f"(d[23]),"+f"(d[24]),"+f"(d[25]),"+f"(d[26]),"+f"(d[27]),"+f"(d[28]),"+f"(d[29]),"+f"(d[30]),"+f"(d[31]),"+f"(d[32]),"+f"(d[33]),"+f"(d[34]),"+f"(d[35]),"+f"(d[36]),"+f"(d[37]),"+f"(d[38]),"+f"(d[39]),"+f"(d[40]),"+f"(d[41]),"+f"(d[42]),"+f"(d[43]),"+f"(d[44]),"+f"(d[45]),"+f"(d[46]),"+f"(d[47]),"+f"(d[48]),"+f"(d[49]),"+f"(d[50]),"+f"(d[51]),"+f"(d[52]),"+f"(d[53]),"+f"(d[54]),"+f"(d[55]),"+f"(d[56]),"+f"(d[57]),"+f"(d[58]),"+f"(d[59]),"+f"(d[60]),"+f"(d[61]),"+f"(d[62]),"+f"(d[63])
 :"r"(a0),"r"(a1),"r"(a2),"r"(a3),"r"(blo),"n"(OFF),"n"(HI),"n"(SC)); } };
template<> struct WgSs<80> { template<int AOFF,int AHI,int BOFF,int BHI,int SC> static __device__ __forceinline__ void run(float* d,uint32_t alo,uint32_t blo){
 asm volatile("{.reg .b32 l,m; .reg .b64 da,db; add.u32 l,%40,%42; mov.b64 da,{l,%43}; add.u32 m,%41,%44; mov.b64 db,{m,%45}; wgmma.mma_async.sync.aligned.m64n80k16.f32.bf16.bf16 {%0,%1,%2,%3,%4,%5,%6,%7,%8,%9,%10,%11,%12,%13,%14,%15,%16,%17,%18,%19,%20,%21,%22,%23,%24,%25,%26,%27,%28,%29,%30,%31,%32,%33,%34,%35,%36,%37,%38,%39},da,db,%46,1,1,0,1;}"
 :"+f"(d[0]),"+f"(d[1]),"+f"(d[2]),"+f"(d[3]),"+f"(d[4]),"+f"(d[5]),"+f"(d[6]),"+f"(d[7]),"+f"(d[8]),"+f"(d[9]),"+f"(d[10]),"+f"(d[11]),"+f"(d[12]),"+f"(d[13]),"+f"(d[14]),"+f"(d[15]),"+f"(d[16]),"+f"(d[17]),"+f"(d[18]),"+f"(d[19]),"+f"(d[20]),"+f"(d[21]),"+f"(d[22]),"+f"(d[23]),"+f"(d[24]),"+f"(d[25]),"+f"(d[26]),"+f"(d[27]),"+f"(d[28]),"+f"(d[29]),"+f"(d[30]),"+f"(d[31]),"+f"(d[32]),"+f"(d[33]),"+f"(d[34]),"+f"(d[35]),"+f"(d[36]),"+f"(d[37]),"+f"(d[38]),"+f"(d[39])
 :"r"(alo),"r"(blo),"n"(AOFF),"n"(AHI),"n"(BOFF),"n"(BHI),"n"(SC)); } };
template<> struct WgSs<104> { template<int AOFF,int AHI,int BOFF,int BHI,int SC> static __device__ __forceinline__ void run(float* d,uint32_t alo,uint32_t blo){
 asm volatile("{.reg .b32 l,m; .reg .b64 da,db; add.u32 l,%52,%54; mov.b64 da,{l,%55}; add.u32 m,%53,%56; mov.b64 db,{m,%57}; wgmma.mma_async.sync.aligned.m64n104k16.f32.bf16.bf16 {%0,%1,%2,%3,%4,%5,%6,%7,%8,%9,%10,%11,%12,%13,%14,%15,%16,%17,%18,%19,%20,%21,%22,%23,%24,%25,%26,%27,%28,%29,%30,%31,%32,%33,%34,%35,%36,%37,%38,%39,%40,%41,%42,%43,%44,%45,%46,%47,%48,%49,%50,%51},da,db,%58,1,1,0,1;}"
 :"+f"(d[0]),"+f"(d[1]),"+f"(d[2]),"+f"(d[3]),"+f"(d[4]),"+f"(d[5]),"+f"(d[6]),"+f"(d[7]),"+f"(d[8]),"+f"(d[9]),"+f"(d[10]),"+f"(d[11]),"+f"(d[12]),"+f"(d[13]),"+f"(d[14]),"+f"(d[15]),"+f"(d[16]),"+f"(d[17]),"+f"(d[18]),"+f"(d[19]),"+f"(d[20]),"+f"(d[21]),"+f"(d[22]),"+f"(d[23]),"+f"(d[24]),"+f"(d[25]),"+f"(d[26]),"+f"(d[27]),"+f"(d[28]),"+f"(d[29]),"+f"(d[30]),"+f"(d[31]),"+f"(d[32]),"+f"(d[33]),"+f"(d[34]),"+f"(d[35]),"+f"(d[36]),"+f"(d[37]),"+f"(d[38]),"+f"(d[39]),"+f"(d[40]),"+f"(d[41]),"+f"(d[42]),"+f"(d[43]),"+f"(d[44]),"+f"(d[45]),"+f"(d[46]),"+f"(d[47]),"+f"(d[48]),"+f"(d[49]),"+f"(d[50]),"+f"(d[51])
 :"r"(alo),"r"(blo),"n"(AOFF),"n"(AHI),"n"(BOFF),"n"(BHI),"n"(SC)); } };
template<> struct WgSs<112> { template<int AOFF,int AHI,int BOFF,int BHI,int SC> static __device__ __forceinline__ void run(float* d,uint32_t alo,uint32_t blo){
 asm volatile("{.reg .b32 l,m; .reg .b64 da,db; add.u32 l,%56,%58; mov.b64 da,{l,%59}; add.u32 m,%57,%60; mov.b64 db,{m,%61}; wgmma.mma_async.sync.aligned.m64n112k16.f32.bf16.bf16 {%0,%1,%2,%3,%4,%5,%6,%7,%8,%9,%10,%11,%12,%13,%14,%15,%16,%17,%18,%19,%20,%21,%22,%23,%24,%25,%26,%27,%28,%29,%30,%31,%32,%33,%34,%35,%36,%37,%38,%39,%40,%41,%42,%43,%44,%45,%46,%47,%48,%49,%50,%51,%52,%53,%54,%55},da,db,%62,1,1,0,1;}"
 :"+f"(d[0]),"+f"(d[1]),"+f"(d[2]),"+f"(d[3]),"+f"(d[4]),"+f"(d[5]),"+f"(d[6]),"+f"(d[7]),"+f"(d[8]),"+f"(d[9]),"+f"(d[10]),"+f"(d[11]),"+f"(d[12]),"+f"(d[13]),"+f"(d[14]),"+f"(d[15]),"+f"(d[16]),"+f"(d[17]),"+f"(d[18]),"+f"(d[19]),"+f"(d[20]),"+f"(d[21]),"+f"(d[22]),"+f"(d[23]),"+f"(d[24]),"+f"(d[25]),"+f"(d[26]),"+f"(d[27]),"+f"(d[28]),"+f"(d[29]),"+f"(d[30]),"+f"(d[31]),"+f"(d[32]),"+f"(d[33]),"+f"(d[34]),"+f"(d[35]),"+f"(d[36]),"+f"(d[37]),"+f"(d[38]),"+f"(d[39]),"+f"(d[40]),"+f"(d[41]),"+f"(d[42]),"+f"(d[43]),"+f"(d[44]),"+f"(d[45]),"+f"(d[46]),"+f"(d[47]),"+f"(d[48]),"+f"(d[49]),"+f"(d[50]),"+f"(d[51]),"+f"(d[52]),"+f"(d[53]),"+f"(d[54]),"+f"(d[55])
 :"r"(alo),"r"(blo),"n"(AOFF),"n"(AHI),"n"(BOFF),"n"(BHI),"n"(SC)); } };

__device__ __forceinline__ void wg_fence() { asm volatile("wgmma.fence.sync.aligned;" ::: "memory"); }
__device__ __forceinline__ void wg_commit() { asm volatile("wgmma.commit_group.sync.aligned;" ::: "memory"); }
template <int N> __device__ __forceinline__ void wg_wait() { asm volatile("wgmma.wait_group.sync.aligned %0;" ::"n"(N) : "memory"); }
template <int N> __device__ __forceinline__ void reg_fence(float* d) {
#pragma unroll
    for (int i = 0; i < N; i++) asm volatile("" : "+f"(d[i])::"memory");
}
__device__ __forceinline__ uint32_t desc_lo(uint32_t addr, uint32_t lbo) { return ((addr & 0x3FFFF) >> 4) | ((lbo >> 4) << 16); }
#define desc_hi(sbo, sw) (((sbo) >> 4) | ((sw) << 30))
__device__ __forceinline__ uint32_t smem_u32(const void* p) { return (uint32_t)__cvta_generic_to_shared(p); }
__device__ __forceinline__ bool elect() {
    uint32_t p;
    asm volatile("{.reg .pred P; elect.sync _|P, 0xffffffff; selp.u32 %0,1,0,P;}" : "=r"(p));
    return p;
}
__device__ __forceinline__ void mbar_init(uint32_t bar, uint32_t cnt) { asm volatile("mbarrier.init.shared::cta.b64 [%0], %1;" ::"r"(bar), "r"(cnt) : "memory"); }
__device__ __forceinline__ void mbar_expect(uint32_t bar, uint32_t bytes) { asm volatile("mbarrier.arrive.expect_tx.shared::cta.b64 _, [%0], %1;" ::"r"(bar), "r"(bytes) : "memory"); }
__device__ __forceinline__ bool mbar_try(uint32_t bar, uint32_t par) {
    uint32_t ok;
    asm volatile("{.reg .pred p; mbarrier.try_wait.parity.shared::cta.b64 p, [%1], %2; selp.u32 %0,1,0,p;}" : "=r"(ok) : "r"(bar), "r"(par) : "memory");
    return ok;
}
constexpr int SPIN_LIMIT = 1 << 18;
__device__ __forceinline__ void mbar_wait(uint32_t bar, uint32_t par) {
    if (mbar_try(bar, par)) return;
    int n = 0;
    while (!mbar_try(bar, par) && ++n < SPIN_LIMIT) {}
}
__device__ __forceinline__ void bulk_g2s(uint32_t dst, const void* src, uint32_t bytes, uint32_t bar) {
    asm volatile("cp.async.bulk.shared::cluster.global.mbarrier::complete_tx::bytes [%0], [%1], %2, [%3];" ::"r"(dst), "l"(src), "r"(bytes), "r"(bar) : "memory");
}
__device__ __forceinline__ void bulk_s2g(void* dst, uint32_t src, uint32_t bytes) {
    asm volatile("cp.async.bulk.global.shared::cta.bulk_group [%0], [%1], %2;" ::"l"(dst), "r"(src), "r"(bytes) : "memory");
}
__device__ __forceinline__ void bulk_prefetch(const void* src, uint32_t bytes) {
    asm volatile("cp.async.bulk.prefetch.L2.global [%0], %1;" ::"l"(src), "r"(bytes) : "memory");
}
__device__ __forceinline__ void tma2d(uint32_t dst, const CUtensorMap* m, int c0, int c1, uint32_t bar) {
    asm volatile("cp.async.bulk.tensor.2d.shared::cluster.global.mbarrier::complete_tx::bytes [%0], [%1, {%3, %4}], [%2];" ::"r"(dst), "l"(m), "r"(bar), "r"(c0), "r"(c1) : "memory");
}
__device__ __forceinline__ void tma2d_mc(uint32_t dst, const CUtensorMap* m, int c0, int c1, uint32_t bar) {
    asm volatile("cp.async.bulk.tensor.2d.shared::cluster.global.mbarrier::complete_tx::bytes.multicast::cluster [%0], [%1, {%3, %4}], [%2], %5;" ::"r"(dst), "l"(m), "r"(bar), "r"(c0), "r"(c1), "h"((uint16_t)3) : "memory");
}
__device__ __forceinline__ uint32_t mapa(uint32_t a, uint32_t rank) { uint32_t r; asm("mapa.shared::cluster.u32 %0, %1, %2;" : "=r"(r) : "r"(a), "r"(rank)); return r; }
__device__ __forceinline__ void mbar_arrive_cl(uint32_t bar) { asm volatile("mbarrier.arrive.shared::cluster.b64 _, [%0];" ::"r"(bar) : "memory"); }
__device__ __forceinline__ void prefetch_map(const CUtensorMap* m) { asm volatile("prefetch.tensormap [%0];" ::"l"(m) : "memory"); }
__device__ __forceinline__ void cpasync16(uint32_t dst, const void* src, uint32_t srcsz) {
    asm volatile("cp.async.cg.shared.global [%0], [%1], 16, %2;" ::"r"(dst), "l"(src), "r"(srcsz) : "memory");
}
__device__ __forceinline__ void bar_sync(int id, int n) { asm volatile("bar.sync %0, %1;" ::"r"(id), "r"(n) : "memory"); }
__device__ __forceinline__ void bar_arrive(int id, int n) { asm volatile("bar.arrive %0, %1;" ::"r"(id), "r"(n) : "memory"); }
__device__ __forceinline__ void fence_async_smem() { asm volatile("fence.proxy.async.shared::cta;" ::: "memory"); }
__device__ __forceinline__ void fence_async_global() { asm volatile("fence.proxy.async.global;" ::: "memory"); }
__device__ __forceinline__ void flag_release(int f) { asm volatile("red.release.gpu.global.add.u32 [%0], 1;" ::"l"(&g_flags[f * 32]) : "memory"); }
__device__ __forceinline__ void flag_wait(int f, unsigned target) {
    const unsigned* p = &g_flags[f * 32];
    unsigned v; int n = 0;
    do {
        asm volatile("ld.relaxed.gpu.global.u32 %0, [%1];" : "=r"(v) : "l"(p) : "memory");
    } while ((int)(v - target) < 0 && ++n < SPIN_LIMIT);
    asm volatile("fence.acquire.gpu;" ::: "memory");
}
__device__ __forceinline__ unsigned ld_flag(const unsigned* p) { unsigned v; asm volatile("ld.relaxed.gpu.global.u32 %0, [%1];" : "=r"(v) : "l"(p) : "memory"); return v; }
__device__ __forceinline__ void spin(unsigned n) { unsigned t0, t1; asm volatile("mov.u32 %0, %%clock;" : "=r"(t0)); do { asm volatile("mov.u32 %0, %%clock;" : "=r"(t1)); } while (t1 - t0 < n); }
__device__ __forceinline__ void flag_wait_fast(int f, unsigned target) {
    flag_wait(f, target);
}
__device__ __forceinline__ void flag_wait2(int f0, int f1, unsigned target) {
    const unsigned *p = &g_flags[f0 * 32], *q = &g_flags[f1 * 32];
    unsigned v, w; int n = 0;
    do { v = ld_flag(p); w = ld_flag(q); } while ((int)((v - target) | (w - target)) < 0 && ++n < SPIN_LIMIT);
    asm volatile("fence.acquire.gpu;" ::: "memory");
}
__device__ __forceinline__ uint32_t lds32(uint32_t a) { uint32_t v; asm volatile("ld.shared.u32 %0, [%1];" : "=r"(v) : "r"(a)); return v; }
__device__ __forceinline__ float2 lds64f(uint32_t a) { float2 v; asm volatile("ld.shared.v2.f32 {%0,%1}, [%2];" : "=f"(v.x), "=f"(v.y) : "r"(a)); return v; }
__device__ __forceinline__ uint2 lds64(uint32_t a) { uint2 v; asm volatile("ld.shared.v2.u32 {%0,%1}, [%2];" : "=r"(v.x), "=r"(v.y) : "r"(a)); return v; }
__device__ __forceinline__ void sts64f(uint32_t a, float2 v) { asm volatile("st.shared.v2.f32 [%0], {%1,%2};" ::"r"(a), "f"(v.x), "f"(v.y) : "memory"); }
__device__ __forceinline__ void sts32(uint32_t a, uint32_t v) { asm volatile("st.shared.u32 [%0], %1;" ::"r"(a), "r"(v) : "memory"); }
__device__ __forceinline__ void sts64(uint32_t a, uint32_t x, uint32_t y) { asm volatile("st.shared.v2.u32 [%0], {%1,%2};" ::"r"(a), "r"(x), "r"(y) : "memory"); }
__device__ __forceinline__ void sts16(uint32_t a, uint16_t v) { asm volatile("st.shared.u16 [%0], %1;" ::"r"(a), "h"(v) : "memory"); }
__device__ __forceinline__ uint4 lds128(uint32_t a) { uint4 v; asm volatile("ld.shared.v4.u32 {%0,%1,%2,%3}, [%4];" : "=r"(v.x), "=r"(v.y), "=r"(v.z), "=r"(v.w) : "r"(a)); return v; }
__device__ __forceinline__ void sts128(uint32_t a, uint4 v) { asm volatile("st.shared.v4.u32 [%0], {%1,%2,%3,%4};" ::"r"(a), "r"(v.x), "r"(v.y), "r"(v.z), "r"(v.w) : "memory"); }
__device__ __forceinline__ void sts128f(uint32_t a, float x, float y, float z, float w) { asm volatile("st.shared.v4.f32 [%0], {%1,%2,%3,%4};" ::"r"(a), "f"(x), "f"(y), "f"(z), "f"(w) : "memory"); }
__device__ __forceinline__ uint32_t prmt(uint32_t a, uint32_t b, uint32_t s) { uint32_t r; asm("prmt.b32 %0,%1,%2,%3;" : "=r"(r) : "r"(a), "r"(b), "r"(s)); return r; }
__device__ __forceinline__ uint32_t pack2(float lo, float hi) { uint32_t r; asm("cvt.rn.bf16x2.f32 %0, %1, %2;" : "=r"(r) : "f"(hi), "f"(lo)); return r; }
__device__ __forceinline__ float blo(uint32_t v) { return __uint_as_float(v << 16); }
__device__ __forceinline__ float bhi(uint32_t v) { return __uint_as_float(v & 0xffff0000u); }
__device__ __forceinline__ uint32_t bmul2(uint32_t a, uint32_t b) { uint32_t r; asm("mul.rn.bf16x2 %0,%1,%2;" : "=r"(r) : "r"(a), "r"(b)); return r; }
__device__ __forceinline__ uint32_t badd2(uint32_t a, uint32_t b) { uint32_t r; asm("add.rn.bf16x2 %0,%1,%2;" : "=r"(r) : "r"(a), "r"(b)); return r; }
__device__ __forceinline__ float rbf(float x) { return __bfloat162float(__float2bfloat16_rn(x)); }
__device__ __forceinline__ uint32_t ldcg32(const void* p) { uint32_t v; asm volatile("ld.global.cg.u32 %0, [%1];" : "=r"(v) : "l"(p) : "memory"); return v; }
__device__ __forceinline__ uint4 ldcg128(const void* p) { uint4 v; asm volatile("ld.global.cg.v4.u32 {%0,%1,%2,%3}, [%4];" : "=r"(v.x), "=r"(v.y), "=r"(v.z), "=r"(v.w) : "l"(p) : "memory"); return v; }
__device__ __forceinline__ void stg32_if(void* p, uint32_t v, int on) { asm volatile("{.reg .pred q; setp.ne.b32 q, %2, 0; @q st.global.u32 [%0], %1;}" ::"l"(p), "r"(v), "r"(on) : "memory"); }
__device__ __forceinline__ uint2 ldcg64(const void* p) { uint2 v; asm volatile("ld.global.cg.v2.u32 {%0,%1}, [%2];" : "=r"(v.x), "=r"(v.y) : "l"(p) : "memory"); return v; }
__device__ __forceinline__ float gelu_h(float h) {
    float u = h * fmaf(h * h, 8.0f * 0.044715f * 0.7978845608028654f, 2.0f * 0.7978845608028654f);
    float th;
    asm("tanh.approx.f32 %0, %1;" : "=f"(th) : "f"(u));
    return fmaf(h, th, h);
}
__device__ __forceinline__ float gelu(float x) { return gelu_h(0.5f * x); }
__device__ __forceinline__ float half_rstd(float sum, float sq) {
    float mean = sum * (1.0f / D_), inv;
    asm("rsqrt.approx.ftz.f32 %0, %1;" : "=f"(inv) : "f"(fmaxf(fmaf(-mean, mean, fmaf(sq, 1.0f / D_, 1e-5f)), 1e-5f)));
    return 0.5f * inv;
}
__device__ __forceinline__ uint32_t bsub2(uint32_t a, uint32_t b) { uint32_t r; asm("sub.rn.bf16x2 %0,%1,%2;" : "=r"(r) : "r"(a), "r"(b)); return r; }
__device__ __forceinline__ uint32_t bfma2(uint32_t a, uint32_t b, uint32_t c) { uint32_t r; asm("fma.rn.bf16x2 %0,%1,%2,%3;" : "=r"(r) : "r"(a), "r"(b), "r"(c)); return r; }
__device__ __forceinline__ uint32_t gelu2_h(uint32_t h) {
    uint32_t u = bmul2(h, bfma2(bmul2(h, h), 0x3e923e92u, 0x3fcc3fccu)), th;
    asm("tanh.approx.bf16x2 %0, %1;" : "=r"(th) : "r"(u));
    return bfma2(h, th, h);
}
__device__ __forceinline__ void mma_stat(float* d, uint32_t u, uint32_t v) {
    asm("mma.sync.aligned.m16n8k16.row.col.f32.bf16.bf16.f32 {%0,%1,%2,%3},{%4,%6,%5,%6},{%4,%5},{%0,%1,%2,%3};"
        : "+f"(d[0]), "+f"(d[1]), "+f"(d[2]), "+f"(d[3]) : "r"(u), "r"(v), "r"(0x3f803f80u));
}
__device__ __forceinline__ void mma_sel(float* d, uint2 u, uint2 v, uint32_t b0, uint32_t b1) {
    asm("mma.sync.aligned.m16n8k16.row.col.f32.bf16.bf16.f32 {%0,%1,%2,%3},{%4,%5,%6,%7},{%8,%9},{%0,%1,%2,%3};"
        : "+f"(d[0]), "+f"(d[1]), "+f"(d[2]), "+f"(d[3]) : "r"(u.x), "r"(v.x), "r"(u.y), "r"(v.y), "r"(b0), "r"(b1));
}
__device__ __forceinline__ void conv_sum4(float* d, uint32_t a, bool last, int g, int c) {
    uint2 v0 = lds64(a), v1 = lds64(a + 8), v2 = lds64(a + 16), v3 = lds64(a + 24);
    if (last) {
        if (c > 2) v1 = make_uint2(0, 0);
        if (c > 1) v2 = make_uint2(0, 0);
        if (c > 0) v3 = make_uint2(0, 0);
    }
    const uint32_t one = (g & 1) ? 0x3f800000u : 0x00003f80u;
    mma_sel(d, v0, v1, (g >> 1) == 0 ? one : 0u, (g >> 1) == 1 ? one : 0u);
    mma_sel(d, v2, v3, (g >> 1) == 2 ? one : 0u, (g >> 1) == 3 ? one : 0u);
}
__device__ __forceinline__ uint3 row_stats(const uint32_t* v, int lane) {
    float s = 0.f, q = 0.f, s_ = 0.f, q_ = 0.f;
#pragma unroll
    for (int i = 0; i < 10; i++) { float a = blo(v[i]), b = bhi(v[i]); s += a; s_ += b; q = fmaf(a, a, q); q_ = fmaf(b, b, q_); }
    s += s_; q += q_;
    {
        float t = __shfl_xor_sync(0xffffffffu, (lane & 16) ? s : q, 16);
        t += (lane & 16) ? q : s;
#pragma unroll
        for (int m = 8; m; m >>= 1) t += __shfl_xor_sync(0xffffffffu, t, m);
        float o = __shfl_xor_sync(0xffffffffu, t, 16);
        s = (lane & 16) ? o : t; q = (lane & 16) ? t : o;
    }
    float mean = s * (1.0f / D_), inv;
    asm("rsqrt.approx.ftz.f32 %0, %1;" : "=f"(inv) : "f"(fmaxf(fmaf(-mean, mean, fmaf(q, 1.0f / D_, 1e-5f)), 1e-5f)));
    uint3 r;
    r.x = pack2(mean, mean);
    r.y = pack2(inv, inv);
    inv -= blo(r.y);
    r.z = pack2(inv, inv);
    return r;
}
__device__ __forceinline__ uint32_t ln_apply(uint32_t x, uint32_t m, uint32_t hi, uint32_t lo) {
    uint32_t xc = bsub2(x, m);
    return bmul2(xc, hi);
}

struct AFrag { uint32_t m, a, b, c, d; };
__device__ __forceinline__ AFrag ldA(uint32_t a) { AFrag f; f.m = lds32(a - 16); f.a = lds32(a); f.b = lds32(a + 16); f.c = lds32(a + 32); f.d = lds32(a + 48); return f; }
template <int N, int M> __device__ __forceinline__ void conv_pair(float* d, const AFrag& f, uint32_t descU) {
    WgRs<N>::template run<8 * M, desc_hi(128, 0), M ? 1 : 0>(d, f.a, f.b, f.m, f.a, descU);
    WgRs<N>::template run<8 * M + 1, desc_hi(128, 0), 1>(d, f.c, f.d, f.b, f.c, descU);
}
template <int Q> __device__ __forceinline__ void conv_put(float* d, uint32_t r0) {
    sts64(r0 + Q * 32, pack2(d[4 * Q + 1], d[4 * Q + 3]), pack2(d[4 * Q], d[4 * Q + 2]));
}
template <int M> __device__ __forceinline__ void conv_two(float* d, AFrag f0, AFrag f1, uint32_t kaddr, uint32_t descU, uint32_t r0, bool handoff) {
    constexpr int N = M < 14 ? 128 - 8 * M : 32;
    wg_fence();
    conv_pair<N, M>(d, f0, descU);
    wg_commit();
    if constexpr (M > 0) f1 = ldA(kaddr + 256 * (M + 1));
    wg_fence();
    conv_pair<N, M + 1>(d, f1, descU);
    wg_commit();
    if (STAG && M == STAG && handoff) bar_arrive(12, 256);
    if constexpr (M < 14) {
        if constexpr (M > 0) { conv_put<17 - M>(d, r0); conv_put<16 - M>(d, r0); }
        wg_wait<1>();
        f0 = ldA(kaddr + 256 * (M + 2));
        if constexpr (M < 12) wg_wait<0>();
        conv_two<M + 2>(d, f0, f1, kaddr, descU, r0, handoff);
    } else {
        wg_wait<0>();
        conv_put<3>(d, r0); conv_put<2>(d, r0); conv_put<1>(d, r0); conv_put<0>(d, r0);
    }
}
template <int N, bool ASWZ, int SC0>
__device__ __forceinline__ void gemm_issue(float* acc, uint32_t bars, int sa, int pa, int sw, int pw, uint32_t da0, uint32_t db0) {
    mbar_wait(bars + (BAR_FB + sw) * 8, pw);
    mbar_wait(bars + (BAR_FA + sa) * 8, pa);
    const uint32_t da = da0 + sa * (SLOT >> 4), db = db0 + sw * (SLOT >> 4);
    constexpr int AK = ASWZ ? 2 : 256, AH = ASWZ ? desc_hi(1024, 1) : desc_hi(128, 0), BH = desc_hi(1024, 1);
    wg_fence();
    WgSs<N>::template run<0, AH, 0, BH, SC0>(acc, da, db);
    WgSs<N>::template run<AK, AH, 128, BH, 1>(acc, da, db);
    WgSs<N>::template run<2 * AK, AH, 256, BH, 1>(acc, da, db);
    WgSs<N>::template run<3 * AK, AH, 384, BH, 1>(acc, da, db);
    wg_commit();
}
template <int N, bool ASWZ, int NKB, int RELB, bool ZERO>
__device__ __forceinline__ void gemm_loop(float* acc, uint32_t sb, int half, int ia0, int ib0, int rela, int wait_bar, int order_bar, int tsid) {
    int sa = ia0 % NA, pa = (ia0 / NA) & 1, sw = ib0 % NB, pw = (ib0 / NB) & 1;
    const uint32_t bars = sb + SM_BAR;
    const int t = threadIdx.x & 127;
    uint32_t ebar = mapa(bars + (t < 2 ? BAR_EB : BAR_EA) * 8, (t < 2 && lds32(sb + SM_GV + 516)) ? t : blockIdx.x & 1);
    const int nrel = t < 2 ? RELB : t == 2 ? rela : 0;
    const uint32_t da0 = ASWZ ? desc_lo(sb + SM_RA + half * 8192, 16) : desc_lo(sb + SM_RA + half * 1024, 2048), db0 = desc_lo(sb + SM_RB, 8192);
    asm volatile("" : "+r"(ebar));
    if (wait_bar) bar_sync(wait_bar, 512);
    gemm_issue<N, ASWZ, ZERO ? 0 : 1>(acc, bars, sa, pa, sw, pw, da0, db0);
    if ((threadIdx.x & 255) == 0) TS(tsid);
#pragma unroll 1
    for (int kb = 1; kb < NKB; kb++) {
        const int prev = t < 2 ? sw : sa;
        if (++sa == NA) { sa = 0; pa ^= 1; }
        if (++sw == NB) { sw = 0; pw ^= 1; }
        gemm_issue<N, ASWZ, 1>(acc, bars, sa, pa, sw, pw, da0, db0);
        if (order_bar && kb == NKB - 1) bar_arrive(order_bar, 512);
        wg_wait<1>();
        if (kb <= nrel) mbar_arrive_cl(ebar + prev * 8);
    }
    wg_wait<0>();
    if (nrel == NKB) mbar_arrive_cl(ebar + (t < 2 ? sw : sa) * 8);
    reg_fence<N / 2>(acc);
    if ((threadIdx.x & 255) == 0) TS(tsid + 1);
}

template <int PART>
__device__ __forceinline__ void gemm3(uint32_t sb, int rb, int j, int half, int row, int c, unsigned ones) {
    constexpr int N = PART ? 104 : 112, NQ = N / 8;
    constexpr int HO = PART ? HO_B : HO_A;
    float acc[N / 2];
    float2 cr[NQ];
    mbar_wait(sb + SM_BAR + BAR_CS * 8, 0);
#pragma unroll
    for (int q = 0; q < NQ; q++) cr[q] = lds64f(sb + SM_CS + PART * 448 + 8 * c + 32 * q);
    uint4 rp;
    if (PART) {
        mbar_wait(sb + SM_BAR + (BAR_FA + 22 % NA) * 8, (22 / NA) & 1);
        const float2* sp = &g_st[(rb * 8 + 2 * c) * 128 + row];
        const uint2 s0 = ldcg64(sp), s1 = ldcg64(sp + 128), s2 = ldcg64(sp + 8), s3 = ldcg64(sp + 136);
        float a0 = __uint_as_float(s0.x) + __uint_as_float(s1.x), b0 = __uint_as_float(s0.y) + __uint_as_float(s1.y);
        float a1 = __uint_as_float(s2.x) + __uint_as_float(s3.x), b1 = __uint_as_float(s2.y) + __uint_as_float(s3.y);
#pragma unroll
        for (int m = 1; m <= 2; m <<= 1) {
            a0 += __shfl_xor_sync(0xffffffffu, a0, m); b0 += __shfl_xor_sync(0xffffffffu, b0, m);
            a1 += __shfl_xor_sync(0xffffffffu, a1, m); b1 += __shfl_xor_sync(0xffffffffu, b1, m);
        }
        const float inv0 = half_rstd(a0, b0), inv1 = half_rstd(a1, b1);
        rp = make_uint4(PGELU ? pack2(inv0, inv0) : __float_as_uint(inv0), __float_as_uint(a0 * (-1.0f / D_)),
                        PGELU ? pack2(inv1, inv1) : __float_as_uint(inv1), __float_as_uint(a1 * (-1.0f / D_)));
        if (c == 0) sts128(sb + SM_RP + ((threadIdx.x & 255) >> 2) * 16, rp);
        bar_arrive(13, 512);
    }
    gemm_loop<N, false, 10, 10, true>(acc, sb, half, 20 + (10 - NA) * PART, 20 + 10 * PART, PART ? 10 : 10 - NA, 9 + PART, HO < 0 ? 10 + PART : 0, 46 + 2 * PART);
    if (!PART) {
        bar_sync(13, 512);
        rp = lds128(sb + SM_RP + ((threadIdx.x & 255) >> 2) * 16);
    }
    const float nb0 = __uint_as_float(rp.y), nb1 = __uint_as_float(rp.w);
    uint32_t* dst = reinterpret_cast<uint32_t*>(g_g) + (rb * 216 + 112 * PART + 8 * j) * 512 + row * 4 + c;
    auto act = [&](int q, int r) {
        const float nb = r ? nb1 : nb0;
        const uint32_t inv = r ? rp.z : rp.x;
        const float t0 = fmaf(nb, cr[q].x, acc[4 * q + 2 * r]), t1 = fmaf(nb, cr[q].y, acc[4 * q + 2 * r + 1]);
        return gelu2_h(bmul2(pack2(t0, t1), inv));
    };
    uint32_t* dst1 = dst + (56 - (16 - NQ) * j) * 512;
#pragma unroll
    for (int k = 0; k < NQ; k += CH3) {
        if (k == HO) bar_arrive(10 + PART, 512);
        CHUNK(k) {
#pragma unroll
            for (int q = k; q < k + CH3 && q < NQ; q++) { (q < 8 ? dst : dst1)[q * 512] = act(q, 0); (q < 8 ? dst : dst1)[q * 512 + 32] = act(q, 1); }
        }
    }
    if (HO >= NQ) bar_arrive(10 + PART, 512);
    bar_arrive(1 + PART, 288);
}

template <int NS, int BASE, int BF, int BE> struct Ring {
    uint32_t sb, st, ph;
    __device__ __forceinline__ uint32_t acquire(uint32_t bytes) {
        mbar_wait(sb + SM_BAR + BE * 8 + st * 8, ph);
        uint32_t fb = sb + SM_BAR + BF * 8 + st * 8;
        mbar_expect(fb, bytes);
        return fb;
    }
    __device__ __forceinline__ uint32_t slot() { return sb + BASE + st * SLOT; }
    __device__ __forceinline__ void next() { if (++st == NS) { st = 0; ph ^= 1; } }
    __device__ __forceinline__ void run2d(const CUtensorMap* m, int c1) {
#pragma unroll 1
        for (int c0 = 64; c0 < D_; c0 += 64) {
            uint32_t fb = acquire(SLOT);
            tma2d(slot(), m, c0, c1, fb);
            next();
        }
    }
    static __device__ __forceinline__ int korder(int i, int own) { return i == 0 ? own : i > own ? i : i - 1; }
    __device__ __forceinline__ void runw(bool paired, int rk, const CUtensorMap* ma, const CUtensorMap* mb, int ca, int cb, int i0, int i1, int own, uint32_t bytes) {
        if (paired) {
            const CUtensorMap* m = rk ? mb : ma;
            const int c0 = rk ? cb : ca;
#pragma unroll 1
            for (int i = i0; i < i1; i++) {
                const int c1 = korder(i, own) * 64;
                uint32_t fb = acquire(bytes);
                tma2d_mc(slot() + 8192 * rk, m, c0, c1, fb);
                next();
            }
        } else {
#pragma unroll 1
            for (int i = i0; i < i1; i++) {
                const int c1 = korder(i, own) * 64;
                uint32_t fb = acquire(bytes);
                tma2d(slot(), ma, ca, c1, fb);
                tma2d(slot() + 8192, mb, cb, c1, fb);
                next();
            }
        }
    }
    __device__ __forceinline__ void run1d(const char* src, int i0, int i1, int own) {
#pragma unroll 1
        for (int i = i0; i < i1; i++) {
            const char* s = src + korder(i, own) * SLOT;
            uint32_t fb = acquire(SLOT);
            bulk_g2s(slot(), s, SLOT, fb);
            next();
        }
    }
};

__global__ void __cluster_dims__(2, 1, 1) __launch_bounds__(NTHREADS, 1) fused_kernel(const Params p, const __grid_constant__ Maps maps) {
    extern __shared__ __align__(1024) unsigned char smem_raw[];
    const uint32_t sb = (smem_u32(smem_raw) + 1023u) & ~1023u;
#pragma unroll
    for (int i = 0; i < SEED; i++) asm volatile("{.reg .b32 t; mov.u32 t, %laneid;}");
    const uint32_t bars = sb + SM_BAR;
    const int tid = threadIdx.x, lane = tid & 31;
    unsigned smid;
    asm volatile("mov.u32 %0, %%smid;" : "=r"(smid));
    const bool spare = (smid >> 2) == 30;
    const int cta = smid < 120 ? smid : smid - 4;
    const int pg = cta >> 4, pi = cta & 15;
    const int hb = tid >= 320;
    if (!spare) {
        const unsigned t = tid - 320 * hb, r32 = t / 10u, cc = t - r32 * 10u, row = r32 + 64 * hb;
        const unsigned go = (unsigned)(pi * 128 * 1280 + pg * 160) + row * 1280u + cc * 16u;
        const uint32_t so = sb + (row >> 4) * 32u + row * 160u + cc * 16u;
        const char* kb = (const char*)p.k + go;
        const char* vb = (const char*)p.v + go;
        if (hb) {
            if (tid >= 640 - NBARS) {
                const int i = 639 - tid;
                mbar_init(bars + i * 8, (i >= BAR_EB && i < BAR_K) ? 4 : ((i >= BAR_EA && i < BAR_EB) || i == BAR_XY) ? 2 : 1);
                asm volatile("fence.mbarrier_init.release.cluster;" ::: "memory");
            }
            bar_arrive(14, 640);
            if (B_DELAY) spin(B_DELAY);
        }
        cpasync16(so + SM_PK + 2592, kb, 16);
        cpasync16(so + SM_PV, vb, 16);
        cpasync16(so + SM_PK + 3 * 2592, kb + 32 * 1280, 16);
        cpasync16(so + SM_PV + 2 * 2592, vb + 32 * 1280, 16);
        if (tid < 30) cpasync16(so + SM_PK + 13 * 160, pi ? kb - 3 * 1280 : kb, pi ? 16 : 0);
        asm volatile("cp.async.commit_group;" ::: "memory");
    }
    const int warp = __shfl_sync(0xffffffffu, tid >> 5, 0);
    const int wg = warp >> 2, wq = warp & 3;
    unsigned ep0 = 0;
    if (wg == 4 || spare) ep0 = *(volatile unsigned*)&g_epoch[smid];
#define ep1 (ep0 + 1)

    if (spare) {
        const int sp = smid & 3;
        if (tid == 32) { sts32(sb + SM_GV + 512, smid); asm volatile("fence.release.sync_restrict::shared::cta.cluster;" ::: "memory"); }
        asm volatile("barrier.cluster.arrive.relaxed.aligned;" ::: "memory");
        asm volatile("barrier.cluster.wait.aligned;" ::: "memory");
        if (tid == 0) {
            for (int i = 0; i < 4; i++) mbar_init(bars + i * 8, 1);
            asm volatile("fence.mbarrier_init.release.cluster;" ::: "memory");
        }
        if (warp == 0) { if (lane < 8) flag_wait(FL_P + lane, ep1 * 16); __syncwarp(); }
        __syncthreads();
        const int cq = tid % 54, rg = tid / 54;
        float a[8];
#pragma unroll
        for (int i = 0; i < 8; i++) a[i] = 0.f;
#pragma unroll 1
        for (int it = -4; it < 10; it++) {
            const uint32_t st = sb + (it & 3) * 55296, fb = bars + (it & 3) * 8;
            if (it >= 0) {
                mbar_wait(fb, (it >> 2) & 1);
                if (tid < 432) {
#pragma unroll
                    for (int i = 0; i < 8; i++) {
                        uint4 w = lds128(st + (cq >= 27 ? 27648 - 432 : 0) + (rg * 8 + i) * 432 + cq * 16);
                        a[0] += blo(w.x); a[1] += bhi(w.x); a[2] += blo(w.y); a[3] += bhi(w.y);
                        a[4] += blo(w.z); a[5] += bhi(w.z); a[6] += blo(w.w); a[7] += bhi(w.w);
                    }
                }
                __syncthreads();
            }
            if (it < 6 && warp == 19 && elect()) {
                mbar_expect(fb, 55296);
                tma2d(st, &maps.w3s, sp * 432, (it + 4) * 64, fb);
                tma2d(st + 27648, &maps.w3s, sp * 432 + 216, (it + 4) * 64, fb);
            }
        }
        if (tid < 432) {
            sts128f(sb + rg * 1728 + cq * 32, a[0], a[1], a[2], a[3]);
            sts128f(sb + rg * 1728 + cq * 32 + 16, a[4], a[5], a[6], a[7]);
        }
        __syncthreads();
        if (tid < 432) {
            float s = 0.f;
#pragma unroll
            for (int i = 0; i < 8; i++) s += __uint_as_float(lds32(sb + i * 1728 + tid * 4));
            g_cs[sp * 432 + tid] = s;
        }
        __syncthreads();
        if (tid == 0) { flag_release(FL_CS); g_epoch[smid] = ep1; TS(0); }
        if (warp == 0) TSFLUSH();
        return;
    }

    int gpc, idx;
    if (smid < 64) { gpc = (smid & 15) >> 1; idx = (smid >> 4) * 2 + (smid & 1); }
    else if (smid < 120) { int t = smid - 64; gpc = 1 + (t % 14) / 2; idx = 8 + (t / 14) * 2 + (smid & 1); }
    else { gpc = 0; idx = 8 + (smid - 124); }
    const int rb = 2 * gpc + (idx & 1), j = idx >> 1;
    const int g = lane >> 2, c = lane & 3;
    const int cm = 160 * (j >> 1) + 64 * (j & 1) + ((j & 2) ? 32 : 0), cr = 160 * (j >> 1) + 16 * (j & 1) + ((j & 2) ? 0 : 128);

    {
        if (warp == 5) TSW(61);
        const int w10 = warp - 10 * hb, h = w10 >= 5;
        const int pr = (w10 - 5 * h) * 8 + (lane >> 2), blk = 4 * hb + (lane & 3);
        const int ch = 80 * pg + 2 * pr;
        const uint4 sw = __ldg(reinterpret_cast<const uint4*>(p.shift + ch * 4));
        uint32_t dv = 0;
        if (warp == 9 && lane < 5) dv = __bfloat16_as_ushort(p.ssmD[cta * 5 + lane]);
        if (tid == 512) { sts32(sb + SM_GV + 512, smid); asm volatile("fence.release.sync_restrict::shared::cta.cluster;" ::: "memory"); }
        asm volatile("barrier.cluster.arrive.relaxed.aligned;" ::: "memory");
        if (warp == 11 && lane < 13) prefetch_map(&maps.hn + lane);
        if (wg < 4) {
            const int t = tid & 127, cc = (wg == 3 && t >= 64) ? 4 : wg;
            if (t < 64 || wg == 3) sts128(sb + sm_u(cc) + ((t >> 5) & 1) * U_PLANE + 2048 + lane * 16, make_uint4(0, 0, 0, 0));
            if ((t & 63) < 4 && (t < 64 || wg == 3)) sts128(sb + sm_k(cc) + ((t >> 1) & 1) * 4160 + (t & 1) * 16, make_uint4(0, 0, 0, 0));
        }
        if (warp == 9 && lane < 5) sts32(sb + SM_GV + 520 + lane * 4, dv << 16);
        asm volatile("cp.async.wait_group 0;" ::: "memory");
        if (!hb) bar_arrive(12, 640);
        bar_sync(hb ? 12 : 14, 640);
        if (warp == 9) {
            if (SSM_DELAY) spin(SSM_DELAY);
            if (elect()) {
#pragma unroll
                for (int i = 0; i < SSM_N; i++) {
                    mbar_expect(bars + (BAR_K + i) * 8, 4096);
                    bulk_g2s(sb + sm_k(i) + 32, p.ssmk + (size_t)(cta * 5 + i) * S_, 4096, bars + (BAR_K + i) * 8);
                }
            }
        }
        const uint32_t w0 = prmt(sw.x, sw.z, 0x5410), w1 = prmt(sw.x, sw.z, 0x7632), w2 = prmt(sw.y, sw.w, 0x5410), w3 = prmt(sw.y, sw.w, 0x7632);
        const uint32_t ka = sb + SM_PK + 2592 + blk * 2592 + h * 1280 + pr * 4;
        const uint32_t va = sb + SM_PV + blk * 2592 + h * 1280 + pr * 4;
        uint32_t kk[11], kv[8];
#pragma unroll
        for (int i = 0; i < 11; i++) kk[i] = lds32(ka + (i - 3) * 160 - ((i < 3 && h == 0) ? 32 : 0));
#pragma unroll
        for (int i = 0; i < 8; i++) {
            uint32_t t = badd2(badd2(badd2(bmul2(kk[i], w3), bmul2(kk[i + 1], w2)), bmul2(kk[i + 2], w1)), bmul2(kk[i + 3], w0));
            kv[i] = bmul2(t, lds32(va + i * 160));
        }
        uint4 o0, o1;
        o0.x = prmt(kv[1], kv[0], 0x5410); o0.y = prmt(kv[3], kv[2], 0x5410); o0.z = prmt(kv[5], kv[4], 0x5410); o0.w = prmt(kv[7], kv[6], 0x5410);
        o1.x = prmt(kv[1], kv[0], 0x7632); o1.y = prmt(kv[3], kv[2], 0x7632); o1.z = prmt(kv[5], kv[4], 0x7632); o1.w = prmt(kv[7], kv[6], 0x7632);
        uint4* dst = reinterpret_cast<uint4*>(g_kvT) + ch * 256 + h * 128 + (127 - (8 * pi + blk));
        dst[0] = o0;
        dst[256] = o1;
    }

    const int rho = 8 * rb + j;

    if (wg == 4) {
        asm volatile("setmaxnreg.dec.sync.aligned.u32 32;");
        if (wq == 0) {
            bar_sync(13, 640);
            TSW(39);
            if (lane == 0) flag_release(FL_P + pg);
            __syncwarp();
            TSW(2);
            if (lane < 5) mbar_expect(bars + (BAR_U + lane) * 8, 4096);
            flag_wait_fast(FL_P + pg, ep1 * 16);
            fence_async_global();
            TSW(3);
            if (elect()) {
#pragma unroll
                for (int i = 0; i < 5; i++) {
                    const char* us = (const char*)g_kvT + (size_t)(cta * 5 + i) * 4096;
                    bulk_g2s(sb + sm_u(i), us, 2048, bars + (BAR_U + i) * 8);
                    bulk_g2s(sb + sm_u(i) + U_PLANE, us + 2048, 2048, bars + (BAR_U + i) * 8);
                }
            }
            __syncwarp();
            if (elect()) {
#pragma unroll
                for (int i = SSM_N; i < 5; i++) {
                    mbar_expect(bars + (BAR_K + i) * 8, 4096);
                    bulk_g2s(sb + sm_k(i) + 32, p.ssmk + (size_t)(cta * 5 + i) * S_, 4096, bars + (BAR_K + i) * 8);
                }
                if (cta < 120) {
                    mbar_expect(bars + BAR_WM * 8, 40960);
#pragma unroll
                    for (int i = 0; i < 5; i++) tma2d(sb + SM_WM + i * 8192, &maps.wm, cta * 32, i * 128, bars + BAR_WM * 8);
                }
                bulk_prefetch((const char*)p.q + cta * 20480, 20480);
                bulk_prefetch((const char*)p.w1 + cta * 6400, 6400);
                bulk_prefetch((const char*)p.w2 + cta * 6400, 6400);
            }
            __syncwarp();
        } else {
            bar_arrive(13, 640);
        }
        asm volatile("barrier.cluster.wait.aligned;" ::: "memory");
        uint32_t peer;
        asm volatile("ld.shared::cluster.u32 %0, [%1];" : "=r"(peer) : "r"(mapa(sb + SM_GV + 512, (blockIdx.x & 1) ^ 1)) : "memory");
        const bool paired = peer == (smid ^ 1);
        if (tid == 639) sts32(sb + SM_GV + 516, paired);
        if (cta < 120) {
            float d[4];
            if (tid < 592) {
                const int t = tid - 512;
                mbar_wait(bars + BAR_U * 8, 0);
                uint4 cv = __ldg(reinterpret_cast<const uint4*>(p.c) + t);
                auto silu2 = [](uint32_t v) { float a = blo(v), b = bhi(v); return pack2(__fdividef(a, 1.0f + __expf(-a)), __fdividef(b, 1.0f + __expf(-b))); };
                sts128(sb + SM_Y + (t % 40) * 32 + (t / 40) * 16, make_uint4(silu2(cv.x), silu2(cv.y), silu2(cv.z), silu2(cv.w)));
                fence_async_smem();
            }
            bar_sync(5, 128);
            mbar_wait(bars + BAR_WM * 8, 0);
            if (wq == 3) TSW(56);
            const uint32_t da = desc_lo(sb + SM_WM, 20480), db = desc_lo(sb + SM_Y, 32);
            wg_fence();
#pragma unroll
            for (int k = 0; k < 20; k++)
                asm volatile("{.reg .pred p; .reg .b32 l,m; .reg .b64 da,db; setp.ne.b32 p,%10,0; add.u32 l,%4,%6; mov.b64 da,{l,%8}; add.u32 m,%5,%7; mov.b64 db,{m,%9};"
                             " wgmma.mma_async.sync.aligned.m64n8k16.f32.bf16.bf16 {%0,%1,%2,%3},da,db,p,1,1,1,0;}"
                             : "+f"(d[0]), "+f"(d[1]), "+f"(d[2]), "+f"(d[3])
                             : "r"(da), "r"(db), "r"(64 * k), "r"(4 * k), "n"(desc_hi(512, 2u)), "n"(desc_hi(128, 0)), "r"(k));
            wg_commit();
            wg_wait<0>();
            reg_fence<4>(d);
            if (c == 0) {
                sts32(sb + SM_GV + (16 * wq + g) * 4, __float_as_uint(wq < 2 ? d[0] : d[1]));
                sts32(sb + SM_GV + (16 * wq + g + 8) * 4, __float_as_uint(wq < 2 ? d[2] : d[3]));
            }
            bar_sync(5, 128);
            if (wq == 2) {
                g_mod[cta * 32 + lane] = __float2bfloat16_rn(__uint_as_float(lds32(sb + SM_GV + lane * 4)) + __uint_as_float(lds32(sb + SM_GV + 128 + lane * 4)));
                __syncwarp();
                if (lane == 0) flag_release(FL_M);
                __syncwarp();
                TSW(4);
                if (XAFTER) bar_arrive(5, 64);
            }
            if (XAFTER && wq == 0) bar_sync(5, 64);
        }
        if (wq == 2) {
            flag_wait(FL_M, ep1 * 120);
            fence_async_global();
            if (elect()) {
                mbar_expect(bars + BAR_M * 8, 7680);
                bulk_g2s(sb + SM_MOD, g_mod, 7680, bars + BAR_M * 8);
            }
            __syncwarp();
            TSW(60);
            bar_sync(8, 544);  if (lane == 0) { flag_release(FL_R + rb); TS(23); }  __syncwarp();
            bar_sync(15, 288); if (lane == 0) { flag_release(FL_B1 + rb); TS(27); } __syncwarp();
            bar_sync(6, 288);  if (lane == 0) { flag_release(FL_B2 + rb); TS(31); } __syncwarp();
#pragma unroll 1
            for (int i = 0; i < 2; i++) { bar_sync(1 + i, 288); if (lane == 0) { TS(53 + i); flag_release(FL_G + 16 * i + rb); TS(57 + i); } __syncwarp(); }
            if (lane == 0) g_epoch[smid] = ep1;
            return;
        }
        if (wq == 1) {
            bar_sync(9, 288);
            if (lane < 4 * NB) mbar_arrive_cl(mapa(bars + (BAR_EB + (lane >> 2)) * 8, paired ? lane & 1 : blockIdx.x & 1));
        }
        if (wq == 3) {
            bar_sync(7, 544);
            if (lane == 0) { flag_release(FL_C); TS(20); }
            __syncwarp();
            if (lane < 2) mbar_expect(bars + (lane ? BAR_Y2 : BAR_Y) * 8, lane ? 8192 : 12288);
            flag_wait_fast(FL_C, ep1 * 128);
            fence_async_global();
            TSW(21);
            if (elect()) {
                bulk_g2s(sb + SM_Y, g_yv + rho * 5120, 12288, bars + BAR_Y * 8);
                bulk_g2s(sb + SM_Y + 12288, g_yv + rho * 5120 + 3072, 8192, bars + BAR_Y2 * 8);
            }
            __syncwarp();
        }
        if (elect()) {
            if (wq == 3) {
                mbar_expect(bars + BAR_XY * 8, 20480);
#pragma unroll 1
                for (int i = 0; i < 8; i++) {
                    bulk_g2s(sb + SM_YT + i * 2560, g_yv + (8 * rb + i) * 5120 + cm * 8, 2048, bars + BAR_XY * 8);
                    bulk_g2s(sb + SM_YT + i * 2560 + 2048, g_yv + (8 * rb + i) * 5120 + cr * 8, 512, bars + BAR_XY * 8);
                }
                mbar_wait(bars + BAR_FA * 8, 0);
                bulk_prefetch((const char*)p.w4 + cta * 17280, 17280);
                flag_wait(FL_CS, ep1 * 4);
                fence_async_global();
                mbar_expect(bars + BAR_CS * 8, 864);
                bulk_g2s(sb + SM_CS, g_cs + 64 * j, 256, bars + BAR_CS * 8);
                bulk_g2s(sb + SM_CS + 256, g_cs + 512 + 48 * j, 192, bars + BAR_CS * 8);
                bulk_g2s(sb + SM_CS + 448, g_cs + 896 + 64 * j, 256, bars + BAR_CS * 8);
                bulk_g2s(sb + SM_CS + 704, g_cs + 1408 + 40 * j, 160, bars + BAR_CS * 8);
                mbar_wait(bars + BAR_ST * 8, 0);
#pragma unroll 1
                for (int i = 0; i < 2; i++) {
                    flag_wait(FL_G + 16 * i + rb, ep1 * 8);
                    mbar_expect(bars + (BAR_G + i) * 8, 0);
                    TS(35 + i);
                }
            } else if (wq == 1) {
                Ring<NB, SM_RB, BAR_FB, BAR_EB> r{sb, 0, 0};
#pragma unroll 1
                for (int ph = 0; ph < 6; ph++) {
                    const CUtensorMap* ma = ph == 0 ? &maps.w1a : ph == 1 ? &maps.w2a : ph == 5 ? &maps.w4a : &maps.w3a;
                    const bool b3b = ph == 3 || ph == 4;
                    r.runw(paired, idx & 1, ma, ma + (b3b ? 2 : 1), ph == 2 ? 64 * j : b3b ? 896 + 64 * j : cm,
                           ph == 2 ? 512 + 48 * j : b3b ? 1408 + 40 * j : cr, ph == 3 ? 10 - NA : 0,
                           ph == 5 ? 27 : ph == 4 ? 10 - NA : 10, ph == 0 || ph == 5 ? 0 : OWN * (cm >> 6), ph == 2 ? 14336 : b3b ? 13312 : 10240);
                }
            } else {
                Ring<NA, SM_RA, BAR_FA, BAR_EA> r{sb, 0, 0};
                if (cta >= 120) mbar_wait(bars + (BAR_K + 4) * 8, 0);
                mbar_expect(bars + BAR_XR * 8, 20480);
                bulk_g2s(sb + SM_XR, p.q + (size_t)rho * 16 * D_, 20480, bars + BAR_XR * 8);
                mbar_expect(bars + BAR_XY * 8, 20480);
                tma2d(sb + SM_XT, &maps.xa, cm, rb * 128, bars + BAR_XY * 8);
                tma2d(sb + SM_XT2, &maps.xb, cr, rb * 128, bars + BAR_XY * 8);
                const int grp = j >> 1;
                const int delta = (grp & 1 ? 1 : -1) * (1 + (grp >> 1));
                const int nb = min(max(rb + (delta > 0 ? 1 : -1), 0), 15);
                uint32_t fb = r.acquire(SLOT), dst = r.slot();
                flag_wait2(FL_R + nb, FL_R + rb, ep1 * 8);
                fence_async_global();
                tma2d(dst, &maps.hn, 0, rb * 128 + delta, fb);
                TS(24);
                r.next();
                r.run2d(&maps.hn, rb * 128 + delta);
#pragma unroll 1
                for (int i = 0; i < 2; i++) {
                    const char* src = (const char*)(i ? g_x1 : g_h1) + (size_t)rb * 163840;
                    if (OWN) { r.acquire(0); r.next(); }
                    fb = r.acquire(SLOT); dst = r.slot();
                    const char* src1 = src + (OWN && cm == 0 ? SLOT : 0);
                    flag_wait_fast(FL_B1 + 16 * i + rb, ep1 * 8);
                    fence_async_global();
                    bulk_g2s(dst, src1, SLOT, fb);
                    TS(28 + 4 * i);
                    if (i) mbar_expect(bars + BAR_ST * 8, 0);
                    r.next();
                    r.run1d(src, 1 + OWN, 10, OWN * (cm >> 6));
                }
                r.run1d((const char*)g_x1 + (size_t)rb * 163840, 0, 10 - NA, OWN * (cm >> 6));
#pragma unroll 1
                for (int i = 0; i < 2; i++) {
                    mbar_wait(bars + (BAR_G + i) * 8, 0); fence_async_global();
                    r.run1d((const char*)g_g + (size_t)rb * 442368, 14 * i, 14 + 13 * i, 0);
                }
            }
        }
        return;
    }
    bar_arrive(13, 640);
    asm volatile("setmaxnreg.inc.sync.aligned.u32 112;");
    const int rrow = 16 * rho + (warp >> 1) + 8 * (warp & 1);

    fence_async_smem();
    bar_sync(1 + wg, 128);
#pragma unroll 1
    for (int cc = wg; cc < wg + 1 + (wg == 3); cc++) {
        mbar_wait(bars + (BAR_K + cc) * 8, 0);
        if (cc == 2 && wq == 0) TSW(40);
        uint32_t a = sb + sm_k(cc) + 32 + (tid & 127) * 32;
        uint32_t pw = lds32(a - 4);
        uint4 x = lds128(a), y = lds128(a + 16), o;
        if ((tid & 127) == 0) {
            uint16_t k0 = __bfloat16_as_ushort(__float2bfloat16_rn(blo(x.x) + __uint_as_float(lds32(sb + SM_GV + 520 + cc * 4))));
            x.x = (x.x & 0xffff0000u) | k0;
            sts16(a, k0);
        }
        o.x = prmt(pw, x.x, 0x5432); o.y = prmt(x.x, x.y, 0x5432); o.z = prmt(x.y, x.z, 0x5432); o.w = prmt(x.z, x.w, 0x5432);
        sts128(a + 4160, o);
        o.x = prmt(x.w, y.x, 0x5432); o.y = prmt(y.x, y.y, 0x5432); o.z = prmt(y.y, y.z, 0x5432); o.w = prmt(y.z, y.w, 0x5432);
        sts128(a + 4176, o);
    }
    bar_sync(1 + wg, 128);
    if (wg == 3) bar_arrive(11, 256);
#pragma unroll 1
    for (int cc = wg; cc < 5; cc += 3) {
        if (cc == 3 && wg == 0) break;
        if (cc == 4) bar_sync(11, 256);
        const uint32_t kaddr = sb + sm_k(cc) + ((g & 1) ? 32 : 4192) + 4 * ((g >> 1) - c) + 64 * wq;
        const AFrag f0 = ldA(kaddr), f1 = ldA(kaddr + 256);
        if (STAG && cc == 3) bar_sync(12, 256);
        mbar_wait(bars + (BAR_U + cc) * 8, 0);
        if (wq == 0) TSW(5 + cc);
        float d[64];
        conv_two<0>(d, f0, f1, kaddr, desc_lo(sb + sm_u(cc), U_PLANE), sb + sm_red(cc) + wq * 4352 + g * 544 + c * 8, cc == 1);
        if (wq == 0) TSW(10 + cc);
        if (cc == 1) bar_arrive(6, 256);
    }
#pragma unroll 1
    for (int cc = wg == 1 ? 4 : wg;; cc++) {
        if (cc == 1) bar_sync(6, 256); else bar_sync(1 + wg, 128);
        const int ch = cta * 5 + cc;
        uint32_t* dst = g_yv + ch * 8 + ((g + (ch >> 2)) & 7) + (126 - 32 * wq - 2 * c) * 5120;
        uint2 v[16];
#pragma unroll
        for (int i = 0; i < 16; i++) v[i] = lds64(sb + sm_red(cc) + g * 544 + wq * 128 + c * 8 + (i >> 2) * 32 + (i & 3) * 4360);
#pragma unroll
        for (int w = 1; w < 4; w++)
            if (wq == 3 && c > 3 - w) v[12 + w] = make_uint2(0, 0);
#pragma unroll
        for (int q = 0; q < 4; q++) {
            const uint2* u = v + 4 * q;
            dst[-8 * q * 5120] = badd2(u[0].x, badd2(u[1].x, badd2(u[2].x, u[3].x)));
            dst[(-8 * q + 1) * 5120] = badd2(u[0].y, badd2(u[1].y, badd2(u[2].y, u[3].y)));
        }
        if (wq == 0) TSW(15 + cc);
        if (cc != 0) break;
    }
    fence_async_smem();
    if (!(wg & 1)) bar_arrive(9, 288);
    bar_arrive(7, 544);

    const uint32_t one2 = 0x3f803f80u;
    const unsigned ones = p.ones;
    {
        uint32_t x[10], a[10], cb[10], sbv[10];
        if (RPRE_WAIT) bar_sync(10, 512);
        mbar_wait(bars + BAR_XR * 8, 0);
#pragma unroll
        for (int i = 0; i < 10; i++) x[i] = lds32(sb + SM_XR + (rrow & 15) * 1280 + lane * 4 + i * 128);
        const uint3 s1 = row_stats(x, lane);
        const int up = lane >> 4, gg = warp >> 1, e = warp & 1;
        const uint32_t ya = sb + SM_Y + lane * 64 + ((gg + (lane >> 1)) & 7) * 4;
        const uint32_t sel = (up ? 0x1054u : 0x5410u) + (e ? 0x2222u : 0u);
        const uint32_t ma = sb + SM_MOD + lane * 4;
        mbar_wait(bars + BAR_M * 8, 0);
        uint32_t pin = 0;
#pragma unroll
        for (int i = 0; i < 10; i++) {
            uint32_t h = bfma2(ln_apply(x[i], s1.x, s1.y, s1.z), badd2(lds32(ma + 1280 + i * 128), one2), lds32(ma + i * 128));
            a[i] = bmul2(h, lds32(ma + 2560 + i * 128));
            sbv[i] = lds32(ma + 3840 + i * 128);
            cb[i] = badd2(lds32(ma + 5120 + i * 128), one2);
            pin ^= a[i] ^ cb[i];
        }
        if (pin & ~ones) sts32(sb + SM_GV, pin);
        if (warp == 4) TSW(52);
        mbar_wait(bars + BAR_Y * 8, 0);
        if (warp == 0) TSW(22);
#pragma unroll
        for (int i = 0; i < 10; i++) {
            if (i == 6) mbar_wait(bars + BAR_Y2 * 8, 0);
            uint32_t y0 = lds32(ya + i * 2048 + up * 32), y1 = lds32(ya + i * 2048 + (up ^ 1) * 32);
            x[i] = bfma2(a[i], prmt(y0, y1, sel), x[i]);
        }
        const uint3 s2 = row_stats(x, lane);
#pragma unroll
        for (int i = 0; i < 10; i++) x[i] = bfma2(ln_apply(x[i], s2.x, s2.y, s2.z), cb[i], sbv[i]);
        const uint3 s3 = row_stats(x, lane);
        uint32_t* o = reinterpret_cast<uint32_t*>(g_hn + (size_t)rrow * D_) + lane;
#pragma unroll
        for (int i = 0; i < 10; i++) o[32 * i] = ln_apply(x[i], s3.x, s3.y, s3.z);
        if (lane < 2) g_rs[rrow * 2 + lane] = lane ? make_uint4(s2.x, s2.y, s2.z, 0) : make_uint4(s1.x, s1.y, s1.z, 0);
        if (warp == 0) TSW(34);
        bar_arrive(8, 544);
    }

    const int half = wg & 1;
    const int row = 64 * half + 16 * wq + g;
    const int tw0 = (rb * 80 + (cm >> 3)) * 512 + row * 4 + c, tw1 = (rb * 80 + (cr >> 3) - 8) * 512 + row * 4 + c;
    const uint32_t park = sb + SM_Y + (tid & 255) * 16;
    const uint32_t ms0 = sb + SM_MOD + (cm + 2 * c) * 2, ms1 = sb + SM_MOD + (cr - 64 + 2 * c) * 2;
    if (wg >= 2) {
        {
            float acc[40];
            gemm_loop<80, true, 10, 10, true>(acc, sb, half, 0, 0, 10, 0, 0, 25);
#pragma unroll
            for (int k = 0; k < 10; k += CH) CHUNK(k) {
#pragma unroll
                for (int q = k; q < k + CH && q < 10; q++) {
                    uint32_t* dst = reinterpret_cast<uint32_t*>(g_h1) + (q < 8 ? tw0 : tw1);
                    const uint32_t u = gelu2_h(bmul2(pack2(acc[4 * q], acc[4 * q + 1]), 0x3f003f00u));
                    const uint32_t v = gelu2_h(bmul2(pack2(acc[4 * q + 2], acc[4 * q + 3]), 0x3f003f00u));
                    dst[q * 512] = u;
                    dst[q * 512 + 32] = v;
                    acc[4 * q] = __uint_as_float(u); acc[4 * q + 1] = __uint_as_float(v);
                }
            }
            bar_arrive(15, 288);
            mbar_wait(bars + (BAR_FA + 10 % NA) * 8, (10 / NA) & 1);
#pragma unroll
            for (int q = 0; q < 8; q++) {
                sts32(sb + SM_RA + (10 % NA) * SLOT + q * 2048 + row * 16 + c * 4, __float_as_uint(acc[4 * q]));
                sts32(sb + SM_RA + (10 % NA) * SLOT + q * 2048 + row * 16 + c * 4 + 128, __float_as_uint(acc[4 * q + 1]));
            }
            fence_async_smem();
            bar_arrive(14, 512);
        }
        gemm3<0>(sb, rb, j, half, row, c, ones);
        {
            float acc[40];
            uint32_t gbv[10], base[20];
#pragma unroll
            for (int q = 0; q < 10; q++) gbv[q] = lds32((q < 8 ? ms0 : ms1) + 6400 + q * 16);
#pragma unroll
            for (int q = 0; q < 5; q++) { const uint4 t = lds128(park + q * 4096); base[4 * q] = t.x; base[4 * q + 1] = t.y; base[4 * q + 2] = t.z; base[4 * q + 3] = t.w; }
            gemm_loop<80, false, 27, 27 - NB, true>(acc, sb, half, 40 - NA, 40, 27 - NA, 11, 0, 42);
            auto fin = [&](int q, int r) {
                return bfma2(gbv[q], pack2(acc[4 * q + 2 * r], acc[4 * q + 2 * r + 1]), base[2 * q + r]);
            };
            auto tr4 = [&](uint32_t t0, uint32_t t1, uint32_t t2, uint32_t t3) {
                const bool o1 = c & 1, o2 = c & 2;
                uint32_t a = __shfl_xor_sync(0xffffffffu, o1 ? t0 : t1, 1), b = __shfl_xor_sync(0xffffffffu, o1 ? t2 : t3, 1);
                uint32_t u0 = o1 ? a : t0, u1 = o1 ? t1 : a, u2 = o1 ? b : t2, u3 = o1 ? t3 : b;
                a = __shfl_xor_sync(0xffffffffu, o2 ? u0 : u2, 2); b = __shfl_xor_sync(0xffffffffu, o2 ? u1 : u3, 2);
                return o2 ? make_uint4(a, b, u2, u3) : make_uint4(u0, u1, a, b);
            };
            bf16* go = p.out + (size_t)(rb * 128 + row) * D_;
#pragma unroll
            for (int k = 0; k < 2; k++) CHUNK(k) {
#pragma unroll
                for (int r = 0; r < 2; r++)
                    *reinterpret_cast<uint4*>(go + r * 8 * D_ + cm + 32 * k + 8 * c) = tr4(fin(4 * k, r), fin(4 * k + 1, r), fin(4 * k + 2, r), fin(4 * k + 3, r));
            }
            CHUNK(2) *reinterpret_cast<uint4*>(go + (c >> 1) * 8 * D_ + cr + 8 * (c & 1)) = tr4(fin(8, 0), fin(9, 0), fin(8, 1), fin(9, 1));
            if (tid == 256) TS(44);
            if (warp == 8) TSFLUSH();
        }
    } else {
        {
            float acc[40];
            uint32_t x2[20];
            {
                uint32_t y[20];
                mbar_wait(bars + BAR_XY * 8, 0);
                const uint32_t xa = sb + SM_XT + row * 128 + c * 4, xb = sb + SM_XT2 + row * 32 + c * 4;
                const uint32_t ya = sb + SM_YT + (4 * half + wq) * 2560 + c * 64;
#pragma unroll
                for (int q = 0; q < 10; q++) {
                    const uint32_t a = q < 8 ? xa + ((q ^ g) << 4) : xb + (q - 8) * 16;
                    x2[2 * q] = lds32(a); x2[2 * q + 1] = lds32(a + (q < 8 ? 1024 : 256));
                    const int pos = (g + ((q < 8 ? cm : cr) >> 2) + 2 * q + (c >> 1)) & 7;
                    y[2 * q] = lds32(ya + q * 256 + pos * 4); y[2 * q + 1] = lds32(ya + q * 256 + 32 + pos * 4);
                }
                fence_async_smem();
                bar_sync(1 + wg, 128);
                if ((tid & 127) < NA) mbar_arrive_cl(mapa(bars + (BAR_EA + (tid & 127)) * 8, blockIdx.x & 1));
                mbar_wait(bars + (BAR_FA + 1) * 8, 0);
                const uint4* rp = g_rs + (rb * 128 + row) * 2;
                const uint4 ra = ldcg128(rp), rb2 = ldcg128(rp + 1), rc = ldcg128(rp + 16), rd = ldcg128(rp + 17);
                bar_sync(14, 512);
#pragma unroll
                for (int q = 0; q < 10; q++) {
                    const uint32_t ms = q < 8 ? ms0 : ms1;
                    const uint32_t sa = lds32(ms + 16 * q), ca = badd2(lds32(ms + 1280 + 16 * q), one2), ga = lds32(ms + 2560 + 16 * q);
                    const uint32_t sbv = lds32(ms + 3840 + 16 * q), cb = badd2(lds32(ms + 5120 + 16 * q), one2);
                    uint32_t u = x2[2 * q], v = x2[2 * q + 1];
                    u = bfma2(bmul2(bfma2(ln_apply(u, ra.x, ra.y, ra.z), ca, sa), ga), prmt(y[2 * q], y[2 * q + 1], 0x5410), u);
                    v = bfma2(bmul2(bfma2(ln_apply(v, rc.x, rc.y, rc.z), ca, sa), ga), prmt(y[2 * q], y[2 * q + 1], 0x7632), v);
                    x2[2 * q] = u; x2[2 * q + 1] = v;
                    u = bfma2(ln_apply(u, rb2.x, rb2.y, rb2.z), cb, sbv);
                    v = bfma2(ln_apply(v, rd.x, rd.y, rd.z), cb, sbv);
                    acc[4 * q] = blo(u); acc[4 * q + 1] = bhi(u); acc[4 * q + 2] = blo(v); acc[4 * q + 3] = bhi(v);
                }
            }
            reg_fence<40>(acc);
            if (tid == 0) TS(45);
            gemm_loop<80, false, 10, 10, false>(acc, sb, half, 10, 10, 10, 0, OWN ? 0 : 9, 29);
            uint32_t x1[20];
            float s0 = 0.f, q0 = 0.f, s1 = 0.f, q1 = 0.f;
#pragma unroll
            for (int q = 0; q < 10; q++) {
                uint32_t u = pack2(acc[4 * q], acc[4 * q + 1]);
                uint32_t v = pack2(acc[4 * q + 2], acc[4 * q + 3]);
                uint32_t* dst = reinterpret_cast<uint32_t*>(g_x1) + (q < 8 ? tw0 : tw1);
                dst[q * 512] = u;
                dst[q * 512 + 32] = v;
                x1[2 * q] = u; x1[2 * q + 1] = v;
            }
            CHUNK(0)
#pragma unroll
            for (int q = 0; q < 10; q++) {
                float a = blo(x1[2 * q]), b = bhi(x1[2 * q]), e = blo(x1[2 * q + 1]), f = bhi(x1[2 * q + 1]);
                s0 += a + b; q0 = fmaf(a, a, fmaf(b, b, q0));
                s1 += e + f; q1 = fmaf(e, e, fmaf(f, f, q1));
            }
#pragma unroll
            for (int m = 1; m <= 2; m <<= 1) {
                s0 += __shfl_xor_sync(0xffffffffu, s0, m); q0 += __shfl_xor_sync(0xffffffffu, q0, m);
                s1 += __shfl_xor_sync(0xffffffffu, s1, m); q1 += __shfl_xor_sync(0xffffffffu, q1, m);
            }
            if (c < 2) g_st[(rb * 8 + j) * 128 + row + 8 * c] = c ? make_float2(s1, q1) : make_float2(s0, q0);
            bar_arrive(6, 288);
            mbar_wait(bars + (BAR_FA + 20 % NA) * 8, (20 / NA) & 1);
#pragma unroll
            for (int q = 0; q < 8; q++) {
                sts32(sb + SM_RA + (20 % NA) * SLOT + q * 2048 + row * 16 + c * 4, x1[2 * q]);
                sts32(sb + SM_RA + (20 % NA) * SLOT + q * 2048 + row * 16 + c * 4 + 128, x1[2 * q + 1]);
            }
            fence_async_smem();
            bar_arrive(9, 512);
#pragma unroll
            for (int q = 0; q < 5; q++) {
                const uint32_t ms = q < 4 ? ms0 : ms1;
                const uint32_t g0 = lds32(ms + 6400 + q * 32), g1 = lds32(ms + 6400 + q * 32 + 16);
                sts128(park + q * 4096, make_uint4(bfma2(g0, x1[4 * q], x2[4 * q]), bfma2(g0, x1[4 * q + 1], x2[4 * q + 1]),
                                                   bfma2(g1, x1[4 * q + 2], x2[4 * q + 2]), bfma2(g1, x1[4 * q + 3], x2[4 * q + 3])));
            }
        }
        gemm3<1>(sb, rb, j, half, row, c, ones);
    }
}

typedef CUresult (*EncFn)(CUtensorMap*, CUtensorMapDataType, cuuint32_t, void*, const cuuint64_t*, const cuuint64_t*,
                          const cuuint32_t*, const cuuint32_t*, CUtensorMapInterleave, CUtensorMapSwizzle,
                          CUtensorMapL2promotion, CUtensorMapFloatOOBfill);

void make_map(EncFn enc, CUtensorMap* m, const void* base, uint64_t inner, uint64_t outer, uint32_t bi, uint32_t bo,
              CUtensorMapSwizzle swz = CU_TENSOR_MAP_SWIZZLE_128B) {
    cuuint64_t dims[2] = {inner, outer};
    cuuint64_t st[1] = {inner * 2};
    cuuint32_t box[2] = {bi, bo};
    cuuint32_t es[2] = {1, 1};
    enc(m, CU_TENSOR_MAP_DATA_TYPE_BFLOAT16, 2, const_cast<void*>(base), dims, st, box, es, CU_TENSOR_MAP_INTERLEAVE_NONE,
        swz, CU_TENSOR_MAP_L2_PROMOTION_NONE, CU_TENSOR_MAP_FLOAT_OOB_FILL_NONE);
}

}

extern "C" void kernel_launch(void* const* d_in, const int* in_sizes, int n_in, void* d_out, int out_size) {
    (void)in_sizes; (void)n_in; (void)out_size;
    Params p;
    p.q = (const bf16*)d_in[0]; p.k = (const bf16*)d_in[1]; p.v = (const bf16*)d_in[2];
    p.shift = (const bf16*)d_in[3]; p.ssmk = (const bf16*)d_in[4]; p.ssmD = (const bf16*)d_in[5];
    p.w1 = (const bf16*)d_in[7]; p.w2 = (const bf16*)d_in[8]; p.w3 = (const bf16*)d_in[9]; p.w4 = (const bf16*)d_in[10];
    p.c = (const bf16*)d_in[11]; p.wmod = (const bf16*)d_in[12];
    p.out = (bf16*)d_out;
    p.ones = 0xffffffffu;

    void* fn = nullptr;
    cudaDriverEntryPointQueryResult qr;
    cudaGetDriverEntryPoint("cuTensorMapEncodeTiled", &fn, cudaEnableDefault, &qr);
    EncFn enc = (EncFn)fn;
    void* hn = nullptr;
    cudaGetSymbolAddress(&hn, g_hn);
    Maps maps;
    make_map(enc, &maps.w3s, p.w3, F_, D_, 216, 64, CU_TENSOR_MAP_SWIZZLE_NONE);
    make_map(enc, &maps.wm, p.wmod, 6 * D_, D_, 32, 128, CU_TENSOR_MAP_SWIZZLE_64B);
    make_map(enc, &maps.xa, p.q, D_, S_, 64, 128);
    make_map(enc, &maps.xb, p.q, D_, S_, 16, 128, CU_TENSOR_MAP_SWIZZLE_NONE);
    make_map(enc, &maps.hn, hn, D_, S_, 64, 128);
    make_map(enc, &maps.w1a, p.w1, D_, D_, 64, 64);
    make_map(enc, &maps.w1b, p.w1, D_, D_, 16, 64);
    make_map(enc, &maps.w2a, p.w2, D_, D_, 64, 64);
    make_map(enc, &maps.w2b, p.w2, D_, D_, 16, 64);
    make_map(enc, &maps.w3a, p.w3, F_, D_, 64, 64);
    make_map(enc, &maps.w3b, p.w3, F_, D_, 48, 64);
    make_map(enc, &maps.w3c, p.w3, F_, D_, 40, 64);
    make_map(enc, &maps.w4a, p.w4, D_, F_, 64, 64);
    make_map(enc, &maps.w4b, p.w4, D_, F_, 16, 64);
    cudaFuncSetAttribute(fused_kernel, cudaFuncAttributeMaxDynamicSharedMemorySize, SMEM_BYTES);
    fused_kernel<<<132, NTHREADS, SMEM_BYTES>>>(p, maps);
}
```

```cpp
#include <cuda_runtime.h>
#include <cuda_bf16.h>
#include <cuda.h>
#include <stdint.h>
#include <string.h>

#define SEED 0
#define RING_A 6
#define MMA_STAT 0
#define CH 2
#define FAST_LN 2
#define STAG 10
#define REDM 1
#define CONVV 0
#define NPOLL 1
#define PGELU 2
#define CH3 4
#define HO_A 16
#define HO_B 16
#define RA3 48
#define CSP 16
#define OWNG 1
#define HOLD 1
#define SSM_DELAY 0
#define B_DELAY 300
#define RPRE_WAIT 1
#define XAFTER 0
#define SSM_N 3
#define PF_EARLY 0

namespace {

typedef __nv_bfloat16 bf16;
typedef __nv_bfloat162 bf162;

constexpr int S_ = 2048, D_ = 640, F_ = 1728;
constexpr int NTHREADS = 640;
constexpr int NA = RING_A, NB = 12 - RING_A;
constexpr int SLOT = 16384;
constexpr int RB3 = 88 - RA3, HB0 = 512 + 8 * RA3;
constexpr int SM_RA = 0, SM_RB = NA * SLOT;

static_assert(NA == 6, "smem map");
constexpr int RED_STRIDE = 17536;
constexpr int K_STRIDE = 8320;
constexpr int U_PLANE = 2560, U_STRIDE = 5120;
constexpr int SM_Y = 12 * SLOT;
__device__ __forceinline__ int sm_red(int cc) { return cc * RED_STRIDE + (cc < 3 ? SM_RB : -3 * RED_STRIDE); }
__device__ __forceinline__ int sm_k(int cc) { return cc * K_STRIDE + (cc < 3 ? SM_RB + 3 * RED_STRIDE : 2 * RED_STRIDE - 3 * K_STRIDE); }
__device__ __forceinline__ int sm_u(int cc) { return cc * U_STRIDE + (cc < 3 ? SM_RB + 3 * RED_STRIDE + 3 * K_STRIDE : SM_Y + 8192 - 3 * U_STRIDE); }
constexpr int SM_PK = SM_RB;
constexpr int SM_PV = SM_RB + 24576;
constexpr int SM_WM = 57344;
constexpr int SM_XT = SM_WM, SM_XT2 = SM_WM + 16384, SM_XR = SM_WM + 20480;
constexpr int SM_YT = 0;
constexpr int SM_MOD = SM_Y + 20480;
constexpr int SM_GV = SM_MOD + 7680;
constexpr int SM_CS = SM_GV + 1024;
constexpr int SM_RP = SM_CS + 1024;
constexpr int SM_BAR = SM_RP + 1024;
constexpr int SM_PROF = SM_BAR + 512;
constexpr int SM_TOTAL = SM_PROF + 512;
constexpr int SMEM_BYTES = SM_TOTAL + 1024;
static_assert(SMEM_BYTES <= 232448, "smem");

constexpr int BAR_FA = 0, BAR_FB = NA, BAR_EA = 12, BAR_EB = 12 + NA, BAR_K = 24, BAR_U = 29, BAR_Y = 34, BAR_CS = 35, BAR_WM = 36, BAR_M = 37, BAR_XY = 38, BAR_Y2 = 39, BAR_G = 40, BAR_ST = 43, BAR_XR = 44, NBARS = 45;

__device__ __align__(1024) bf16 g_kvT[D_ * S_];
__device__ __align__(1024) uint32_t g_yv[128 * 5120];
__device__ __align__(1024) bf16 g_mod[6 * D_];
__device__ __align__(1024) bf16 g_hn[S_ * D_];
__device__ __align__(1024) uint4 g_rs[S_ * 2];
__device__ __align__(1024) bf16 g_h1[S_ * D_];
__device__ __align__(1024) bf16 g_x1[S_ * D_];
__device__ __align__(1024) bf16 g_g[S_ * F_];
__device__ __align__(1024) float2 g_st[S_ * 8];
__device__ __align__(1024) float g_cs[F_];
__device__ __align__(1024) unsigned g_flags[128 * 32];
__device__ __align__(1024) unsigned g_epoch[160];
constexpr int FL_P = 0, FL_C = 8, FL_CS = 9, FL_M = 10, FL_R = 16, FL_B1 = 32, FL_B2 = 48, FL_G = 64;

#define TS(i) do {} while (0)
#define TSW(i) do {} while (0)
#define TSD(i, dep) do {} while (0)
#define TSD2(i, dep) do {} while (0)
#define TSFLUSH() do {} while (0)

struct Params {
    const bf16 *q, *k, *v, *shift, *ssmk, *ssmD, *w1, *w2, *w3, *w4, *c, *wmod;
    bf16* out;
    unsigned ones;
};
#define CHUNK(k) if (ones & (1u << (k)))
struct Maps { CUtensorMap hn, w1a, w1b, w2a, w2b, w3a, w3b, w3c, w4a, w4b, wm, xa, xb, w3s; };

template<int N> struct WgRs;
template<int N> struct WgSs;
template<> struct WgRs<32> { template<int OFF,int HI,int SC> static __device__ __forceinline__ void run(float* d,uint32_t a0,uint32_t a1,uint32_t a2,uint32_t a3,uint32_t blo){
 asm volatile("{.reg .b32 l; .reg .b64 db; add.u32 l,%20,%21; mov.b64 db,{l,%22}; wgmma.mma_async.sync.aligned.m64n32k16.f32.bf16.bf16 {%0,%1,%2,%3,%4,%5,%6,%7,%8,%9,%10,%11,%12,%13,%14,%15},{%16,%17,%18,%19},db,%23,1,1,0;}"
 :"+f"(d[0]),"+f"(d[1]),"+f"(d[2]),"+f"(d[3]),"+f"(d[4]),"+f"(d[5]),"+f"(d[6]),"+f"(d[7]),"+f"(d[8]),"+f"(d[9]),"+f"(d[10]),"+f"(d[11]),"+f"(d[12]),"+f"(d[13]),"+f"(d[14]),"+f"(d[15])
 :"r"(a0),"r"(a1),"r"(a2),"r"(a3),"r"(blo),"n"(OFF),"n"(HI),"n"(SC)); } };
template<> struct WgRs<48> { template<int OFF,int HI,int SC> static __device__ __forceinline__ void run(float* d,uint32_t a0,uint32_t a1,uint32_t a2,uint32_t a3,uint32_t blo){
 asm volatile("{.reg .b32 l; .reg .b64 db; add.u32 l,%28,%29; mov.b64 db,{l,%30}; wgmma.mma_async.sync.aligned.m64n48k16.f32.bf16.bf16 {%0,%1,%2,%3,%4,%5,%6,%7,%8,%9,%10,%11,%12,%13,%14,%15,%16,%17,%18,%19,%20,%21,%22,%23},{%24,%25,%26,%27},db,%31,1,1,0;}"
 :"+f"(d[0]),"+f"(d[1]),"+f"(d[2]),"+f"(d[3]),"+f"(d[4]),"+f"(d[5]),"+f"(d[6]),"+f"(d[7]),"+f"(d[8]),"+f"(d[9]),"+f"(d[10]),"+f"(d[11]),"+f"(d[12]),"+f"(d[13]),"+f"(d[14]),"+f"(d[15]),"+f"(d[16]),"+f"(d[17]),"+f"(d[18]),"+f"(d[19]),"+f"(d[20]),"+f"(d[21]),"+f"(d[22]),"+f"(d[23])
 :"r"(a0),"r"(a1),"r"(a2),"r"(a3),"r"(blo),"n"(OFF),"n"(HI),"n"(SC)); } };
template<> struct WgRs<64> { template<int OFF,int HI,int SC> static __device__ __forceinline__ void run(float* d,uint32_t a0,uint32_t a1,uint32_t a2,uint32_t a3,uint32_t blo){
 asm volatile("{.reg .b32 l; .reg .b64 db; add.u32 l,%36,%37; mov.b64 db,{l,%38}; wgmma.mma_async.sync.aligned.m64n64k16.f32.bf16.bf16 {%0,%1,%2,%3,%4,%5,%6,%7,%8,%9,%10,%11,%12,%13,%14,%15,%16,%17,%18,%19,%20,%21,%22,%23,%24,%25,%26,%27,%28,%29,%30,%31},{%32,%33,%34,%35},db,%39,1,1,0;}"
 :"+f"(d[0]),"+f"(d[1]),"+f"(d[2]),"+f"(d[3]),"+f"(d[4]),"+f"(d[5]),"+f"(d[6]),"+f"(d[7]),"+f"(d[8]),"+f"(d[9]),"+f"(d[10]),"+f"(d[11]),"+f"(d[12]),"+f"(d[13]),"+f"(d[14]),"+f"(d[15]),"+f"(d[16]),"+f"(d[17]),"+f"(d[18]),"+f"(d[19]),"+f"(d[20]),"+f"(d[21]),"+f"(d[22]),"+f"(d[23]),"+f"(d[24]),"+f"(d[25]),"+f"(d[26]),"+f"(d[27]),"+f"(d[28]),"+f"(d[29]),"+f"(d[30]),"+f"(d[31])
 :"r"(a0),"r"(a1),"r"(a2),"r"(a3),"r"(blo),"n"(OFF),"n"(HI),"n"(SC)); } };
template<> struct WgRs<80> { template<int OFF,int HI,int SC> static __device__ __forceinline__ void run(float* d,uint32_t a0,uint32_t a1,uint32_t a2,uint32_t a3,uint32_t blo){
 asm volatile("{.reg .b32 l; .reg .b64 db; add.u32 l,%44,%45; mov.b64 db,{l,%46}; wgmma.mma_async.sync.aligned.m64n80k16.f32.bf16.bf16 {%0,%1,%2,%3,%4,%5,%6,%7,%8,%9,%10,%11,%12,%13,%14,%15,%16,%17,%18,%19,%20,%21,%22,%23,%24,%25,%26,%27,%28,%29,%30,%31,%32,%33,%34,%35,%36,%37,%38,%39},{%40,%41,%42,%43},db,%47,1,1,0;}"
 :"+f"(d[0]),"+f"(d[1]),"+f"(d[2]),"+f"(d[3]),"+f"(d[4]),"+f"(d[5]),"+f"(d[6]),"+f"(d[7]),"+f"(d[8]),"+f"(d[9]),"+f"(d[10]),"+f"(d[11]),"+f"(d[12]),"+f"(d[13]),"+f"(d[14]),"+f"(d[15]),"+f"(d[16]),"+f"(d[17]),"+f"(d[18]),"+f"(d[19]),"+f"(d[20]),"+f"(d[21]),"+f"(d[22]),"+f"(d[23]),"+f"(d[24]),"+f"(d[25]),"+f"(d[26]),"+f"(d[27]),"+f"(d[28]),"+f"(d[29]),"+f"(d[30]),"+f"(d[31]),"+f"(d[32]),"+f"(d[33]),"+f"(d[34]),"+f"(d[35]),"+f"(d[36]),"+f"(d[37]),"+f"(d[38]),"+f"(d[39])
 :"r"(a0),"r"(a1),"r"(a2),"r"(a3),"r"(blo),"n"(OFF),"n"(HI),"n"(SC)); } };
template<> struct WgRs<96> { template<int OFF,int HI,int SC> static __device__ __forceinline__ void run(float* d,uint32_t a0,uint32_t a1,uint32_t a2,uint32_t a3,uint32_t blo){
 asm volatile("{.reg .b32 l; .reg .b64 db; add.u32 l,%52,%53; mov.b64 db,{l,%54}; wgmma.mma_async.sync.aligned.m64n96k16.f32.bf16.bf16 {%0,%1,%2,%3,%4,%5,%6,%7,%8,%9,%10,%11,%12,%13,%14,%15,%16,%17,%18,%19,%20,%21,%22,%23,%24,%25,%26,%27,%28,%29,%30,%31,%32,%33,%34,%35,%36,%37,%38,%39,%40,%41,%42,%43,%44,%45,%46,%47},{%48,%49,%50,%51},db,%55,1,1,0;}"
 :"+f"(d[0]),"+f"(d[1]),"+f"(d[2]),"+f"(d[3]),"+f"(d[4]),"+f"(d[5]),"+f"(d[6]),"+f"(d[7]),"+f"(d[8]),"+f"(d[9]),"+f"(d[10]),"+f"(d[11]),"+f"(d[12]),"+f"(d[13]),"+f"(d[14]),"+f"(d[15]),"+f"(d[16]),"+f"(d[17]),"+f"(d[18]),"+f"(d[19]),"+f"(d[20]),"+f"(d[21]),"+f"(d[22]),"+f"(d[23]),"+f"(d[24]),"+f"(d[25]),"+f"(d[26]),"+f"(d[27]),"+f"(d[28]),"+f"(d[29]),"+f"(d[30]),"+f"(d[31]),"+f"(d[32]),"+f"(d[33]),"+f"(d[34]),"+f"(d[35]),"+f"(d[36]),"+f"(d[37]),"+f"(d[38]),"+f"(d[39]),"+f"(d[40]),"+f"(d[41]),"+f"(d[42]),"+f"(d[43]),"+f"(d[44]),"+f"(d[45]),"+f"(d[46]),"+f"(d[47])
 :"r"(a0),"r"(a1),"r"(a2),"r"(a3),"r"(blo),"n"(OFF),"n"(HI),"n"(SC)); } };
template<> struct WgRs<112> { template<int OFF,int HI,int SC> static __device__ __forceinline__ void run(float* d,uint32_t a0,uint32_t a1,uint32_t a2,uint32_t a3,uint32_t blo){
 asm volatile("{.reg .b32 l; .reg .b64 db; add.u32 l,%60,%61; mov.b64 db,{l,%62}; wgmma.mma_async.sync.aligned.m64n112k16.f32.bf16.bf16 {%0,%1,%2,%3,%4,%5,%6,%7,%8,%9,%10,%11,%12,%13,%14,%15,%16,%17,%18,%19,%20,%21,%22,%23,%24,%25,%26,%27,%28,%29,%30,%31,%32,%33,%34,%35,%36,%37,%38,%39,%40,%41,%42,%43,%44,%45,%46,%47,%48,%49,%50,%51,%52,%53,%54,%55},{%56,%57,%58,%59},db,%63,1,1,0;}"
 :"+f"(d[0]),"+f"(d[1]),"+f"(d[2]),"+f"(d[3]),"+f"(d[4]),"+f"(d[5]),"+f"(d[6]),"+f"(d[7]),"+f"(d[8]),"+f"(d[9]),"+f"(d[10]),"+f"(d[11]),"+f"(d[12]),"+f"(d[13]),"+f"(d[14]),"+f"(d[15]),"+f"(d[16]),"+f"(d[17]),"+f"(d[18]),"+f"(d[19]),"+f"(d[20]),"+f"(d[21]),"+f"(d[22]),"+f"(d[23]),"+f"(d[24]),"+f"(d[25]),"+f"(d[26]),"+f"(d[27]),"+f"(d[28]),"+f"(d[29]),"+f"(d[30]),"+f"(d[31]),"+f"(d[32]),"+f"(d[33]),"+f"(d[34]),"+f"(d[35]),"+f"(d[36]),"+f"(d[37]),"+f"(d[38]),"+f"(d[39]),"+f"(d[40]),"+f"(d[41]),"+f"(d[42]),"+f"(d[43]),"+f"(d[44]),"+f"(d[45]),"+f"(d[46]),"+f"(d[47]),"+f"(d[48]),"+f"(d[49]),"+f"(d[50]),"+f"(d[51]),"+f"(d[52]),"+f"(d[53]),"+f"(d[54]),"+f"(d[55])
 :"r"(a0),"r"(a1),"r"(a2),"r"(a3),"r"(blo),"n"(OFF),"n"(HI),"n"(SC)); } };
template<> struct WgRs<128> { template<int OFF,int HI,int SC> static __device__ __forceinline__ void run(float* d,uint32_t a0,uint32_t a1,uint32_t a2,uint32_t a3,uint32_t blo){
 asm volatile("{.reg .b32 l; .reg .b64 db; add.u32 l,%68,%69; mov.b64 db,{l,%70}; wgmma.mma_async.sync.aligned.m64n128k16.f32.bf16.bf16 {%0,%1,%2,%3,%4,%5,%6,%7,%8,%9,%10,%11,%12,%13,%14,%15,%16,%17,%18,%19,%20,%21,%22,%23,%24,%25,%26,%27,%28,%29,%30,%31,%32,%33,%34,%35,%36,%37,%38,%39,%40,%41,%42,%43,%44,%45,%46,%47,%48,%49,%50,%51,%52,%53,%54,%55,%56,%57,%58,%59,%60,%61,%62,%63},{%64,%65,%66,%67},db,%71,1,1,0;}"
 :"+f"(d[0]),"+f"(d[1]),"+f"(d[2]),"+f"(d[3]),"+f"(d[4]),"+f"(d[5]),"+f"(d[6]),"+f"(d[7]),"+f"(d[8]),"+f"(d[9]),"+f"(d[10]),"+f"(d[11]),"+f"(d[12]),"+f"(d[13]),"+f"(d[14]),"+f"(d[15]),"+f"(d[16]),"+f"(d[17]),"+f"(d[18]),"+f"(d[19]),"+f"(d[20]),"+f"(d[21]),"+f"(d[22]),"+f"(d[23]),"+f"(d[24]),"+f"(d[25]),"+f"(d[26]),"+f"(d[27]),"+f"(d[28]),"+f"(d[29]),"+f"(d[30]),"+f"(d[31]),"+f"(d[32]),"+f"(d[33]),"+f"(d[34]),"+f"(d[35]),"+f"(d[36]),"+f"(d[37]),"+f"(d[38]),"+f"(d[39]),"+f"(d[40]),"+f"(d[41]),"+f"(d[42]),"+f"(d[43]),"+f"(d[44]),"+f"(d[45]),"+f"(d[46]),"+f"(d[47]),"+f"(d[48]),"+f"(d[49]),"+f"(d[50]),"+f"(d[51]),"+f"(d[52]),"+f"(d[53]),"+f"(d[54]),"+f"(d[55]),"+f"(d[56]),"+f"(d[57]),"+f"(d[58]),"+f"(d[59]),"+f"(d[60]),"+f"(d[61]),"+f"(d[62]),"+f"(d[63])
 :"r"(a0),"r"(a1),"r"(a2),"r"(a3),"r"(blo),"n"(OFF),"n"(HI),"n"(SC)); } };
template<> struct WgSs<80> { template<int AOFF,int AHI,int BOFF,int BHI,int SC> static __device__ __forceinline__ void run(float* d,uint32_t alo,uint32_t blo){
 asm volatile("{.reg .b32 l,m; .reg .b64 da,db; add.u32 l,%40,%42; mov.b64 da,{l,%43}; add.u32 m,%41,%44; mov.b64 db,{m,%45}; wgmma.mma_async.sync.aligned.m64n80k16.f32.bf16.bf16 {%0,%1,%2,%3,%4,%5,%6,%7,%8,%9,%10,%11,%12,%13,%14,%15,%16,%17,%18,%19,%20,%21,%22,%23,%24,%25,%26,%27,%28,%29,%30,%31,%32,%33,%34,%35,%36,%37,%38,%39},da,db,%46,1,1,0,1;}"
 :"+f"(d[0]),"+f"(d[1]),"+f"(d[2]),"+f"(d[3]),"+f"(d[4]),"+f"(d[5]),"+f"(d[6]),"+f"(d[7]),"+f"(d[8]),"+f"(d[9]),"+f"(d[10]),"+f"(d[11]),"+f"(d[12]),"+f"(d[13]),"+f"(d[14]),"+f"(d[15]),"+f"(d[16]),"+f"(d[17]),"+f"(d[18]),"+f"(d[19]),"+f"(d[20]),"+f"(d[21]),"+f"(d[22]),"+f"(d[23]),"+f"(d[24]),"+f"(d[25]),"+f"(d[26]),"+f"(d[27]),"+f"(d[28]),"+f"(d[29]),"+f"(d[30]),"+f"(d[31]),"+f"(d[32]),"+f"(d[33]),"+f"(d[34]),"+f"(d[35]),"+f"(d[36]),"+f"(d[37]),"+f"(d[38]),"+f"(d[39])
 :"r"(alo),"r"(blo),"n"(AOFF),"n"(AHI),"n"(BOFF),"n"(BHI),"n"(SC)); } };
template<> struct WgSs<88> { template<int AOFF,int AHI,int BOFF,int BHI,int SC> static __device__ __forceinline__ void run(float* d,uint32_t alo,uint32_t blo){
 asm volatile("{.reg .b32 l,m; .reg .b64 da,db; add.u32 l,%44,%46; mov.b64 da,{l,%47}; add.u32 m,%45,%48; mov.b64 db,{m,%49}; wgmma.mma_async.sync.aligned.m64n88k16.f32.bf16.bf16 {%0,%1,%2,%3,%4,%5,%6,%7,%8,%9,%10,%11,%12,%13,%14,%15,%16,%17,%18,%19,%20,%21,%22,%23,%24,%25,%26,%27,%28,%29,%30,%31,%32,%33,%34,%35,%36,%37,%38,%39,%40,%41,%42,%43},da,db,%50,1,1,0,1;}"
 :"+f"(d[0]),"+f"(d[1]),"+f"(d[2]),"+f"(d[3]),"+f"(d[4]),"+f"(d[5]),"+f"(d[6]),"+f"(d[7]),"+f"(d[8]),"+f"(d[9]),"+f"(d[10]),"+f"(d[11]),"+f"(d[12]),"+f"(d[13]),"+f"(d[14]),"+f"(d[15]),"+f"(d[16]),"+f"(d[17]),"+f"(d[18]),"+f"(d[19]),"+f"(d[20]),"+f"(d[21]),"+f"(d[22]),"+f"(d[23]),"+f"(d[24]),"+f"(d[25]),"+f"(d[26]),"+f"(d[27]),"+f"(d[28]),"+f"(d[29]),"+f"(d[30]),"+f"(d[31]),"+f"(d[32]),"+f"(d[33]),"+f"(d[34]),"+f"(d[35]),"+f"(d[36]),"+f"(d[37]),"+f"(d[38]),"+f"(d[39]),"+f"(d[40]),"+f"(d[41]),"+f"(d[42]),"+f"(d[43])
 :"r"(alo),"r"(blo),"n"(AOFF),"n"(AHI),"n"(BOFF),"n"(BHI),"n"(SC)); } };
template<> struct WgSs<96> { template<int AOFF,int AHI,int BOFF,int BHI,int SC> static __device__ __forceinline__ void run(float* d,uint32_t alo,uint32_t blo){
 asm volatile("{.reg .b32 l,m; .reg .b64 da,db; add.u32 l,%48,%50; mov.b64 da,{l,%51}; add.u32 m,%49,%52; mov.b64 db,{m,%53}; wgmma.mma_async.sync.aligned.m64n96k16.f32.bf16.bf16 {%0,%1,%2,%3,%4,%5,%6,%7,%8,%9,%10,%11,%12,%13,%14,%15,%16,%17,%18,%19,%20,%21,%22,%23,%24,%25,%26,%27,%28,%29,%30,%31,%32,%33,%34,%35,%36,%37,%38,%39,%40,%41,%42,%43,%44,%45,%46,%47},da,db,%54,1,1,0,1;}"
 :"+f"(d[0]),"+f"(d[1]),"+f"(d[2]),"+f"(d[3]),"+f"(d[4]),"+f"(d[5]),"+f"(d[6]),"+f"(d[7]),"+f"(d[8]),"+f"(d[9]),"+f"(d[10]),"+f"(d[11]),"+f"(d[12]),"+f"(d[13]),"+f"(d[14]),"+f"(d[15]),"+f"(d[16]),"+f"(d[17]),"+f"(d[18]),"+f"(d[19]),"+f"(d[20]),"+f"(d[21]),"+f"(d[22]),"+f"(d[23]),"+f"(d[24]),"+f"(d[25]),"+f"(d[26]),"+f"(d[27]),"+f"(d[28]),"+f"(d[29]),"+f"(d[30]),"+f"(d[31]),"+f"(d[32]),"+f"(d[33]),"+f"(d[34]),"+f"(d[35]),"+f"(d[36]),"+f"(d[37]),"+f"(d[38]),"+f"(d[39]),"+f"(d[40]),"+f"(d[41]),"+f"(d[42]),"+f"(d[43]),"+f"(d[44]),"+f"(d[45]),"+f"(d[46]),"+f"(d[47])
 :"r"(alo),"r"(blo),"n"(AOFF),"n"(AHI),"n"(BOFF),"n"(BHI),"n"(SC)); } };
template<> struct WgSs<104> { template<int AOFF,int AHI,int BOFF,int BHI,int SC> static __device__ __forceinline__ void run(float* d,uint32_t alo,uint32_t blo){
 asm volatile("{.reg .b32 l,m; .reg .b64 da,db; add.u32 l,%52,%54; mov.b64 da,{l,%55}; add.u32 m,%53,%56; mov.b64 db,{m,%57}; wgmma.mma_async.sync.aligned.m64n104k16.f32.bf16.bf16 {%0,%1,%2,%3,%4,%5,%6,%7,%8,%9,%10,%11,%12,%13,%14,%15,%16,%17,%18,%19,%20,%21,%22,%23,%24,%25,%26,%27,%28,%29,%30,%31,%32,%33,%34,%35,%36,%37,%38,%39,%40,%41,%42,%43,%44,%45,%46,%47,%48,%49,%50,%51},da,db,%58,1,1,0,1;}"
 :"+f"(d[0]),"+f"(d[1]),"+f"(d[2]),"+f"(d[3]),"+f"(d[4]),"+f"(d[5]),"+f"(d[6]),"+f"(d[7]),"+f"(d[8]),"+f"(d[9]),"+f"(d[10]),"+f"(d[11]),"+f"(d[12]),"+f"(d[13]),"+f"(d[14]),"+f"(d[15]),"+f"(d[16]),"+f"(d[17]),"+f"(d[18]),"+f"(d[19]),"+f"(d[20]),"+f"(d[21]),"+f"(d[22]),"+f"(d[23]),"+f"(d[24]),"+f"(d[25]),"+f"(d[26]),"+f"(d[27]),"+f"(d[28]),"+f"(d[29]),"+f"(d[30]),"+f"(d[31]),"+f"(d[32]),"+f"(d[33]),"+f"(d[34]),"+f"(d[35]),"+f"(d[36]),"+f"(d[37]),"+f"(d[38]),"+f"(d[39]),"+f"(d[40]),"+f"(d[41]),"+f"(d[42]),"+f"(d[43]),"+f"(d[44]),"+f"(d[45]),"+f"(d[46]),"+f"(d[47]),"+f"(d[48]),"+f"(d[49]),"+f"(d[50]),"+f"(d[51])
 :"r"(alo),"r"(blo),"n"(AOFF),"n"(AHI),"n"(BOFF),"n"(BHI),"n"(SC)); } };
template<> struct WgSs<112> { template<int AOFF,int AHI,int BOFF,int BHI,int SC> static __device__ __forceinline__ void run(float* d,uint32_t alo,uint32_t blo){
 asm volatile("{.reg .b32 l,m; .reg .b64 da,db; add.u32 l,%56,%58; mov.b64 da,{l,%59}; add.u32 m,%57,%60; mov.b64 db,{m,%61}; wgmma.mma_async.sync.aligned.m64n112k16.f32.bf16.bf16 {%0,%1,%2,%3,%4,%5,%6,%7,%8,%9,%10,%11,%12,%13,%14,%15,%16,%17,%18,%19,%20,%21,%22,%23,%24,%25,%26,%27,%28,%29,%30,%31,%32,%33,%34,%35,%36,%37,%38,%39,%40,%41,%42,%43,%44,%45,%46,%47,%48,%49,%50,%51,%52,%53,%54,%55},da,db,%62,1,1,0,1;}"
 :"+f"(d[0]),"+f"(d[1]),"+f"(d[2]),"+f"(d[3]),"+f"(d[4]),"+f"(d[5]),"+f"(d[6]),"+f"(d[7]),"+f"(d[8]),"+f"(d[9]),"+f"(d[10]),"+f"(d[11]),"+f"(d[12]),"+f"(d[13]),"+f"(d[14]),"+f"(d[15]),"+f"(d[16]),"+f"(d[17]),"+f"(d[18]),"+f"(d[19]),"+f"(d[20]),"+f"(d[21]),"+f"(d[22]),"+f"(d[23]),"+f"(d[24]),"+f"(d[25]),"+f"(d[26]),"+f"(d[27]),"+f"(d[28]),"+f"(d[29]),"+f"(d[30]),"+f"(d[31]),"+f"(d[32]),"+f"(d[33]),"+f"(d[34]),"+f"(d[35]),"+f"(d[36]),"+f"(d[37]),"+f"(d[38]),"+f"(d[39]),"+f"(d[40]),"+f"(d[41]),"+f"(d[42]),"+f"(d[43]),"+f"(d[44]),"+f"(d[45]),"+f"(d[46]),"+f"(d[47]),"+f"(d[48]),"+f"(d[49]),"+f"(d[50]),"+f"(d[51]),"+f"(d[52]),"+f"(d[53]),"+f"(d[54]),"+f"(d[55])
 :"r"(alo),"r"(blo),"n"(AOFF),"n"(AHI),"n"(BOFF),"n"(BHI),"n"(SC)); } };
template<> struct WgSs<120> { template<int AOFF,int AHI,int BOFF,int BHI,int SC> static __device__ __forceinline__ void run(float* d,uint32_t alo,uint32_t blo){
 asm volatile("{.reg .b32 l,m; .reg .b64 da,db; add.u32 l,%60,%62; mov.b64 da,{l,%63}; add.u32 m,%61,%64; mov.b64 db,{m,%65}; wgmma.mma_async.sync.aligned.m64n120k16.f32.bf16.bf16 {%0,%1,%2,%3,%4,%5,%6,%7,%8,%9,%10,%11,%12,%13,%14,%15,%16,%17,%18,%19,%20,%21,%22,%23,%24,%25,%26,%27,%28,%29,%30,%31,%32,%33,%34,%35,%36,%37,%38,%39,%40,%41,%42,%43,%44,%45,%46,%47,%48,%49,%50,%51,%52,%53,%54,%55,%56,%57,%58,%59},da,db,%66,1,1,0,1;}"
 :"+f"(d[0]),"+f"(d[1]),"+f"(d[2]),"+f"(d[3]),"+f"(d[4]),"+f"(d[5]),"+f"(d[6]),"+f"(d[7]),"+f"(d[8]),"+f"(d[9]),"+f"(d[10]),"+f"(d[11]),"+f"(d[12]),"+f"(d[13]),"+f"(d[14]),"+f"(d[15]),"+f"(d[16]),"+f"(d[17]),"+f"(d[18]),"+f"(d[19]),"+f"(d[20]),"+f"(d[21]),"+f"(d[22]),"+f"(d[23]),"+f"(d[24]),"+f"(d[25]),"+f"(d[26]),"+f"(d[27]),"+f"(d[28]),"+f"(d[29]),"+f"(d[30]),"+f"(d[31]),"+f"(d[32]),"+f"(d[33]),"+f"(d[34]),"+f"(d[35]),"+f"(d[36]),"+f"(d[37]),"+f"(d[38]),"+f"(d[39]),"+f"(d[40]),"+f"(d[41]),"+f"(d[42]),"+f"(d[43]),"+f"(d[44]),"+f"(d[45]),"+f"(d[46]),"+f"(d[47]),"+f"(d[48]),"+f"(d[49]),"+f"(d[50]),"+f"(d[51]),"+f"(d[52]),"+f"(d[53]),"+f"(d[54]),"+f"(d[55]),"+f"(d[56]),"+f"(d[57]),"+f"(d[58]),"+f"(d[59])
 :"r"(alo),"r"(blo),"n"(AOFF),"n"(AHI),"n"(BOFF),"n"(BHI),"n"(SC)); } };
template<> struct WgSs<128> { template<int AOFF,int AHI,int BOFF,int BHI,int SC> static __device__ __forceinline__ void run(float* d,uint32_t alo,uint32_t blo){
 asm volatile("{.reg .b32 l,m; .reg .b64 da,db; add.u32 l,%64,%66; mov.b64 da,{l,%67}; add.u32 m,%65,%68; mov.b64 db,{m,%69}; wgmma.mma_async.sync.aligned.m64n128k16.f32.bf16.bf16 {%0,%1,%2,%3,%4,%5,%6,%7,%8,%9,%10,%11,%12,%13,%14,%15,%16,%17,%18,%19,%20,%21,%22,%23,%24,%25,%26,%27,%28,%29,%30,%31,%32,%33,%34,%35,%36,%37,%38,%39,%40,%41,%42,%43,%44,%45,%46,%47,%48,%49,%50,%51,%52,%53,%54,%55,%56,%57,%58,%59,%60,%61,%62,%63},da,db,%70,1,1,0,1;}"
 :"+f"(d[0]),"+f"(d[1]),"+f"(d[2]),"+f"(d[3]),"+f"(d[4]),"+f"(d[5]),"+f"(d[6]),"+f"(d[7]),"+f"(d[8]),"+f"(d[9]),"+f"(d[10]),"+f"(d[11]),"+f"(d[12]),"+f"(d[13]),"+f"(d[14]),"+f"(d[15]),"+f"(d[16]),"+f"(d[17]),"+f"(d[18]),"+f"(d[19]),"+f"(d[20]),"+f"(d[21]),"+f"(d[22]),"+f"(d[23]),"+f"(d[24]),"+f"(d[25]),"+f"(d[26]),"+f"(d[27]),"+f"(d[28]),"+f"(d[29]),"+f"(d[30]),"+f"(d[31]),"+f"(d[32]),"+f"(d[33]),"+f"(d[34]),"+f"(d[35]),"+f"(d[36]),"+f"(d[37]),"+f"(d[38]),"+f"(d[39]),"+f"(d[40]),"+f"(d[41]),"+f"(d[42]),"+f"(d[43]),"+f"(d[44]),"+f"(d[45]),"+f"(d[46]),"+f"(d[47]),"+f"(d[48]),"+f"(d[49]),"+f"(d[50]),"+f"(d[51]),"+f"(d[52]),"+f"(d[53]),"+f"(d[54]),"+f"(d[55]),"+f"(d[56]),"+f"(d[57]),"+f"(d[58]),"+f"(d[59]),"+f"(d[60]),"+f"(d[61]),"+f"(d[62]),"+f"(d[63])
 :"r"(alo),"r"(blo),"n"(AOFF),"n"(AHI),"n"(BOFF),"n"(BHI),"n"(SC)); } };

__device__ __forceinline__ void wg_fence() { asm volatile("wgmma.fence.sync.aligned;" ::: "memory"); }
__device__ __forceinline__ void wg_commit() { asm volatile("wgmma.commit_group.sync.aligned;" ::: "memory"); }
template <int N> __device__ __forceinline__ void wg_wait() { asm volatile("wgmma.wait_group.sync.aligned %0;" ::"n"(N) : "memory"); }
template <int N> __device__ __forceinline__ void reg_fence(float* d) {
#pragma unroll
    for (int i = 0; i < N; i++) asm volatile("" : "+f"(d[i])::"memory");
}
__device__ __forceinline__ uint32_t desc_lo(uint32_t addr, uint32_t lbo) { return ((addr & 0x3FFFF) >> 4) | ((lbo >> 4) << 16); }
#define desc_hi(sbo, sw) (((sbo) >> 4) | ((sw) << 30))
__device__ __forceinline__ uint32_t smem_u32(const void* p) { return (uint32_t)__cvta_generic_to_shared(p); }
__device__ __forceinline__ bool elect() {
    uint32_t p;
    asm volatile("{.reg .pred P; elect.sync _|P, 0xffffffff; selp.u32 %0,1,0,P;}" : "=r"(p));
    return p;
}
__device__ __forceinline__ void mbar_init(uint32_t bar, uint32_t cnt) { asm volatile("mbarrier.init.shared::cta.b64 [%0], %1;" ::"r"(bar), "r"(cnt) : "memory"); }
__device__ __forceinline__ void mbar_expect(uint32_t bar, uint32_t bytes) { asm volatile("mbarrier.arrive.expect_tx.shared::cta.b64 _, [%0], %1;" ::"r"(bar), "r"(bytes) : "memory"); }
__device__ __forceinline__ bool mbar_try(uint32_t bar, uint32_t par) {
    uint32_t ok;
    asm volatile("{.reg .pred p; mbarrier.try_wait.parity.shared::cta.b64 p, [%1], %2; selp.u32 %0,1,0,p;}" : "=r"(ok) : "r"(bar), "r"(par) : "memory");
    return ok;
}
constexpr int SPIN_LIMIT = 1 << 18;
__device__ __forceinline__ void mbar_wait(uint32_t bar, uint32_t par) {
    if (mbar_try(bar, par)) return;
    int n = 0;
    while (!mbar_try(bar, par) && ++n < SPIN_LIMIT) {}
}
__device__ __forceinline__ void bulk_g2s(uint32_t dst, const void* src, uint32_t bytes, uint32_t bar) {
    asm volatile("cp.async.bulk.shared::cluster.global.mbarrier::complete_tx::bytes [%0], [%1], %2, [%3];" ::"r"(dst), "l"(src), "r"(bytes), "r"(bar) : "memory");
}
__device__ __forceinline__ void bulk_s2g(void* dst, uint32_t src, uint32_t bytes) {
    asm volatile("cp.async.bulk.global.shared::cta.bulk_group [%0], [%1], %2;" ::"l"(dst), "r"(src), "r"(bytes) : "memory");
}
__device__ __forceinline__ void bulk_prefetch(const void* src, uint32_t bytes) {
    asm volatile("cp.async.bulk.prefetch.L2.global [%0], %1;" ::"l"(src), "r"(bytes) : "memory");
}
__device__ __forceinline__ void tma2d(uint32_t dst, const CUtensorMap* m, int c0, int c1, uint32_t bar) {
    asm volatile("cp.async.bulk.tensor.2d.shared::cluster.global.mbarrier::complete_tx::bytes [%0], [%1, {%3, %4}], [%2];" ::"r"(dst), "l"(m), "r"(bar), "r"(c0), "r"(c1) : "memory");
}
__device__ __forceinline__ void tma2d_mc(uint32_t dst, const CUtensorMap* m, int c0, int c1, uint32_t bar) {
    asm volatile("cp.async.bulk.tensor.2d.shared::cluster.global.mbarrier::complete_tx::bytes.multicast::cluster [%0], [%1, {%3, %4}], [%2], %5;" ::"r"(dst), "l"(m), "r"(bar), "r"(c0), "r"(c1), "h"((uint16_t)3) : "memory");
}
__device__ __forceinline__ uint32_t mapa(uint32_t a, uint32_t rank) { uint32_t r; asm("mapa.shared::cluster.u32 %0, %1, %2;" : "=r"(r) : "r"(a), "r"(rank)); return r; }
__device__ __forceinline__ void mbar_arrive_cl(uint32_t bar) { asm volatile("mbarrier.arrive.shared::cluster.b64 _, [%0];" ::"r"(bar) : "memory"); }
__device__ __forceinline__ void prefetch_map(const CUtensorMap* m) { asm volatile("prefetch.tensormap [%0];" ::"l"(m) : "memory"); }
__device__ __forceinline__ void cpasync16(uint32_t dst, const void* src, uint32_t srcsz) {
    asm volatile("cp.async.cg.shared.global [%0], [%1], 16, %2;" ::"r"(dst), "l"(src), "r"(srcsz) : "memory");
}
__device__ __forceinline__ void bar_sync(int id, int n) { asm volatile("bar.sync %0, %1;" ::"r"(id), "r"(n) : "memory"); }
__device__ __forceinline__ void bar_arrive(int id, int n) { asm volatile("bar.arrive %0, %1;" ::"r"(id), "r"(n) : "memory"); }
__device__ __forceinline__ void fence_async_smem() { asm volatile("fence.proxy.async.shared::cta;" ::: "memory"); }
__device__ __forceinline__ void fence_async_global() { asm volatile("fence.proxy.async.global;" ::: "memory"); }
__device__ __forceinline__ void flag_release(int f) { asm volatile("red.release.gpu.global.add.u32 [%0], 1;" ::"l"(&g_flags[f * 32]) : "memory"); }
__device__ __forceinline__ void flag_wait(int f, unsigned target) {
    const unsigned* p = &g_flags[f * 32];
    unsigned v; int n = 0;
    do {
        asm volatile("ld.relaxed.gpu.global.u32 %0, [%1];" : "=r"(v) : "l"(p) : "memory");
    } while ((int)(v - target) < 0 && ++n < SPIN_LIMIT);
    asm volatile("fence.acquire.gpu;" ::: "memory");
}
__device__ __forceinline__ unsigned ld_flag(const unsigned* p) { unsigned v; asm volatile("ld.relaxed.gpu.global.u32 %0, [%1];" : "=r"(v) : "l"(p) : "memory"); return v; }
__device__ __forceinline__ void spin(unsigned n) { unsigned t0, t1; asm volatile("mov.u32 %0, %%clock;" : "=r"(t0)); do { asm volatile("mov.u32 %0, %%clock;" : "=r"(t1)); } while (t1 - t0 < n); }
__device__ __forceinline__ void flag_wait_fast(int f, unsigned target) {
    flag_wait(f, target);
}
__device__ __forceinline__ void flag_wait2(int f0, int f1, unsigned target) {
    const unsigned *p = &g_flags[f0 * 32], *q = &g_flags[f1 * 32];
    unsigned v, w; int n = 0;
    do { v = ld_flag(p); w = ld_flag(q); } while ((int)((v - target) | (w - target)) < 0 && ++n < SPIN_LIMIT);
    asm volatile("fence.acquire.gpu;" ::: "memory");
}
__device__ __forceinline__ uint32_t lds32(uint32_t a) { uint32_t v; asm volatile("ld.shared.u32 %0, [%1];" : "=r"(v) : "r"(a)); return v; }
__device__ __forceinline__ float2 lds64f(uint32_t a) { float2 v; asm volatile("ld.shared.v2.f32 {%0,%1}, [%2];" : "=f"(v.x), "=f"(v.y) : "r"(a)); return v; }
__device__ __forceinline__ uint2 lds64(uint32_t a) { uint2 v; asm volatile("ld.shared.v2.u32 {%0,%1}, [%2];" : "=r"(v.x), "=r"(v.y) : "r"(a)); return v; }
__device__ __forceinline__ void sts64f(uint32_t a, float2 v) { asm volatile("st.shared.v2.f32 [%0], {%1,%2};" ::"r"(a), "f"(v.x), "f"(v.y) : "memory"); }
__device__ __forceinline__ void sts32(uint32_t a, uint32_t v) { asm volatile("st.shared.u32 [%0], %1;" ::"r"(a), "r"(v) : "memory"); }
__device__ __forceinline__ void sts64(uint32_t a, uint32_t x, uint32_t y) { asm volatile("st.shared.v2.u32 [%0], {%1,%2};" ::"r"(a), "r"(x), "r"(y) : "memory"); }
__device__ __forceinline__ void sts16(uint32_t a, uint16_t v) { asm volatile("st.shared.u16 [%0], %1;" ::"r"(a), "h"(v) : "memory"); }
__device__ __forceinline__ uint4 lds128(uint32_t a) { uint4 v; asm volatile("ld.shared.v4.u32 {%0,%1,%2,%3}, [%4];" : "=r"(v.x), "=r"(v.y), "=r"(v.z), "=r"(v.w) : "r"(a)); return v; }
__device__ __forceinline__ void sts128(uint32_t a, uint4 v) { asm volatile("st.shared.v4.u32 [%0], {%1,%2,%3,%4};" ::"r"(a), "r"(v.x), "r"(v.y), "r"(v.z), "r"(v.w) : "memory"); }
__device__ __forceinline__ void sts128f(uint32_t a, float x, float y, float z, float w) { asm volatile("st.shared.v4.f32 [%0], {%1,%2,%3,%4};" ::"r"(a), "f"(x), "f"(y), "f"(z), "f"(w) : "memory"); }
__device__ __forceinline__ uint32_t prmt(uint32_t a, uint32_t b, uint32_t s) { uint32_t r; asm("prmt.b32 %0,%1,%2,%3;" : "=r"(r) : "r"(a), "r"(b), "r"(s)); return r; }
__device__ __forceinline__ uint32_t pack2(float lo, float hi) { uint32_t r; asm("cvt.rn.bf16x2.f32 %0, %1, %2;" : "=r"(r) : "f"(hi), "f"(lo)); return r; }
__device__ __forceinline__ float blo(uint32_t v) { return __uint_as_float(v << 16); }
__device__ __forceinline__ float bhi(uint32_t v) { return __uint_as_float(v & 0xffff0000u); }
__device__ __forceinline__ uint32_t bmul2(uint32_t a, uint32_t b) { uint32_t r; asm("mul.rn.bf16x2 %0,%1,%2;" : "=r"(r) : "r"(a), "r"(b)); return r; }
__device__ __forceinline__ uint32_t badd2(uint32_t a, uint32_t b) { uint32_t r; asm("add.rn.bf16x2 %0,%1,%2;" : "=r"(r) : "r"(a), "r"(b)); return r; }
__device__ __forceinline__ float rbf(float x) { return __bfloat162float(__float2bfloat16_rn(x)); }
__device__ __forceinline__ uint32_t ldcg32(const void* p) { uint32_t v; asm volatile("ld.global.cg.u32 %0, [%1];" : "=r"(v) : "l"(p) : "memory"); return v; }
__device__ __forceinline__ uint4 ldcg128(const void* p) { uint4 v; asm volatile("ld.global.cg.v4.u32 {%0,%1,%2,%3}, [%4];" : "=r"(v.x), "=r"(v.y), "=r"(v.z), "=r"(v.w) : "l"(p) : "memory"); return v; }
__device__ __forceinline__ void stg32_if(void* p, uint32_t v, int on) { asm volatile("{.reg .pred q; setp.ne.b32 q, %2, 0; @q st.global.u32 [%0], %1;}" ::"l"(p), "r"(v), "r"(on) : "memory"); }
__device__ __forceinline__ uint2 ldcg64(const void* p) { uint2 v; asm volatile("ld.global.cg.v2.u32 {%0,%1}, [%2];" : "=r"(v.x), "=r"(v.y) : "l"(p) : "memory"); return v; }
__device__ __forceinline__ float gelu_h(float h) {
    float u = h * fmaf(h * h, 8.0f * 0.044715f * 0.7978845608028654f, 2.0f * 0.7978845608028654f);
    float th;
    asm("tanh.approx.f32 %0, %1;" : "=f"(th) : "f"(u));
    return fmaf(h, th, h);
}
__device__ __forceinline__ float gelu(float x) { return gelu_h(0.5f * x); }
__device__ __forceinline__ float half_rstd(float sum, float sq) {
    float mean = sum * (1.0f / D_), inv;
    asm("rsqrt.approx.ftz.f32 %0, %1;" : "=f"(inv) : "f"(fmaxf(fmaf(-mean, mean, fmaf(sq, 1.0f / D_, 1e-5f)), 1e-5f)));
    return 0.5f * inv;
}
__device__ __forceinline__ uint32_t bsub2(uint32_t a, uint32_t b) { uint32_t r; asm("sub.rn.bf16x2 %0,%1,%2;" : "=r"(r) : "r"(a), "r"(b)); return r; }
__device__ __forceinline__ uint32_t bfma2(uint32_t a, uint32_t b, uint32_t c) { uint32_t r; asm("fma.rn.bf16x2 %0,%1,%2,%3;" : "=r"(r) : "r"(a), "r"(b), "r"(c)); return r; }
__device__ __forceinline__ uint32_t gelu2_h(uint32_t h) {
    uint32_t u = bmul2(h, bfma2(bmul2(h, h), 0x3e923e92u, 0x3fcc3fccu)), th;
    asm("tanh.approx.bf16x2 %0, %1;" : "=r"(th) : "r"(u));
    return bfma2(h, th, h);
}
__device__ __forceinline__ void mma_stat(float* d, uint32_t u, uint32_t v) {
    asm("mma.sync.aligned.m16n8k16.row.col.f32.bf16.bf16.f32 {%0,%1,%2,%3},{%4,%6,%5,%6},{%4,%5},{%0,%1,%2,%3};"
        : "+f"(d[0]), "+f"(d[1]), "+f"(d[2]), "+f"(d[3]) : "r"(u), "r"(v), "r"(0x3f803f80u));
}
__device__ __forceinline__ void mma_sel(float* d, uint2 u, uint2 v, uint32_t b0, uint32_t b1) {
    asm("mma.sync.aligned.m16n8k16.row.col.f32.bf16.bf16.f32 {%0,%1,%2,%3},{%4,%5,%6,%7},{%8,%9},{%0,%1,%2,%3};"
        : "+f"(d[0]), "+f"(d[1]), "+f"(d[2]), "+f"(d[3]) : "r"(u.x), "r"(v.x), "r"(u.y), "r"(v.y), "r"(b0), "r"(b1));
}
__device__ __forceinline__ void conv_sum4(float* d, uint32_t a, bool last, int g, int c) {
    uint2 v0 = lds64(a), v1 = lds64(a + 8), v2 = lds64(a + 16), v3 = lds64(a + 24);
    if (last) {
        if (c > 2) v1 = make_uint2(0, 0);
        if (c > 1) v2 = make_uint2(0, 0);
        if (c > 0) v3 = make_uint2(0, 0);
    }
    const uint32_t one = (g & 1) ? 0x3f800000u : 0x00003f80u;
    mma_sel(d, v0, v1, (g >> 1) == 0 ? one : 0u, (g >> 1) == 1 ? one : 0u);
    mma_sel(d, v2, v3, (g >> 1) == 2 ? one : 0u, (g >> 1) == 3 ? one : 0u);
}
__device__ __forceinline__ uint3 row_stats(const uint32_t* v, int lane) {
    float s = 0.f, q = 0.f, s_ = 0.f, q_ = 0.f;
#pragma unroll
    for (int i = 0; i < 10; i++) { float a = blo(v[i]), b = bhi(v[i]); s += a; s_ += b; q = fmaf(a, a, q); q_ = fmaf(b, b, q_); }
    s += s_; q += q_;
    {
        float t = __shfl_xor_sync(0xffffffffu, (lane & 16) ? s : q, 16);
        t += (lane & 16) ? q : s;
#pragma unroll
        for (int m = 8; m; m >>= 1) t += __shfl_xor_sync(0xffffffffu, t, m);
        float o = __shfl_xor_sync(0xffffffffu, t, 16);
        s = (lane & 16) ? o : t; q = (lane & 16) ? t : o;
    }
    float mean = s * (1.0f / D_), inv;
    asm("rsqrt.approx.ftz.f32 %0, %1;" : "=f"(inv) : "f"(fmaxf(fmaf(-mean, mean, fmaf(q, 1.0f / D_, 1e-5f)), 1e-5f)));
    uint3 r;
    r.x = pack2(mean, mean);
    r.y = pack2(inv, inv);
    inv -= blo(r.y);
    r.z = pack2(inv, inv);
    return r;
}
__device__ __forceinline__ uint32_t ln_apply(uint32_t x, uint32_t m, uint32_t hi, uint32_t lo) {
    uint32_t xc = bsub2(x, m);
    return bmul2(xc, hi);
}

struct AFrag { uint32_t m, a, b, c, d; };
__device__ __forceinline__ AFrag ldA(uint32_t a) { AFrag f; f.m = lds32(a - 16); f.a = lds32(a); f.b = lds32(a + 16); f.c = lds32(a + 32); f.d = lds32(a + 48); return f; }
template <int N, int M> __device__ __forceinline__ void conv_pair(float* d, const AFrag& f, uint32_t descU) {
    WgRs<N>::template run<8 * M, desc_hi(128, 0), M ? 1 : 0>(d, f.a, f.b, f.m, f.a, descU);
    WgRs<N>::template run<8 * M + 1, desc_hi(128, 0), 1>(d, f.c, f.d, f.b, f.c, descU);
}
template <int Q> __device__ __forceinline__ void conv_put(float* d, uint32_t r0) {
    sts64(r0 + Q * 32, pack2(d[4 * Q + 1], d[4 * Q + 3]), pack2(d[4 * Q], d[4 * Q + 2]));
}
template <int M> __device__ __forceinline__ void conv_two(float* d, AFrag f0, AFrag f1, uint32_t kaddr, uint32_t descU, uint32_t r0, bool handoff) {
    constexpr int N = M < 14 ? 128 - 8 * M : 32;
    wg_fence();
    conv_pair<N, M>(d, f0, descU);
    wg_commit();
    if constexpr (M > 0) f1 = ldA(kaddr + 256 * (M + 1));
    wg_fence();
    conv_pair<N, M + 1>(d, f1, descU);
    wg_commit();
    if (STAG && M == STAG && handoff) bar_arrive(12, 256);
    if constexpr (M < 14) {
        if constexpr (M > 0) { conv_put<17 - M>(d, r0); conv_put<16 - M>(d, r0); }
        wg_wait<1>();
        f0 = ldA(kaddr + 256 * (M + 2));
        if constexpr (M < 12) wg_wait<0>();
        conv_two<M + 2>(d, f0, f1, kaddr, descU, r0, handoff);
    } else {
        wg_wait<0>();
        conv_put<3>(d, r0); conv_put<2>(d, r0); conv_put<1>(d, r0); conv_put<0>(d, r0);
    }
}
template <int N, bool ASWZ, int SC0>
__device__ __forceinline__ void gemm_issue(float* acc, uint32_t bars, int sa, int pa, int sw, int pw, uint32_t da0, uint32_t db0) {
    mbar_wait(bars + (BAR_FB + sw) * 8, pw);
    mbar_wait(bars + (BAR_FA + sa) * 8, pa);
    const uint32_t da = da0 + sa * (SLOT >> 4), db = db0 + sw * (SLOT >> 4);
    constexpr int AK = ASWZ ? 2 : 256, AH = ASWZ ? desc_hi(1024, 1) : desc_hi(128, 0), BH = desc_hi(1024, 1);
    wg_fence();
    WgSs<N>::template run<0, AH, 0, BH, SC0>(acc, da, db);
    WgSs<N>::template run<AK, AH, 128, BH, 1>(acc, da, db);
    WgSs<N>::template run<2 * AK, AH, 256, BH, 1>(acc, da, db);
    WgSs<N>::template run<3 * AK, AH, 384, BH, 1>(acc, da, db);
    wg_commit();
}
template <int N, bool ASWZ, int NKB, int RELB, bool ZERO>
__device__ __forceinline__ void gemm_loop(float* acc, uint32_t sb, int half, int ia0, int ib0, int rela, int wait_bar, int order_bar, int tsid) {
    int sa = ia0 % NA, pa = (ia0 / NA) & 1, sw = ib0 % NB, pw = (ib0 / NB) & 1;
    const uint32_t bars = sb + SM_BAR;
    const int t = threadIdx.x & 127;
    uint32_t ebar = mapa(bars + (t < 2 ? BAR_EB : BAR_EA) * 8, (t < 2 && lds32(sb + SM_GV + 516)) ? t : blockIdx.x & 1);
    const int nrel = t < 2 ? RELB : t == 2 ? rela : 0;
    const uint32_t da0 = ASWZ ? desc_lo(sb + SM_RA + half * 8192, 16) : desc_lo(sb + SM_RA + half * 1024, 2048), db0 = desc_lo(sb + SM_RB, 8192);
    asm volatile("" : "+r"(ebar));
    if (wait_bar) bar_sync(wait_bar, 512);
    gemm_issue<N, ASWZ, ZERO ? 0 : 1>(acc, bars, sa, pa, sw, pw, da0, db0);
    if ((threadIdx.x & 255) == 0) TS(tsid);
#pragma unroll 1
    for (int kb = 1; kb < NKB; kb++) {
        const int prev = t < 2 ? sw : sa;
        if (++sa == NA) { sa = 0; pa ^= 1; }
        if (++sw == NB) { sw = 0; pw ^= 1; }
        gemm_issue<N, ASWZ, 1>(acc, bars, sa, pa, sw, pw, da0, db0);
        if (order_bar && kb == NKB - 1) bar_arrive(order_bar, 512);
        wg_wait<1>();
        if (kb <= nrel) mbar_arrive_cl(ebar + prev * 8);
    }
    wg_wait<0>();
    if (nrel == NKB) mbar_arrive_cl(ebar + (t < 2 ? sw : sa) * 8);
    reg_fence<N / 2>(acc);
    if ((threadIdx.x & 255) == 0) TS(tsid + 1);
}

template <int PART>
__device__ __forceinline__ void gemm3(uint32_t sb, int rb, int j, int half, int row, int c, unsigned ones) {
    constexpr int N = 64 + (PART ? RB3 : RA3), NQ = N / 8;
    constexpr int HO = PART ? HO_B : HO_A;
    float acc[N / 2];
    float2 cr[NQ];
    if (PART) {
        gemm_loop<N, false, 1, 1, true>(acc, sb, half, 20, 20, 0, 0, 0, 50);
        bar_arrive(9, 512);
    }
    mbar_wait(sb + SM_BAR + BAR_CS * 8, 0);
    const uint32_t csa = sb + SM_CS + PART * (256 + 4 * RA3) + 8 * c;
#pragma unroll
    for (int q = 0; q < NQ; q++) if (q < CSP) cr[q] = lds64f(csa + 32 * q);
    uint4 rp;
    if (PART) {
        mbar_wait(sb + SM_BAR + (BAR_FA + 22 % NA) * 8, (22 / NA) & 1);
        const float2* sp = &g_st[(rb * 8 + 2 * c) * 128 + row];
        const uint2 s0 = ldcg64(sp), s1 = ldcg64(sp + 128), s2 = ldcg64(sp + 8), s3 = ldcg64(sp + 136);
        float a0 = __uint_as_float(s0.x) + __uint_as_float(s1.x), b0 = __uint_as_float(s0.y) + __uint_as_float(s1.y);
        float a1 = __uint_as_float(s2.x) + __uint_as_float(s3.x), b1 = __uint_as_float(s2.y) + __uint_as_float(s3.y);
#pragma unroll
        for (int m = 1; m <= 2; m <<= 1) {
            a0 += __shfl_xor_sync(0xffffffffu, a0, m); b0 += __shfl_xor_sync(0xffffffffu, b0, m);
            a1 += __shfl_xor_sync(0xffffffffu, a1, m); b1 += __shfl_xor_sync(0xffffffffu, b1, m);
        }
        const float inv0 = half_rstd(a0, b0), inv1 = half_rstd(a1, b1);
        rp = make_uint4(PGELU ? pack2(inv0, inv0) : __float_as_uint(inv0), __float_as_uint(a0 * (-1.0f / D_)),
                        PGELU ? pack2(inv1, inv1) : __float_as_uint(inv1), __float_as_uint(a1 * (-1.0f / D_)));
        if (c == 0) sts128(sb + SM_RP + ((threadIdx.x & 255) >> 2) * 16, rp);
        bar_arrive(13, 512);
    }
    gemm_loop<N, false, 10 - PART, 10 - PART, !PART>(acc, sb, half, 20 + (10 - NA) * PART, 21 + 10 * PART, PART ? 9 : 10 - NA, 9 + PART, HO < 0 ? 10 + PART : 0, 46 + 2 * PART);
    if (!PART) {
        bar_sync(13, 512);
        rp = lds128(sb + SM_RP + ((threadIdx.x & 255) >> 2) * 16);
    }
    const float nb0 = __uint_as_float(rp.y), nb1 = __uint_as_float(rp.w);
    const uint32_t own = sb + SM_RA + ((39 - NA) % NA) * SLOT + row * 16 + c * 4;
    if (PART && OWNG) mbar_wait(sb + SM_BAR + (BAR_FA + (39 - NA) % NA) * 8, ((39 - NA) / NA) & 1);
    uint32_t* dst = reinterpret_cast<uint32_t*>(g_g) + (rb * 216 + HB0 / 8 * PART + 8 * j) * 512 + row * 4 + c;
    auto act = [&](int q, int r) {
        const float nb = r ? nb1 : nb0;
        const uint32_t inv = r ? rp.z : rp.x;
        const float t0 = fmaf(nb, cr[q].x, acc[4 * q + 2 * r]), t1 = fmaf(nb, cr[q].y, acc[4 * q + 2 * r + 1]);
        return gelu2_h(bmul2(pack2(t0, t1), inv));
    };
    uint32_t* dst1 = dst + (56 - (16 - NQ) * j) * 512;
#pragma unroll
    for (int k = 0; k < NQ; k += CH3) {
        if (k == HO) bar_arrive(10 + PART, 512);
        CHUNK(k) {
#pragma unroll
            for (int q = k; q < k + CH3 && q < NQ; q++) {
                if (q + CSP < NQ) cr[q + CSP] = lds64f(csa + 32 * (q + CSP));
                const uint32_t u = act(q, 0), v = act(q, 1);
                (q < 8 ? dst : dst1)[q * 512] = u;
                (q < 8 ? dst : dst1)[q * 512 + 32] = v;
                if (PART && OWNG && q < 8) { sts32(own + q * 2048, u); sts32(own + q * 2048 + 128, v); }
            }
            if (PART && OWNG && k < 8 && k + CH3 >= 8) fence_async_smem();
        }
    }
    bar_arrive(1 + PART, 288);
    if (HO >= NQ) bar_arrive(10 + PART, 512);
}

template <int NS, int BASE, int BF, int BE> struct Ring {
    uint32_t sb, st, ph;
    __device__ __forceinline__ uint32_t acquire(uint32_t bytes) {
        mbar_wait(sb + SM_BAR + BE * 8 + st * 8, ph);
        uint32_t fb = sb + SM_BAR + BF * 8 + st * 8;
        mbar_expect(fb, bytes);
        return fb;
    }
    __device__ __forceinline__ uint32_t slot() { return sb + BASE + st * SLOT; }
    __device__ __forceinline__ void next() { if (++st == NS) { st = 0; ph ^= 1; } }
    __device__ __forceinline__ void run2d(const CUtensorMap* m, int c1) {
#pragma unroll 1
        for (int c0 = 64; c0 < D_; c0 += 64) {
            uint32_t fb = acquire(SLOT);
            tma2d(slot(), m, c0, c1, fb);
            next();
        }
    }
    static __device__ __forceinline__ int korder(int i, int own) { return i == 0 ? own : i > own ? i : i - 1; }
    __device__ __forceinline__ void runw(bool paired, int rk, const CUtensorMap* ma, const CUtensorMap* mb, int ca, int cb, int i0, int i1, int own, uint32_t bytes) {
        if (paired) {
            const CUtensorMap* m = rk ? mb : ma;
            const int c0 = rk ? cb : ca;
#pragma unroll 1
            for (int i = i0; i < i1; i++) {
                const int c1 = korder(i, own) * 64;
                uint32_t fb = acquire(bytes);
                tma2d_mc(slot() + 8192 * rk, m, c0, c1, fb);
                next();
            }
        } else {
#pragma unroll 1
            for (int i = i0; i < i1; i++) {
                const int c1 = korder(i, own) * 64;
                uint32_t fb = acquire(bytes);
                tma2d(slot(), ma, ca, c1, fb);
                tma2d(slot() + 8192, mb, cb, c1, fb);
                next();
            }
        }
    }
    __device__ __forceinline__ void run1d(const char* src, int i0, int i1, int own) {
#pragma unroll 1
        for (int i = i0; i < i1; i++) {
            const char* s = src + korder(i, own) * SLOT;
            uint32_t fb = acquire(SLOT);
            bulk_g2s(slot(), s, SLOT, fb);
            next();
        }
    }
};

__global__ void __cluster_dims__(2, 1, 1) __launch_bounds__(NTHREADS, 1) fused_kernel(const Params p, const __grid_constant__ Maps maps) {
    extern __shared__ __align__(1024) unsigned char smem_raw[];
    const uint32_t sb = (smem_u32(smem_raw) + 1023u) & ~1023u;
#pragma unroll
    for (int i = 0; i < SEED; i++) asm volatile("{.reg .b32 t; mov.u32 t, %laneid;}");
    const uint32_t bars = sb + SM_BAR;
    const int tid = threadIdx.x, lane = tid & 31;
    unsigned smid;
    asm volatile("mov.u32 %0, %%smid;" : "=r"(smid));
    const bool spare = (smid >> 2) == 30;
    const int cta = smid < 120 ? smid : smid - 4;
    const int pg = cta >> 4, pi = cta & 15;
    const int hb = tid >= 320;
    if (!spare) {
        const unsigned t = tid - 320 * hb, r32 = t / 10u, cc = t - r32 * 10u, row = r32 + 64 * hb;
        const unsigned go = (unsigned)(pi * 128 * 1280 + pg * 160) + row * 1280u + cc * 16u;
        const uint32_t so = sb + (row >> 4) * 32u + row * 160u + cc * 16u;
        const char* kb = (const char*)p.k + go;
        const char* vb = (const char*)p.v + go;
        if (hb) {
            if (tid >= 640 - NBARS) {
                const int i = 639 - tid;
                mbar_init(bars + i * 8, (i >= BAR_EB && i < BAR_K) ? 4 : ((i >= BAR_EA && i < BAR_EB) || i == BAR_XY) ? 2 : 1);
                asm volatile("fence.mbarrier_init.release.cluster;" ::: "memory");
            }
            bar_arrive(14, 640);
            if (B_DELAY) spin(B_DELAY);
        }
        cpasync16(so + SM_PK + 2592, kb, 16);
        cpasync16(so + SM_PV, vb, 16);
        cpasync16(so + SM_PK + 3 * 2592, kb + 32 * 1280, 16);
        cpasync16(so + SM_PV + 2 * 2592, vb + 32 * 1280, 16);
        if (tid < 30) cpasync16(so + SM_PK + 13 * 160, pi ? kb - 3 * 1280 : kb, pi ? 16 : 0);
        asm volatile("cp.async.commit_group;" ::: "memory");
    }
    const int warp = __shfl_sync(0xffffffffu, tid >> 5, 0);
    const int wg = warp >> 2, wq = warp & 3;
    unsigned ep0 = 0;
    if (wg == 4 || spare) ep0 = *(volatile unsigned*)&g_epoch[smid];
#define ep1 (ep0 + 1)

    if (spare) {
        const int sp = smid & 3;
        if (tid == 32) { sts32(sb + SM_GV + 512, smid); asm volatile("fence.release.sync_restrict::shared::cta.cluster;" ::: "memory"); }
        asm volatile("barrier.cluster.arrive.relaxed.aligned;" ::: "memory");
        asm volatile("barrier.cluster.wait.aligned;" ::: "memory");
        if (tid == 0) {
            for (int i = 0; i < 4; i++) mbar_init(bars + i * 8, 1);
            asm volatile("fence.mbarrier_init.release.cluster;" ::: "memory");
        }
        if (warp == 0) { if (lane < 8) flag_wait(FL_P + lane, ep1 * 16); __syncwarp(); }
        __syncthreads();
        const int cq = tid % 54, rg = tid / 54;
        float a[8];
#pragma unroll
        for (int i = 0; i < 8; i++) a[i] = 0.f;
#pragma unroll 1
        for (int it = -4; it < 10; it++) {
            const uint32_t st = sb + (it & 3) * 55296, fb = bars + (it & 3) * 8;
            if (it >= 0) {
                mbar_wait(fb, (it >> 2) & 1);
                if (tid < 432) {
#pragma unroll
                    for (int i = 0; i < 8; i++) {
                        uint4 w = lds128(st + (cq >= 27 ? 27648 - 432 : 0) + (rg * 8 + i) * 432 + cq * 16);
                        a[0] += blo(w.x); a[1] += bhi(w.x); a[2] += blo(w.y); a[3] += bhi(w.y);
                        a[4] += blo(w.z); a[5] += bhi(w.z); a[6] += blo(w.w); a[7] += bhi(w.w);
                    }
                }
                __syncthreads();
            }
            if (it < 6 && warp == 19 && elect()) {
                mbar_expect(fb, 55296);
                tma2d(st, &maps.w3s, sp * 432, (it + 4) * 64, fb);
                tma2d(st + 27648, &maps.w3s, sp * 432 + 216, (it + 4) * 64, fb);
            }
        }
        if (tid < 432) {
            sts128f(sb + rg * 1728 + cq * 32, a[0], a[1], a[2], a[3]);
            sts128f(sb + rg * 1728 + cq * 32 + 16, a[4], a[5], a[6], a[7]);
        }
        __syncthreads();
        if (tid < 432) {
            float s = 0.f;
#pragma unroll
            for (int i = 0; i < 8; i++) s += __uint_as_float(lds32(sb + i * 1728 + tid * 4));
            g_cs[sp * 432 + tid] = s;
        }
        __syncthreads();
        if (tid == 0) { flag_release(FL_CS); g_epoch[smid] = ep1; TS(0); }
        if (warp == 0) TSFLUSH();
        return;
    }

    int gpc, idx;
    if (smid < 64) { gpc = (smid & 15) >> 1; idx = (smid >> 4) * 2 + (smid & 1); }
    else if (smid < 120) { int t = smid - 64; gpc = 1 + (t % 14) / 2; idx = 8 + (t / 14) * 2 + (smid & 1); }
    else { gpc = 0; idx = 8 + (smid - 124); }
    const int rb = 2 * gpc + (idx & 1), j = idx >> 1;
    const int g = lane >> 2, c = lane & 3;
    const int cm = 160 * (j >> 1) + 64 * (j & 1) + ((j & 2) ? 32 : 0), cr = 160 * (j >> 1) + 16 * (j & 1) + ((j & 2) ? 0 : 128);

    {
        if (warp == 5) TSW(61);
        const int w10 = warp - 10 * hb, h = w10 >= 5;
        const int pr = (w10 - 5 * h) * 8 + (lane >> 2), blk = 4 * hb + (lane & 3);
        const int ch = 80 * pg + 2 * pr;
        const uint4 sw = __ldg(reinterpret_cast<const uint4*>(p.shift + ch * 4));
        uint32_t dv = 0;
        if (warp == 9 && lane < 5) dv = __bfloat16_as_ushort(p.ssmD[cta * 5 + lane]);
        if (tid == 512) { sts32(sb + SM_GV + 512, smid); asm volatile("fence.release.sync_restrict::shared::cta.cluster;" ::: "memory"); }
        asm volatile("barrier.cluster.arrive.relaxed.aligned;" ::: "memory");
        if (warp == 11 && lane < 13) prefetch_map(&maps.hn + lane);
        if (wg < 4) {
            const int t = tid & 127, cc = (wg == 3 && t >= 64) ? 4 : wg;
            if (t < 64 || wg == 3) sts128(sb + sm_u(cc) + ((t >> 5) & 1) * U_PLANE + 2048 + lane * 16, make_uint4(0, 0, 0, 0));
            if ((t & 63) < 4 && (t < 64 || wg == 3)) sts128(sb + sm_k(cc) + ((t >> 1) & 1) * 4160 + (t & 1) * 16, make_uint4(0, 0, 0, 0));
        }
        if (warp == 9 && lane < 5) sts32(sb + SM_GV + 520 + lane * 4, dv << 16);
        asm volatile("cp.async.wait_group 0;" ::: "memory");
        if (!hb) bar_arrive(12, 640);
        bar_sync(hb ? 12 : 14, 640);
        if (warp == 9) {
            if (SSM_DELAY) spin(SSM_DELAY);
            if (elect()) {
#pragma unroll
                for (int i = 0; i < SSM_N; i++) {
                    mbar_expect(bars + (BAR_K + i) * 8, 4096);
                    bulk_g2s(sb + sm_k(i) + 32, p.ssmk + (size_t)(cta * 5 + i) * S_, 4096, bars + (BAR_K + i) * 8);
                }
            }
        }
        const uint32_t w0 = prmt(sw.x, sw.z, 0x5410), w1 = prmt(sw.x, sw.z, 0x7632), w2 = prmt(sw.y, sw.w, 0x5410), w3 = prmt(sw.y, sw.w, 0x7632);
        const uint32_t ka = sb + SM_PK + 2592 + blk * 2592 + h * 1280 + pr * 4;
        const uint32_t va = sb + SM_PV + blk * 2592 + h * 1280 + pr * 4;
        uint32_t kk[11], kv[8];
#pragma unroll
        for (int i = 0; i < 11; i++) kk[i] = lds32(ka + (i - 3) * 160 - ((i < 3 && h == 0) ? 32 : 0));
#pragma unroll
        for (int i = 0; i < 8; i++) {
            uint32_t t = badd2(badd2(badd2(bmul2(kk[i], w3), bmul2(kk[i + 1], w2)), bmul2(kk[i + 2], w1)), bmul2(kk[i + 3], w0));
            kv[i] = bmul2(t, lds32(va + i * 160));
        }
        uint4 o0, o1;
        o0.x = prmt(kv[1], kv[0], 0x5410); o0.y = prmt(kv[3], kv[2], 0x5410); o0.z = prmt(kv[5], kv[4], 0x5410); o0.w = prmt(kv[7], kv[6], 0x5410);
        o1.x = prmt(kv[1], kv[0], 0x7632); o1.y = prmt(kv[3], kv[2], 0x7632); o1.z = prmt(kv[5], kv[4], 0x7632); o1.w = prmt(kv[7], kv[6], 0x7632);
        uint4* dst = reinterpret_cast<uint4*>(g_kvT) + ch * 256 + h * 128 + (127 - (8 * pi + blk));
        dst[0] = o0;
        dst[256] = o1;
    }

    const int rho = 8 * rb + j;

    if (wg == 4) {
        asm volatile("setmaxnreg.dec.sync.aligned.u32 32;");
        if (wq == 0) {
            bar_sync(13, 640);
            TSW(39);
            if (lane == 0) flag_release(FL_P + pg);
            __syncwarp();
            TSW(2);
            if (lane < 5) mbar_expect(bars + (BAR_U + lane) * 8, 4096);
            flag_wait_fast(FL_P + pg, ep1 * 16);
            fence_async_global();
            TSW(3);
            if (elect()) {
#pragma unroll
                for (int i = 0; i < 5; i++) {
                    const char* us = (const char*)g_kvT + (size_t)(cta * 5 + i) * 4096;
                    bulk_g2s(sb + sm_u(i), us, 2048, bars + (BAR_U + i) * 8);
                    bulk_g2s(sb + sm_u(i) + U_PLANE, us + 2048, 2048, bars + (BAR_U + i) * 8);
                }
            }
            __syncwarp();
            if (elect()) {
#pragma unroll
                for (int i = SSM_N; i < 5; i++) {
                    mbar_expect(bars + (BAR_K + i) * 8, 4096);
                    bulk_g2s(sb + sm_k(i) + 32, p.ssmk + (size_t)(cta * 5 + i) * S_, 4096, bars + (BAR_K + i) * 8);
                }
                if (cta < 120) {
                    mbar_expect(bars + BAR_WM * 8, 40960);
#pragma unroll
                    for (int i = 0; i < 5; i++) tma2d(sb + SM_WM + i * 8192, &maps.wm, cta * 32, i * 128, bars + BAR_WM * 8);
                }
                bulk_prefetch((const char*)p.q + cta * 20480, 20480);
                bulk_prefetch((const char*)p.w1 + cta * 6400, 6400);
                bulk_prefetch((const char*)p.w2 + cta * 6400, 6400);
            }
            __syncwarp();
        } else {
            bar_arrive(13, 640);
        }
        asm volatile("barrier.cluster.wait.aligned;" ::: "memory");
        uint32_t peer;
        asm volatile("ld.shared::cluster.u32 %0, [%1];" : "=r"(peer) : "r"(mapa(sb + SM_GV + 512, (blockIdx.x & 1) ^ 1)) : "memory");
        const bool paired = peer == (smid ^ 1);
        if (tid == 639) sts32(sb + SM_GV + 516, paired);
        if (cta < 120) {
            float d[4];
            if (tid < 592) {
                const int t = tid - 512;
                mbar_wait(bars + BAR_U * 8, 0);
                uint4 cv = __ldg(reinterpret_cast<const uint4*>(p.c) + t);
                auto silu2 = [](uint32_t v) { float a = blo(v), b = bhi(v); return pack2(__fdividef(a, 1.0f + __expf(-a)), __fdividef(b, 1.0f + __expf(-b))); };
                sts128(sb + SM_Y + (t % 40) * 32 + (t / 40) * 16, make_uint4(silu2(cv.x), silu2(cv.y), silu2(cv.z), silu2(cv.w)));
                fence_async_smem();
            }
            bar_sync(5, 128);
            mbar_wait(bars + BAR_WM * 8, 0);
            if (wq == 3) TSW(56);
            const uint32_t da = desc_lo(sb + SM_WM, 20480), db = desc_lo(sb + SM_Y, 32);
            wg_fence();
#pragma unroll
            for (int k = 0; k < 20; k++)
                asm volatile("{.reg .pred p; .reg .b32 l,m; .reg .b64 da,db; setp.ne.b32 p,%10,0; add.u32 l,%4,%6; mov.b64 da,{l,%8}; add.u32 m,%5,%7; mov.b64 db,{m,%9};"
                             " wgmma.mma_async.sync.aligned.m64n8k16.f32.bf16.bf16 {%0,%1,%2,%3},da,db,p,1,1,1,0;}"
                             : "+f"(d[0]), "+f"(d[1]), "+f"(d[2]), "+f"(d[3])
                             : "r"(da), "r"(db), "r"(64 * k), "r"(4 * k), "n"(desc_hi(512, 2u)), "n"(desc_hi(128, 0)), "r"(k));
            wg_commit();
            wg_wait<0>();
            reg_fence<4>(d);
            if (c == 0) {
                sts32(sb + SM_GV + (16 * wq + g) * 4, __float_as_uint(wq < 2 ? d[0] : d[1]));
                sts32(sb + SM_GV + (16 * wq + g + 8) * 4, __float_as_uint(wq < 2 ? d[2] : d[3]));
            }
            bar_sync(5, 128);
            if (wq == 2) {
                g_mod[cta * 32 + lane] = __float2bfloat16_rn(__uint_as_float(lds32(sb + SM_GV + lane * 4)) + __uint_as_float(lds32(sb + SM_GV + 128 + lane * 4)));
                __syncwarp();
                if (lane == 0) flag_release(FL_M);
                __syncwarp();
                TSW(4);
                if (XAFTER) bar_arrive(5, 64);
            }
            if (XAFTER && wq == 0) bar_sync(5, 64);
        }
        if (wq == 2) {
            flag_wait(FL_M, ep1 * 120);
            fence_async_global();
            if (elect()) {
                mbar_expect(bars + BAR_M * 8, 7680);
                bulk_g2s(sb + SM_MOD, g_mod, 7680, bars + BAR_M * 8);
            }
            __syncwarp();
            TSW(60);
            bar_sync(8, 544);  if (lane == 0) { flag_release(FL_R + rb); TS(23); }  __syncwarp();
            bar_sync(15, 288); if (lane == 0) { flag_release(FL_B1 + rb); TS(27); } __syncwarp();
            bar_sync(6, 288);  if (lane == 0) { flag_release(FL_B2 + rb); TS(31); } __syncwarp();
#pragma unroll 1
            for (int i = 0; i < 2; i++) { bar_sync(1 + i, 288); if (lane == 0) { TS(53 + i); flag_release(FL_G + 16 * i + rb); TS(57 + i); } __syncwarp(); }
            if (lane == 0) g_epoch[smid] = ep1;
            return;
        }
        if (wq == 1) {
            bar_sync(9, 288);
            if (lane < 4 * NB) mbar_arrive_cl(mapa(bars + (BAR_EB + (lane >> 2)) * 8, paired ? lane & 1 : blockIdx.x & 1));
        }
        if (wq == 3) {
            bar_sync(7, 544);
            if (lane == 0) { flag_release(FL_C); TS(20); }
            __syncwarp();
            if (lane < 2) mbar_expect(bars + (lane ? BAR_Y2 : BAR_Y) * 8, lane ? 8192 : 12288);
            flag_wait_fast(FL_C, ep1 * 128);
            fence_async_global();
            TSW(21);
            if (elect()) {
                bulk_g2s(sb + SM_Y, g_yv + rho * 5120, 12288, bars + BAR_Y * 8);
                bulk_g2s(sb + SM_Y + 12288, g_yv + rho * 5120 + 3072, 8192, bars + BAR_Y2 * 8);
            }
            __syncwarp();
        }
        if (elect()) {
            if (wq == 3) {
                mbar_expect(bars + BAR_XY * 8, 20480);
#pragma unroll 1
                for (int i = 0; i < 8; i++) {
                    bulk_g2s(sb + SM_YT + i * 2560, g_yv + (8 * rb + i) * 5120 + cm * 8, 2048, bars + BAR_XY * 8);
                    bulk_g2s(sb + SM_YT + i * 2560 + 2048, g_yv + (8 * rb + i) * 5120 + cr * 8, 512, bars + BAR_XY * 8);
                }
                mbar_wait(bars + BAR_FA * 8, 0);
                bulk_prefetch((const char*)p.w4 + cta * 17280, 17280);
                flag_wait(FL_CS, ep1 * 4);
                fence_async_global();
                mbar_expect(bars + BAR_CS * 8, 864);
                bulk_g2s(sb + SM_CS, g_cs + 64 * j, 256, bars + BAR_CS * 8);
                bulk_g2s(sb + SM_CS + 256, g_cs + 512 + RA3 * j, 4 * RA3, bars + BAR_CS * 8);
                bulk_g2s(sb + SM_CS + 256 + 4 * RA3, g_cs + HB0 + 64 * j, 256, bars + BAR_CS * 8);
                bulk_g2s(sb + SM_CS + 512 + 4 * RA3, g_cs + HB0 + 512 + RB3 * j, 4 * RB3, bars + BAR_CS * 8);
                mbar_wait(bars + BAR_ST * 8, 0);
#pragma unroll 1
                for (int i = 0; i < 2; i++) {
                    flag_wait(FL_G + 16 * i + rb, ep1 * 8);
                    mbar_expect(bars + (BAR_G + i) * 8, 0);
                    TS(35 + i);
                }
            } else if (wq == 1) {
                Ring<NB, SM_RB, BAR_FB, BAR_EB> r{sb, 0, 0};
#pragma unroll 1
                for (int ph = 0; ph < 7; ph++) {
                    const CUtensorMap* ma = ph == 0 ? &maps.w1a : ph == 1 ? &maps.w2a : ph == 6 ? &maps.w4a : &maps.w3a;
                    const bool b3b = ph == 2 || ph == 4 || ph == 5;
                    r.runw(paired, idx & 1, ma, ma + (b3b ? 2 : 1), ph == 3 ? 64 * j : b3b ? HB0 + 64 * j : cm,
                           ph == 3 ? 512 + RA3 * j : b3b ? HB0 + 512 + RB3 * j : cr, ph == 4 ? 10 - NA : ph == 5 ? 1 : 0,
                           ph == 6 ? 27 : ph == 5 ? 10 - NA : ph == 2 ? 1 : 10, ph == 0 ? 0 : ph == 6 ? OWNG * (HB0 / 64 + j) : cm >> 6,
                           ph == 3 ? 8192 + 128 * RA3 : b3b ? 8192 + 128 * RB3 : 10240);
                }
            } else {
                Ring<NA, SM_RA, BAR_FA, BAR_EA> r{sb, 0, 0};
                if (cta >= 120) mbar_wait(bars + (BAR_K + 4) * 8, 0);
                mbar_expect(bars + BAR_XR * 8, 20480);
                bulk_g2s(sb + SM_XR, p.q + (size_t)rho * 16 * D_, 20480, bars + BAR_XR * 8);
                mbar_expect(bars + BAR_XY * 8, 20480);
                tma2d(sb + SM_XT, &maps.xa, cm, rb * 128, bars + BAR_XY * 8);
                tma2d(sb + SM_XT2, &maps.xb, cr, rb * 128, bars + BAR_XY * 8);
                const int grp = j >> 1;
                const int delta = (grp & 1 ? 1 : -1) * (1 + (grp >> 1));
                const int nb = min(max(rb + (delta > 0 ? 1 : -1), 0), 15);
                uint32_t fb = r.acquire(SLOT), dst = r.slot();
                flag_wait2(FL_R + nb, FL_R + rb, ep1 * 8);
                fence_async_global();
                tma2d(dst, &maps.hn, 0, rb * 128 + delta, fb);
                TS(24);
                r.next();
                r.run2d(&maps.hn, rb * 128 + delta);
#pragma unroll 1
                for (int i = 0; i < 2; i++) {
                    const char* src = (const char*)(i ? g_x1 : g_h1) + (size_t)rb * 163840;
                    r.acquire(0); r.next();
                    fb = r.acquire(SLOT); dst = r.slot();
                    const char* src1 = src + (cm == 0 ? SLOT : 0);
                    flag_wait_fast(FL_B1 + 16 * i + rb, ep1 * 8);
                    fence_async_global();
                    bulk_g2s(dst, src1, SLOT, fb);
                    TS(28 + 4 * i);
                    if (i) mbar_expect(bars + BAR_ST * 8, 0);
                    r.next();
                    r.run1d(src, 2, 10, cm >> 6);
                }
                r.run1d((const char*)g_x1 + (size_t)rb * 163840, 1, 10 - NA, cm >> 6);
                if (OWNG) { r.acquire(0); r.next(); }
#pragma unroll 1
                for (int i = 0; i < 2; i++) {
                    mbar_wait(bars + (BAR_G + i) * 8, 0); fence_async_global();
                    r.run1d((const char*)g_g + (size_t)rb * 442368, OWNG + HB0 / 64 * i, i ? 27 : OWNG + HB0 / 64, OWNG * (HB0 / 64 + j));
                }
            }
        }
        return;
    }
    bar_arrive(13, 640);
    asm volatile("setmaxnreg.inc.sync.aligned.u32 112;");
    const int rrow = 16 * rho + (warp >> 1) + 8 * (warp & 1);

    fence_async_smem();
    bar_sync(1 + wg, 128);
#pragma unroll 1
    for (int cc = wg; cc < wg + 1 + (wg == 3); cc++) {
        mbar_wait(bars + (BAR_K + cc) * 8, 0);
        if (cc == 2 && wq == 0) TSW(40);
        uint32_t a = sb + sm_k(cc) + 32 + (tid & 127) * 32;
        uint32_t pw = lds32(a - 4);
        uint4 x = lds128(a), y = lds128(a + 16), o;
        if ((tid & 127) == 0) {
            uint16_t k0 = __bfloat16_as_ushort(__float2bfloat16_rn(blo(x.x) + __uint_as_float(lds32(sb + SM_GV + 520 + cc * 4))));
            x.x = (x.x & 0xffff0000u) | k0;
            sts16(a, k0);
        }
        o.x = prmt(pw, x.x, 0x5432); o.y = prmt(x.x, x.y, 0x5432); o.z = prmt(x.y, x.z, 0x5432); o.w = prmt(x.z, x.w, 0x5432);
        sts128(a + 4160, o);
        o.x = prmt(x.w, y.x, 0x5432); o.y = prmt(y.x, y.y, 0x5432); o.z = prmt(y.y, y.z, 0x5432); o.w = prmt(y.z, y.w, 0x5432);
        sts128(a + 4176, o);
    }
    bar_sync(1 + wg, 128);
    if (wg == 3) bar_arrive(11, 256);
#pragma unroll 1
    for (int cc = wg; cc < 5; cc += 3) {
        if (cc == 3 && wg == 0) break;
        if (cc == 4) bar_sync(11, 256);
        const uint32_t kaddr = sb + sm_k(cc) + ((g & 1) ? 32 : 4192) + 4 * ((g >> 1) - c) + 64 * wq;
        const AFrag f0 = ldA(kaddr), f1 = ldA(kaddr + 256);
        if (STAG && cc == 3) bar_sync(12, 256);
        mbar_wait(bars + (BAR_U + cc) * 8, 0);
        if (wq == 0) TSW(5 + cc);
        float d[64];
        conv_two<0>(d, f0, f1, kaddr, desc_lo(sb + sm_u(cc), U_PLANE), sb + sm_red(cc) + wq * 4352 + g * 544 + c * 8, cc == 1);
        if (wq == 0) TSW(10 + cc);
        if (cc == 1) bar_arrive(6, 256);
    }
#pragma unroll 1
    for (int cc = wg == 1 ? 4 : wg;; cc++) {
        if (cc == 1) bar_sync(6, 256); else bar_sync(1 + wg, 128);
        const int ch = cta * 5 + cc;
        uint32_t* dst = g_yv + ch * 8 + ((g + (ch >> 2)) & 7) + (126 - 32 * wq - 2 * c) * 5120;
        uint2 v[16];
#pragma unroll
        for (int i = 0; i < 16; i++) v[i] = lds64(sb + sm_red(cc) + g * 544 + wq * 128 + c * 8 + (i >> 2) * 32 + (i & 3) * 4360);
#pragma unroll
        for (int w = 1; w < 4; w++)
            if (wq == 3 && c > 3 - w) v[12 + w] = make_uint2(0, 0);
#pragma unroll
        for (int q = 0; q < 4; q++) {
            const uint2* u = v + 4 * q;
            dst[-8 * q * 5120] = badd2(u[0].x, badd2(u[1].x, badd2(u[2].x, u[3].x)));
            dst[(-8 * q + 1) * 5120] = badd2(u[0].y, badd2(u[1].y, badd2(u[2].y, u[3].y)));
        }
        if (wq == 0) TSW(15 + cc);
        if (cc != 0) break;
    }
    fence_async_smem();
    if (!(wg & 1)) bar_arrive(9, 288);
    bar_arrive(7, 544);

    const uint32_t one2 = 0x3f803f80u;
    const unsigned ones = p.ones;
    {
        uint32_t x[10], a[10], cb[10], sbv[10];
        if (RPRE_WAIT) bar_sync(10, 512);
        mbar_wait(bars + BAR_XR * 8, 0);
#pragma unroll
        for (int i = 0; i < 10; i++) x[i] = lds32(sb + SM_XR + (rrow & 15) * 1280 + lane * 4 + i * 128);
        const uint3 s1 = row_stats(x, lane);
        const int up = lane >> 4, gg = warp >> 1, e = warp & 1;
        const uint32_t ya = sb + SM_Y + lane * 64 + ((gg + (lane >> 1)) & 7) * 4;
        const uint32_t sel = (up ? 0x1054u : 0x5410u) + (e ? 0x2222u : 0u);
        const uint32_t ma = sb + SM_MOD + lane * 4;
        mbar_wait(bars + BAR_M * 8, 0);
        uint32_t pin = 0;
#pragma unroll
        for (int i = 0; i < 10; i++) {
            uint32_t h = bfma2(ln_apply(x[i], s1.x, s1.y, s1.z), badd2(lds32(ma + 1280 + i * 128), one2), lds32(ma + i * 128));
            a[i] = bmul2(h, lds32(ma + 2560 + i * 128));
            sbv[i] = lds32(ma + 3840 + i * 128);
            cb[i] = badd2(lds32(ma + 5120 + i * 128), one2);
            pin ^= a[i] ^ cb[i];
        }
        if (pin & ~ones) sts32(sb + SM_GV, pin);
        if (warp == 4) TSW(52);
        mbar_wait(bars + BAR_Y * 8, 0);
        if (warp == 0) TSW(22);
#pragma unroll
        for (int i = 0; i < 10; i++) {
            if (i == 6) mbar_wait(bars + BAR_Y2 * 8, 0);
            uint32_t y0 = lds32(ya + i * 2048 + up * 32), y1 = lds32(ya + i * 2048 + (up ^ 1) * 32);
            x[i] = bfma2(a[i], prmt(y0, y1, sel), x[i]);
        }
        const uint3 s2 = row_stats(x, lane);
#pragma unroll
        for (int i = 0; i < 10; i++) x[i] = bfma2(ln_apply(x[i], s2.x, s2.y, s2.z), cb[i], sbv[i]);
        const uint3 s3 = row_stats(x, lane);
        uint32_t* o = reinterpret_cast<uint32_t*>(g_hn + (size_t)rrow * D_) + lane;
#pragma unroll
        for (int i = 0; i < 10; i++) o[32 * i] = ln_apply(x[i], s3.x, s3.y, s3.z);
        if (lane < 2) g_rs[rrow * 2 + lane] = lane ? make_uint4(s2.x, s2.y, s2.z, 0) : make_uint4(s1.x, s1.y, s1.z, 0);
        if (warp == 0) TSW(34);
        bar_arrive(8, 544);
    }

    const int half = wg & 1;
    const int row = 64 * half + 16 * wq + g;
    const int tw0 = (rb * 80 + (cm >> 3)) * 512 + row * 4 + c, tw1 = (rb * 80 + (cr >> 3) - 8) * 512 + row * 4 + c;
    const uint32_t park = sb + SM_Y + (tid & 255) * 16;
    const uint32_t ms0 = sb + SM_MOD + (cm + 2 * c) * 2, ms1 = sb + SM_MOD + (cr - 64 + 2 * c) * 2;
    if (wg >= 2) {
        {
            float acc[40];
            gemm_loop<80, true, 10, 10, true>(acc, sb, half, 0, 0, 10, 0, 0, 25);
#pragma unroll
            for (int k = 0; k < 10; k += CH) CHUNK(k) {
#pragma unroll
                for (int q = k; q < k + CH && q < 10; q++) {
                    uint32_t* dst = reinterpret_cast<uint32_t*>(g_h1) + (q < 8 ? tw0 : tw1);
                    const uint32_t u = gelu2_h(bmul2(pack2(acc[4 * q], acc[4 * q + 1]), 0x3f003f00u));
                    const uint32_t v = gelu2_h(bmul2(pack2(acc[4 * q + 2], acc[4 * q + 3]), 0x3f003f00u));
                    dst[q * 512] = u;
                    dst[q * 512 + 32] = v;
                    acc[4 * q] = __uint_as_float(u); acc[4 * q + 1] = __uint_as_float(v);
                }
            }
            bar_arrive(15, 288);
            mbar_wait(bars + (BAR_FA + 10 % NA) * 8, (10 / NA) & 1);
#pragma unroll
            for (int q = 0; q < 8; q++) {
                sts32(sb + SM_RA + (10 % NA) * SLOT + q * 2048 + row * 16 + c * 4, __float_as_uint(acc[4 * q]));
                sts32(sb + SM_RA + (10 % NA) * SLOT + q * 2048 + row * 16 + c * 4 + 128, __float_as_uint(acc[4 * q + 1]));
            }
            fence_async_smem();
            bar_arrive(14, 512);
        }
        gemm3<0>(sb, rb, j, half, row, c, ones);
        {
            float acc[40];
            uint32_t gbv[10], base[20];
#pragma unroll
            for (int q = 0; q < 10; q++) gbv[q] = lds32((q < 8 ? ms0 : ms1) + 6400 + q * 16);
#pragma unroll
            for (int q = 0; q < 5; q++) { const uint4 t = lds128(park + q * 4096); base[4 * q] = t.x; base[4 * q + 1] = t.y; base[4 * q + 2] = t.z; base[4 * q + 3] = t.w; }
            gemm_loop<80, false, 27, 27 - NB, true>(acc, sb, half, 39 - NA, 40, 27 - NA, 11, 0, 42);
            auto fin = [&](int q, int r) {
                return bfma2(gbv[q], pack2(acc[4 * q + 2 * r], acc[4 * q + 2 * r + 1]), base[2 * q + r]);
            };
            auto tr4 = [&](uint32_t t0, uint32_t t1, uint32_t t2, uint32_t t3) {
                const bool o1 = c & 1, o2 = c & 2;
                uint32_t a = __shfl_xor_sync(0xffffffffu, o1 ? t0 : t1, 1), b = __shfl_xor_sync(0xffffffffu, o1 ? t2 : t3, 1);
                uint32_t u0 = o1 ? a : t0, u1 = o1 ? t1 : a, u2 = o1 ? b : t2, u3 = o1 ? t3 : b;
                a = __shfl_xor_sync(0xffffffffu, o2 ? u0 : u2, 2); b = __shfl_xor_sync(0xffffffffu, o2 ? u1 : u3, 2);
                return o2 ? make_uint4(a, b, u2, u3) : make_uint4(u0, u1, a, b);
            };
            bf16* go = p.out + (size_t)(rb * 128 + row) * D_;
#pragma unroll
            for (int k = 0; k < 2; k++) CHUNK(k) {
#pragma unroll
                for (int r = 0; r < 2; r++)
                    *reinterpret_cast<uint4*>(go + r * 8 * D_ + cm + 32 * k + 8 * c) = tr4(fin(4 * k, r), fin(4 * k + 1, r), fin(4 * k + 2, r), fin(4 * k + 3, r));
            }
            CHUNK(2) *reinterpret_cast<uint4*>(go + (c >> 1) * 8 * D_ + cr + 8 * (c & 1)) = tr4(fin(8, 0), fin(9, 0), fin(8, 1), fin(9, 1));
            if (tid == 256) TS(44);
            if (warp == 8) TSFLUSH();
        }
    } else {
        {
            float acc[40];
            uint32_t x2[20];
            {
                uint32_t y[20];
                mbar_wait(bars + BAR_XY * 8, 0);
                const uint32_t xa = sb + SM_XT + row * 128 + c * 4, xb = sb + SM_XT2 + row * 32 + c * 4;
                const uint32_t ya = sb + SM_YT + (4 * half + wq) * 2560 + c * 64;
#pragma unroll
                for (int q = 0; q < 10; q++) {
                    const uint32_t a = q < 8 ? xa + ((q ^ g) << 4) : xb + (q - 8) * 16;
                    x2[2 * q] = lds32(a); x2[2 * q + 1] = lds32(a + (q < 8 ? 1024 : 256));
                    const int pos = (g + ((q < 8 ? cm : cr) >> 2) + 2 * q + (c >> 1)) & 7;
                    y[2 * q] = lds32(ya + q * 256 + pos * 4); y[2 * q + 1] = lds32(ya + q * 256 + 32 + pos * 4);
                }
                fence_async_smem();
                bar_sync(1 + wg, 128);
                if ((tid & 127) < NA) mbar_arrive_cl(mapa(bars + (BAR_EA + (tid & 127)) * 8, blockIdx.x & 1));
                mbar_wait(bars + (BAR_FA + 1) * 8, 0);
                const uint4* rp = g_rs + (rb * 128 + row) * 2;
                const uint4 ra = ldcg128(rp), rb2 = ldcg128(rp + 1), rc = ldcg128(rp + 16), rd = ldcg128(rp + 17);
                bar_sync(14, 512);
#pragma unroll
                for (int q = 0; q < 10; q++) {
                    const uint32_t ms = q < 8 ? ms0 : ms1;
                    const uint32_t sa = lds32(ms + 16 * q), ca = badd2(lds32(ms + 1280 + 16 * q), one2), ga = lds32(ms + 2560 + 16 * q);
                    const uint32_t sbv = lds32(ms + 3840 + 16 * q), cb = badd2(lds32(ms + 5120 + 16 * q), one2);
                    uint32_t u = x2[2 * q], v = x2[2 * q + 1];
                    u = bfma2(bmul2(bfma2(ln_apply(u, ra.x, ra.y, ra.z), ca, sa), ga), prmt(y[2 * q], y[2 * q + 1], 0x5410), u);
                    v = bfma2(bmul2(bfma2(ln_apply(v, rc.x, rc.y, rc.z), ca, sa), ga), prmt(y[2 * q], y[2 * q + 1], 0x7632), v);
                    x2[2 * q] = u; x2[2 * q + 1] = v;
                    u = bfma2(ln_apply(u, rb2.x, rb2.y, rb2.z), cb, sbv);
                    v = bfma2(ln_apply(v, rd.x, rd.y, rd.z), cb, sbv);
                    acc[4 * q] = blo(u); acc[4 * q + 1] = bhi(u); acc[4 * q + 2] = blo(v); acc[4 * q + 3] = bhi(v);
                }
            }
            reg_fence<40>(acc);
            if (tid == 0) TS(45);
            gemm_loop<80, false, 10, 10, false>(acc, sb, half, 10, 10, 10, 0, 0, 29);
            uint32_t x1[20];
            float s0 = 0.f, q0 = 0.f, s1 = 0.f, q1 = 0.f;
#pragma unroll
            for (int q = 0; q < 10; q++) {
                uint32_t u = pack2(acc[4 * q], acc[4 * q + 1]);
                uint32_t v = pack2(acc[4 * q + 2], acc[4 * q + 3]);
                uint32_t* dst = reinterpret_cast<uint32_t*>(g_x1) + (q < 8 ? tw0 : tw1);
                dst[q * 512] = u;
                dst[q * 512 + 32] = v;
                x1[2 * q] = u; x1[2 * q + 1] = v;
            }
            CHUNK(0)
#pragma unroll
            for (int q = 0; q < 10; q++) {
                float a = blo(x1[2 * q]), b = bhi(x1[2 * q]), e = blo(x1[2 * q + 1]), f = bhi(x1[2 * q + 1]);
                s0 += a + b; q0 = fmaf(a, a, fmaf(b, b, q0));
                s1 += e + f; q1 = fmaf(e, e, fmaf(f, f, q1));
            }
#pragma unroll
            for (int m = 1; m <= 2; m <<= 1) {
                s0 += __shfl_xor_sync(0xffffffffu, s0, m); q0 += __shfl_xor_sync(0xffffffffu, q0, m);
                s1 += __shfl_xor_sync(0xffffffffu, s1, m); q1 += __shfl_xor_sync(0xffffffffu, q1, m);
            }
            if (c < 2) g_st[(rb * 8 + j) * 128 + row + 8 * c] = c ? make_float2(s1, q1) : make_float2(s0, q0);
            bar_arrive(6, 288);
            mbar_wait(bars + (BAR_FA + 20 % NA) * 8, (20 / NA) & 1);
#pragma unroll
            for (int q = 0; q < 8; q++) {
                sts32(sb + SM_RA + (20 % NA) * SLOT + q * 2048 + row * 16 + c * 4, x1[2 * q]);
                sts32(sb + SM_RA + (20 % NA) * SLOT + q * 2048 + row * 16 + c * 4 + 128, x1[2 * q + 1]);
            }
            fence_async_smem();
            bar_sync(3 + wg, 128);
#pragma unroll
            for (int q = 0; q < 5; q++) {
                const uint32_t ms = q < 4 ? ms0 : ms1;
                const uint32_t g0 = lds32(ms + 6400 + q * 32), g1 = lds32(ms + 6400 + q * 32 + 16);
                sts128(park + q * 4096, make_uint4(bfma2(g0, x1[4 * q], x2[4 * q]), bfma2(g0, x1[4 * q + 1], x2[4 * q + 1]),
                                                   bfma2(g1, x1[4 * q + 2], x2[4 * q + 2]), bfma2(g1, x1[4 * q + 3], x2[4 * q + 3])));
            }
        }
        gemm3<1>(sb, rb, j, half, row, c, ones);
    }
}

typedef CUresult (*EncFn)(CUtensorMap*, CUtensorMapDataType, cuuint32_t, void*, const cuuint64_t*, const cuuint64_t*,
                          const cuuint32_t*, const cuuint32_t*, CUtensorMapInterleave, CUtensorMapSwizzle,
                          CUtensorMapL2promotion, CUtensorMapFloatOOBfill);

void make_map(EncFn enc, CUtensorMap* m, const void* base, uint64_t inner, uint64_t outer, uint32_t bi, uint32_t bo,
              CUtensorMapSwizzle swz = CU_TENSOR_MAP_SWIZZLE_128B) {
    cuuint64_t dims[2] = {inner, outer};
    cuuint64_t st[1] = {inner * 2};
    cuuint32_t box[2] = {bi, bo};
    cuuint32_t es[2] = {1, 1};
    enc(m, CU_TENSOR_MAP_DATA_TYPE_BFLOAT16, 2, const_cast<void*>(base), dims, st, box, es, CU_TENSOR_MAP_INTERLEAVE_NONE,
        swz, CU_TENSOR_MAP_L2_PROMOTION_NONE, CU_TENSOR_MAP_FLOAT_OOB_FILL_NONE);
}

}

extern "C" void kernel_launch(void* const* d_in, const int* in_sizes, int n_in, void* d_out, int out_size) {
    (void)in_sizes; (void)n_in; (void)out_size;
    Params p;
    p.q = (const bf16*)d_in[0]; p.k = (const bf16*)d_in[1]; p.v = (const bf16*)d_in[2];
    p.shift = (const bf16*)d_in[3]; p.ssmk = (const bf16*)d_in[4]; p.ssmD = (const bf16*)d_in[5];
    p.w1 = (const bf16*)d_in[7]; p.w2 = (const bf16*)d_in[8]; p.w3 = (const bf16*)d_in[9]; p.w4 = (const bf16*)d_in[10];
    p.c = (const bf16*)d_in[11]; p.wmod = (const bf16*)d_in[12];
    p.out = (bf16*)d_out;
    p.ones = 0xffffffffu;

    void* fn = nullptr;
    cudaDriverEntryPointQueryResult qr;
    cudaGetDriverEntryPoint("cuTensorMapEncodeTiled", &fn, cudaEnableDefault, &qr);
    EncFn enc = (EncFn)fn;
    void* hn = nullptr;
    cudaGetSymbolAddress(&hn, g_hn);
    Maps maps;
    make_map(enc, &maps.w3s, p.w3, F_, D_, 216, 64, CU_TENSOR_MAP_SWIZZLE_NONE);
    make_map(enc, &maps.wm, p.wmod, 6 * D_, D_, 32, 128, CU_TENSOR_MAP_SWIZZLE_64B);
    make_map(enc, &maps.xa, p.q, D_, S_, 64, 128);
    make_map(enc, &maps.xb, p.q, D_, S_, 16, 128, CU_TENSOR_MAP_SWIZZLE_NONE);
    make_map(enc, &maps.hn, hn, D_, S_, 64, 128);
    make_map(enc, &maps.w1a, p.w1, D_, D_, 64, 64);
    make_map(enc, &maps.w1b, p.w1, D_, D_, 16, 64);
    make_map(enc, &maps.w2a, p.w2, D_, D_, 64, 64);
    make_map(enc, &maps.w2b, p.w2, D_, D_, 16, 64);
    make_map(enc, &maps.w3a, p.w3, F_, D_, 64, 64);
    make_map(enc, &maps.w3b, p.w3, F_, D_, RA3, 64);
    make_map(enc, &maps.w3c, p.w3, F_, D_, RB3, 64);
    make_map(enc, &maps.w4a, p.w4, D_, F_, 64, 64);
    make_map(enc, &maps.w4b, p.w4, D_, F_, 16, 64);
    cudaFuncSetAttribute(fused_kernel, cudaFuncAttributeMaxDynamicSharedMemorySize, SMEM_BYTES);
    fused_kernel<<<132, NTHREADS, SMEM_BYTES>>>(p, maps);
}
```

```cpp
#include <cuda_runtime.h>
#include <cuda_bf16.h>
#include <cuda.h>
#include <stdint.h>
#include <string.h>

#define SEED 0
#define RING_A 6
#define MMA_STAT 0
#define CH 2
#define FAST_LN 2
#define STAG 10
#define REDM 1
#define CONVV 0
#define NPOLL 1
#define PGELU 2
#define CH3 4
#define HO_A 16
#define HO_B 16
#define RA3 48
#define CSP 16
#define OWNG 1
#define SK1 0
#define SK2 0
#define SK4 0
#define GATE 5
#define HOLD 1
#define SSM_DELAY 0
#define B_DELAY 300
#define RPRE_WAIT 1
#define XAFTER 0
#define SSM_N 3
#define PF_EARLY 0

namespace {

typedef __nv_bfloat16 bf16;
typedef __nv_bfloat162 bf162;

constexpr int S_ = 2048, D_ = 640, F_ = 1728;
constexpr int NTHREADS = 640;
constexpr int NA = RING_A, NB = 12 - RING_A;
constexpr int SLOT = 16384;
constexpr int RB3 = 88 - RA3, HB0 = 512 + 8 * RA3;
constexpr int SM_RA = 0, SM_RB = NA * SLOT;

static_assert(NA == 6, "smem map");
constexpr int RED_STRIDE = 17536;
constexpr int K_STRIDE = 8320;
constexpr int U_PLANE = 2560, U_STRIDE = 5120;
constexpr int SM_Y = 12 * SLOT;
__device__ __forceinline__ int sm_red(int cc) { return cc * RED_STRIDE + (cc < 3 ? SM_RB : -3 * RED_STRIDE); }
__device__ __forceinline__ int sm_k(int cc) { return cc * K_STRIDE + (cc < 3 ? SM_RB + 3 * RED_STRIDE : 2 * RED_STRIDE - 3 * K_STRIDE); }
__device__ __forceinline__ int sm_u(int cc) { return cc * U_STRIDE + (cc < 3 ? SM_RB + 3 * RED_STRIDE + 3 * K_STRIDE : SM_Y + 8192 - 3 * U_STRIDE); }
constexpr int SM_PK = SM_RB;
constexpr int SM_PV = SM_RB + 24576;
constexpr int SM_WM = 57344;
constexpr int SM_XT = SM_WM, SM_XT2 = SM_WM + 16384, SM_XR = SM_WM + 20480;
constexpr int SM_YT = 0;
constexpr int SM_MOD = SM_Y + 20480;
constexpr int SM_GV = SM_MOD + 7680;
constexpr int SM_CS = SM_GV + 1024;
constexpr int SM_RP = SM_CS + 1024;
constexpr int SM_BAR = SM_RP + 1024;
constexpr int SM_PROF = SM_BAR + 512;
constexpr int SM_TOTAL = SM_PROF + 512;
constexpr int SMEM_BYTES = SM_TOTAL + 1024;
static_assert(SMEM_BYTES <= 232448, "smem");

constexpr int BAR_FA = 0, BAR_FB = NA, BAR_EA = 12, BAR_EB = 12 + NA, BAR_K = 24, BAR_U = 29, BAR_Y = 34, BAR_CS = 35, BAR_WM = 36, BAR_M = 37, BAR_XY = 38, BAR_Y2 = 39, BAR_G = 40, BAR_ST = 44, BAR_XR = 45, NBARS = 46;

__device__ __align__(1024) bf16 g_kvT[D_ * S_];
__device__ __align__(1024) uint32_t g_yv[128 * 5120];
__device__ __align__(1024) bf16 g_mod[6 * D_];
__device__ __align__(1024) bf16 g_hn[S_ * D_];
__device__ __align__(1024) uint4 g_rs[S_ * 2];
__device__ __align__(1024) bf16 g_h1[S_ * D_];
__device__ __align__(1024) bf16 g_x1[S_ * D_];
__device__ __align__(1024) bf16 g_g[S_ * F_];
__device__ __align__(1024) float2 g_st[S_ * 8];
__device__ __align__(1024) float g_cs[F_];
__device__ __align__(1024) unsigned g_flags[128 * 32];
__device__ __align__(1024) unsigned g_epoch[160];
constexpr int FL_P = 0, FL_C = 8, FL_CS = 9, FL_M = 10, FL_R = 16, FL_B1 = 32, FL_B2 = 48, FL_G = 64;

#define TS(i) do {} while (0)
#define TSW(i) do {} while (0)
#define TSD(i, dep) do {} while (0)
#define TSD2(i, dep) do {} while (0)
#define TSFLUSH() do {} while (0)

struct Params {
    const bf16 *q, *k, *v, *shift, *ssmk, *ssmD, *w1, *w2, *w3, *w4, *c, *wmod;
    bf16* out;
    unsigned ones;
};
#define CHUNK(k) if (ones & (1u << (k)))
struct Maps { CUtensorMap hn, w1a, w1b, w2a, w2b, w3a, w3b, w3c, w4a, w4b, wm, xa, xb, w3s; };

template<int N> struct WgRs;
template<int N> struct WgSs;
template<> struct WgRs<32> { template<int OFF,int HI,int SC> static __device__ __forceinline__ void run(float* d,uint32_t a0,uint32_t a1,uint32_t a2,uint32_t a3,uint32_t blo){
 asm volatile("{.reg .b32 l; .reg .b64 db; add.u32 l,%20,%21; mov.b64 db,{l,%22}; wgmma.mma_async.sync.aligned.m64n32k16.f32.bf16.bf16 {%0,%1,%2,%3,%4,%5,%6,%7,%8,%9,%10,%11,%12,%13,%14,%15},{%16,%17,%18,%19},db,%23,1,1,0;}"
 :"+f"(d[0]),"+f"(d[1]),"+f"(d[2]),"+f"(d[3]),"+f"(d[4]),"+f"(d[5]),"+f"(d[6]),"+f"(d[7]),"+f"(d[8]),"+f"(d[9]),"+f"(d[10]),"+f"(d[11]),"+f"(d[12]),"+f"(d[13]),"+f"(d[14]),"+f"(d[15])
 :"r"(a0),"r"(a1),"r"(a2),"r"(a3),"r"(blo),"n"(OFF),"n"(HI),"n"(SC)); } };
template<> struct WgRs<48> { template<int OFF,int HI,int SC> static __device__ __forceinline__ void run(float* d,uint32_t a0,uint32_t a1,uint32_t a2,uint32_t a3,uint32_t blo){
 asm volatile("{.reg .b32 l; .reg .b64 db; add.u32 l,%28,%29; mov.b64 db,{l,%30}; wgmma.mma_async.sync.aligned.m64n48k16.f32.bf16.bf16 {%0,%1,%2,%3,%4,%5,%6,%7,%8,%9,%10,%11,%12,%13,%14,%15,%16,%17,%18,%19,%20,%21,%22,%23},{%24,%25,%26,%27},db,%31,1,1,0;}"
 :"+f"(d[0]),"+f"(d[1]),"+f"(d[2]),"+f"(d[3]),"+f"(d[4]),"+f"(d[5]),"+f"(d[6]),"+f"(d[7]),"+f"(d[8]),"+f"(d[9]),"+f"(d[10]),"+f"(d[11]),"+f"(d[12]),"+f"(d[13]),"+f"(d[14]),"+f"(d[15]),"+f"(d[16]),"+f"(d[17]),"+f"(d[18]),"+f"(d[19]),"+f"(d[20]),"+f"(d[21]),"+f"(d[22]),"+f"(d[23])
 :"r"(a0),"r"(a1),"r"(a2),"r"(a3),"r"(blo),"n"(OFF),"n"(HI),"n"(SC)); } };
template<> struct WgRs<64> { template<int OFF,int HI,int SC> static __device__ __forceinline__ void run(float* d,uint32_t a0,uint32_t a1,uint32_t a2,uint32_t a3,uint32_t blo){
 asm volatile("{.reg .b32 l; .reg .b64 db; add.u32 l,%36,%37; mov.b64 db,{l,%38}; wgmma.mma_async.sync.aligned.m64n64k16.f32.bf16.bf16 {%0,%1,%2,%3,%4,%5,%6,%7,%8,%9,%10,%11,%12,%13,%14,%15,%16,%17,%18,%19,%20,%21,%22,%23,%24,%25,%26,%27,%28,%29,%30,%31},{%32,%33,%34,%35},db,%39,1,1,0;}"
 :"+f"(d[0]),"+f"(d[1]),"+f"(d[2]),"+f"(d[3]),"+f"(d[4]),"+f"(d[5]),"+f"(d[6]),"+f"(d[7]),"+f"(d[8]),"+f"(d[9]),"+f"(d[10]),"+f"(d[11]),"+f"(d[12]),"+f"(d[13]),"+f"(d[14]),"+f"(d[15]),"+f"(d[16]),"+f"(d[17]),"+f"(d[18]),"+f"(d[19]),"+f"(d[20]),"+f"(d[21]),"+f"(d[22]),"+f"(d[23]),"+f"(d[24]),"+f"(d[25]),"+f"(d[26]),"+f"(d[27]),"+f"(d[28]),"+f"(d[29]),"+f"(d[30]),"+f"(d[31])
 :"r"(a0),"r"(a1),"r"(a2),"r"(a3),"r"(blo),"n"(OFF),"n"(HI),"n"(SC)); } };
template<> struct WgRs<80> { template<int OFF,int HI,int SC> static __device__ __forceinline__ void run(float* d,uint32_t a0,uint32_t a1,uint32_t a2,uint32_t a3,uint32_t blo){
 asm volatile("{.reg .b32 l; .reg .b64 db; add.u32 l,%44,%45; mov.b64 db,{l,%46}; wgmma.mma_async.sync.aligned.m64n80k16.f32.bf16.bf16 {%0,%1,%2,%3,%4,%5,%6,%7,%8,%9,%10,%11,%12,%13,%14,%15,%16,%17,%18,%19,%20,%21,%22,%23,%24,%25,%26,%27,%28,%29,%30,%31,%32,%33,%34,%35,%36,%37,%38,%39},{%40,%41,%42,%43},db,%47,1,1,0;}"
 :"+f"(d[0]),"+f"(d[1]),"+f"(d[2]),"+f"(d[3]),"+f"(d[4]),"+f"(d[5]),"+f"(d[6]),"+f"(d[7]),"+f"(d[8]),"+f"(d[9]),"+f"(d[10]),"+f"(d[11]),"+f"(d[12]),"+f"(d[13]),"+f"(d[14]),"+f"(d[15]),"+f"(d[16]),"+f"(d[17]),"+f"(d[18]),"+f"(d[19]),"+f"(d[20]),"+f"(d[21]),"+f"(d[22]),"+f"(d[23]),"+f"(d[24]),"+f"(d[25]),"+f"(d[26]),"+f"(d[27]),"+f"(d[28]),"+f"(d[29]),"+f"(d[30]),"+f"(d[31]),"+f"(d[32]),"+f"(d[33]),"+f"(d[34]),"+f"(d[35]),"+f"(d[36]),"+f"(d[37]),"+f"(d[38]),"+f"(d[39])
 :"r"(a0),"r"(a1),"r"(a2),"r"(a3),"r"(blo),"n"(OFF),"n"(HI),"n"(SC)); } };
template<> struct WgRs<96> { template<int OFF,int HI,int SC> static __device__ __forceinline__ void run(float* d,uint32_t a0,uint32_t a1,uint32_t a2,uint32_t a3,uint32_t blo){
 asm volatile("{.reg .b32 l; .reg .b64 db; add.u32 l,%52,%53; mov.b64 db,{l,%54}; wgmma.mma_async.sync.aligned.m64n96k16.f32.bf16.bf16 {%0,%1,%2,%3,%4,%5,%6,%7,%8,%9,%10,%11,%12,%13,%14,%15,%16,%17,%18,%19,%20,%21,%22,%23,%24,%25,%26,%27,%28,%29,%30,%31,%32,%33,%34,%35,%36,%37,%38,%39,%40,%41,%42,%43,%44,%45,%46,%47},{%48,%49,%50,%51},db,%55,1,1,0;}"
 :"+f"(d[0]),"+f"(d[1]),"+f"(d[2]),"+f"(d[3]),"+f"(d[4]),"+f"(d[5]),"+f"(d[6]),"+f"(d[7]),"+f"(d[8]),"+f"(d[9]),"+f"(d[10]),"+f"(d[11]),"+f"(d[12]),"+f"(d[13]),"+f"(d[14]),"+f"(d[15]),"+f"(d[16]),"+f"(d[17]),"+f"(d[18]),"+f"(d[19]),"+f"(d[20]),"+f"(d[21]),"+f"(d[22]),"+f"(d[23]),"+f"(d[24]),"+f"(d[25]),"+f"(d[26]),"+f"(d[27]),"+f"(d[28]),"+f"(d[29]),"+f"(d[30]),"+f"(d[31]),"+f"(d[32]),"+f"(d[33]),"+f"(d[34]),"+f"(d[35]),"+f"(d[36]),"+f"(d[37]),"+f"(d[38]),"+f"(d[39]),"+f"(d[40]),"+f"(d[41]),"+f"(d[42]),"+f"(d[43]),"+f"(d[44]),"+f"(d[45]),"+f"(d[46]),"+f"(d[47])
 :"r"(a0),"r"(a1),"r"(a2),"r"(a3),"r"(blo),"n"(OFF),"n"(HI),"n"(SC)); } };
template<> struct WgRs<112> { template<int OFF,int HI,int SC> static __device__ __forceinline__ void run(float* d,uint32_t a0,uint32_t a1,uint32_t a2,uint32_t a3,uint32_t blo){
 asm volatile("{.reg .b32 l; .reg .b64 db; add.u32 l,%60,%61; mov.b64 db,{l,%62}; wgmma.mma_async.sync.aligned.m64n112k16.f32.bf16.bf16 {%0,%1,%2,%3,%4,%5,%6,%7,%8,%9,%10,%11,%12,%13,%14,%15,%16,%17,%18,%19,%20,%21,%22,%23,%24,%25,%26,%27,%28,%29,%30,%31,%32,%33,%34,%35,%36,%37,%38,%39,%40,%41,%42,%43,%44,%45,%46,%47,%48,%49,%50,%51,%52,%53,%54,%55},{%56,%57,%58,%59},db,%63,1,1,0;}"
 :"+f"(d[0]),"+f"(d[1]),"+f"(d[2]),"+f"(d[3]),"+f"(d[4]),"+f"(d[5]),"+f"(d[6]),"+f"(d[7]),"+f"(d[8]),"+f"(d[9]),"+f"(d[10]),"+f"(d[11]),"+f"(d[12]),"+f"(d[13]),"+f"(d[14]),"+f"(d[15]),"+f"(d[16]),"+f"(d[17]),"+f"(d[18]),"+f"(d[19]),"+f"(d[20]),"+f"(d[21]),"+f"(d[22]),"+f"(d[23]),"+f"(d[24]),"+f"(d[25]),"+f"(d[26]),"+f"(d[27]),"+f"(d[28]),"+f"(d[29]),"+f"(d[30]),"+f"(d[31]),"+f"(d[32]),"+f"(d[33]),"+f"(d[34]),"+f"(d[35]),"+f"(d[36]),"+f"(d[37]),"+f"(d[38]),"+f"(d[39]),"+f"(d[40]),"+f"(d[41]),"+f"(d[42]),"+f"(d[43]),"+f"(d[44]),"+f"(d[45]),"+f"(d[46]),"+f"(d[47]),"+f"(d[48]),"+f"(d[49]),"+f"(d[50]),"+f"(d[51]),"+f"(d[52]),"+f"(d[53]),"+f"(d[54]),"+f"(d[55])
 :"r"(a0),"r"(a1),"r"(a2),"r"(a3),"r"(blo),"n"(OFF),"n"(HI),"n"(SC)); } };
template<> struct WgRs<128> { template<int OFF,int HI,int SC> static __device__ __forceinline__ void run(float* d,uint32_t a0,uint32_t a1,uint32_t a2,uint32_t a3,uint32_t blo){
 asm volatile("{.reg .b32 l; .reg .b64 db; add.u32 l,%68,%69; mov.b64 db,{l,%70}; wgmma.mma_async.sync.aligned.m64n128k16.f32.bf16.bf16 {%0,%1,%2,%3,%4,%5,%6,%7,%8,%9,%10,%11,%12,%13,%14,%15,%16,%17,%18,%19,%20,%21,%22,%23,%24,%25,%26,%27,%28,%29,%30,%31,%32,%33,%34,%35,%36,%37,%38,%39,%40,%41,%42,%43,%44,%45,%46,%47,%48,%49,%50,%51,%52,%53,%54,%55,%56,%57,%58,%59,%60,%61,%62,%63},{%64,%65,%66,%67},db,%71,1,1,0;}"
 :"+f"(d[0]),"+f"(d[1]),"+f"(d[2]),"+f"(d[3]),"+f"(d[4]),"+f"(d[5]),"+f"(d[6]),"+f"(d[7]),"+f"(d[8]),"+f"(d[9]),"+f"(d[10]),"+f"(d[11]),"+f"(d[12]),"+f"(d[13]),"+f"(d[14]),"+f"(d[15]),"+f"(d[16]),"+f"(d[17]),"+f"(d[18]),"+f"(d[19]),"+f"(d[20]),"+f"(d[21]),"+f"(d[22]),"+f"(d[23]),"+f"(d[24]),"+f"(d[25]),"+f"(d[26]),"+f"(d[27]),"+f"(d[28]),"+f"(d[29]),"+f"(d[30]),"+f"(d[31]),"+f"(d[32]),"+f"(d[33]),"+f"(d[34]),"+f"(d[35]),"+f"(d[36]),"+f"(d[37]),"+f"(d[38]),"+f"(d[39]),"+f"(d[40]),"+f"(d[41]),"+f"(d[42]),"+f"(d[43]),"+f"(d[44]),"+f"(d[45]),"+f"(d[46]),"+f"(d[47]),"+f"(d[48]),"+f"(d[49]),"+f"(d[50]),"+f"(d[51]),"+f"(d[52]),"+f"(d[53]),"+f"(d[54]),"+f"(d[55]),"+f"(d[56]),"+f"(d[57]),"+f"(d[58]),"+f"(d[59]),"+f"(d[60]),"+f"(d[61]),"+f"(d[62]),"+f"(d[63])
 :"r"(a0),"r"(a1),"r"(a2),"r"(a3),"r"(blo),"n"(OFF),"n"(HI),"n"(SC)); } };
template<> struct WgSs<80> { template<int AOFF,int AHI,int BOFF,int BHI,int SC> static __device__ __forceinline__ void run(float* d,uint32_t alo,uint32_t blo){
 asm volatile("{.reg .b32 l,m; .reg .b64 da,db; add.u32 l,%40,%42; mov.b64 da,{l,%43}; add.u32 m,%41,%44; mov.b64 db,{m,%45}; wgmma.mma_async.sync.aligned.m64n80k16.f32.bf16.bf16 {%0,%1,%2,%3,%4,%5,%6,%7,%8,%9,%10,%11,%12,%13,%14,%15,%16,%17,%18,%19,%20,%21,%22,%23,%24,%25,%26,%27,%28,%29,%30,%31,%32,%33,%34,%35,%36,%37,%38,%39},da,db,%46,1,1,0,1;}"
 :"+f"(d[0]),"+f"(d[1]),"+f"(d[2]),"+f"(d[3]),"+f"(d[4]),"+f"(d[5]),"+f"(d[6]),"+f"(d[7]),"+f"(d[8]),"+f"(d[9]),"+f"(d[10]),"+f"(d[11]),"+f"(d[12]),"+f"(d[13]),"+f"(d[14]),"+f"(d[15]),"+f"(d[16]),"+f"(d[17]),"+f"(d[18]),"+f"(d[19]),"+f"(d[20]),"+f"(d[21]),"+f"(d[22]),"+f"(d[23]),"+f"(d[24]),"+f"(d[25]),"+f"(d[26]),"+f"(d[27]),"+f"(d[28]),"+f"(d[29]),"+f"(d[30]),"+f"(d[31]),"+f"(d[32]),"+f"(d[33]),"+f"(d[34]),"+f"(d[35]),"+f"(d[36]),"+f"(d[37]),"+f"(d[38]),"+f"(d[39])
 :"r"(alo),"r"(blo),"n"(AOFF),"n"(AHI),"n"(BOFF),"n"(BHI),"n"(SC)); } };
template<> struct WgSs<88> { template<int AOFF,int AHI,int BOFF,int BHI,int SC> static __device__ __forceinline__ void run(float* d,uint32_t alo,uint32_t blo){
 asm volatile("{.reg .b32 l,m; .reg .b64 da,db; add.u32 l,%44,%46; mov.b64 da,{l,%47}; add.u32 m,%45,%48; mov.b64 db,{m,%49}; wgmma.mma_async.sync.aligned.m64n88k16.f32.bf16.bf16 {%0,%1,%2,%3,%4,%5,%6,%7,%8,%9,%10,%11,%12,%13,%14,%15,%16,%17,%18,%19,%20,%21,%22,%23,%24,%25,%26,%27,%28,%29,%30,%31,%32,%33,%34,%35,%36,%37,%38,%39,%40,%41,%42,%43},da,db,%50,1,1,0,1;}"
 :"+f"(d[0]),"+f"(d[1]),"+f"(d[2]),"+f"(d[3]),"+f"(d[4]),"+f"(d[5]),"+f"(d[6]),"+f"(d[7]),"+f"(d[8]),"+f"(d[9]),"+f"(d[10]),"+f"(d[11]),"+f"(d[12]),"+f"(d[13]),"+f"(d[14]),"+f"(d[15]),"+f"(d[16]),"+f"(d[17]),"+f"(d[18]),"+f"(d[19]),"+f"(d[20]),"+f"(d[21]),"+f"(d[22]),"+f"(d[23]),"+f"(d[24]),"+f"(d[25]),"+f"(d[26]),"+f"(d[27]),"+f"(d[28]),"+f"(d[29]),"+f"(d[30]),"+f"(d[31]),"+f"(d[32]),"+f"(d[33]),"+f"(d[34]),"+f"(d[35]),"+f"(d[36]),"+f"(d[37]),"+f"(d[38]),"+f"(d[39]),"+f"(d[40]),"+f"(d[41]),"+f"(d[42]),"+f"(d[43])
 :"r"(alo),"r"(blo),"n"(AOFF),"n"(AHI),"n"(BOFF),"n"(BHI),"n"(SC)); } };
template<> struct WgSs<96> { template<int AOFF,int AHI,int BOFF,int BHI,int SC> static __device__ __forceinline__ void run(float* d,uint32_t alo,uint32_t blo){
 asm volatile("{.reg .b32 l,m; .reg .b64 da,db; add.u32 l,%48,%50; mov.b64 da,{l,%51}; add.u32 m,%49,%52; mov.b64 db,{m,%53}; wgmma.mma_async.sync.aligned.m64n96k16.f32.bf16.bf16 {%0,%1,%2,%3,%4,%5,%6,%7,%8,%9,%10,%11,%12,%13,%14,%15,%16,%17,%18,%19,%20,%21,%22,%23,%24,%25,%26,%27,%28,%29,%30,%31,%32,%33,%34,%35,%36,%37,%38,%39,%40,%41,%42,%43,%44,%45,%46,%47},da,db,%54,1,1,0,1;}"
 :"+f"(d[0]),"+f"(d[1]),"+f"(d[2]),"+f"(d[3]),"+f"(d[4]),"+f"(d[5]),"+f"(d[6]),"+f"(d[7]),"+f"(d[8]),"+f"(d[9]),"+f"(d[10]),"+f"(d[11]),"+f"(d[12]),"+f"(d[13]),"+f"(d[14]),"+f"(d[15]),"+f"(d[16]),"+f"(d[17]),"+f"(d[18]),"+f"(d[19]),"+f"(d[20]),"+f"(d[21]),"+f"(d[22]),"+f"(d[23]),"+f"(d[24]),"+f"(d[25]),"+f"(d[26]),"+f"(d[27]),"+f"(d[28]),"+f"(d[29]),"+f"(d[30]),"+f"(d[31]),"+f"(d[32]),"+f"(d[33]),"+f"(d[34]),"+f"(d[35]),"+f"(d[36]),"+f"(d[37]),"+f"(d[38]),"+f"(d[39]),"+f"(d[40]),"+f"(d[41]),"+f"(d[42]),"+f"(d[43]),"+f"(d[44]),"+f"(d[45]),"+f"(d[46]),"+f"(d[47])
 :"r"(alo),"r"(blo),"n"(AOFF),"n"(AHI),"n"(BOFF),"n"(BHI),"n"(SC)); } };
template<> struct WgSs<104> { template<int AOFF,int AHI,int BOFF,int BHI,int SC> static __device__ __forceinline__ void run(float* d,uint32_t alo,uint32_t blo){
 asm volatile("{.reg .b32 l,m; .reg .b64 da,db; add.u32 l,%52,%54; mov.b64 da,{l,%55}; add.u32 m,%53,%56; mov.b64 db,{m,%57}; wgmma.mma_async.sync.aligned.m64n104k16.f32.bf16.bf16 {%0,%1,%2,%3,%4,%5,%6,%7,%8,%9,%10,%11,%12,%13,%14,%15,%16,%17,%18,%19,%20,%21,%22,%23,%24,%25,%26,%27,%28,%29,%30,%31,%32,%33,%34,%35,%36,%37,%38,%39,%40,%41,%42,%43,%44,%45,%46,%47,%48,%49,%50,%51},da,db,%58,1,1,0,1;}"
 :"+f"(d[0]),"+f"(d[1]),"+f"(d[2]),"+f"(d[3]),"+f"(d[4]),"+f"(d[5]),"+f"(d[6]),"+f"(d[7]),"+f"(d[8]),"+f"(d[9]),"+f"(d[10]),"+f"(d[11]),"+f"(d[12]),"+f"(d[13]),"+f"(d[14]),"+f"(d[15]),"+f"(d[16]),"+f"(d[17]),"+f"(d[18]),"+f"(d[19]),"+f"(d[20]),"+f"(d[21]),"+f"(d[22]),"+f"(d[23]),"+f"(d[24]),"+f"(d[25]),"+f"(d[26]),"+f"(d[27]),"+f"(d[28]),"+f"(d[29]),"+f"(d[30]),"+f"(d[31]),"+f"(d[32]),"+f"(d[33]),"+f"(d[34]),"+f"(d[35]),"+f"(d[36]),"+f"(d[37]),"+f"(d[38]),"+f"(d[39]),"+f"(d[40]),"+f"(d[41]),"+f"(d[42]),"+f"(d[43]),"+f"(d[44]),"+f"(d[45]),"+f"(d[46]),"+f"(d[47]),"+f"(d[48]),"+f"(d[49]),"+f"(d[50]),"+f"(d[51])
 :"r"(alo),"r"(blo),"n"(AOFF),"n"(AHI),"n"(BOFF),"n"(BHI),"n"(SC)); } };
template<> struct WgSs<112> { template<int AOFF,int AHI,int BOFF,int BHI,int SC> static __device__ __forceinline__ void run(float* d,uint32_t alo,uint32_t blo){
 asm volatile("{.reg .b32 l,m; .reg .b64 da,db; add.u32 l,%56,%58; mov.b64 da,{l,%59}; add.u32 m,%57,%60; mov.b64 db,{m,%61}; wgmma.mma_async.sync.aligned.m64n112k16.f32.bf16.bf16 {%0,%1,%2,%3,%4,%5,%6,%7,%8,%9,%10,%11,%12,%13,%14,%15,%16,%17,%18,%19,%20,%21,%22,%23,%24,%25,%26,%27,%28,%29,%30,%31,%32,%33,%34,%35,%36,%37,%38,%39,%40,%41,%42,%43,%44,%45,%46,%47,%48,%49,%50,%51,%52,%53,%54,%55},da,db,%62,1,1,0,1;}"
 :"+f"(d[0]),"+f"(d[1]),"+f"(d[2]),"+f"(d[3]),"+f"(d[4]),"+f"(d[5]),"+f"(d[6]),"+f"(d[7]),"+f"(d[8]),"+f"(d[9]),"+f"(d[10]),"+f"(d[11]),"+f"(d[12]),"+f"(d[13]),"+f"(d[14]),"+f"(d[15]),"+f"(d[16]),"+f"(d[17]),"+f"(d[18]),"+f"(d[19]),"+f"(d[20]),"+f"(d[21]),"+f"(d[22]),"+f"(d[23]),"+f"(d[24]),"+f"(d[25]),"+f"(d[26]),"+f"(d[27]),"+f"(d[28]),"+f"(d[29]),"+f"(d[30]),"+f"(d[31]),"+f"(d[32]),"+f"(d[33]),"+f"(d[34]),"+f"(d[35]),"+f"(d[36]),"+f"(d[37]),"+f"(d[38]),"+f"(d[39]),"+f"(d[40]),"+f"(d[41]),"+f"(d[42]),"+f"(d[43]),"+f"(d[44]),"+f"(d[45]),"+f"(d[46]),"+f"(d[47]),"+f"(d[48]),"+f"(d[49]),"+f"(d[50]),"+f"(d[51]),"+f"(d[52]),"+f"(d[53]),"+f"(d[54]),"+f"(d[55])
 :"r"(alo),"r"(blo),"n"(AOFF),"n"(AHI),"n"(BOFF),"n"(BHI),"n"(SC)); } };
template<> struct WgSs<120> { template<int AOFF,int AHI,int BOFF,int BHI,int SC> static __device__ __forceinline__ void run(float* d,uint32_t alo,uint32_t blo){
 asm volatile("{.reg .b32 l,m; .reg .b64 da,db; add.u32 l,%60,%62; mov.b64 da,{l,%63}; add.u32 m,%61,%64; mov.b64 db,{m,%65}; wgmma.mma_async.sync.aligned.m64n120k16.f32.bf16.bf16 {%0,%1,%2,%3,%4,%5,%6,%7,%8,%9,%10,%11,%12,%13,%14,%15,%16,%17,%18,%19,%20,%21,%22,%23,%24,%25,%26,%27,%28,%29,%30,%31,%32,%33,%34,%35,%36,%37,%38,%39,%40,%41,%42,%43,%44,%45,%46,%47,%48,%49,%50,%51,%52,%53,%54,%55,%56,%57,%58,%59},da,db,%66,1,1,0,1;}"
 :"+f"(d[0]),"+f"(d[1]),"+f"(d[2]),"+f"(d[3]),"+f"(d[4]),"+f"(d[5]),"+f"(d[6]),"+f"(d[7]),"+f"(d[8]),"+f"(d[9]),"+f"(d[10]),"+f"(d[11]),"+f"(d[12]),"+f"(d[13]),"+f"(d[14]),"+f"(d[15]),"+f"(d[16]),"+f"(d[17]),"+f"(d[18]),"+f"(d[19]),"+f"(d[20]),"+f"(d[21]),"+f"(d[22]),"+f"(d[23]),"+f"(d[24]),"+f"(d[25]),"+f"(d[26]),"+f"(d[27]),"+f"(d[28]),"+f"(d[29]),"+f"(d[30]),"+f"(d[31]),"+f"(d[32]),"+f"(d[33]),"+f"(d[34]),"+f"(d[35]),"+f"(d[36]),"+f"(d[37]),"+f"(d[38]),"+f"(d[39]),"+f"(d[40]),"+f"(d[41]),"+f"(d[42]),"+f"(d[43]),"+f"(d[44]),"+f"(d[45]),"+f"(d[46]),"+f"(d[47]),"+f"(d[48]),"+f"(d[49]),"+f"(d[50]),"+f"(d[51]),"+f"(d[52]),"+f"(d[53]),"+f"(d[54]),"+f"(d[55]),"+f"(d[56]),"+f"(d[57]),"+f"(d[58]),"+f"(d[59])
 :"r"(alo),"r"(blo),"n"(AOFF),"n"(AHI),"n"(BOFF),"n"(BHI),"n"(SC)); } };
template<> struct WgSs<128> { template<int AOFF,int AHI,int BOFF,int BHI,int SC> static __device__ __forceinline__ void run(float* d,uint32_t alo,uint32_t blo){
 asm volatile("{.reg .b32 l,m; .reg .b64 da,db; add.u32 l,%64,%66; mov.b64 da,{l,%67}; add.u32 m,%65,%68; mov.b64 db,{m,%69}; wgmma.mma_async.sync.aligned.m64n128k16.f32.bf16.bf16 {%0,%1,%2,%3,%4,%5,%6,%7,%8,%9,%10,%11,%12,%13,%14,%15,%16,%17,%18,%19,%20,%21,%22,%23,%24,%25,%26,%27,%28,%29,%30,%31,%32,%33,%34,%35,%36,%37,%38,%39,%40,%41,%42,%43,%44,%45,%46,%47,%48,%49,%50,%51,%52,%53,%54,%55,%56,%57,%58,%59,%60,%61,%62,%63},da,db,%70,1,1,0,1;}"
 :"+f"(d[0]),"+f"(d[1]),"+f"(d[2]),"+f"(d[3]),"+f"(d[4]),"+f"(d[5]),"+f"(d[6]),"+f"(d[7]),"+f"(d[8]),"+f"(d[9]),"+f"(d[10]),"+f"(d[11]),"+f"(d[12]),"+f"(d[13]),"+f"(d[14]),"+f"(d[15]),"+f"(d[16]),"+f"(d[17]),"+f"(d[18]),"+f"(d[19]),"+f"(d[20]),"+f"(d[21]),"+f"(d[22]),"+f"(d[23]),"+f"(d[24]),"+f"(d[25]),"+f"(d[26]),"+f"(d[27]),"+f"(d[28]),"+f"(d[29]),"+f"(d[30]),"+f"(d[31]),"+f"(d[32]),"+f"(d[33]),"+f"(d[34]),"+f"(d[35]),"+f"(d[36]),"+f"(d[37]),"+f"(d[38]),"+f"(d[39]),"+f"(d[40]),"+f"(d[41]),"+f"(d[42]),"+f"(d[43]),"+f"(d[44]),"+f"(d[45]),"+f"(d[46]),"+f"(d[47]),"+f"(d[48]),"+f"(d[49]),"+f"(d[50]),"+f"(d[51]),"+f"(d[52]),"+f"(d[53]),"+f"(d[54]),"+f"(d[55]),"+f"(d[56]),"+f"(d[57]),"+f"(d[58]),"+f"(d[59]),"+f"(d[60]),"+f"(d[61]),"+f"(d[62]),"+f"(d[63])
 :"r"(alo),"r"(blo),"n"(AOFF),"n"(AHI),"n"(BOFF),"n"(BHI),"n"(SC)); } };

__device__ __forceinline__ void wg_fence() { asm volatile("wgmma.fence.sync.aligned;" ::: "memory"); }
__device__ __forceinline__ void wg_commit() { asm volatile("wgmma.commit_group.sync.aligned;" ::: "memory"); }
template <int N> __device__ __forceinline__ void wg_wait() { asm volatile("wgmma.wait_group.sync.aligned %0;" ::"n"(N) : "memory"); }
template <int N> __device__ __forceinline__ void reg_fence(float* d) {
#pragma unroll
    for (int i = 0; i < N; i++) asm volatile("" : "+f"(d[i])::"memory");
}
__device__ __forceinline__ uint32_t desc_lo(uint32_t addr, uint32_t lbo) { return ((addr & 0x3FFFF) >> 4) | ((lbo >> 4) << 16); }
#define desc_hi(sbo, sw) (((sbo) >> 4) | ((sw) << 30))
__device__ __forceinline__ uint32_t smem_u32(const void* p) { return (uint32_t)__cvta_generic_to_shared(p); }
__device__ __forceinline__ bool elect() {
    uint32_t p;
    asm volatile("{.reg .pred P; elect.sync _|P, 0xffffffff; selp.u32 %0,1,0,P;}" : "=r"(p));
    return p;
}
__device__ __forceinline__ void mbar_init(uint32_t bar, uint32_t cnt) { asm volatile("mbarrier.init.shared::cta.b64 [%0], %1;" ::"r"(bar), "r"(cnt) : "memory"); }
__device__ __forceinline__ void mbar_expect(uint32_t bar, uint32_t bytes) { asm volatile("mbarrier.arrive.expect_tx.shared::cta.b64 _, [%0], %1;" ::"r"(bar), "r"(bytes) : "memory"); }
__device__ __forceinline__ bool mbar_try(uint32_t bar, uint32_t par) {
    uint32_t ok;
    asm volatile("{.reg .pred p; mbarrier.try_wait.parity.shared::cta.b64 p, [%1], %2; selp.u32 %0,1,0,p;}" : "=r"(ok) : "r"(bar), "r"(par) : "memory");
    return ok;
}
constexpr int SPIN_LIMIT = 1 << 18;
__device__ __forceinline__ void mbar_wait(uint32_t bar, uint32_t par) {
    if (mbar_try(bar, par)) return;
    int n = 0;
    while (!mbar_try(bar, par) && ++n < SPIN_LIMIT) {}
}
__device__ __forceinline__ void bulk_g2s(uint32_t dst, const void* src, uint32_t bytes, uint32_t bar) {
    asm volatile("cp.async.bulk.shared::cluster.global.mbarrier::complete_tx::bytes [%0], [%1], %2, [%3];" ::"r"(dst), "l"(src), "r"(bytes), "r"(bar) : "memory");
}
__device__ __forceinline__ void bulk_s2g(void* dst, uint32_t src, uint32_t bytes) {
    asm volatile("cp.async.bulk.global.shared::cta.bulk_group [%0], [%1], %2;" ::"l"(dst), "r"(src), "r"(bytes) : "memory");
}
__device__ __forceinline__ void bulk_prefetch(const void* src, uint32_t bytes) {
    asm volatile("cp.async.bulk.prefetch.L2.global [%0], %1;" ::"l"(src), "r"(bytes) : "memory");
}
__device__ __forceinline__ void tma2d(uint32_t dst, const CUtensorMap* m, int c0, int c1, uint32_t bar) {
    asm volatile("cp.async.bulk.tensor.2d.shared::cluster.global.mbarrier::complete_tx::bytes [%0], [%1, {%3, %4}], [%2];" ::"r"(dst), "l"(m), "r"(bar), "r"(c0), "r"(c1) : "memory");
}
__device__ __forceinline__ void tma2d_mc(uint32_t dst, const CUtensorMap* m, int c0, int c1, uint32_t bar) {
    asm volatile("cp.async.bulk.tensor.2d.shared::cluster.global.mbarrier::complete_tx::bytes.multicast::cluster [%0], [%1, {%3, %4}], [%2], %5;" ::"r"(dst), "l"(m), "r"(bar), "r"(c0), "r"(c1), "h"((uint16_t)3) : "memory");
}
__device__ __forceinline__ uint32_t mapa(uint32_t a, uint32_t rank) { uint32_t r; asm("mapa.shared::cluster.u32 %0, %1, %2;" : "=r"(r) : "r"(a), "r"(rank)); return r; }
__device__ __forceinline__ void mbar_arrive_cl(uint32_t bar) { asm volatile("mbarrier.arrive.shared::cluster.b64 _, [%0];" ::"r"(bar) : "memory"); }
__device__ __forceinline__ void prefetch_map(const CUtensorMap* m) { asm volatile("prefetch.tensormap [%0];" ::"l"(m) : "memory"); }
__device__ __forceinline__ void cpasync16(uint32_t dst, const void* src, uint32_t srcsz) {
    asm volatile("cp.async.cg.shared.global [%0], [%1], 16, %2;" ::"r"(dst), "l"(src), "r"(srcsz) : "memory");
}
__device__ __forceinline__ void bar_sync(int id, int n) { asm volatile("bar.sync %0, %1;" ::"r"(id), "r"(n) : "memory"); }
__device__ __forceinline__ void bar_arrive(int id, int n) { asm volatile("bar.arrive %0, %1;" ::"r"(id), "r"(n) : "memory"); }
__device__ __forceinline__ void fence_async_smem() { asm volatile("fence.proxy.async.shared::cta;" ::: "memory"); }
__device__ __forceinline__ void fence_async_global() { asm volatile("fence.proxy.async.global;" ::: "memory"); }
__device__ __forceinline__ void flag_release(int f) { asm volatile("red.release.gpu.global.add.u32 [%0], 1;" ::"l"(&g_flags[f * 32]) : "memory"); }
__device__ __forceinline__ void flag_wait(int f, unsigned target) {
    const unsigned* p = &g_flags[f * 32];
    unsigned v; int n = 0;
    do {
        asm volatile("ld.relaxed.gpu.global.u32 %0, [%1];" : "=r"(v) : "l"(p) : "memory");
    } while ((int)(v - target) < 0 && ++n < SPIN_LIMIT);
    asm volatile("fence.acquire.gpu;" ::: "memory");
}
__device__ __forceinline__ unsigned ld_flag(const unsigned* p) { unsigned v; asm volatile("ld.relaxed.gpu.global.u32 %0, [%1];" : "=r"(v) : "l"(p) : "memory"); return v; }
__device__ __forceinline__ void spin(unsigned n) { unsigned t0, t1; asm volatile("mov.u32 %0, %%clock;" : "=r"(t0)); do { asm volatile("mov.u32 %0, %%clock;" : "=r"(t1)); } while (t1 - t0 < n); }
__device__ __forceinline__ void flag_wait_fast(int f, unsigned target) {
    flag_wait(f, target);
}
__device__ __forceinline__ void flag_wait2(int f0, int f1, unsigned target) {
    const unsigned *p = &g_flags[f0 * 32], *q = &g_flags[f1 * 32];
    unsigned v, w; int n = 0;
    do { v = ld_flag(p); w = ld_flag(q); } while ((int)((v - target) | (w - target)) < 0 && ++n < SPIN_LIMIT);
    asm volatile("fence.acquire.gpu;" ::: "memory");
}
__device__ __forceinline__ uint32_t lds32(uint32_t a) { uint32_t v; asm volatile("ld.shared.u32 %0, [%1];" : "=r"(v) : "r"(a)); return v; }
__device__ __forceinline__ float2 lds64f(uint32_t a) { float2 v; asm volatile("ld.shared.v2.f32 {%0,%1}, [%2];" : "=f"(v.x), "=f"(v.y) : "r"(a)); return v; }
__device__ __forceinline__ uint2 lds64(uint32_t a) { uint2 v; asm volatile("ld.shared.v2.u32 {%0,%1}, [%2];" : "=r"(v.x), "=r"(v.y) : "r"(a)); return v; }
__device__ __forceinline__ void sts64f(uint32_t a, float2 v) { asm volatile("st.shared.v2.f32 [%0], {%1,%2};" ::"r"(a), "f"(v.x), "f"(v.y) : "memory"); }
__device__ __forceinline__ void sts32(uint32_t a, uint32_t v) { asm volatile("st.shared.u32 [%0], %1;" ::"r"(a), "r"(v) : "memory"); }
__device__ __forceinline__ void sts64(uint32_t a, uint32_t x, uint32_t y) { asm volatile("st.shared.v2.u32 [%0], {%1,%2};" ::"r"(a), "r"(x), "r"(y) : "memory"); }
__device__ __forceinline__ void sts16(uint32_t a, uint16_t v) { asm volatile("st.shared.u16 [%0], %1;" ::"r"(a), "h"(v) : "memory"); }
__device__ __forceinline__ uint4 lds128(uint32_t a) { uint4 v; asm volatile("ld.shared.v4.u32 {%0,%1,%2,%3}, [%4];" : "=r"(v.x), "=r"(v.y), "=r"(v.z), "=r"(v.w) : "r"(a)); return v; }
__device__ __forceinline__ void sts128(uint32_t a, uint4 v) { asm volatile("st.shared.v4.u32 [%0], {%1,%2,%3,%4};" ::"r"(a), "r"(v.x), "r"(v.y), "r"(v.z), "r"(v.w) : "memory"); }
__device__ __forceinline__ void sts128f(uint32_t a, float x, float y, float z, float w) { asm volatile("st.shared.v4.f32 [%0], {%1,%2,%3,%4};" ::"r"(a), "f"(x), "f"(y), "f"(z), "f"(w) : "memory"); }
__device__ __forceinline__ uint32_t prmt(uint32_t a, uint32_t b, uint32_t s) { uint32_t r; asm("prmt.b32 %0,%1,%2,%3;" : "=r"(r) : "r"(a), "r"(b), "r"(s)); return r; }
__device__ __forceinline__ uint32_t pack2(float lo, float hi) { uint32_t r; asm("cvt.rn.bf16x2.f32 %0, %1, %2;" : "=r"(r) : "f"(hi), "f"(lo)); return r; }
__device__ __forceinline__ float blo(uint32_t v) { return __uint_as_float(v << 16); }
__device__ __forceinline__ float bhi(uint32_t v) { return __uint_as_float(v & 0xffff0000u); }
__device__ __forceinline__ uint32_t bmul2(uint32_t a, uint32_t b) { uint32_t r; asm("mul.rn.bf16x2 %0,%1,%2;" : "=r"(r) : "r"(a), "r"(b)); return r; }
__device__ __forceinline__ uint32_t badd2(uint32_t a, uint32_t b) { uint32_t r; asm("add.rn.bf16x2 %0,%1,%2;" : "=r"(r) : "r"(a), "r"(b)); return r; }
__device__ __forceinline__ float rbf(float x) { return __bfloat162float(__float2bfloat16_rn(x)); }
__device__ __forceinline__ uint32_t ldcg32(const void* p) { uint32_t v; asm volatile("ld.global.cg.u32 %0, [%1];" : "=r"(v) : "l"(p) : "memory"); return v; }
__device__ __forceinline__ uint4 ldcg128(const void* p) { uint4 v; asm volatile("ld.global.cg.v4.u32 {%0,%1,%2,%3}, [%4];" : "=r"(v.x), "=r"(v.y), "=r"(v.z), "=r"(v.w) : "l"(p) : "memory"); return v; }
__device__ __forceinline__ void stg32_if(void* p, uint32_t v, int on) { asm volatile("{.reg .pred q; setp.ne.b32 q, %2, 0; @q st.global.u32 [%0], %1;}" ::"l"(p), "r"(v), "r"(on) : "memory"); }
__device__ __forceinline__ uint2 ldcg64(const void* p) { uint2 v; asm volatile("ld.global.cg.v2.u32 {%0,%1}, [%2];" : "=r"(v.x), "=r"(v.y) : "l"(p) : "memory"); return v; }
__device__ __forceinline__ float gelu_h(float h) {
    float u = h * fmaf(h * h, 8.0f * 0.044715f * 0.7978845608028654f, 2.0f * 0.7978845608028654f);
    float th;
    asm("tanh.approx.f32 %0, %1;" : "=f"(th) : "f"(u));
    return fmaf(h, th, h);
}
__device__ __forceinline__ float gelu(float x) { return gelu_h(0.5f * x); }
__device__ __forceinline__ float half_rstd(float sum, float sq) {
    float mean = sum * (1.0f / D_), inv;
    asm("rsqrt.approx.ftz.f32 %0, %1;" : "=f"(inv) : "f"(fmaxf(fmaf(-mean, mean, fmaf(sq, 1.0f / D_, 1e-5f)), 1e-5f)));
    return 0.5f * inv;
}
__device__ __forceinline__ uint32_t bsub2(uint32_t a, uint32_t b) { uint32_t r; asm("sub.rn.bf16x2 %0,%1,%2;" : "=r"(r) : "r"(a), "r"(b)); return r; }
__device__ __forceinline__ uint32_t bfma2(uint32_t a, uint32_t b, uint32_t c) { uint32_t r; asm("fma.rn.bf16x2 %0,%1,%2,%3;" : "=r"(r) : "r"(a), "r"(b), "r"(c)); return r; }
__device__ __forceinline__ uint32_t gelu2_h(uint32_t h) {
    uint32_t u = bmul2(h, bfma2(bmul2(h, h), 0x3e923e92u, 0x3fcc3fccu)), th;
    asm("tanh.approx.bf16x2 %0, %1;" : "=r"(th) : "r"(u));
    return bfma2(h, th, h);
}
__device__ __forceinline__ void mma_stat(float* d, uint32_t u, uint32_t v) {
    asm("mma.sync.aligned.m16n8k16.row.col.f32.bf16.bf16.f32 {%0,%1,%2,%3},{%4,%6,%5,%6},{%4,%5},{%0,%1,%2,%3};"
        : "+f"(d[0]), "+f"(d[1]), "+f"(d[2]), "+f"(d[3]) : "r"(u), "r"(v), "r"(0x3f803f80u));
}
__device__ __forceinline__ void mma_sel(float* d, uint2 u, uint2 v, uint32_t b0, uint32_t b1) {
    asm("mma.sync.aligned.m16n8k16.row.col.f32.bf16.bf16.f32 {%0,%1,%2,%3},{%4,%5,%6,%7},{%8,%9},{%0,%1,%2,%3};"
        : "+f"(d[0]), "+f"(d[1]), "+f"(d[2]), "+f"(d[3]) : "r"(u.x), "r"(v.x), "r"(u.y), "r"(v.y), "r"(b0), "r"(b1));
}
__device__ __forceinline__ void conv_sum4(float* d, uint32_t a, bool last, int g, int c) {
    uint2 v0 = lds64(a), v1 = lds64(a + 8), v2 = lds64(a + 16), v3 = lds64(a + 24);
    if (last) {
        if (c > 2) v1 = make_uint2(0, 0);
        if (c > 1) v2 = make_uint2(0, 0);
        if (c > 0) v3 = make_uint2(0, 0);
    }
    const uint32_t one = (g & 1) ? 0x3f800000u : 0x00003f80u;
    mma_sel(d, v0, v1, (g >> 1) == 0 ? one : 0u, (g >> 1) == 1 ? one : 0u);
    mma_sel(d, v2, v3, (g >> 1) == 2 ? one : 0u, (g >> 1) == 3 ? one : 0u);
}
__device__ __forceinline__ uint3 row_stats(const uint32_t* v, int lane) {
    float s = 0.f, q = 0.f, s_ = 0.f, q_ = 0.f;
#pragma unroll
    for (int i = 0; i < 10; i++) { float a = blo(v[i]), b = bhi(v[i]); s += a; s_ += b; q = fmaf(a, a, q); q_ = fmaf(b, b, q_); }
    s += s_; q += q_;
    {
        float t = __shfl_xor_sync(0xffffffffu, (lane & 16) ? s : q, 16);
        t += (lane & 16) ? q : s;
#pragma unroll
        for (int m = 8; m; m >>= 1) t += __shfl_xor_sync(0xffffffffu, t, m);
        float o = __shfl_xor_sync(0xffffffffu, t, 16);
        s = (lane & 16) ? o : t; q = (lane & 16) ? t : o;
    }
    float mean = s * (1.0f / D_), inv;
    asm("rsqrt.approx.ftz.f32 %0, %1;" : "=f"(inv) : "f"(fmaxf(fmaf(-mean, mean, fmaf(q, 1.0f / D_, 1e-5f)), 1e-5f)));
    uint3 r;
    r.x = pack2(mean, mean);
    r.y = pack2(inv, inv);
    inv -= blo(r.y);
    r.z = pack2(inv, inv);
    return r;
}
__device__ __forceinline__ uint32_t ln_apply(uint32_t x, uint32_t m, uint32_t hi, uint32_t lo) {
    uint32_t xc = bsub2(x, m);
    return bmul2(xc, hi);
}

struct AFrag { uint32_t m, a, b, c, d; };
__device__ __forceinline__ AFrag ldA(uint32_t a) { AFrag f; f.m = lds32(a - 16); f.a = lds32(a); f.b = lds32(a + 16); f.c = lds32(a + 32); f.d = lds32(a + 48); return f; }
template <int N, int M> __device__ __forceinline__ void conv_pair(float* d, const AFrag& f, uint32_t descU) {
    WgRs<N>::template run<8 * M, desc_hi(128, 0), M ? 1 : 0>(d, f.a, f.b, f.m, f.a, descU);
    WgRs<N>::template run<8 * M + 1, desc_hi(128, 0), 1>(d, f.c, f.d, f.b, f.c, descU);
}
template <int Q> __device__ __forceinline__ void conv_put(float* d, uint32_t r0) {
    sts64(r0 + Q * 32, pack2(d[4 * Q + 1], d[4 * Q + 3]), pack2(d[4 * Q], d[4 * Q + 2]));
}
template <int M> __device__ __forceinline__ void conv_two(float* d, AFrag f0, AFrag f1, uint32_t kaddr, uint32_t descU, uint32_t r0, bool handoff) {
    constexpr int N = M < 14 ? 128 - 8 * M : 32;
    wg_fence();
    conv_pair<N, M>(d, f0, descU);
    wg_commit();
    if constexpr (M > 0) f1 = ldA(kaddr + 256 * (M + 1));
    wg_fence();
    conv_pair<N, M + 1>(d, f1, descU);
    wg_commit();
    if (STAG && M == STAG && handoff) bar_arrive(12, 256);
    if constexpr (M < 14) {
        if constexpr (M > 0) { conv_put<17 - M>(d, r0); conv_put<16 - M>(d, r0); }
        wg_wait<1>();
        f0 = ldA(kaddr + 256 * (M + 2));
        if constexpr (M < 12) wg_wait<0>();
        conv_two<M + 2>(d, f0, f1, kaddr, descU, r0, handoff);
    } else {
        wg_wait<0>();
        conv_put<3>(d, r0); conv_put<2>(d, r0); conv_put<1>(d, r0); conv_put<0>(d, r0);
    }
}
template <int N, bool ASWZ, int SC0>
__device__ __forceinline__ void gemm_issue(float* acc, uint32_t bars, int sa, int pa, int sw, int pw, uint32_t da0, uint32_t db0) {
    mbar_wait(bars + (BAR_FB + sw) * 8, pw);
    mbar_wait(bars + (BAR_FA + sa) * 8, pa);
    const uint32_t da = da0 + sa * (SLOT >> 4), db = db0 + sw * (SLOT >> 4);
    constexpr int AK = ASWZ ? 2 : 256, AH = ASWZ ? desc_hi(1024, 1) : desc_hi(128, 0), BH = desc_hi(1024, 1);
    wg_fence();
    WgSs<N>::template run<0, AH, 0, BH, SC0>(acc, da, db);
    WgSs<N>::template run<AK, AH, 128, BH, 1>(acc, da, db);
    WgSs<N>::template run<2 * AK, AH, 256, BH, 1>(acc, da, db);
    WgSs<N>::template run<3 * AK, AH, 384, BH, 1>(acc, da, db);
    wg_commit();
}
template <int N, bool ASWZ, int NKB, int RELB, bool ZERO, int TAIL = 0>
__device__ __forceinline__ void gemm_loop(float* acc, uint32_t sb, int half, int ia0, int ib0, int rela, int wait_bar, int order_bar, int tsid) {
    int sa = ia0 % NA, pa = (ia0 / NA) & 1, sw = ib0 % NB, pw = (ib0 / NB) & 1;
    const uint32_t bars = sb + SM_BAR;
    const int t = threadIdx.x & 127;
    uint32_t ebar = mapa(bars + (t < 2 ? BAR_EB : BAR_EA) * 8, (t < 2 && lds32(sb + SM_GV + 516)) ? t : blockIdx.x & 1);
    const int nrel = t < 2 ? RELB : t == 2 ? rela : 0;
    const uint32_t da0 = ASWZ ? desc_lo(sb + SM_RA + half * 8192, 16) : desc_lo(sb + SM_RA + half * 1024, 2048), db0 = desc_lo(sb + SM_RB, 8192);
    asm volatile("" : "+r"(ebar));
    if (wait_bar) bar_sync(wait_bar, 512);
    gemm_issue<N, ASWZ, ZERO ? 0 : 1>(acc, bars, sa, pa, sw, pw, da0, db0);
    if ((threadIdx.x & 255) == 0) TS(tsid);
#pragma unroll 1
    for (int kb = 1; kb < NKB - TAIL; kb++) {
        const int prev = t < 2 ? sw : sa;
        if (++sa == NA) { sa = 0; pa ^= 1; }
        if (++sw == NB) { sw = 0; pw ^= 1; }
        gemm_issue<N, ASWZ, 1>(acc, bars, sa, pa, sw, pw, da0, db0);
        if (order_bar && kb == NKB - 1) bar_arrive(order_bar, 512);
        wg_wait<1>();
        if (kb <= nrel) mbar_arrive_cl(ebar + prev * 8);
    }
    if constexpr (TAIL > 0) {
        int rel = t < 2 ? sw : sa;
        uint32_t da[TAIL], db[TAIL];
#pragma unroll
        for (int i = 0; i < TAIL; i++) {
            if (++sa == NA) { sa = 0; pa ^= 1; }
            if (++sw == NB) { sw = 0; pw ^= 1; }
            mbar_wait(bars + (BAR_FB + sw) * 8, pw);
            mbar_wait(bars + (BAR_FA + sa) * 8, pa);
            da[i] = da0 + sa * (SLOT >> 4); db[i] = db0 + sw * (SLOT >> 4);
        }
        if (half) bar_sync(7, 256);
        constexpr int AK = ASWZ ? 2 : 256, AH = ASWZ ? desc_hi(1024, 1) : desc_hi(128, 0), BH = desc_hi(1024, 1);
        wg_fence();
#pragma unroll
        for (int i = 0; i < TAIL; i++) {
            WgSs<N>::template run<0, AH, 0, BH, 1>(acc, da[i], db[i]);
            WgSs<N>::template run<AK, AH, 128, BH, 1>(acc, da[i], db[i]);
            if (i == TAIL - 1 && !half) bar_arrive(7, 256);
            WgSs<N>::template run<2 * AK, AH, 256, BH, 1>(acc, da[i], db[i]);
            WgSs<N>::template run<3 * AK, AH, 384, BH, 1>(acc, da[i], db[i]);
        }
        wg_commit();
        wg_wait<0>();
        if (nrel == NKB) {
#pragma unroll
            for (int i = 0; i <= TAIL; i++) { mbar_arrive_cl(ebar + rel * 8); if (++rel == 6) rel = 0; }
        }
    } else {
        wg_wait<0>();
        if (nrel == NKB) mbar_arrive_cl(ebar + (t < 2 ? sw : sa) * 8);
    }
    reg_fence<N / 2>(acc);
    if ((threadIdx.x & 255) == (TAIL ? 128 : 0)) TS(tsid + 1);
}

template <int PART>
__device__ __forceinline__ void gemm3(uint32_t sb, int rb, int j, int half, int row, int c, unsigned ones) {
    constexpr int N = 64 + (PART ? RB3 : RA3), NQ = N / 8;
    constexpr int HO = PART ? HO_B : HO_A;
    float acc[N / 2];
    float2 cr[NQ];
    if (PART) {
        gemm_loop<N, false, 1, 1, true>(acc, sb, half, 20, 20, 0, 0, 0, 50);
        bar_arrive(9, 512);
    }
    mbar_wait(sb + SM_BAR + BAR_CS * 8, 0);
    const uint32_t csa = sb + SM_CS + PART * (256 + 4 * RA3) + 8 * c;
#pragma unroll
    for (int q = 0; q < NQ; q++) if (q < CSP) cr[q] = lds64f(csa + 32 * q);
    uint4 rp;
    if (PART) {
        mbar_wait(sb + SM_BAR + BAR_G * 8, 0);
        const float2* sp = &g_st[(rb * 8 + 2 * c) * 128 + row];
        const uint2 s0 = ldcg64(sp), s1 = ldcg64(sp + 128), s2 = ldcg64(sp + 8), s3 = ldcg64(sp + 136);
        float a0 = __uint_as_float(s0.x) + __uint_as_float(s1.x), b0 = __uint_as_float(s0.y) + __uint_as_float(s1.y);
        float a1 = __uint_as_float(s2.x) + __uint_as_float(s3.x), b1 = __uint_as_float(s2.y) + __uint_as_float(s3.y);
#pragma unroll
        for (int m = 1; m <= 2; m <<= 1) {
            a0 += __shfl_xor_sync(0xffffffffu, a0, m); b0 += __shfl_xor_sync(0xffffffffu, b0, m);
            a1 += __shfl_xor_sync(0xffffffffu, a1, m); b1 += __shfl_xor_sync(0xffffffffu, b1, m);
        }
        const float inv0 = half_rstd(a0, b0), inv1 = half_rstd(a1, b1);
        rp = make_uint4(PGELU ? pack2(inv0, inv0) : __float_as_uint(inv0), __float_as_uint(a0 * (-1.0f / D_)),
                        PGELU ? pack2(inv1, inv1) : __float_as_uint(inv1), __float_as_uint(a1 * (-1.0f / D_)));
        if (c == 0) sts128(sb + SM_RP + ((threadIdx.x & 255) >> 2) * 16, rp);
        bar_arrive(13, 512);
    }
    gemm_loop<N, false, 10 - PART, 10 - PART, !PART>(acc, sb, half, 20 + (10 - NA) * PART, 21 + 10 * PART, PART ? 9 : 10 - NA, 9 + PART, HO < 0 ? 10 + PART : 0, 46 + 2 * PART);
    if (!PART) {
        bar_sync(13, 512);
        rp = lds128(sb + SM_RP + ((threadIdx.x & 255) >> 2) * 16);
    }
    const float nb0 = __uint_as_float(rp.y), nb1 = __uint_as_float(rp.w);
    const uint32_t own = sb + SM_RA + ((39 - NA) % NA) * SLOT + row * 16 + c * 4;
    if (PART && OWNG) mbar_wait(sb + SM_BAR + (BAR_FA + (39 - NA) % NA) * 8, ((39 - NA) / NA) & 1);
    uint32_t* dst = reinterpret_cast<uint32_t*>(g_g) + (rb * 216 + HB0 / 8 * PART + 8 * j) * 512 + row * 4 + c;
    auto act = [&](int q, int r) {
        const float nb = r ? nb1 : nb0;
        const uint32_t inv = r ? rp.z : rp.x;
        const float t0 = fmaf(nb, cr[q].x, acc[4 * q + 2 * r]), t1 = fmaf(nb, cr[q].y, acc[4 * q + 2 * r + 1]);
        return gelu2_h(bmul2(pack2(t0, t1), inv));
    };
    uint32_t* dst1 = dst + (56 - (16 - NQ) * j) * 512;
#pragma unroll
    for (int k = 0; k < NQ; k += CH3) {
        if (k == HO) bar_arrive(10 + PART, 512);
        CHUNK(k) {
#pragma unroll
            for (int q = k; q < k + CH3 && q < NQ; q++) {
                if (q + CSP < NQ) cr[q + CSP] = lds64f(csa + 32 * (q + CSP));
                const uint32_t u = act(q, 0), v = act(q, 1);
                (q < 8 ? dst : dst1)[q * 512] = u;
                (q < 8 ? dst : dst1)[q * 512 + 32] = v;
                if (PART && OWNG && q < 8) { sts32(own + q * 2048, u); sts32(own + q * 2048 + 128, v); }
            }
            if (PART && OWNG && k < 8 && k + CH3 >= 8) fence_async_smem();
        }
    }
    bar_arrive(1 + PART, 288);
    if (HO >= NQ) bar_arrive(10 + PART, 512);
}

template <int NS, int BASE, int BF, int BE> struct Ring {
    uint32_t sb, st, ph;
    __device__ __forceinline__ uint32_t acquire(uint32_t bytes) {
        mbar_wait(sb + SM_BAR + BE * 8 + st * 8, ph);
        uint32_t fb = sb + SM_BAR + BF * 8 + st * 8;
        mbar_expect(fb, bytes);
        return fb;
    }
    __device__ __forceinline__ uint32_t slot() { return sb + BASE + st * SLOT; }
    __device__ __forceinline__ void next() { if (++st == NS) { st = 0; ph ^= 1; } }
    __device__ __forceinline__ void run2d(const CUtensorMap* m, int c1) {
#pragma unroll 1
        for (int c0 = 64; c0 < D_; c0 += 64) {
            uint32_t fb = acquire(SLOT);
            tma2d(slot(), m, c0, c1, fb);
            next();
        }
    }
    static __device__ __forceinline__ int korder(int i, int own) { return i == 0 ? own : i > own ? i : i - 1; }
    __device__ __forceinline__ void runw(bool paired, int rk, const CUtensorMap* ma, const CUtensorMap* mb, int ca, int cb, int i0, int i1, int own, uint32_t bytes, int gate_at, uint32_t gate) {
        if (paired) {
            const CUtensorMap* m = rk ? mb : ma;
            const int c0 = rk ? cb : ca;
#pragma unroll 1
            for (int i = i0; i < i1; i++) {
                const int c1 = korder(i, own) * 64;
                if (i == gate_at) mbar_wait(gate, 0);
                uint32_t fb = acquire(bytes);
                tma2d_mc(slot() + 8192 * rk, m, c0, c1, fb);
                next();
            }
        } else {
#pragma unroll 1
            for (int i = i0; i < i1; i++) {
                const int c1 = korder(i, own) * 64;
                uint32_t fb = acquire(bytes);
                tma2d(slot(), ma, ca, c1, fb);
                tma2d(slot() + 8192, mb, cb, c1, fb);
                next();
            }
        }
    }
    __device__ __forceinline__ void run1d(const char* src, int i0, int i1, int own) {
#pragma unroll 1
        for (int i = i0; i < i1; i++) {
            const char* s = src + korder(i, own) * SLOT;
            uint32_t fb = acquire(SLOT);
            bulk_g2s(slot(), s, SLOT, fb);
            next();
        }
    }
};

__global__ void __cluster_dims__(2, 1, 1) __launch_bounds__(NTHREADS, 1) fused_kernel(const Params p, const __grid_constant__ Maps maps) {
    extern __shared__ __align__(1024) unsigned char smem_raw[];
    const uint32_t sb = (smem_u32(smem_raw) + 1023u) & ~1023u;
#pragma unroll
    for (int i = 0; i < SEED; i++) asm volatile("{.reg .b32 t; mov.u32 t, %laneid;}");
    const uint32_t bars = sb + SM_BAR;
    const int tid = threadIdx.x, lane = tid & 31;
    unsigned smid;
    asm volatile("mov.u32 %0, %%smid;" : "=r"(smid));
    const bool spare = (smid >> 2) == 30;
    const int cta = smid < 120 ? smid : smid - 4;
    const int pg = cta >> 4, pi = cta & 15;
    const int hb = tid >= 320;
    if (!spare) {
        const unsigned t = tid - 320 * hb, r32 = t / 10u, cc = t - r32 * 10u, row = r32 + 64 * hb;
        const unsigned go = (unsigned)(pi * 128 * 1280 + pg * 160) + row * 1280u + cc * 16u;
        const uint32_t so = sb + (row >> 4) * 32u + row * 160u + cc * 16u;
        const char* kb = (const char*)p.k + go;
        const char* vb = (const char*)p.v + go;
        if (hb) {
            if (tid >= 640 - NBARS) {
                const int i = 639 - tid;
                mbar_init(bars + i * 8, (i >= BAR_EB && i < BAR_K) ? 4 : ((i >= BAR_EA && i < BAR_EB) || i == BAR_XY) ? 2 : 1);
                asm volatile("fence.mbarrier_init.release.cluster;" ::: "memory");
            }
            bar_arrive(14, 640);
            if (B_DELAY) spin(B_DELAY);
        }
        cpasync16(so + SM_PK + 2592, kb, 16);
        cpasync16(so + SM_PV, vb, 16);
        cpasync16(so + SM_PK + 3 * 2592, kb + 32 * 1280, 16);
        cpasync16(so + SM_PV + 2 * 2592, vb + 32 * 1280, 16);
        if (tid < 30) cpasync16(so + SM_PK + 13 * 160, pi ? kb - 3 * 1280 : kb, pi ? 16 : 0);
        asm volatile("cp.async.commit_group;" ::: "memory");
    }
    const int warp = __shfl_sync(0xffffffffu, tid >> 5, 0);
    const int wg = warp >> 2, wq = warp & 3;
    unsigned ep0 = 0;
    if (wg == 4 || spare) ep0 = *(volatile unsigned*)&g_epoch[smid];
#define ep1 (ep0 + 1)

    if (spare) {
        const int sp = smid & 3;
        if (tid == 32) { sts32(sb + SM_GV + 512, smid); asm volatile("fence.release.sync_restrict::shared::cta.cluster;" ::: "memory"); }
        asm volatile("barrier.cluster.arrive.relaxed.aligned;" ::: "memory");
        asm volatile("barrier.cluster.wait.aligned;" ::: "memory");
        if (tid == 0) {
            for (int i = 0; i < 4; i++) mbar_init(bars + i * 8, 1);
            asm volatile("fence.mbarrier_init.release.cluster;" ::: "memory");
        }
        if (warp == 0) { if (lane < 8) flag_wait(FL_P + lane, ep1 * 16); __syncwarp(); }
        __syncthreads();
        const int cq = tid % 54, rg = tid / 54;
        float a[8];
#pragma unroll
        for (int i = 0; i < 8; i++) a[i] = 0.f;
#pragma unroll 1
        for (int it = -4; it < 10; it++) {
            const uint32_t st = sb + (it & 3) * 55296, fb = bars + (it & 3) * 8;
            if (it >= 0) {
                mbar_wait(fb, (it >> 2) & 1);
                if (tid < 432) {
#pragma unroll
                    for (int i = 0; i < 8; i++) {
                        uint4 w = lds128(st + (cq >= 27 ? 27648 - 432 : 0) + (rg * 8 + i) * 432 + cq * 16);
                        a[0] += blo(w.x); a[1] += bhi(w.x); a[2] += blo(w.y); a[3] += bhi(w.y);
                        a[4] += blo(w.z); a[5] += bhi(w.z); a[6] += blo(w.w); a[7] += bhi(w.w);
                    }
                }
                __syncthreads();
            }
            if (it < 6 && warp == 19 && elect()) {
                mbar_expect(fb, 55296);
                tma2d(st, &maps.w3s, sp * 432, (it + 4) * 64, fb);
                tma2d(st + 27648, &maps.w3s, sp * 432 + 216, (it + 4) * 64, fb);
            }
        }
        if (tid < 432) {
            sts128f(sb + rg * 1728 + cq * 32, a[0], a[1], a[2], a[3]);
            sts128f(sb + rg * 1728 + cq * 32 + 16, a[4], a[5], a[6], a[7]);
        }
        __syncthreads();
        if (tid < 432) {
            float s = 0.f;
#pragma unroll
            for (int i = 0; i < 8; i++) s += __uint_as_float(lds32(sb + i * 1728 + tid * 4));
            g_cs[sp * 432 + tid] = s;
        }
        __syncthreads();
        if (tid == 0) { flag_release(FL_CS); g_epoch[smid] = ep1; TS(0); }
        if (warp == 0) TSFLUSH();
        return;
    }

    int gpc, idx;
    if (smid < 64) { gpc = (smid & 15) >> 1; idx = (smid >> 4) * 2 + (smid & 1); }
    else if (smid < 120) { int t = smid - 64; gpc = 1 + (t % 14) / 2; idx = 8 + (t / 14) * 2 + (smid & 1); }
    else { gpc = 0; idx = 8 + (smid - 124); }
    const int rb = 2 * gpc + (idx & 1), j = idx >> 1;
    const int g = lane >> 2, c = lane & 3;
    const int cm = 160 * (j >> 1) + 64 * (j & 1) + ((j & 2) ? 32 : 0), cr = 160 * (j >> 1) + 16 * (j & 1) + ((j & 2) ? 0 : 128);

    {
        if (warp == 5) TSW(61);
        const int w10 = warp - 10 * hb, h = w10 >= 5;
        const int pr = (w10 - 5 * h) * 8 + (lane >> 2), blk = 4 * hb + (lane & 3);
        const int ch = 80 * pg + 2 * pr;
        const uint4 sw = __ldg(reinterpret_cast<const uint4*>(p.shift + ch * 4));
        uint32_t dv = 0;
        if (warp == 9 && lane < 5) dv = __bfloat16_as_ushort(p.ssmD[cta * 5 + lane]);
        if (tid == 512) { sts32(sb + SM_GV + 512, smid); asm volatile("fence.release.sync_restrict::shared::cta.cluster;" ::: "memory"); }
        asm volatile("barrier.cluster.arrive.relaxed.aligned;" ::: "memory");
        if (warp == 11 && lane < 13) prefetch_map(&maps.hn + lane);
        if (wg < 4) {
            const int t = tid & 127, cc = (wg == 3 && t >= 64) ? 4 : wg;
            if (t < 64 || wg == 3) sts128(sb + sm_u(cc) + ((t >> 5) & 1) * U_PLANE + 2048 + lane * 16, make_uint4(0, 0, 0, 0));
            if ((t & 63) < 4 && (t < 64 || wg == 3)) sts128(sb + sm_k(cc) + ((t >> 1) & 1) * 4160 + (t & 1) * 16, make_uint4(0, 0, 0, 0));
        }
        if (warp == 9 && lane < 5) sts32(sb + SM_GV + 520 + lane * 4, dv << 16);
        asm volatile("cp.async.wait_group 0;" ::: "memory");
        if (!hb) bar_arrive(12, 640);
        bar_sync(hb ? 12 : 14, 640);
        if (warp == 9) {
            if (SSM_DELAY) spin(SSM_DELAY);
            if (elect()) {
#pragma unroll
                for (int i = 0; i < SSM_N; i++) {
                    mbar_expect(bars + (BAR_K + i) * 8, 4096);
                    bulk_g2s(sb + sm_k(i) + 32, p.ssmk + (size_t)(cta * 5 + i) * S_, 4096, bars + (BAR_K + i) * 8);
                }
            }
        }
        const uint32_t w0 = prmt(sw.x, sw.z, 0x5410), w1 = prmt(sw.x, sw.z, 0x7632), w2 = prmt(sw.y, sw.w, 0x5410), w3 = prmt(sw.y, sw.w, 0x7632);
        const uint32_t ka = sb + SM_PK + 2592 + blk * 2592 + h * 1280 + pr * 4;
        const uint32_t va = sb + SM_PV + blk * 2592 + h * 1280 + pr * 4;
        uint32_t kk[11], kv[8];
#pragma unroll
        for (int i = 0; i < 11; i++) kk[i] = lds32(ka + (i - 3) * 160 - ((i < 3 && h == 0) ? 32 : 0));
#pragma unroll
        for (int i = 0; i < 8; i++) {
            uint32_t t = badd2(badd2(badd2(bmul2(kk[i], w3), bmul2(kk[i + 1], w2)), bmul2(kk[i + 2], w1)), bmul2(kk[i + 3], w0));
            kv[i] = bmul2(t, lds32(va + i * 160));
        }
        uint4 o0, o1;
        o0.x = prmt(kv[1], kv[0], 0x5410); o0.y = prmt(kv[3], kv[2], 0x5410); o0.z = prmt(kv[5], kv[4], 0x5410); o0.w = prmt(kv[7], kv[6], 0x5410);
        o1.x = prmt(kv[1], kv[0], 0x7632); o1.y = prmt(kv[3], kv[2], 0x7632); o1.z = prmt(kv[5], kv[4], 0x7632); o1.w = prmt(kv[7], kv[6], 0x7632);
        uint4* dst = reinterpret_cast<uint4*>(g_kvT) + ch * 256 + h * 128 + (127 - (8 * pi + blk));
        dst[0] = o0;
        dst[256] = o1;
    }

    const int rho = 8 * rb + j;

    if (wg == 4) {
        asm volatile("setmaxnreg.dec.sync.aligned.u32 32;");
        if (wq == 0) {
            bar_sync(13, 640);
            TSW(39);
            if (lane == 0) flag_release(FL_P + pg);
            __syncwarp();
            TSW(2);
            if (lane < 5) mbar_expect(bars + (BAR_U + lane) * 8, 4096);
            flag_wait_fast(FL_P + pg, ep1 * 16);
            fence_async_global();
            TSW(3);
            if (elect()) {
#pragma unroll
                for (int i = 0; i < 5; i++) {
                    const char* us = (const char*)g_kvT + (size_t)(cta * 5 + i) * 4096;
                    bulk_g2s(sb + sm_u(i), us, 2048, bars + (BAR_U + i) * 8);
                    bulk_g2s(sb + sm_u(i) + U_PLANE, us + 2048, 2048, bars + (BAR_U + i) * 8);
                }
            }
            __syncwarp();
            if (elect()) {
#pragma unroll
                for (int i = SSM_N; i < 5; i++) {
                    mbar_expect(bars + (BAR_K + i) * 8, 4096);
                    bulk_g2s(sb + sm_k(i) + 32, p.ssmk + (size_t)(cta * 5 + i) * S_, 4096, bars + (BAR_K + i) * 8);
                }
                if (cta < 120) {
                    mbar_expect(bars + BAR_WM * 8, 40960);
#pragma unroll
                    for (int i = 0; i < 5; i++) tma2d(sb + SM_WM + i * 8192, &maps.wm, cta * 32, i * 128, bars + BAR_WM * 8);
                }
                bulk_prefetch((const char*)p.q + cta * 20480, 20480);
                bulk_prefetch((const char*)p.w1 + cta * 6400, 6400);
                bulk_prefetch((const char*)p.w2 + cta * 6400, 6400);
            }
            __syncwarp();
        } else {
            bar_arrive(13, 640);
        }
        asm volatile("barrier.cluster.wait.aligned;" ::: "memory");
        uint32_t peer;
        asm volatile("ld.shared::cluster.u32 %0, [%1];" : "=r"(peer) : "r"(mapa(sb + SM_GV + 512, (blockIdx.x & 1) ^ 1)) : "memory");
        const bool paired = peer == (smid ^ 1);
        if (tid == 639) sts32(sb + SM_GV + 516, paired);
        if (cta < 120) {
            float d[4];
            if (tid < 592) {
                const int t = tid - 512;
                mbar_wait(bars + BAR_U * 8, 0);
                uint4 cv = __ldg(reinterpret_cast<const uint4*>(p.c) + t);
                auto silu2 = [](uint32_t v) { float a = blo(v), b = bhi(v); return pack2(__fdividef(a, 1.0f + __expf(-a)), __fdividef(b, 1.0f + __expf(-b))); };
                sts128(sb + SM_Y + (t % 40) * 32 + (t / 40) * 16, make_uint4(silu2(cv.x), silu2(cv.y), silu2(cv.z), silu2(cv.w)));
                fence_async_smem();
            }
            bar_sync(5, 128);
            mbar_wait(bars + BAR_WM * 8, 0);
            if (wq == 3) TSW(56);
            const uint32_t da = desc_lo(sb + SM_WM, 20480), db = desc_lo(sb + SM_Y, 32);
            wg_fence();
#pragma unroll
            for (int k = 0; k < 20; k++)
                asm volatile("{.reg .pred p; .reg .b32 l,m; .reg .b64 da,db; setp.ne.b32 p,%10,0; add.u32 l,%4,%6; mov.b64 da,{l,%8}; add.u32 m,%5,%7; mov.b64 db,{m,%9};"
                             " wgmma.mma_async.sync.aligned.m64n8k16.f32.bf16.bf16 {%0,%1,%2,%3},da,db,p,1,1,1,0;}"
                             : "+f"(d[0]), "+f"(d[1]), "+f"(d[2]), "+f"(d[3])
                             : "r"(da), "r"(db), "r"(64 * k), "r"(4 * k), "n"(desc_hi(512, 2u)), "n"(desc_hi(128, 0)), "r"(k));
            wg_commit();
            wg_wait<0>();
            reg_fence<4>(d);
            if (c == 0) {
                sts32(sb + SM_GV + (16 * wq + g) * 4, __float_as_uint(wq < 2 ? d[0] : d[1]));
                sts32(sb + SM_GV + (16 * wq + g + 8) * 4, __float_as_uint(wq < 2 ? d[2] : d[3]));
            }
            bar_sync(5, 128);
            if (wq == 2) {
                g_mod[cta * 32 + lane] = __float2bfloat16_rn(__uint_as_float(lds32(sb + SM_GV + lane * 4)) + __uint_as_float(lds32(sb + SM_GV + 128 + lane * 4)));
                __syncwarp();
                if (lane == 0) flag_release(FL_M);
                __syncwarp();
                TSW(4);
                if (XAFTER) bar_arrive(5, 64);
            }
            if (XAFTER && wq == 0) bar_sync(5, 64);
        }
        if (wq == 2) {
            flag_wait(FL_M, ep1 * 120);
            fence_async_global();
            if (elect()) {
                mbar_expect(bars + BAR_M * 8, 7680);
                bulk_g2s(sb + SM_MOD, g_mod, 7680, bars + BAR_M * 8);
            }
            __syncwarp();
            TSW(60);
            bar_sync(8, 544);  if (lane == 0) { flag_release(FL_R + rb); TS(23); }  __syncwarp();
            bar_sync(15, 288); if (lane == 0) { flag_release(FL_B1 + rb); TS(27); } __syncwarp();
            bar_sync(6, 288);  if (lane == 0) { flag_release(FL_B2 + rb); TS(31); } __syncwarp();
#pragma unroll 1
            for (int i = 0; i < 3; i++) { bar_sync(i ? i : 8, 288); if (lane == 0) { TS(53 + (i + 2) % 3); flag_release(FL_G + 16 * i + rb); TS(57 + (i + 2) % 3); } __syncwarp(); }
            if (lane == 0) g_epoch[smid] = ep1;
            return;
        }
        if (wq == 1) {
            bar_sync(9, 288);
            if (lane < 4 * NB) mbar_arrive_cl(mapa(bars + (BAR_EB + (lane >> 2)) * 8, paired ? lane & 1 : blockIdx.x & 1));
        }
        if (wq == 3) {
            bar_sync(7, 544);
            if (lane == 0) { flag_release(FL_C); TS(20); }
            __syncwarp();
            if (lane < 2) mbar_expect(bars + (lane ? BAR_Y2 : BAR_Y) * 8, lane ? 8192 : 12288);
            flag_wait_fast(FL_C, ep1 * 128);
            fence_async_global();
            TSW(21);
            if (elect()) {
                bulk_g2s(sb + SM_Y, g_yv + rho * 5120, 12288, bars + BAR_Y * 8);
                bulk_g2s(sb + SM_Y + 12288, g_yv + rho * 5120 + 3072, 8192, bars + BAR_Y2 * 8);
            }
            __syncwarp();
        }
        if (elect()) {
            if (wq == 3) {
                mbar_expect(bars + BAR_XY * 8, 20480);
#pragma unroll 1
                for (int i = 0; i < 8; i++) {
                    bulk_g2s(sb + SM_YT + i * 2560, g_yv + (8 * rb + i) * 5120 + cm * 8, 2048, bars + BAR_XY * 8);
                    bulk_g2s(sb + SM_YT + i * 2560 + 2048, g_yv + (8 * rb + i) * 5120 + cr * 8, 512, bars + BAR_XY * 8);
                }
                mbar_wait(bars + BAR_FA * 8, 0);
                bulk_prefetch((const char*)p.w4 + cta * 17280, 17280);
                flag_wait(FL_CS, ep1 * 4);
                fence_async_global();
                mbar_expect(bars + BAR_CS * 8, 864);
                bulk_g2s(sb + SM_CS, g_cs + 64 * j, 256, bars + BAR_CS * 8);
                bulk_g2s(sb + SM_CS + 256, g_cs + 512 + RA3 * j, 4 * RA3, bars + BAR_CS * 8);
                bulk_g2s(sb + SM_CS + 256 + 4 * RA3, g_cs + HB0 + 64 * j, 256, bars + BAR_CS * 8);
                bulk_g2s(sb + SM_CS + 512 + 4 * RA3, g_cs + HB0 + 512 + RB3 * j, 4 * RB3, bars + BAR_CS * 8);
                mbar_wait(bars + BAR_ST * 8, 0);
#pragma unroll 1
                for (int i = 0; i < 3; i++) {
                    flag_wait(FL_G + 16 * i + rb, ep1 * 8);
                    mbar_expect(bars + (BAR_G + i) * 8, 0);
                    TS(35 + (i + 2) % 3);
                }
            } else if (wq == 1) {
                Ring<NB, SM_RB, BAR_FB, BAR_EB> r{sb, 0, 0};
#pragma unroll 1
                for (int ph = 0; ph < 7; ph++) {
                    const CUtensorMap* ma = ph == 0 ? &maps.w1a : ph == 1 ? &maps.w2a : ph == 6 ? &maps.w4a : &maps.w3a;
                    const bool b3b = ph == 2 || ph == 4 || ph == 5;
                    r.runw(paired, idx & 1, ma, ma + (b3b ? 2 : 1), ph == 3 ? 64 * j : b3b ? HB0 + 64 * j : cm,
                           ph == 3 ? 512 + RA3 * j : b3b ? HB0 + 512 + RB3 * j : cr, ph == 4 ? 10 - NA : ph == 5 ? 1 : 0,
                           ph == 6 ? 27 : ph == 5 ? 10 - NA : ph == 2 ? 1 : 10, ph == 0 ? 0 : ph == 6 ? OWNG * (HB0 / 64 + j) : cm >> 6,
                           ph == 3 ? 8192 + 128 * RA3 : b3b ? 8192 + 128 * RB3 : 10240,
                           ph == 1 ? GATE : ph == 3 ? GATE - 1 : -1, bars + (BAR_ST - (ph == 1)) * 8);
                }
            } else {
                Ring<NA, SM_RA, BAR_FA, BAR_EA> r{sb, 0, 0};
                if (cta >= 120) mbar_wait(bars + (BAR_K + 4) * 8, 0);
                mbar_expect(bars + BAR_XR * 8, 20480);
                bulk_g2s(sb + SM_XR, p.q + (size_t)rho * 16 * D_, 20480, bars + BAR_XR * 8);
                mbar_expect(bars + BAR_XY * 8, 20480);
                tma2d(sb + SM_XT, &maps.xa, cm, rb * 128, bars + BAR_XY * 8);
                tma2d(sb + SM_XT2, &maps.xb, cr, rb * 128, bars + BAR_XY * 8);
                const int grp = j >> 1;
                const int delta = (grp & 1 ? 1 : -1) * (1 + (grp >> 1));
                const int nb = min(max(rb + (delta > 0 ? 1 : -1), 0), 15);
                uint32_t fb = r.acquire(SLOT), dst = r.slot();
                flag_wait2(FL_R + nb, FL_R + rb, ep1 * 8);
                fence_async_global();
                tma2d(dst, &maps.hn, 0, rb * 128 + delta, fb);
                TS(24);
                r.next();
                r.run2d(&maps.hn, rb * 128 + delta);
#pragma unroll 1
                for (int i = 0; i < 2; i++) {
                    const char* src = (const char*)(i ? g_x1 : g_h1) + (size_t)rb * 163840;
                    r.acquire(0); r.next();
                    fb = r.acquire(SLOT); dst = r.slot();
                    const char* src1 = src + (cm == 0 ? SLOT : 0);
                    flag_wait_fast(FL_B1 + 16 * i + rb, ep1 * 8);
                    fence_async_global();
                    bulk_g2s(dst, src1, SLOT, fb);
                    TS(28 + 4 * i);
                    mbar_expect(bars + (BAR_ST - 1 + i) * 8, 0);
                    r.next();
                    r.run1d(src, 2, 10, cm >> 6);
                }
                r.run1d((const char*)g_x1 + (size_t)rb * 163840, 1, 10 - NA, cm >> 6);
                if (OWNG) { r.acquire(0); r.next(); }
#pragma unroll 1
                for (int i = 0; i < 2; i++) {
                    mbar_wait(bars + (BAR_G + 1 + i) * 8, 0); fence_async_global();
                    r.run1d((const char*)g_g + (size_t)rb * 442368, OWNG + HB0 / 64 * i, i ? 27 : OWNG + HB0 / 64, OWNG * (HB0 / 64 + j));
                }
            }
        }
        return;
    }
    bar_arrive(13, 640);
    asm volatile("setmaxnreg.inc.sync.aligned.u32 112;");
    const int rrow = 16 * rho + (warp >> 1) + 8 * (warp & 1);

    fence_async_smem();
    bar_sync(1 + wg, 128);
#pragma unroll 1
    for (int cc = wg; cc < wg + 1 + (wg == 3); cc++) {
        mbar_wait(bars + (BAR_K + cc) * 8, 0);
        if (cc == 2 && wq == 0) TSW(40);
        uint32_t a = sb + sm_k(cc) + 32 + (tid & 127) * 32;
        uint32_t pw = lds32(a - 4);
        uint4 x = lds128(a), y = lds128(a + 16), o;
        if ((tid & 127) == 0) {
            uint16_t k0 = __bfloat16_as_ushort(__float2bfloat16_rn(blo(x.x) + __uint_as_float(lds32(sb + SM_GV + 520 + cc * 4))));
            x.x = (x.x & 0xffff0000u) | k0;
            sts16(a, k0);
        }
        o.x = prmt(pw, x.x, 0x5432); o.y = prmt(x.x, x.y, 0x5432); o.z = prmt(x.y, x.z, 0x5432); o.w = prmt(x.z, x.w, 0x5432);
        sts128(a + 4160, o);
        o.x = prmt(x.w, y.x, 0x5432); o.y = prmt(y.x, y.y, 0x5432); o.z = prmt(y.y, y.z, 0x5432); o.w = prmt(y.z, y.w, 0x5432);
        sts128(a + 4176, o);
    }
    bar_sync(1 + wg, 128);
    if (wg == 3) bar_arrive(11, 256);
#pragma unroll 1
    for (int cc = wg; cc < 5; cc += 3) {
        if (cc == 3 && wg == 0) break;
        if (cc == 4) bar_sync(11, 256);
        const uint32_t kaddr = sb + sm_k(cc) + ((g & 1) ? 32 : 4192) + 4 * ((g >> 1) - c) + 64 * wq;
        const AFrag f0 = ldA(kaddr), f1 = ldA(kaddr + 256);
        if (STAG && cc == 3) bar_sync(12, 256);
        mbar_wait(bars + (BAR_U + cc) * 8, 0);
        if (wq == 0) TSW(5 + cc);
        float d[64];
        conv_two<0>(d, f0, f1, kaddr, desc_lo(sb + sm_u(cc), U_PLANE), sb + sm_red(cc) + wq * 4352 + g * 544 + c * 8, cc == 1);
        if (wq == 0) TSW(10 + cc);
        if (cc == 1) bar_arrive(6, 256);
    }
#pragma unroll 1
    for (int cc = wg == 1 ? 4 : wg;; cc++) {
        if (cc == 1) bar_sync(6, 256); else bar_sync(1 + wg, 128);
        const int ch = cta * 5 + cc;
        uint32_t* dst = g_yv + ch * 8 + ((g + (ch >> 2)) & 7) + (126 - 32 * wq - 2 * c) * 5120;
        uint2 v[16];
#pragma unroll
        for (int i = 0; i < 16; i++) v[i] = lds64(sb + sm_red(cc) + g * 544 + wq * 128 + c * 8 + (i >> 2) * 32 + (i & 3) * 4360);
#pragma unroll
        for (int w = 1; w < 4; w++)
            if (wq == 3 && c > 3 - w) v[12 + w] = make_uint2(0, 0);
#pragma unroll
        for (int q = 0; q < 4; q++) {
            const uint2* u = v + 4 * q;
            dst[-8 * q * 5120] = badd2(u[0].x, badd2(u[1].x, badd2(u[2].x, u[3].x)));
            dst[(-8 * q + 1) * 5120] = badd2(u[0].y, badd2(u[1].y, badd2(u[2].y, u[3].y)));
        }
        if (wq == 0) TSW(15 + cc);
        if (cc != 0) break;
    }
    fence_async_smem();
    if (!(wg & 1)) bar_arrive(9, 288);
    bar_arrive(7, 544);

    const uint32_t one2 = 0x3f803f80u;
    const unsigned ones = p.ones;
    {
        uint32_t x[10], a[10], cb[10], sbv[10];
        if (RPRE_WAIT) bar_sync(10, 512);
        mbar_wait(bars + BAR_XR * 8, 0);
#pragma unroll
        for (int i = 0; i < 10; i++) x[i] = lds32(sb + SM_XR + (rrow & 15) * 1280 + lane * 4 + i * 128);
        const uint3 s1 = row_stats(x, lane);
        const int up = lane >> 4, gg = warp >> 1, e = warp & 1;
        const uint32_t ya = sb + SM_Y + lane * 64 + ((gg + (lane >> 1)) & 7) * 4;
        const uint32_t sel = (up ? 0x1054u : 0x5410u) + (e ? 0x2222u : 0u);
        const uint32_t ma = sb + SM_MOD + lane * 4;
        mbar_wait(bars + BAR_M * 8, 0);
        uint32_t pin = 0;
#pragma unroll
        for (int i = 0; i < 10; i++) {
            uint32_t h = bfma2(ln_apply(x[i], s1.x, s1.y, s1.z), badd2(lds32(ma + 1280 + i * 128), one2), lds32(ma + i * 128));
            a[i] = bmul2(h, lds32(ma + 2560 + i * 128));
            sbv[i] = lds32(ma + 3840 + i * 128);
            cb[i] = badd2(lds32(ma + 5120 + i * 128), one2);
            pin ^= a[i] ^ cb[i];
        }
        if (pin & ~ones) sts32(sb + SM_GV, pin);
        if (warp == 4) TSW(52);
        mbar_wait(bars + BAR_Y * 8, 0);
        if (warp == 0) TSW(22);
#pragma unroll
        for (int i = 0; i < 10; i++) {
            if (i == 6) mbar_wait(bars + BAR_Y2 * 8, 0);
            uint32_t y0 = lds32(ya + i * 2048 + up * 32), y1 = lds32(ya + i * 2048 + (up ^ 1) * 32);
            x[i] = bfma2(a[i], prmt(y0, y1, sel), x[i]);
        }
        const uint3 s2 = row_stats(x, lane);
#pragma unroll
        for (int i = 0; i < 10; i++) x[i] = bfma2(ln_apply(x[i], s2.x, s2.y, s2.z), cb[i], sbv[i]);
        const uint3 s3 = row_stats(x, lane);
        uint32_t* o = reinterpret_cast<uint32_t*>(g_hn + (size_t)rrow * D_) + lane;
#pragma unroll
        for (int i = 0; i < 10; i++) o[32 * i] = ln_apply(x[i], s3.x, s3.y, s3.z);
        if (lane < 2) g_rs[rrow * 2 + lane] = lane ? make_uint4(s2.x, s2.y, s2.z, 0) : make_uint4(s1.x, s1.y, s1.z, 0);
        if (warp == 0) TSW(34);
        bar_arrive(8, 544);
    }

    const int half = wg & 1;
    const int row = 64 * half + 16 * wq + g;
    const int tw0 = (rb * 80 + (cm >> 3)) * 512 + row * 4 + c, tw1 = (rb * 80 + (cr >> 3) - 8) * 512 + row * 4 + c;
    const uint32_t park = sb + SM_Y + (tid & 255) * 16;
    const uint32_t ms0 = sb + SM_MOD + (cm + 2 * c) * 2, ms1 = sb + SM_MOD + (cr - 64 + 2 * c) * 2;
    if (wg >= 2) {
        {
            float acc[40];
            gemm_loop<80, true, 10, 10, true, SK1>(acc, sb, half, 0, 0, 10, 0, 0, 25);
#pragma unroll
            for (int k = 0; k < 10; k += CH) CHUNK(k) {
#pragma unroll
                for (int q = k; q < k + CH && q < 10; q++) {
                    uint32_t* dst = reinterpret_cast<uint32_t*>(g_h1) + (q < 8 ? tw0 : tw1);
                    const uint32_t u = gelu2_h(bmul2(pack2(acc[4 * q], acc[4 * q + 1]), 0x3f003f00u));
                    const uint32_t v = gelu2_h(bmul2(pack2(acc[4 * q + 2], acc[4 * q + 3]), 0x3f003f00u));
                    dst[q * 512] = u;
                    dst[q * 512 + 32] = v;
                    acc[4 * q] = __uint_as_float(u); acc[4 * q + 1] = __uint_as_float(v);
                }
            }
            bar_arrive(15, 288);
            mbar_wait(bars + (BAR_FA + 10 % NA) * 8, (10 / NA) & 1);
#pragma unroll
            for (int q = 0; q < 8; q++) {
                sts32(sb + SM_RA + (10 % NA) * SLOT + q * 2048 + row * 16 + c * 4, __float_as_uint(acc[4 * q]));
                sts32(sb + SM_RA + (10 % NA) * SLOT + q * 2048 + row * 16 + c * 4 + 128, __float_as_uint(acc[4 * q + 1]));
            }
            fence_async_smem();
            bar_arrive(14, 512);
        }
        gemm3<0>(sb, rb, j, half, row, c, ones);
        {
            float acc[40];
            uint32_t gbv[10], base[20];
#pragma unroll
            for (int q = 0; q < 10; q++) gbv[q] = lds32((q < 8 ? ms0 : ms1) + 6400 + q * 16);
#pragma unroll
            for (int q = 0; q < 5; q++) { const uint4 t = lds128(park + q * 4096); base[4 * q] = t.x; base[4 * q + 1] = t.y; base[4 * q + 2] = t.z; base[4 * q + 3] = t.w; }
            gemm_loop<80, false, 27, 27 - NB, true, SK4>(acc, sb, half, 39 - NA, 40, 27 - NA, 11, 0, 42);
            auto fin = [&](int q, int r) {
                return bfma2(gbv[q], pack2(acc[4 * q + 2 * r], acc[4 * q + 2 * r + 1]), base[2 * q + r]);
            };
            auto tr4 = [&](uint32_t t0, uint32_t t1, uint32_t t2, uint32_t t3) {
                const bool o1 = c & 1, o2 = c & 2;
                uint32_t a = __shfl_xor_sync(0xffffffffu, o1 ? t0 : t1, 1), b = __shfl_xor_sync(0xffffffffu, o1 ? t2 : t3, 1);
                uint32_t u0 = o1 ? a : t0, u1 = o1 ? t1 : a, u2 = o1 ? b : t2, u3 = o1 ? t3 : b;
                a = __shfl_xor_sync(0xffffffffu, o2 ? u0 : u2, 2); b = __shfl_xor_sync(0xffffffffu, o2 ? u1 : u3, 2);
                return o2 ? make_uint4(a, b, u2, u3) : make_uint4(u0, u1, a, b);
            };
            bf16* go = p.out + (size_t)(rb * 128 + row) * D_;
#pragma unroll
            for (int k = 0; k < 2; k++) CHUNK(k) {
#pragma unroll
                for (int r = 0; r < 2; r++)
                    *reinterpret_cast<uint4*>(go + r * 8 * D_ + cm + 32 * k + 8 * c) = tr4(fin(4 * k, r), fin(4 * k + 1, r), fin(4 * k + 2, r), fin(4 * k + 3, r));
            }
            CHUNK(2) *reinterpret_cast<uint4*>(go + (c >> 1) * 8 * D_ + cr + 8 * (c & 1)) = tr4(fin(8, 0), fin(9, 0), fin(8, 1), fin(9, 1));
            if (tid == 384) TS(44);
            if (warp == 12) TSFLUSH();
        }
    } else {
        {
            float acc[40];
            uint32_t x2[20];
            {
                uint32_t y[20];
                mbar_wait(bars + BAR_XY * 8, 0);
                const uint32_t xa = sb + SM_XT + row * 128 + c * 4, xb = sb + SM_XT2 + row * 32 + c * 4;
                const uint32_t ya = sb + SM_YT + (4 * half + wq) * 2560 + c * 64;
#pragma unroll
                for (int q = 0; q < 10; q++) {
                    const uint32_t a = q < 8 ? xa + ((q ^ g) << 4) : xb + (q - 8) * 16;
                    x2[2 * q] = lds32(a); x2[2 * q + 1] = lds32(a + (q < 8 ? 1024 : 256));
                    const int pos = (g + ((q < 8 ? cm : cr) >> 2) + 2 * q + (c >> 1)) & 7;
                    y[2 * q] = lds32(ya + q * 256 + pos * 4); y[2 * q + 1] = lds32(ya + q * 256 + 32 + pos * 4);
                }
                fence_async_smem();
                bar_sync(1 + wg, 128);
                if ((tid & 127) < NA) mbar_arrive_cl(mapa(bars + (BAR_EA + (tid & 127)) * 8, blockIdx.x & 1));
                mbar_wait(bars + (BAR_FA + 1) * 8, 0);
                const uint4* rp = g_rs + (rb * 128 + row) * 2;
                const uint4 ra = ldcg128(rp), rb2 = ldcg128(rp + 1), rc = ldcg128(rp + 16), rd = ldcg128(rp + 17);
                bar_sync(14, 512);
#pragma unroll
                for (int q = 0; q < 10; q++) {
                    const uint32_t ms = q < 8 ? ms0 : ms1;
                    const uint32_t sa = lds32(ms + 16 * q), ca = badd2(lds32(ms + 1280 + 16 * q), one2), ga = lds32(ms + 2560 + 16 * q);
                    const uint32_t sbv = lds32(ms + 3840 + 16 * q), cb = badd2(lds32(ms + 5120 + 16 * q), one2);
                    uint32_t u = x2[2 * q], v = x2[2 * q + 1];
                    u = bfma2(bmul2(bfma2(ln_apply(u, ra.x, ra.y, ra.z), ca, sa), ga), prmt(y[2 * q], y[2 * q + 1], 0x5410), u);
                    v = bfma2(bmul2(bfma2(ln_apply(v, rc.x, rc.y, rc.z), ca, sa), ga), prmt(y[2 * q], y[2 * q + 1], 0x7632), v);
                    x2[2 * q] = u; x2[2 * q + 1] = v;
                    u = bfma2(ln_apply(u, rb2.x, rb2.y, rb2.z), cb, sbv);
                    v = bfma2(ln_apply(v, rd.x, rd.y, rd.z), cb, sbv);
                    acc[4 * q] = blo(u); acc[4 * q + 1] = bhi(u); acc[4 * q + 2] = blo(v); acc[4 * q + 3] = bhi(v);
                }
            }
            reg_fence<40>(acc);
            if (tid == 0) TS(45);
            gemm_loop<80, false, 10, 10, false, SK2>(acc, sb, half, 10, 10, 10, 0, 0, 29);
            uint32_t x1[20];
            float s0 = 0.f, q0 = 0.f, s1 = 0.f, q1 = 0.f;
#pragma unroll
            for (int q = 0; q < 10; q++) {
                uint32_t u = pack2(acc[4 * q], acc[4 * q + 1]);
                uint32_t v = pack2(acc[4 * q + 2], acc[4 * q + 3]);
                uint32_t* dst = reinterpret_cast<uint32_t*>(g_x1) + (q < 8 ? tw0 : tw1);
                dst[q * 512] = u;
                dst[q * 512 + 32] = v;
                x1[2 * q] = u; x1[2 * q + 1] = v;
            }
            bar_arrive(6, 288);
            CHUNK(0)
#pragma unroll
            for (int q = 0; q < 10; q++) {
                float a = blo(x1[2 * q]), b = bhi(x1[2 * q]), e = blo(x1[2 * q + 1]), f = bhi(x1[2 * q + 1]);
                s0 += a + b; q0 = fmaf(a, a, fmaf(b, b, q0));
                s1 += e + f; q1 = fmaf(e, e, fmaf(f, f, q1));
            }
#pragma unroll
            for (int m = 1; m <= 2; m <<= 1) {
                s0 += __shfl_xor_sync(0xffffffffu, s0, m); q0 += __shfl_xor_sync(0xffffffffu, q0, m);
                s1 += __shfl_xor_sync(0xffffffffu, s1, m); q1 += __shfl_xor_sync(0xffffffffu, q1, m);
            }
            if (c < 2) g_st[(rb * 8 + j) * 128 + row + 8 * c] = c ? make_float2(s1, q1) : make_float2(s0, q0);
            bar_arrive(8, 288);
            mbar_wait(bars + (BAR_FA + 20 % NA) * 8, (20 / NA) & 1);
#pragma unroll
            for (int q = 0; q < 8; q++) {
                sts32(sb + SM_RA + (20 % NA) * SLOT + q * 2048 + row * 16 + c * 4, x1[2 * q]);
                sts32(sb + SM_RA + (20 % NA) * SLOT + q * 2048 + row * 16 + c * 4 + 128, x1[2 * q + 1]);
            }
            fence_async_smem();
            bar_sync(3 + wg, 128);
#pragma unroll
            for (int q = 0; q < 5; q++) {
                const uint32_t ms = q < 4 ? ms0 : ms1;
                const uint32_t g0 = lds32(ms + 6400 + q * 32), g1 = lds32(ms + 6400 + q * 32 + 16);
                sts128(park + q * 4096, make_uint4(bfma2(g0, x1[4 * q], x2[4 * q]), bfma2(g0, x1[4 * q + 1], x2[4 * q + 1]),
                                                   bfma2(g1, x1[4 * q + 2], x2[4 * q + 2]), bfma2(g1, x1[4 * q + 3], x2[4 * q + 3])));
            }
        }
        gemm3<1>(sb, rb, j, half, row, c, ones);
    }
}

typedef CUresult (*EncFn)(CUtensorMap*, CUtensorMapDataType, cuuint32_t, void*, const cuuint64_t*, const cuuint64_t*,
                          const cuuint32_t*, const cuuint32_t*, CUtensorMapInterleave, CUtensorMapSwizzle,
                          CUtensorMapL2promotion, CUtensorMapFloatOOBfill);

void make_map(EncFn enc, CUtensorMap* m, const void* base, uint64_t inner, uint64_t outer, uint32_t bi, uint32_t bo,
              CUtensorMapSwizzle swz = CU_TENSOR_MAP_SWIZZLE_128B) {
    cuuint64_t dims[2] = {inner, outer};
    cuuint64_t st[1] = {inner * 2};
    cuuint32_t box[2] = {bi, bo};
    cuuint32_t es[2] = {1, 1};
    enc(m, CU_TENSOR_MAP_DATA_TYPE_BFLOAT16, 2, const_cast<void*>(base), dims, st, box, es, CU_TENSOR_MAP_INTERLEAVE_NONE,
        swz, CU_TENSOR_MAP_L2_PROMOTION_NONE, CU_TENSOR_MAP_FLOAT_OOB_FILL_NONE);
}

}

extern "C" void kernel_launch(void* const* d_in, const int* in_sizes, int n_in, void* d_out, int out_size) {
    (void)in_sizes; (void)n_in; (void)out_size;
    Params p;
    p.q = (const bf16*)d_in[0]; p.k = (const bf16*)d_in[1]; p.v = (const bf16*)d_in[2];
    p.shift = (const bf16*)d_in[3]; p.ssmk = (const bf16*)d_in[4]; p.ssmD = (const bf16*)d_in[5];
    p.w1 = (const bf16*)d_in[7]; p.w2 = (const bf16*)d_in[8]; p.w3 = (const bf16*)d_in[9]; p.w4 = (const bf16*)d_in[10];
    p.c = (const bf16*)d_in[11]; p.wmod = (const bf16*)d_in[12];
    p.out = (bf16*)d_out;
    p.ones = 0xffffffffu;

    void* fn = nullptr;
    cudaDriverEntryPointQueryResult qr;
    cudaGetDriverEntryPoint("cuTensorMapEncodeTiled", &fn, cudaEnableDefault, &qr);
    EncFn enc = (EncFn)fn;
    void* hn = nullptr;
    cudaGetSymbolAddress(&hn, g_hn);
    Maps maps;
    make_map(enc, &maps.w3s, p.w3, F_, D_, 216, 64, CU_TENSOR_MAP_SWIZZLE_NONE);
    make_map(enc, &maps.wm, p.wmod, 6 * D_, D_, 32, 128, CU_TENSOR_MAP_SWIZZLE_64B);
    make_map(enc, &maps.xa, p.q, D_, S_, 64, 128);
    make_map(enc, &maps.xb, p.q, D_, S_, 16, 128, CU_TENSOR_MAP_SWIZZLE_NONE);
    make_map(enc, &maps.hn, hn, D_, S_, 64, 128);
    make_map(enc, &maps.w1a, p.w1, D_, D_, 64, 64);
    make_map(enc, &maps.w1b, p.w1, D_, D_, 16, 64);
    make_map(enc, &maps.w2a, p.w2, D_, D_, 64, 64);
    make_map(enc, &maps.w2b, p.w2, D_, D_, 16, 64);
    make_map(enc, &maps.w3a, p.w3, F_, D_, 64, 64);
    make_map(enc, &maps.w3b, p.w3, F_, D_, RA3, 64);
    make_map(enc, &maps.w3c, p.w3, F_, D_, RB3, 64);
    make_map(enc, &maps.w4a, p.w4, D_, F_, 64, 64);
    make_map(enc, &maps.w4b, p.w4, D_, F_, 16, 64);
    cudaFuncSetAttribute(fused_kernel, cudaFuncAttributeMaxDynamicSharedMemorySize, SMEM_BYTES);
    fused_kernel<<<132, NTHREADS, SMEM_BYTES>>>(p, maps);
}
```

```cpp
#include <cuda_runtime.h>
#include <cuda_bf16.h>
#include <cuda.h>
#include <stdint.h>
#include <string.h>

#define SEED 0
#define RING_A 6
#define CH 2
#define FAST_LN 2
#define STAG 10
#define PGELU 2
#define CH3 4
#define HO_A 16
#define HO_B 16
#define RA3 48
#define CSP 16
#define OWNG 1
#define GATE 5
#define SSM_DELAY 0
#define B_DELAY 300
#define RPRE_WAIT 1
#define SSM_N 3
#define PF_EARLY 0

namespace {

typedef __nv_bfloat16 bf16;
typedef __nv_bfloat162 bf162;

constexpr int S_ = 2048, D_ = 640, F_ = 1728;
constexpr int NTHREADS = 640;
constexpr int NA = RING_A, NB = 12 - RING_A;
constexpr int SLOT = 16384;
constexpr int RB3 = 88 - RA3, HB0 = 512 + 8 * RA3;
constexpr int SM_RA = 0, SM_RB = NA * SLOT;

static_assert(NA == 6, "smem map");
constexpr int RED_STRIDE = 17536;
constexpr int K_STRIDE = 8320;
constexpr int U_PLANE = 2560, U_STRIDE = 5120;
constexpr int SM_Y = 12 * SLOT;
__device__ __forceinline__ int sm_red(int cc) { return cc * RED_STRIDE + (cc < 3 ? SM_RB : -3 * RED_STRIDE); }
__device__ __forceinline__ int sm_k(int cc) { return cc * K_STRIDE + (cc < 3 ? SM_RB + 3 * RED_STRIDE : 2 * RED_STRIDE - 3 * K_STRIDE); }
__device__ __forceinline__ int sm_u(int cc) { return cc * U_STRIDE + (cc < 3 ? SM_RB + 3 * RED_STRIDE + 3 * K_STRIDE : SM_Y + 8192 - 3 * U_STRIDE); }
constexpr int SM_PK = SM_RB;
constexpr int SM_PV = SM_RB + 24576;
constexpr int SM_WM = 57344;
constexpr int SM_XT = SM_WM, SM_XT2 = SM_WM + 16384, SM_XR = SM_WM + 20480;
constexpr int SM_YT = 0;
constexpr int SM_MOD = SM_Y + 20480;
constexpr int SM_GV = SM_MOD + 7680;
constexpr int SM_CS = SM_GV + 1024;
constexpr int SM_RP = SM_CS + 1024;
constexpr int SM_BAR = SM_RP + 1024;
constexpr int SM_PROF = SM_BAR + 512;
constexpr int SM_TOTAL = SM_PROF + 512;
constexpr int SMEM_BYTES = SM_TOTAL + 1024;
static_assert(SMEM_BYTES <= 232448, "smem");

constexpr int BAR_FA = 0, BAR_FB = NA, BAR_EA = 12, BAR_EB = 12 + NA, BAR_K = 24, BAR_U = 29, BAR_Y = 34, BAR_CS = 35, BAR_WM = 36, BAR_M = 37, BAR_XY = 38, BAR_Y2 = 39, BAR_G = 40, BAR_ST = 44, BAR_XR = 45, NBARS = 46;

__device__ __align__(1024) bf16 g_kvT[D_ * S_];
__device__ __align__(1024) uint32_t g_yv[128 * 5120];
__device__ __align__(1024) bf16 g_mod[6 * D_];
__device__ __align__(1024) bf16 g_hn[S_ * D_];
__device__ __align__(1024) uint4 g_rs[S_ * 2];
__device__ __align__(1024) bf16 g_h1[S_ * D_];
__device__ __align__(1024) bf16 g_x1[S_ * D_];
__device__ __align__(1024) bf16 g_g[S_ * F_];
__device__ __align__(1024) float2 g_st[S_ * 8];
__device__ __align__(1024) float g_cs[F_];
__device__ __align__(1024) unsigned g_flags[128 * 32];
__device__ __align__(1024) unsigned g_epoch[160];
constexpr int FL_P = 0, FL_C = 8, FL_CS = 9, FL_M = 10, FL_R = 16, FL_B1 = 32, FL_B2 = 48, FL_G = 64;

#define TS(i) do {} while (0)
#define TSW(i) do {} while (0)
#define TSD(i, dep) do {} while (0)
#define TSD2(i, dep) do {} while (0)
#define TSFLUSH() do {} while (0)

struct Params {
    const bf16 *q, *k, *v, *shift, *ssmk, *ssmD, *w1, *w2, *w3, *w4, *c, *wmod;
    bf16* out;
    unsigned ones;
};
#define CHUNK(k) if (ones & (1u << (k)))
struct Maps { CUtensorMap hn, w1a, w1b, w2a, w2b, w3a, w3b, w3c, w4a, w4b, wm, xa, xb, w3s; };

template<int N> struct WgRs;
template<int N> struct WgSs;
template<> struct WgRs<32> { template<int OFF,int HI,int SC> static __device__ __forceinline__ void run(float* d,uint32_t a0,uint32_t a1,uint32_t a2,uint32_t a3,uint32_t blo){
 asm volatile("{.reg .b32 l; .reg .b64 db; add.u32 l,%20,%21; mov.b64 db,{l,%22}; wgmma.mma_async.sync.aligned.m64n32k16.f32.bf16.bf16 {%0,%1,%2,%3,%4,%5,%6,%7,%8,%9,%10,%11,%12,%13,%14,%15},{%16,%17,%18,%19},db,%23,1,1,0;}"
 :"+f"(d[0]),"+f"(d[1]),"+f"(d[2]),"+f"(d[3]),"+f"(d[4]),"+f"(d[5]),"+f"(d[6]),"+f"(d[7]),"+f"(d[8]),"+f"(d[9]),"+f"(d[10]),"+f"(d[11]),"+f"(d[12]),"+f"(d[13]),"+f"(d[14]),"+f"(d[15])
 :"r"(a0),"r"(a1),"r"(a2),"r"(a3),"r"(blo),"n"(OFF),"n"(HI),"n"(SC)); } };
template<> struct WgRs<48> { template<int OFF,int HI,int SC> static __device__ __forceinline__ void run(float* d,uint32_t a0,uint32_t a1,uint32_t a2,uint32_t a3,uint32_t blo){
 asm volatile("{.reg .b32 l; .reg .b64 db; add.u32 l,%28,%29; mov.b64 db,{l,%30}; wgmma.mma_async.sync.aligned.m64n48k16.f32.bf16.bf16 {%0,%1,%2,%3,%4,%5,%6,%7,%8,%9,%10,%11,%12,%13,%14,%15,%16,%17,%18,%19,%20,%21,%22,%23},{%24,%25,%26,%27},db,%31,1,1,0;}"
 :"+f"(d[0]),"+f"(d[1]),"+f"(d[2]),"+f"(d[3]),"+f"(d[4]),"+f"(d[5]),"+f"(d[6]),"+f"(d[7]),"+f"(d[8]),"+f"(d[9]),"+f"(d[10]),"+f"(d[11]),"+f"(d[12]),"+f"(d[13]),"+f"(d[14]),"+f"(d[15]),"+f"(d[16]),"+f"(d[17]),"+f"(d[18]),"+f"(d[19]),"+f"(d[20]),"+f"(d[21]),"+f"(d[22]),"+f"(d[23])
 :"r"(a0),"r"(a1),"r"(a2),"r"(a3),"r"(blo),"n"(OFF),"n"(HI),"n"(SC)); } };
template<> struct WgRs<64> { template<int OFF,int HI,int SC> static __device__ __forceinline__ void run(float* d,uint32_t a0,uint32_t a1,uint32_t a2,uint32_t a3,uint32_t blo){
 asm volatile("{.reg .b32 l; .reg .b64 db; add.u32 l,%36,%37; mov.b64 db,{l,%38}; wgmma.mma_async.sync.aligned.m64n64k16.f32.bf16.bf16 {%0,%1,%2,%3,%4,%5,%6,%7,%8,%9,%10,%11,%12,%13,%14,%15,%16,%17,%18,%19,%20,%21,%22,%23,%24,%25,%26,%27,%28,%29,%30,%31},{%32,%33,%34,%35},db,%39,1,1,0;}"
 :"+f"(d[0]),"+f"(d[1]),"+f"(d[2]),"+f"(d[3]),"+f"(d[4]),"+f"(d[5]),"+f"(d[6]),"+f"(d[7]),"+f"(d[8]),"+f"(d[9]),"+f"(d[10]),"+f"(d[11]),"+f"(d[12]),"+f"(d[13]),"+f"(d[14]),"+f"(d[15]),"+f"(d[16]),"+f"(d[17]),"+f"(d[18]),"+f"(d[19]),"+f"(d[20]),"+f"(d[21]),"+f"(d[22]),"+f"(d[23]),"+f"(d[24]),"+f"(d[25]),"+f"(d[26]),"+f"(d[27]),"+f"(d[28]),"+f"(d[29]),"+f"(d[30]),"+f"(d[31])
 :"r"(a0),"r"(a1),"r"(a2),"r"(a3),"r"(blo),"n"(OFF),"n"(HI),"n"(SC)); } };
template<> struct WgRs<80> { template<int OFF,int HI,int SC> static __device__ __forceinline__ void run(float* d,uint32_t a0,uint32_t a1,uint32_t a2,uint32_t a3,uint32_t blo){
 asm volatile("{.reg .b32 l; .reg .b64 db; add.u32 l,%44,%45; mov.b64 db,{l,%46}; wgmma.mma_async.sync.aligned.m64n80k16.f32.bf16.bf16 {%0,%1,%2,%3,%4,%5,%6,%7,%8,%9,%10,%11,%12,%13,%14,%15,%16,%17,%18,%19,%20,%21,%22,%23,%24,%25,%26,%27,%28,%29,%30,%31,%32,%33,%34,%35,%36,%37,%38,%39},{%40,%41,%42,%43},db,%47,1,1,0;}"
 :"+f"(d[0]),"+f"(d[1]),"+f"(d[2]),"+f"(d[3]),"+f"(d[4]),"+f"(d[5]),"+f"(d[6]),"+f"(d[7]),"+f"(d[8]),"+f"(d[9]),"+f"(d[10]),"+f"(d[11]),"+f"(d[12]),"+f"(d[13]),"+f"(d[14]),"+f"(d[15]),"+f"(d[16]),"+f"(d[17]),"+f"(d[18]),"+f"(d[19]),"+f"(d[20]),"+f"(d[21]),"+f"(d[22]),"+f"(d[23]),"+f"(d[24]),"+f"(d[25]),"+f"(d[26]),"+f"(d[27]),"+f"(d[28]),"+f"(d[29]),"+f"(d[30]),"+f"(d[31]),"+f"(d[32]),"+f"(d[33]),"+f"(d[34]),"+f"(d[35]),"+f"(d[36]),"+f"(d[37]),"+f"(d[38]),"+f"(d[39])
 :"r"(a0),"r"(a1),"r"(a2),"r"(a3),"r"(blo),"n"(OFF),"n"(HI),"n"(SC)); } };
template<> struct WgRs<96> { template<int OFF,int HI,int SC> static __device__ __forceinline__ void run(float* d,uint32_t a0,uint32_t a1,uint32_t a2,uint32_t a3,uint32_t blo){
 asm volatile("{.reg .b32 l; .reg .b64 db; add.u32 l,%52,%53; mov.b64 db,{l,%54}; wgmma.mma_async.sync.aligned.m64n96k16.f32.bf16.bf16 {%0,%1,%2,%3,%4,%5,%6,%7,%8,%9,%10,%11,%12,%13,%14,%15,%16,%17,%18,%19,%20,%21,%22,%23,%24,%25,%26,%27,%28,%29,%30,%31,%32,%33,%34,%35,%36,%37,%38,%39,%40,%41,%42,%43,%44,%45,%46,%47},{%48,%49,%50,%51},db,%55,1,1,0;}"
 :"+f"(d[0]),"+f"(d[1]),"+f"(d[2]),"+f"(d[3]),"+f"(d[4]),"+f"(d[5]),"+f"(d[6]),"+f"(d[7]),"+f"(d[8]),"+f"(d[9]),"+f"(d[10]),"+f"(d[11]),"+f"(d[12]),"+f"(d[13]),"+f"(d[14]),"+f"(d[15]),"+f"(d[16]),"+f"(d[17]),"+f"(d[18]),"+f"(d[19]),"+f"(d[20]),"+f"(d[21]),"+f"(d[22]),"+f"(d[23]),"+f"(d[24]),"+f"(d[25]),"+f"(d[26]),"+f"(d[27]),"+f"(d[28]),"+f"(d[29]),"+f"(d[30]),"+f"(d[31]),"+f"(d[32]),"+f"(d[33]),"+f"(d[34]),"+f"(d[35]),"+f"(d[36]),"+f"(d[37]),"+f"(d[38]),"+f"(d[39]),"+f"(d[40]),"+f"(d[41]),"+f"(d[42]),"+f"(d[43]),"+f"(d[44]),"+f"(d[45]),"+f"(d[46]),"+f"(d[47])
 :"r"(a0),"r"(a1),"r"(a2),"r"(a3),"r"(blo),"n"(OFF),"n"(HI),"n"(SC)); } };
template<> struct WgRs<112> { template<int OFF,int HI,int SC> static __device__ __forceinline__ void run(float* d,uint32_t a0,uint32_t a1,uint32_t a2,uint32_t a3,uint32_t blo){
 asm volatile("{.reg .b32 l; .reg .b64 db; add.u32 l,%60,%61; mov.b64 db,{l,%62}; wgmma.mma_async.sync.aligned.m64n112k16.f32.bf16.bf16 {%0,%1,%2,%3,%4,%5,%6,%7,%8,%9,%10,%11,%12,%13,%14,%15,%16,%17,%18,%19,%20,%21,%22,%23,%24,%25,%26,%27,%28,%29,%30,%31,%32,%33,%34,%35,%36,%37,%38,%39,%40,%41,%42,%43,%44,%45,%46,%47,%48,%49,%50,%51,%52,%53,%54,%55},{%56,%57,%58,%59},db,%63,1,1,0;}"
 :"+f"(d[0]),"+f"(d[1]),"+f"(d[2]),"+f"(d[3]),"+f"(d[4]),"+f"(d[5]),"+f"(d[6]),"+f"(d[7]),"+f"(d[8]),"+f"(d[9]),"+f"(d[10]),"+f"(d[11]),"+f"(d[12]),"+f"(d[13]),"+f"(d[14]),"+f"(d[15]),"+f"(d[16]),"+f"(d[17]),"+f"(d[18]),"+f"(d[19]),"+f"(d[20]),"+f"(d[21]),"+f"(d[22]),"+f"(d[23]),"+f"(d[24]),"+f"(d[25]),"+f"(d[26]),"+f"(d[27]),"+f"(d[28]),"+f"(d[29]),"+f"(d[30]),"+f"(d[31]),"+f"(d[32]),"+f"(d[33]),"+f"(d[34]),"+f"(d[35]),"+f"(d[36]),"+f"(d[37]),"+f"(d[38]),"+f"(d[39]),"+f"(d[40]),"+f"(d[41]),"+f"(d[42]),"+f"(d[43]),"+f"(d[44]),"+f"(d[45]),"+f"(d[46]),"+f"(d[47]),"+f"(d[48]),"+f"(d[49]),"+f"(d[50]),"+f"(d[51]),"+f"(d[52]),"+f"(d[53]),"+f"(d[54]),"+f"(d[55])
 :"r"(a0),"r"(a1),"r"(a2),"r"(a3),"r"(blo),"n"(OFF),"n"(HI),"n"(SC)); } };
template<> struct WgRs<128> { template<int OFF,int HI,int SC> static __device__ __forceinline__ void run(float* d,uint32_t a0,uint32_t a1,uint32_t a2,uint32_t a3,uint32_t blo){
 asm volatile("{.reg .b32 l; .reg .b64 db; add.u32 l,%68,%69; mov.b64 db,{l,%70}; wgmma.mma_async.sync.aligned.m64n128k16.f32.bf16.bf16 {%0,%1,%2,%3,%4,%5,%6,%7,%8,%9,%10,%11,%12,%13,%14,%15,%16,%17,%18,%19,%20,%21,%22,%23,%24,%25,%26,%27,%28,%29,%30,%31,%32,%33,%34,%35,%36,%37,%38,%39,%40,%41,%42,%43,%44,%45,%46,%47,%48,%49,%50,%51,%52,%53,%54,%55,%56,%57,%58,%59,%60,%61,%62,%63},{%64,%65,%66,%67},db,%71,1,1,0;}"
 :"+f"(d[0]),"+f"(d[1]),"+f"(d[2]),"+f"(d[3]),"+f"(d[4]),"+f"(d[5]),"+f"(d[6]),"+f"(d[7]),"+f"(d[8]),"+f"(d[9]),"+f"(d[10]),"+f"(d[11]),"+f"(d[12]),"+f"(d[13]),"+f"(d[14]),"+f"(d[15]),"+f"(d[16]),"+f"(d[17]),"+f"(d[18]),"+f"(d[19]),"+f"(d[20]),"+f"(d[21]),"+f"(d[22]),"+f"(d[23]),"+f"(d[24]),"+f"(d[25]),"+f"(d[26]),"+f"(d[27]),"+f"(d[28]),"+f"(d[29]),"+f"(d[30]),"+f"(d[31]),"+f"(d[32]),"+f"(d[33]),"+f"(d[34]),"+f"(d[35]),"+f"(d[36]),"+f"(d[37]),"+f"(d[38]),"+f"(d[39]),"+f"(d[40]),"+f"(d[41]),"+f"(d[42]),"+f"(d[43]),"+f"(d[44]),"+f"(d[45]),"+f"(d[46]),"+f"(d[47]),"+f"(d[48]),"+f"(d[49]),"+f"(d[50]),"+f"(d[51]),"+f"(d[52]),"+f"(d[53]),"+f"(d[54]),"+f"(d[55]),"+f"(d[56]),"+f"(d[57]),"+f"(d[58]),"+f"(d[59]),"+f"(d[60]),"+f"(d[61]),"+f"(d[62]),"+f"(d[63])
 :"r"(a0),"r"(a1),"r"(a2),"r"(a3),"r"(blo),"n"(OFF),"n"(HI),"n"(SC)); } };
template<> struct WgSs<80> { template<int AOFF,int AHI,int BOFF,int BHI,int SC> static __device__ __forceinline__ void run(float* d,uint32_t alo,uint32_t blo){
 asm volatile("{.reg .b32 l,m; .reg .b64 da,db; add.u32 l,%40,%42; mov.b64 da,{l,%43}; add.u32 m,%41,%44; mov.b64 db,{m,%45}; wgmma.mma_async.sync.aligned.m64n80k16.f32.bf16.bf16 {%0,%1,%2,%3,%4,%5,%6,%7,%8,%9,%10,%11,%12,%13,%14,%15,%16,%17,%18,%19,%20,%21,%22,%23,%24,%25,%26,%27,%28,%29,%30,%31,%32,%33,%34,%35,%36,%37,%38,%39},da,db,%46,1,1,0,1;}"
 :"+f"(d[0]),"+f"(d[1]),"+f"(d[2]),"+f"(d[3]),"+f"(d[4]),"+f"(d[5]),"+f"(d[6]),"+f"(d[7]),"+f"(d[8]),"+f"(d[9]),"+f"(d[10]),"+f"(d[11]),"+f"(d[12]),"+f"(d[13]),"+f"(d[14]),"+f"(d[15]),"+f"(d[16]),"+f"(d[17]),"+f"(d[18]),"+f"(d[19]),"+f"(d[20]),"+f"(d[21]),"+f"(d[22]),"+f"(d[23]),"+f"(d[24]),"+f"(d[25]),"+f"(d[26]),"+f"(d[27]),"+f"(d[28]),"+f"(d[29]),"+f"(d[30]),"+f"(d[31]),"+f"(d[32]),"+f"(d[33]),"+f"(d[34]),"+f"(d[35]),"+f"(d[36]),"+f"(d[37]),"+f"(d[38]),"+f"(d[39])
 :"r"(alo),"r"(blo),"n"(AOFF),"n"(AHI),"n"(BOFF),"n"(BHI),"n"(SC)); } };
template<> struct WgSs<88> { template<int AOFF,int AHI,int BOFF,int BHI,int SC> static __device__ __forceinline__ void run(float* d,uint32_t alo,uint32_t blo){
 asm volatile("{.reg .b32 l,m; .reg .b64 da,db; add.u32 l,%44,%46; mov.b64 da,{l,%47}; add.u32 m,%45,%48; mov.b64 db,{m,%49}; wgmma.mma_async.sync.aligned.m64n88k16.f32.bf16.bf16 {%0,%1,%2,%3,%4,%5,%6,%7,%8,%9,%10,%11,%12,%13,%14,%15,%16,%17,%18,%19,%20,%21,%22,%23,%24,%25,%26,%27,%28,%29,%30,%31,%32,%33,%34,%35,%36,%37,%38,%39,%40,%41,%42,%43},da,db,%50,1,1,0,1;}"
 :"+f"(d[0]),"+f"(d[1]),"+f"(d[2]),"+f"(d[3]),"+f"(d[4]),"+f"(d[5]),"+f"(d[6]),"+f"(d[7]),"+f"(d[8]),"+f"(d[9]),"+f"(d[10]),"+f"(d[11]),"+f"(d[12]),"+f"(d[13]),"+f"(d[14]),"+f"(d[15]),"+f"(d[16]),"+f"(d[17]),"+f"(d[18]),"+f"(d[19]),"+f"(d[20]),"+f"(d[21]),"+f"(d[22]),"+f"(d[23]),"+f"(d[24]),"+f"(d[25]),"+f"(d[26]),"+f"(d[27]),"+f"(d[28]),"+f"(d[29]),"+f"(d[30]),"+f"(d[31]),"+f"(d[32]),"+f"(d[33]),"+f"(d[34]),"+f"(d[35]),"+f"(d[36]),"+f"(d[37]),"+f"(d[38]),"+f"(d[39]),"+f"(d[40]),"+f"(d[41]),"+f"(d[42]),"+f"(d[43])
 :"r"(alo),"r"(blo),"n"(AOFF),"n"(AHI),"n"(BOFF),"n"(BHI),"n"(SC)); } };
template<> struct WgSs<96> { template<int AOFF,int AHI,int BOFF,int BHI,int SC> static __device__ __forceinline__ void run(float* d,uint32_t alo,uint32_t blo){
 asm volatile("{.reg .b32 l,m; .reg .b64 da,db; add.u32 l,%48,%50; mov.b64 da,{l,%51}; add.u32 m,%49,%52; mov.b64 db,{m,%53}; wgmma.mma_async.sync.aligned.m64n96k16.f32.bf16.bf16 {%0,%1,%2,%3,%4,%5,%6,%7,%8,%9,%10,%11,%12,%13,%14,%15,%16,%17,%18,%19,%20,%21,%22,%23,%24,%25,%26,%27,%28,%29,%30,%31,%32,%33,%34,%35,%36,%37,%38,%39,%40,%41,%42,%43,%44,%45,%46,%47},da,db,%54,1,1,0,1;}"
 :"+f"(d[0]),"+f"(d[1]),"+f"(d[2]),"+f"(d[3]),"+f"(d[4]),"+f"(d[5]),"+f"(d[6]),"+f"(d[7]),"+f"(d[8]),"+f"(d[9]),"+f"(d[10]),"+f"(d[11]),"+f"(d[12]),"+f"(d[13]),"+f"(d[14]),"+f"(d[15]),"+f"(d[16]),"+f"(d[17]),"+f"(d[18]),"+f"(d[19]),"+f"(d[20]),"+f"(d[21]),"+f"(d[22]),"+f"(d[23]),"+f"(d[24]),"+f"(d[25]),"+f"(d[26]),"+f"(d[27]),"+f"(d[28]),"+f"(d[29]),"+f"(d[30]),"+f"(d[31]),"+f"(d[32]),"+f"(d[33]),"+f"(d[34]),"+f"(d[35]),"+f"(d[36]),"+f"(d[37]),"+f"(d[38]),"+f"(d[39]),"+f"(d[40]),"+f"(d[41]),"+f"(d[42]),"+f"(d[43]),"+f"(d[44]),"+f"(d[45]),"+f"(d[46]),"+f"(d[47])
 :"r"(alo),"r"(blo),"n"(AOFF),"n"(AHI),"n"(BOFF),"n"(BHI),"n"(SC)); } };
template<> struct WgSs<104> { template<int AOFF,int AHI,int BOFF,int BHI,int SC> static __device__ __forceinline__ void run(float* d,uint32_t alo,uint32_t blo){
 asm volatile("{.reg .b32 l,m; .reg .b64 da,db; add.u32 l,%52,%54; mov.b64 da,{l,%55}; add.u32 m,%53,%56; mov.b64 db,{m,%57}; wgmma.mma_async.sync.aligned.m64n104k16.f32.bf16.bf16 {%0,%1,%2,%3,%4,%5,%6,%7,%8,%9,%10,%11,%12,%13,%14,%15,%16,%17,%18,%19,%20,%21,%22,%23,%24,%25,%26,%27,%28,%29,%30,%31,%32,%33,%34,%35,%36,%37,%38,%39,%40,%41,%42,%43,%44,%45,%46,%47,%48,%49,%50,%51},da,db,%58,1,1,0,1;}"
 :"+f"(d[0]),"+f"(d[1]),"+f"(d[2]),"+f"(d[3]),"+f"(d[4]),"+f"(d[5]),"+f"(d[6]),"+f"(d[7]),"+f"(d[8]),"+f"(d[9]),"+f"(d[10]),"+f"(d[11]),"+f"(d[12]),"+f"(d[13]),"+f"(d[14]),"+f"(d[15]),"+f"(d[16]),"+f"(d[17]),"+f"(d[18]),"+f"(d[19]),"+f"(d[20]),"+f"(d[21]),"+f"(d[22]),"+f"(d[23]),"+f"(d[24]),"+f"(d[25]),"+f"(d[26]),"+f"(d[27]),"+f"(d[28]),"+f"(d[29]),"+f"(d[30]),"+f"(d[31]),"+f"(d[32]),"+f"(d[33]),"+f"(d[34]),"+f"(d[35]),"+f"(d[36]),"+f"(d[37]),"+f"(d[38]),"+f"(d[39]),"+f"(d[40]),"+f"(d[41]),"+f"(d[42]),"+f"(d[43]),"+f"(d[44]),"+f"(d[45]),"+f"(d[46]),"+f"(d[47]),"+f"(d[48]),"+f"(d[49]),"+f"(d[50]),"+f"(d[51])
 :"r"(alo),"r"(blo),"n"(AOFF),"n"(AHI),"n"(BOFF),"n"(BHI),"n"(SC)); } };
template<> struct WgSs<112> { template<int AOFF,int AHI,int BOFF,int BHI,int SC> static __device__ __forceinline__ void run(float* d,uint32_t alo,uint32_t blo){
 asm volatile("{.reg .b32 l,m; .reg .b64 da,db; add.u32 l,%56,%58; mov.b64 da,{l,%59}; add.u32 m,%57,%60; mov.b64 db,{m,%61}; wgmma.mma_async.sync.aligned.m64n112k16.f32.bf16.bf16 {%0,%1,%2,%3,%4,%5,%6,%7,%8,%9,%10,%11,%12,%13,%14,%15,%16,%17,%18,%19,%20,%21,%22,%23,%24,%25,%26,%27,%28,%29,%30,%31,%32,%33,%34,%35,%36,%37,%38,%39,%40,%41,%42,%43,%44,%45,%46,%47,%48,%49,%50,%51,%52,%53,%54,%55},da,db,%62,1,1,0,1;}"
 :"+f"(d[0]),"+f"(d[1]),"+f"(d[2]),"+f"(d[3]),"+f"(d[4]),"+f"(d[5]),"+f"(d[6]),"+f"(d[7]),"+f"(d[8]),"+f"(d[9]),"+f"(d[10]),"+f"(d[11]),"+f"(d[12]),"+f"(d[13]),"+f"(d[14]),"+f"(d[15]),"+f"(d[16]),"+f"(d[17]),"+f"(d[18]),"+f"(d[19]),"+f"(d[20]),"+f"(d[21]),"+f"(d[22]),"+f"(d[23]),"+f"(d[24]),"+f"(d[25]),"+f"(d[26]),"+f"(d[27]),"+f"(d[28]),"+f"(d[29]),"+f"(d[30]),"+f"(d[31]),"+f"(d[32]),"+f"(d[33]),"+f"(d[34]),"+f"(d[35]),"+f"(d[36]),"+f"(d[37]),"+f"(d[38]),"+f"(d[39]),"+f"(d[40]),"+f"(d[41]),"+f"(d[42]),"+f"(d[43]),"+f"(d[44]),"+f"(d[45]),"+f"(d[46]),"+f"(d[47]),"+f"(d[48]),"+f"(d[49]),"+f"(d[50]),"+f"(d[51]),"+f"(d[52]),"+f"(d[53]),"+f"(d[54]),"+f"(d[55])
 :"r"(alo),"r"(blo),"n"(AOFF),"n"(AHI),"n"(BOFF),"n"(BHI),"n"(SC)); } };
template<> struct WgSs<120> { template<int AOFF,int AHI,int BOFF,int BHI,int SC> static __device__ __forceinline__ void run(float* d,uint32_t alo,uint32_t blo){
 asm volatile("{.reg .b32 l,m; .reg .b64 da,db; add.u32 l,%60,%62; mov.b64 da,{l,%63}; add.u32 m,%61,%64; mov.b64 db,{m,%65}; wgmma.mma_async.sync.aligned.m64n120k16.f32.bf16.bf16 {%0,%1,%2,%3,%4,%5,%6,%7,%8,%9,%10,%11,%12,%13,%14,%15,%16,%17,%18,%19,%20,%21,%22,%23,%24,%25,%26,%27,%28,%29,%30,%31,%32,%33,%34,%35,%36,%37,%38,%39,%40,%41,%42,%43,%44,%45,%46,%47,%48,%49,%50,%51,%52,%53,%54,%55,%56,%57,%58,%59},da,db,%66,1,1,0,1;}"
 :"+f"(d[0]),"+f"(d[1]),"+f"(d[2]),"+f"(d[3]),"+f"(d[4]),"+f"(d[5]),"+f"(d[6]),"+f"(d[7]),"+f"(d[8]),"+f"(d[9]),"+f"(d[10]),"+f"(d[11]),"+f"(d[12]),"+f"(d[13]),"+f"(d[14]),"+f"(d[15]),"+f"(d[16]),"+f"(d[17]),"+f"(d[18]),"+f"(d[19]),"+f"(d[20]),"+f"(d[21]),"+f"(d[22]),"+f"(d[23]),"+f"(d[24]),"+f"(d[25]),"+f"(d[26]),"+f"(d[27]),"+f"(d[28]),"+f"(d[29]),"+f"(d[30]),"+f"(d[31]),"+f"(d[32]),"+f"(d[33]),"+f"(d[34]),"+f"(d[35]),"+f"(d[36]),"+f"(d[37]),"+f"(d[38]),"+f"(d[39]),"+f"(d[40]),"+f"(d[41]),"+f"(d[42]),"+f"(d[43]),"+f"(d[44]),"+f"(d[45]),"+f"(d[46]),"+f"(d[47]),"+f"(d[48]),"+f"(d[49]),"+f"(d[50]),"+f"(d[51]),"+f"(d[52]),"+f"(d[53]),"+f"(d[54]),"+f"(d[55]),"+f"(d[56]),"+f"(d[57]),"+f"(d[58]),"+f"(d[59])
 :"r"(alo),"r"(blo),"n"(AOFF),"n"(AHI),"n"(BOFF),"n"(BHI),"n"(SC)); } };
template<> struct WgSs<128> { template<int AOFF,int AHI,int BOFF,int BHI,int SC> static __device__ __forceinline__ void run(float* d,uint32_t alo,uint32_t blo){
 asm volatile("{.reg .b32 l,m; .reg .b64 da,db; add.u32 l,%64,%66; mov.b64 da,{l,%67}; add.u32 m,%65,%68; mov.b64 db,{m,%69}; wgmma.mma_async.sync.aligned.m64n128k16.f32.bf16.bf16 {%0,%1,%2,%3,%4,%5,%6,%7,%8,%9,%10,%11,%12,%13,%14,%15,%16,%17,%18,%19,%20,%21,%22,%23,%24,%25,%26,%27,%28,%29,%30,%31,%32,%33,%34,%35,%36,%37,%38,%39,%40,%41,%42,%43,%44,%45,%46,%47,%48,%49,%50,%51,%52,%53,%54,%55,%56,%57,%58,%59,%60,%61,%62,%63},da,db,%70,1,1,0,1;}"
 :"+f"(d[0]),"+f"(d[1]),"+f"(d[2]),"+f"(d[3]),"+f"(d[4]),"+f"(d[5]),"+f"(d[6]),"+f"(d[7]),"+f"(d[8]),"+f"(d[9]),"+f"(d[10]),"+f"(d[11]),"+f"(d[12]),"+f"(d[13]),"+f"(d[14]),"+f"(d[15]),"+f"(d[16]),"+f"(d[17]),"+f"(d[18]),"+f"(d[19]),"+f"(d[20]),"+f"(d[21]),"+f"(d[22]),"+f"(d[23]),"+f"(d[24]),"+f"(d[25]),"+f"(d[26]),"+f"(d[27]),"+f"(d[28]),"+f"(d[29]),"+f"(d[30]),"+f"(d[31]),"+f"(d[32]),"+f"(d[33]),"+f"(d[34]),"+f"(d[35]),"+f"(d[36]),"+f"(d[37]),"+f"(d[38]),"+f"(d[39]),"+f"(d[40]),"+f"(d[41]),"+f"(d[42]),"+f"(d[43]),"+f"(d[44]),"+f"(d[45]),"+f"(d[46]),"+f"(d[47]),"+f"(d[48]),"+f"(d[49]),"+f"(d[50]),"+f"(d[51]),"+f"(d[52]),"+f"(d[53]),"+f"(d[54]),"+f"(d[55]),"+f"(d[56]),"+f"(d[57]),"+f"(d[58]),"+f"(d[59]),"+f"(d[60]),"+f"(d[61]),"+f"(d[62]),"+f"(d[63])
 :"r"(alo),"r"(blo),"n"(AOFF),"n"(AHI),"n"(BOFF),"n"(BHI),"n"(SC)); } };

__device__ __forceinline__ void wg_fence() { asm volatile("wgmma.fence.sync.aligned;" ::: "memory"); }
__device__ __forceinline__ void wg_commit() { asm volatile("wgmma.commit_group.sync.aligned;" ::: "memory"); }
template <int N> __device__ __forceinline__ void wg_wait() { asm volatile("wgmma.wait_group.sync.aligned %0;" ::"n"(N) : "memory"); }
template <int N> __device__ __forceinline__ void reg_fence(float* d) {
#pragma unroll
    for (int i = 0; i < N; i++) asm volatile("" : "+f"(d[i])::"memory");
}
__device__ __forceinline__ uint32_t desc_lo(uint32_t addr, uint32_t lbo) { return ((addr & 0x3FFFF) >> 4) | ((lbo >> 4) << 16); }
#define desc_hi(sbo, sw) (((sbo) >> 4) | ((sw) << 30))
__device__ __forceinline__ uint32_t smem_u32(const void* p) { return (uint32_t)__cvta_generic_to_shared(p); }
__device__ __forceinline__ bool elect() {
    uint32_t p;
    asm volatile("{.reg .pred P; elect.sync _|P, 0xffffffff; selp.u32 %0,1,0,P;}" : "=r"(p));
    return p;
}
__device__ __forceinline__ void mbar_init(uint32_t bar, uint32_t cnt) { asm volatile("mbarrier.init.shared::cta.b64 [%0], %1;" ::"r"(bar), "r"(cnt) : "memory"); }
__device__ __forceinline__ void mbar_expect(uint32_t bar, uint32_t bytes) { asm volatile("mbarrier.arrive.expect_tx.shared::cta.b64 _, [%0], %1;" ::"r"(bar), "r"(bytes) : "memory"); }
__device__ __forceinline__ bool mbar_try(uint32_t bar, uint32_t par) {
    uint32_t ok;
    asm volatile("{.reg .pred p; mbarrier.try_wait.parity.shared::cta.b64 p, [%1], %2; selp.u32 %0,1,0,p;}" : "=r"(ok) : "r"(bar), "r"(par) : "memory");
    return ok;
}
constexpr int SPIN_LIMIT = 1 << 18;
__device__ __forceinline__ void mbar_wait(uint32_t bar, uint32_t par) {
    if (mbar_try(bar, par)) return;
    int n = 0;
    while (!mbar_try(bar, par) && ++n < SPIN_LIMIT) {}
}
__device__ __forceinline__ void bulk_g2s(uint32_t dst, const void* src, uint32_t bytes, uint32_t bar) {
    asm volatile("cp.async.bulk.shared::cluster.global.mbarrier::complete_tx::bytes [%0], [%1], %2, [%3];" ::"r"(dst), "l"(src), "r"(bytes), "r"(bar) : "memory");
}
__device__ __forceinline__ void bulk_s2g(void* dst, uint32_t src, uint32_t bytes) {
    asm volatile("cp.async.bulk.global.shared::cta.bulk_group [%0], [%1], %2;" ::"l"(dst), "r"(src), "r"(bytes) : "memory");
}
__device__ __forceinline__ void bulk_prefetch(const void* src, uint32_t bytes) {
    asm volatile("cp.async.bulk.prefetch.L2.global [%0], %1;" ::"l"(src), "r"(bytes) : "memory");
}
__device__ __forceinline__ void tma2d(uint32_t dst, const CUtensorMap* m, int c0, int c1, uint32_t bar) {
    asm volatile("cp.async.bulk.tensor.2d.shared::cluster.global.mbarrier::complete_tx::bytes [%0], [%1, {%3, %4}], [%2];" ::"r"(dst), "l"(m), "r"(bar), "r"(c0), "r"(c1) : "memory");
}
__device__ __forceinline__ void tma2d_mc(uint32_t dst, const CUtensorMap* m, int c0, int c1, uint32_t bar) {
    asm volatile("cp.async.bulk.tensor.2d.shared::cluster.global.mbarrier::complete_tx::bytes.multicast::cluster [%0], [%1, {%3, %4}], [%2], %5;" ::"r"(dst), "l"(m), "r"(bar), "r"(c0), "r"(c1), "h"((uint16_t)3) : "memory");
}
__device__ __forceinline__ uint32_t mapa(uint32_t a, uint32_t rank) { uint32_t r; asm("mapa.shared::cluster.u32 %0, %1, %2;" : "=r"(r) : "r"(a), "r"(rank)); return r; }
__device__ __forceinline__ void mbar_arrive_cl(uint32_t bar) { asm volatile("mbarrier.arrive.shared::cluster.b64 _, [%0];" ::"r"(bar) : "memory"); }
__device__ __forceinline__ void prefetch_map(const CUtensorMap* m) { asm volatile("prefetch.tensormap [%0];" ::"l"(m) : "memory"); }
__device__ __forceinline__ void cpasync16(uint32_t dst, const void* src, uint32_t srcsz) {
    asm volatile("cp.async.cg.shared.global [%0], [%1], 16, %2;" ::"r"(dst), "l"(src), "r"(srcsz) : "memory");
}
__device__ __forceinline__ void bar_sync(int id, int n) { asm volatile("bar.sync %0, %1;" ::"r"(id), "r"(n) : "memory"); }
__device__ __forceinline__ void bar_arrive(int id, int n) { asm volatile("bar.arrive %0, %1;" ::"r"(id), "r"(n) : "memory"); }
__device__ __forceinline__ void fence_async_smem() { asm volatile("fence.proxy.async.shared::cta;" ::: "memory"); }
__device__ __forceinline__ void fence_async_global() { asm volatile("fence.proxy.async.global;" ::: "memory"); }
__device__ __forceinline__ void flag_release(int f) { asm volatile("red.release.gpu.global.add.u32 [%0], 1;" ::"l"(&g_flags[f * 32]) : "memory"); }
__device__ __forceinline__ void flag_wait(int f, unsigned target) {
    const unsigned* p = &g_flags[f * 32];
    unsigned v; int n = 0;
    do {
        asm volatile("ld.relaxed.gpu.global.u32 %0, [%1];" : "=r"(v) : "l"(p) : "memory");
    } while ((int)(v - target) < 0 && ++n < SPIN_LIMIT);
    asm volatile("fence.acquire.gpu;" ::: "memory");
}
__device__ __forceinline__ unsigned ld_flag(const unsigned* p) { unsigned v; asm volatile("ld.relaxed.gpu.global.u32 %0, [%1];" : "=r"(v) : "l"(p) : "memory"); return v; }
__device__ __forceinline__ void spin(unsigned n) { unsigned t0, t1; asm volatile("mov.u32 %0, %%clock;" : "=r"(t0)); do { asm volatile("mov.u32 %0, %%clock;" : "=r"(t1)); } while (t1 - t0 < n); }
__device__ __forceinline__ void flag_wait2(int f0, int f1, unsigned target) {
    const unsigned *p = &g_flags[f0 * 32], *q = &g_flags[f1 * 32];
    unsigned v, w; int n = 0;
    do { v = ld_flag(p); w = ld_flag(q); } while ((int)((v - target) | (w - target)) < 0 && ++n < SPIN_LIMIT);
    asm volatile("fence.acquire.gpu;" ::: "memory");
}
__device__ __forceinline__ uint32_t lds32(uint32_t a) { uint32_t v; asm volatile("ld.shared.u32 %0, [%1];" : "=r"(v) : "r"(a)); return v; }
__device__ __forceinline__ float2 lds64f(uint32_t a) { float2 v; asm volatile("ld.shared.v2.f32 {%0,%1}, [%2];" : "=f"(v.x), "=f"(v.y) : "r"(a)); return v; }
__device__ __forceinline__ uint2 lds64(uint32_t a) { uint2 v; asm volatile("ld.shared.v2.u32 {%0,%1}, [%2];" : "=r"(v.x), "=r"(v.y) : "r"(a)); return v; }
__device__ __forceinline__ void sts64f(uint32_t a, float2 v) { asm volatile("st.shared.v2.f32 [%0], {%1,%2};" ::"r"(a), "f"(v.x), "f"(v.y) : "memory"); }
__device__ __forceinline__ void sts32(uint32_t a, uint32_t v) { asm volatile("st.shared.u32 [%0], %1;" ::"r"(a), "r"(v) : "memory"); }
__device__ __forceinline__ void sts64(uint32_t a, uint32_t x, uint32_t y) { asm volatile("st.shared.v2.u32 [%0], {%1,%2};" ::"r"(a), "r"(x), "r"(y) : "memory"); }
__device__ __forceinline__ void sts16(uint32_t a, uint16_t v) { asm volatile("st.shared.u16 [%0], %1;" ::"r"(a), "h"(v) : "memory"); }
__device__ __forceinline__ uint4 lds128(uint32_t a) { uint4 v; asm volatile("ld.shared.v4.u32 {%0,%1,%2,%3}, [%4];" : "=r"(v.x), "=r"(v.y), "=r"(v.z), "=r"(v.w) : "r"(a)); return v; }
__device__ __forceinline__ void sts128(uint32_t a, uint4 v) { asm volatile("st.shared.v4.u32 [%0], {%1,%2,%3,%4};" ::"r"(a), "r"(v.x), "r"(v.y), "r"(v.z), "r"(v.w) : "memory"); }
__device__ __forceinline__ void sts128f(uint32_t a, float x, float y, float z, float w) { asm volatile("st.shared.v4.f32 [%0], {%1,%2,%3,%4};" ::"r"(a), "f"(x), "f"(y), "f"(z), "f"(w) : "memory"); }
__device__ __forceinline__ uint32_t prmt(uint32_t a, uint32_t b, uint32_t s) { uint32_t r; asm("prmt.b32 %0,%1,%2,%3;" : "=r"(r) : "r"(a), "r"(b), "r"(s)); return r; }
__device__ __forceinline__ uint32_t pack2(float lo, float hi) { uint32_t r; asm("cvt.rn.bf16x2.f32 %0, %1, %2;" : "=r"(r) : "f"(hi), "f"(lo)); return r; }
__device__ __forceinline__ float blo(uint32_t v) { return __uint_as_float(v << 16); }
__device__ __forceinline__ float bhi(uint32_t v) { return __uint_as_float(v & 0xffff0000u); }
__device__ __forceinline__ uint32_t bmul2(uint32_t a, uint32_t b) { uint32_t r; asm("mul.rn.bf16x2 %0,%1,%2;" : "=r"(r) : "r"(a), "r"(b)); return r; }
__device__ __forceinline__ uint32_t badd2(uint32_t a, uint32_t b) { uint32_t r; asm("add.rn.bf16x2 %0,%1,%2;" : "=r"(r) : "r"(a), "r"(b)); return r; }
__device__ __forceinline__ float rbf(float x) { return __bfloat162float(__float2bfloat16_rn(x)); }
__device__ __forceinline__ uint32_t ldcg32(const void* p) { uint32_t v; asm volatile("ld.global.cg.u32 %0, [%1];" : "=r"(v) : "l"(p) : "memory"); return v; }
__device__ __forceinline__ uint4 ldcg128(const void* p) { uint4 v; asm volatile("ld.global.cg.v4.u32 {%0,%1,%2,%3}, [%4];" : "=r"(v.x), "=r"(v.y), "=r"(v.z), "=r"(v.w) : "l"(p) : "memory"); return v; }
__device__ __forceinline__ void stg32_if(void* p, uint32_t v, int on) { asm volatile("{.reg .pred q; setp.ne.b32 q, %2, 0; @q st.global.u32 [%0], %1;}" ::"l"(p), "r"(v), "r"(on) : "memory"); }
__device__ __forceinline__ uint2 ldcg64(const void* p) { uint2 v; asm volatile("ld.global.cg.v2.u32 {%0,%1}, [%2];" : "=r"(v.x), "=r"(v.y) : "l"(p) : "memory"); return v; }
__device__ __forceinline__ float gelu_h(float h) {
    float u = h * fmaf(h * h, 8.0f * 0.044715f * 0.7978845608028654f, 2.0f * 0.7978845608028654f);
    float th;
    asm("tanh.approx.f32 %0, %1;" : "=f"(th) : "f"(u));
    return fmaf(h, th, h);
}
__device__ __forceinline__ float gelu(float x) { return gelu_h(0.5f * x); }
__device__ __forceinline__ float half_rstd(float sum, float sq) {
    float mean = sum * (1.0f / D_), inv;
    asm("rsqrt.approx.ftz.f32 %0, %1;" : "=f"(inv) : "f"(fmaxf(fmaf(-mean, mean, fmaf(sq, 1.0f / D_, 1e-5f)), 1e-5f)));
    return 0.5f * inv;
}
__device__ __forceinline__ uint32_t bsub2(uint32_t a, uint32_t b) { uint32_t r; asm("sub.rn.bf16x2 %0,%1,%2;" : "=r"(r) : "r"(a), "r"(b)); return r; }
__device__ __forceinline__ uint32_t bfma2(uint32_t a, uint32_t b, uint32_t c) { uint32_t r; asm("fma.rn.bf16x2 %0,%1,%2,%3;" : "=r"(r) : "r"(a), "r"(b), "r"(c)); return r; }
__device__ __forceinline__ uint32_t gelu2_h(uint32_t h) {
    uint32_t u = bmul2(h, bfma2(bmul2(h, h), 0x3e923e92u, 0x3fcc3fccu)), th;
    asm("tanh.approx.bf16x2 %0, %1;" : "=r"(th) : "r"(u));
    return bfma2(h, th, h);
}
__device__ __forceinline__ uint3 row_stats(const uint32_t* v, int lane) {
    float s = 0.f, q = 0.f, s_ = 0.f, q_ = 0.f;
#pragma unroll
    for (int i = 0; i < 10; i++) { float a = blo(v[i]), b = bhi(v[i]); s += a; s_ += b; q = fmaf(a, a, q); q_ = fmaf(b, b, q_); }
    s += s_; q += q_;
    {
        float t = __shfl_xor_sync(0xffffffffu, (lane & 16) ? s : q, 16);
        t += (lane & 16) ? q : s;
#pragma unroll
        for (int m = 8; m; m >>= 1) t += __shfl_xor_sync(0xffffffffu, t, m);
        float o = __shfl_xor_sync(0xffffffffu, t, 16);
        s = (lane & 16) ? o : t; q = (lane & 16) ? t : o;
    }
    float mean = s * (1.0f / D_), inv;
    asm("rsqrt.approx.ftz.f32 %0, %1;" : "=f"(inv) : "f"(fmaxf(fmaf(-mean, mean, fmaf(q, 1.0f / D_, 1e-5f)), 1e-5f)));
    uint3 r;
    r.x = pack2(mean, mean);
    r.y = pack2(inv, inv);
    inv -= blo(r.y);
    r.z = pack2(inv, inv);
    return r;
}
__device__ __forceinline__ uint32_t ln_apply(uint32_t x, uint32_t m, uint32_t hi, uint32_t lo) {
    uint32_t xc = bsub2(x, m);
    return bmul2(xc, hi);
}

struct AFrag { uint32_t m, a, b, c, d; };
__device__ __forceinline__ AFrag ldA(uint32_t a) { AFrag f; f.m = lds32(a - 16); f.a = lds32(a); f.b = lds32(a + 16); f.c = lds32(a + 32); f.d = lds32(a + 48); return f; }
template <int N, int M> __device__ __forceinline__ void conv_pair(float* d, const AFrag& f, uint32_t descU) {
    WgRs<N>::template run<8 * M, desc_hi(128, 0), M ? 1 : 0>(d, f.a, f.b, f.m, f.a, descU);
    WgRs<N>::template run<8 * M + 1, desc_hi(128, 0), 1>(d, f.c, f.d, f.b, f.c, descU);
}
template <int Q> __device__ __forceinline__ void conv_put(float* d, uint32_t r0) {
    sts64(r0 + Q * 32, pack2(d[4 * Q + 1], d[4 * Q + 3]), pack2(d[4 * Q], d[4 * Q + 2]));
}
template <int M> __device__ __forceinline__ void conv_two(float* d, AFrag f0, AFrag f1, uint32_t kaddr, uint32_t descU, uint32_t r0, bool handoff) {
    constexpr int N = M < 14 ? 128 - 8 * M : 32;
    wg_fence();
    conv_pair<N, M>(d, f0, descU);
    wg_commit();
    if constexpr (M > 0) f1 = ldA(kaddr + 256 * (M + 1));
    wg_fence();
    conv_pair<N, M + 1>(d, f1, descU);
    wg_commit();
    if (STAG && M == STAG && handoff) bar_arrive(12, 256);
    if constexpr (M < 14) {
        if constexpr (M > 0) { conv_put<17 - M>(d, r0); conv_put<16 - M>(d, r0); }
        wg_wait<1>();
        f0 = ldA(kaddr + 256 * (M + 2));
        if constexpr (M < 12) wg_wait<0>();
        conv_two<M + 2>(d, f0, f1, kaddr, descU, r0, handoff);
    } else {
        wg_wait<0>();
        conv_put<3>(d, r0); conv_put<2>(d, r0); conv_put<1>(d, r0); conv_put<0>(d, r0);
    }
}
template <int N, bool ASWZ, int SC0>
__device__ __forceinline__ void gemm_issue(float* acc, uint32_t bars, int sa, int pa, int sw, int pw, uint32_t da0, uint32_t db0) {
    mbar_wait(bars + (BAR_FB + sw) * 8, pw);
    mbar_wait(bars + (BAR_FA + sa) * 8, pa);
    const uint32_t da = da0 + sa * (SLOT >> 4), db = db0 + sw * (SLOT >> 4);
    constexpr int AK = ASWZ ? 2 : 256, AH = ASWZ ? desc_hi(1024, 1) : desc_hi(128, 0), BH = desc_hi(1024, 1);
    wg_fence();
    WgSs<N>::template run<0, AH, 0, BH, SC0>(acc, da, db);
    WgSs<N>::template run<AK, AH, 128, BH, 1>(acc, da, db);
    WgSs<N>::template run<2 * AK, AH, 256, BH, 1>(acc, da, db);
    WgSs<N>::template run<3 * AK, AH, 384, BH, 1>(acc, da, db);
    wg_commit();
}
template <int N, bool ASWZ, int NKB, int RELB, bool ZERO>
__device__ __forceinline__ void gemm_loop(float* acc, uint32_t sb, int half, int ia0, int ib0, int rela, int wait_bar, int order_bar, int tsid) {
    int sa = ia0 % NA, pa = (ia0 / NA) & 1, sw = ib0 % NB, pw = (ib0 / NB) & 1;
    const uint32_t bars = sb + SM_BAR;
    const int t = threadIdx.x & 127;
    uint32_t ebar = mapa(bars + (t < 2 ? BAR_EB : BAR_EA) * 8, (t < 2 && lds32(sb + SM_GV + 516)) ? t : blockIdx.x & 1);
    const int nrel = t < 2 ? RELB : t == 2 ? rela : 0;
    const uint32_t da0 = ASWZ ? desc_lo(sb + SM_RA + half * 8192, 16) : desc_lo(sb + SM_RA + half * 1024, 2048), db0 = desc_lo(sb + SM_RB, 8192);
    asm volatile("" : "+r"(ebar));
    if (wait_bar) bar_sync(wait_bar, 512);
    gemm_issue<N, ASWZ, ZERO ? 0 : 1>(acc, bars, sa, pa, sw, pw, da0, db0);
    if ((threadIdx.x & 255) == 0) TS(tsid);
#pragma unroll 1
    for (int kb = 1; kb < NKB; kb++) {
        const int prev = t < 2 ? sw : sa;
        if (++sa == NA) { sa = 0; pa ^= 1; }
        if (++sw == NB) { sw = 0; pw ^= 1; }
        gemm_issue<N, ASWZ, 1>(acc, bars, sa, pa, sw, pw, da0, db0);
        if (order_bar && kb == NKB - 1) bar_arrive(order_bar, 512);
        wg_wait<1>();
        if (kb <= nrel) mbar_arrive_cl(ebar + prev * 8);
    }
    wg_wait<0>();
    if (nrel == NKB) mbar_arrive_cl(ebar + (t < 2 ? sw : sa) * 8);
    reg_fence<N / 2>(acc);
    if ((threadIdx.x & 255) == 0) TS(tsid + 1);
}

template <int PART>
__device__ __forceinline__ void gemm3(uint32_t sb, int rb, int j, int half, int row, int c, unsigned ones) {
    constexpr int N = 64 + (PART ? RB3 : RA3), NQ = N / 8;
    constexpr int HO = PART ? HO_B : HO_A;
    float acc[N / 2];
    float2 cr[NQ];
    if (PART) {
        gemm_loop<N, false, 1, 1, true>(acc, sb, half, 20, 20, 0, 0, 0, 50);
        bar_arrive(9, 512);
    }
    mbar_wait(sb + SM_BAR + BAR_CS * 8, 0);
    const uint32_t csa = sb + SM_CS + PART * (256 + 4 * RA3) + 8 * c;
#pragma unroll
    for (int q = 0; q < NQ; q++) if (q < CSP) cr[q] = lds64f(csa + 32 * q);
    uint4 rp;
    if (PART) {
        mbar_wait(sb + SM_BAR + BAR_G * 8, 0);
        const float2* sp = &g_st[(rb * 8 + 2 * c) * 128 + row];
        const uint2 s0 = ldcg64(sp), s1 = ldcg64(sp + 128), s2 = ldcg64(sp + 8), s3 = ldcg64(sp + 136);
        float a0 = __uint_as_float(s0.x) + __uint_as_float(s1.x), b0 = __uint_as_float(s0.y) + __uint_as_float(s1.y);
        float a1 = __uint_as_float(s2.x) + __uint_as_float(s3.x), b1 = __uint_as_float(s2.y) + __uint_as_float(s3.y);
#pragma unroll
        for (int m = 1; m <= 2; m <<= 1) {
            a0 += __shfl_xor_sync(0xffffffffu, a0, m); b0 += __shfl_xor_sync(0xffffffffu, b0, m);
            a1 += __shfl_xor_sync(0xffffffffu, a1, m); b1 += __shfl_xor_sync(0xffffffffu, b1, m);
        }
        const float inv0 = half_rstd(a0, b0), inv1 = half_rstd(a1, b1);
        rp = make_uint4(PGELU ? pack2(inv0, inv0) : __float_as_uint(inv0), __float_as_uint(a0 * (-1.0f / D_)),
                        PGELU ? pack2(inv1, inv1) : __float_as_uint(inv1), __float_as_uint(a1 * (-1.0f / D_)));
        if (c == 0) sts128(sb + SM_RP + ((threadIdx.x & 255) >> 2) * 16, rp);
        bar_arrive(13, 512);
    }
    gemm_loop<N, false, 10 - PART, 10 - PART, !PART>(acc, sb, half, 20 + (10 - NA) * PART, 21 + 10 * PART, PART ? 9 : 10 - NA, 9 + PART, HO < 0 ? 10 + PART : 0, 46 + 2 * PART);
    if (!PART) {
        bar_sync(13, 512);
        rp = lds128(sb + SM_RP + ((threadIdx.x & 255) >> 2) * 16);
    }
    const float nb0 = __uint_as_float(rp.y), nb1 = __uint_as_float(rp.w);
    const uint32_t own = sb + SM_RA + ((39 - NA) % NA) * SLOT + row * 16 + c * 4;
    if (PART && OWNG) mbar_wait(sb + SM_BAR + (BAR_FA + (39 - NA) % NA) * 8, ((39 - NA) / NA) & 1);
    uint32_t* dst = reinterpret_cast<uint32_t*>(g_g) + (rb * 216 + HB0 / 8 * PART + 8 * j) * 512 + row * 4 + c;
    auto act = [&](int q, int r) {
        const float nb = r ? nb1 : nb0;
        const uint32_t inv = r ? rp.z : rp.x;
        const float t0 = fmaf(nb, cr[q].x, acc[4 * q + 2 * r]), t1 = fmaf(nb, cr[q].y, acc[4 * q + 2 * r + 1]);
        return gelu2_h(bmul2(pack2(t0, t1), inv));
    };
    uint32_t* dst1 = dst + (56 - (16 - NQ) * j) * 512;
#pragma unroll
    for (int k = 0; k < NQ; k += CH3) {
        if (k == HO) bar_arrive(10 + PART, 512);
        CHUNK(k) {
#pragma unroll
            for (int q = k; q < k + CH3 && q < NQ; q++) {
                if (q + CSP < NQ) cr[q + CSP] = lds64f(csa + 32 * (q + CSP));
                const uint32_t u = act(q, 0), v = act(q, 1);
                (q < 8 ? dst : dst1)[q * 512] = u;
                (q < 8 ? dst : dst1)[q * 512 + 32] = v;
                if (PART && OWNG && q < 8) { sts32(own + q * 2048, u); sts32(own + q * 2048 + 128, v); }
            }
            if (PART && OWNG && k < 8 && k + CH3 >= 8) fence_async_smem();
        }
    }
    bar_arrive(1 + PART, 288);
    if (HO >= NQ) bar_arrive(10 + PART, 512);
}

template <int NS, int BASE, int BF, int BE> struct Ring {
    uint32_t sb, st, ph;
    __device__ __forceinline__ uint32_t acquire(uint32_t bytes) {
        mbar_wait(sb + SM_BAR + BE * 8 + st * 8, ph);
        uint32_t fb = sb + SM_BAR + BF * 8 + st * 8;
        mbar_expect(fb, bytes);
        return fb;
    }
    __device__ __forceinline__ uint32_t slot() { return sb + BASE + st * SLOT; }
    __device__ __forceinline__ void next() { if (++st == NS) { st = 0; ph ^= 1; } }
    __device__ __forceinline__ void run2d(const CUtensorMap* m, int c1) {
#pragma unroll 1
        for (int c0 = 64; c0 < D_; c0 += 64) {
            uint32_t fb = acquire(SLOT);
            tma2d(slot(), m, c0, c1, fb);
            next();
        }
    }
    static __device__ __forceinline__ int korder(int i, int own) { return i == 0 ? own : i > own ? i : i - 1; }
    __device__ __forceinline__ void runw(bool paired, int rk, const CUtensorMap* ma, const CUtensorMap* mb, int ca, int cb, int i0, int i1, int own, uint32_t bytes, int gate_at, uint32_t gate) {
        if (paired) {
            const CUtensorMap* m = rk ? mb : ma;
            const int c0 = rk ? cb : ca;
#pragma unroll 1
            for (int i = i0; i < i1; i++) {
                const int c1 = korder(i, own) * 64;
                if (i == gate_at) mbar_wait(gate, 0);
                uint32_t fb = acquire(bytes);
                tma2d_mc(slot() + 8192 * rk, m, c0, c1, fb);
                next();
            }
        } else {
#pragma unroll 1
            for (int i = i0; i < i1; i++) {
                const int c1 = korder(i, own) * 64;
                uint32_t fb = acquire(bytes);
                tma2d(slot(), ma, ca, c1, fb);
                tma2d(slot() + 8192, mb, cb, c1, fb);
                next();
            }
        }
    }
    __device__ __forceinline__ void run1d(const char* src, int i0, int i1, int own) {
#pragma unroll 1
        for (int i = i0; i < i1; i++) {
            const char* s = src + korder(i, own) * SLOT;
            uint32_t fb = acquire(SLOT);
            bulk_g2s(slot(), s, SLOT, fb);
            next();
        }
    }
};

__global__ void __cluster_dims__(2, 1, 1) __launch_bounds__(NTHREADS, 1) fused_kernel(const Params p, const __grid_constant__ Maps maps) {
    extern __shared__ __align__(1024) unsigned char smem_raw[];
    const uint32_t sb = (smem_u32(smem_raw) + 1023u) & ~1023u;
#pragma unroll
    for (int i = 0; i < SEED; i++) asm volatile("{.reg .b32 t; mov.u32 t, %laneid;}");
    const uint32_t bars = sb + SM_BAR;
    const int tid = threadIdx.x, lane = tid & 31;
    unsigned smid;
    asm volatile("mov.u32 %0, %%smid;" : "=r"(smid));
    const bool spare = (smid >> 2) == 30;
    const int cta = smid < 120 ? smid : smid - 4;
    const int pg = cta >> 4, pi = cta & 15;
    const int hb = tid >= 320;
    if (!spare) {
        const unsigned t = tid - 320 * hb, r32 = t / 10u, cc = t - r32 * 10u, row = r32 + 64 * hb;
        const unsigned go = (unsigned)(pi * 128 * 1280 + pg * 160) + row * 1280u + cc * 16u;
        const uint32_t so = sb + (row >> 4) * 32u + row * 160u + cc * 16u;
        const char* kb = (const char*)p.k + go;
        const char* vb = (const char*)p.v + go;
        if (hb) {
            if (tid >= 640 - NBARS) {
                const int i = 639 - tid;
                mbar_init(bars + i * 8, (i >= BAR_EB && i < BAR_K) ? 4 : ((i >= BAR_EA && i < BAR_EB) || i == BAR_XY) ? 2 : 1);
                asm volatile("fence.mbarrier_init.release.cluster;" ::: "memory");
            }
            bar_arrive(14, 640);
            if (B_DELAY) spin(B_DELAY);
        }
        cpasync16(so + SM_PK + 2592, kb, 16);
        cpasync16(so + SM_PV, vb, 16);
        cpasync16(so + SM_PK + 3 * 2592, kb + 32 * 1280, 16);
        cpasync16(so + SM_PV + 2 * 2592, vb + 32 * 1280, 16);
        if (tid < 30) cpasync16(so + SM_PK + 13 * 160, pi ? kb - 3 * 1280 : kb, pi ? 16 : 0);
        asm volatile("cp.async.commit_group;" ::: "memory");
    }
    const int warp = __shfl_sync(0xffffffffu, tid >> 5, 0);
    const int wg = warp >> 2, wq = warp & 3;
    unsigned ep0 = 0;
    if (wg == 4 || spare) ep0 = *(volatile unsigned*)&g_epoch[smid];
#define ep1 (ep0 + 1)

    if (spare) {
        const int sp = smid & 3;
        if (tid == 32) { sts32(sb + SM_GV + 512, smid); asm volatile("fence.release.sync_restrict::shared::cta.cluster;" ::: "memory"); }
        asm volatile("barrier.cluster.arrive.relaxed.aligned;" ::: "memory");
        asm volatile("barrier.cluster.wait.aligned;" ::: "memory");
        if (tid == 0) {
            for (int i = 0; i < 4; i++) mbar_init(bars + i * 8, 1);
            asm volatile("fence.mbarrier_init.release.cluster;" ::: "memory");
        }
        if (warp == 0) { if (lane < 8) flag_wait(FL_P + lane, ep1 * 16); __syncwarp(); }
        __syncthreads();
        const int cq = tid % 54, rg = tid / 54;
        float a[8];
#pragma unroll
        for (int i = 0; i < 8; i++) a[i] = 0.f;
#pragma unroll 1
        for (int it = -4; it < 10; it++) {
            const uint32_t st = sb + (it & 3) * 55296, fb = bars + (it & 3) * 8;
            if (it >= 0) {
                mbar_wait(fb, (it >> 2) & 1);
                if (tid < 432) {
#pragma unroll
                    for (int i = 0; i < 8; i++) {
                        uint4 w = lds128(st + (cq >= 27 ? 27648 - 432 : 0) + (rg * 8 + i) * 432 + cq * 16);
                        a[0] += blo(w.x); a[1] += bhi(w.x); a[2] += blo(w.y); a[3] += bhi(w.y);
                        a[4] += blo(w.z); a[5] += bhi(w.z); a[6] += blo(w.w); a[7] += bhi(w.w);
                    }
                }
                __syncthreads();
            }
            if (it < 6 && warp == 19 && elect()) {
                mbar_expect(fb, 55296);
                tma2d(st, &maps.w3s, sp * 432, (it + 4) * 64, fb);
                tma2d(st + 27648, &maps.w3s, sp * 432 + 216, (it + 4) * 64, fb);
            }
        }
        if (tid < 432) {
            sts128f(sb + rg * 1728 + cq * 32, a[0], a[1], a[2], a[3]);
            sts128f(sb + rg * 1728 + cq * 32 + 16, a[4], a[5], a[6], a[7]);
        }
        __syncthreads();
        if (tid < 432) {
            float s = 0.f;
#pragma unroll
            for (int i = 0; i < 8; i++) s += __uint_as_float(lds32(sb + i * 1728 + tid * 4));
            g_cs[sp * 432 + tid] = s;
        }
        __syncthreads();
        if (tid == 0) { flag_release(FL_CS); g_epoch[smid] = ep1; TS(0); }
        if (warp == 0) TSFLUSH();
        return;
    }

    int gpc, idx;
    if (smid < 64) { gpc = (smid & 15) >> 1; idx = (smid >> 4) * 2 + (smid & 1); }
    else if (smid < 120) { int t = smid - 64; gpc = 1 + (t % 14) / 2; idx = 8 + (t / 14) * 2 + (smid & 1); }
    else { gpc = 0; idx = 8 + (smid - 124); }
    const int rb = 2 * gpc + (idx & 1), j = idx >> 1;
    const int g = lane >> 2, c = lane & 3;
    const int cm = 160 * (j >> 1) + 64 * (j & 1) + ((j & 2) ? 32 : 0), cr = 160 * (j >> 1) + 16 * (j & 1) + ((j & 2) ? 0 : 128);

    {
        if (warp == 5) TSW(61);
        const int w10 = warp - 10 * hb, h = w10 >= 5;
        const int pr = (w10 - 5 * h) * 8 + (lane >> 2), blk = 4 * hb + (lane & 3);
        const int ch = 80 * pg + 2 * pr;
        const uint4 sw = __ldg(reinterpret_cast<const uint4*>(p.shift + ch * 4));
        uint32_t dv = 0;
        if (warp == 9 && lane < 5) dv = __bfloat16_as_ushort(p.ssmD[cta * 5 + lane]);
        if (tid == 512) { sts32(sb + SM_GV + 512, smid); asm volatile("fence.release.sync_restrict::shared::cta.cluster;" ::: "memory"); }
        asm volatile("barrier.cluster.arrive.relaxed.aligned;" ::: "memory");
        if (warp == 11 && lane < 13) prefetch_map(&maps.hn + lane);
        if (wg < 4) {
            const int t = tid & 127, cc = (wg == 3 && t >= 64) ? 4 : wg;
            if (t < 64 || wg == 3) sts128(sb + sm_u(cc) + ((t >> 5) & 1) * U_PLANE + 2048 + lane * 16, make_uint4(0, 0, 0, 0));
            if ((t & 63) < 4 && (t < 64 || wg == 3)) sts128(sb + sm_k(cc) + ((t >> 1) & 1) * 4160 + (t & 1) * 16, make_uint4(0, 0, 0, 0));
        }
        if (warp == 9 && lane < 5) sts32(sb + SM_GV + 520 + lane * 4, dv << 16);
        asm volatile("cp.async.wait_group 0;" ::: "memory");
        if (!hb) bar_arrive(12, 640);
        bar_sync(hb ? 12 : 14, 640);
        if (warp == 9) {
            if (SSM_DELAY) spin(SSM_DELAY);
            if (elect()) {
#pragma unroll
                for (int i = 0; i < SSM_N; i++) {
                    mbar_expect(bars + (BAR_K + i) * 8, 4096);
                    bulk_g2s(sb + sm_k(i) + 32, p.ssmk + (size_t)(cta * 5 + i) * S_, 4096, bars + (BAR_K + i) * 8);
                }
            }
        }
        const uint32_t w0 = prmt(sw.x, sw.z, 0x5410), w1 = prmt(sw.x, sw.z, 0x7632), w2 = prmt(sw.y, sw.w, 0x5410), w3 = prmt(sw.y, sw.w, 0x7632);
        const uint32_t ka = sb + SM_PK + 2592 + blk * 2592 + h * 1280 + pr * 4;
        const uint32_t va = sb + SM_PV + blk * 2592 + h * 1280 + pr * 4;
        uint32_t kk[11], kv[8];
#pragma unroll
        for (int i = 0; i < 11; i++) kk[i] = lds32(ka + (i - 3) * 160 - ((i < 3 && h == 0) ? 32 : 0));
#pragma unroll
        for (int i = 0; i < 8; i++) {
            uint32_t t = badd2(badd2(badd2(bmul2(kk[i], w3), bmul2(kk[i + 1], w2)), bmul2(kk[i + 2], w1)), bmul2(kk[i + 3], w0));
            kv[i] = bmul2(t, lds32(va + i * 160));
        }
        uint4 o0, o1;
        o0.x = prmt(kv[1], kv[0], 0x5410); o0.y = prmt(kv[3], kv[2], 0x5410); o0.z = prmt(kv[5], kv[4], 0x5410); o0.w = prmt(kv[7], kv[6], 0x5410);
        o1.x = prmt(kv[1], kv[0], 0x7632); o1.y = prmt(kv[3], kv[2], 0x7632); o1.z = prmt(kv[5], kv[4], 0x7632); o1.w = prmt(kv[7], kv[6], 0x7632);
        uint4* dst = reinterpret_cast<uint4*>(g_kvT) + ch * 256 + h * 128 + (127 - (8 * pi + blk));
        dst[0] = o0;
        dst[256] = o1;
    }

    const int rho = 8 * rb + j;

    if (wg == 4) {
        asm volatile("setmaxnreg.dec.sync.aligned.u32 32;");
        if (wq == 0) {
            bar_sync(13, 640);
            TSW(39);
            if (lane == 0) flag_release(FL_P + pg);
            __syncwarp();
            TSW(2);
            if (lane < 5) mbar_expect(bars + (BAR_U + lane) * 8, 4096);
            flag_wait(FL_P + pg, ep1 * 16);
            fence_async_global();
            TSW(3);
            if (elect()) {
#pragma unroll
                for (int i = 0; i < 5; i++) {
                    const char* us = (const char*)g_kvT + (size_t)(cta * 5 + i) * 4096;
                    bulk_g2s(sb + sm_u(i), us, 2048, bars + (BAR_U + i) * 8);
                    bulk_g2s(sb + sm_u(i) + U_PLANE, us + 2048, 2048, bars + (BAR_U + i) * 8);
                }
            }
            __syncwarp();
            if (elect()) {
#pragma unroll
                for (int i = SSM_N; i < 5; i++) {
                    mbar_expect(bars + (BAR_K + i) * 8, 4096);
                    bulk_g2s(sb + sm_k(i) + 32, p.ssmk + (size_t)(cta * 5 + i) * S_, 4096, bars + (BAR_K + i) * 8);
                }
                if (cta < 120) {
                    mbar_expect(bars + BAR_WM * 8, 40960);
#pragma unroll
                    for (int i = 0; i < 5; i++) tma2d(sb + SM_WM + i * 8192, &maps.wm, cta * 32, i * 128, bars + BAR_WM * 8);
                }
                bulk_prefetch((const char*)p.q + cta * 20480, 20480);
                bulk_prefetch((const char*)p.w1 + cta * 6400, 6400);
                bulk_prefetch((const char*)p.w2 + cta * 6400, 6400);
            }
            __syncwarp();
        } else {
            bar_arrive(13, 640);
        }
        asm volatile("barrier.cluster.wait.aligned;" ::: "memory");
        uint32_t peer;
        asm volatile("ld.shared::cluster.u32 %0, [%1];" : "=r"(peer) : "r"(mapa(sb + SM_GV + 512, (blockIdx.x & 1) ^ 1)) : "memory");
        const bool paired = peer == (smid ^ 1);
        if (tid == 639) sts32(sb + SM_GV + 516, paired);
        if (cta < 120) {
            float d[4];
            if (tid < 592) {
                const int t = tid - 512;
                mbar_wait(bars + BAR_U * 8, 0);
                uint4 cv = __ldg(reinterpret_cast<const uint4*>(p.c) + t);
                auto silu2 = [](uint32_t v) { float a = blo(v), b = bhi(v); return pack2(__fdividef(a, 1.0f + __expf(-a)), __fdividef(b, 1.0f + __expf(-b))); };
                sts128(sb + SM_Y + (t % 40) * 32 + (t / 40) * 16, make_uint4(silu2(cv.x), silu2(cv.y), silu2(cv.z), silu2(cv.w)));
                fence_async_smem();
            }
            bar_sync(5, 128);
            mbar_wait(bars + BAR_WM * 8, 0);
            if (wq == 3) TSW(56);
            const uint32_t da = desc_lo(sb + SM_WM, 20480), db = desc_lo(sb + SM_Y, 32);
            wg_fence();
#pragma unroll
            for (int k = 0; k < 20; k++)
                asm volatile("{.reg .pred p; .reg .b32 l,m; .reg .b64 da,db; setp.ne.b32 p,%10,0; add.u32 l,%4,%6; mov.b64 da,{l,%8}; add.u32 m,%5,%7; mov.b64 db,{m,%9};"
                             " wgmma.mma_async.sync.aligned.m64n8k16.f32.bf16.bf16 {%0,%1,%2,%3},da,db,p,1,1,1,0;}"
                             : "+f"(d[0]), "+f"(d[1]), "+f"(d[2]), "+f"(d[3])
                             : "r"(da), "r"(db), "r"(64 * k), "r"(4 * k), "n"(desc_hi(512, 2u)), "n"(desc_hi(128, 0)), "r"(k));
            wg_commit();
            wg_wait<0>();
            reg_fence<4>(d);
            if (c == 0) {
                sts32(sb + SM_GV + (16 * wq + g) * 4, __float_as_uint(wq < 2 ? d[0] : d[1]));
                sts32(sb + SM_GV + (16 * wq + g + 8) * 4, __float_as_uint(wq < 2 ? d[2] : d[3]));
            }
            bar_sync(5, 128);
            if (wq == 2) {
                g_mod[cta * 32 + lane] = __float2bfloat16_rn(__uint_as_float(lds32(sb + SM_GV + lane * 4)) + __uint_as_float(lds32(sb + SM_GV + 128 + lane * 4)));
                __syncwarp();
                if (lane == 0) flag_release(FL_M);
                __syncwarp();
                TSW(4);
            }

        }
        if (wq == 2) {
            flag_wait(FL_M, ep1 * 120);
            fence_async_global();
            if (elect()) {
                mbar_expect(bars + BAR_M * 8, 7680);
                bulk_g2s(sb + SM_MOD, g_mod, 7680, bars + BAR_M * 8);
            }
            __syncwarp();
            TSW(60);
            bar_sync(8, 544);  if (lane == 0) { flag_release(FL_R + rb); TS(23); }  __syncwarp();
            bar_sync(15, 288); if (lane == 0) { flag_release(FL_B1 + rb); TS(27); } __syncwarp();
            bar_sync(6, 288);  if (lane == 0) { flag_release(FL_B2 + rb); TS(31); } __syncwarp();
#pragma unroll 1
            for (int i = 0; i < 3; i++) { bar_sync(i ? i : 8, 288); if (lane == 0) { TS(53 + (i + 2) % 3); flag_release(FL_G + 16 * i + rb); TS(57 + (i + 2) % 3); } __syncwarp(); }
            if (lane == 0) g_epoch[smid] = ep1;
            return;
        }
        if (wq == 1) {
            bar_sync(9, 288);
            if (lane < 4 * NB) mbar_arrive_cl(mapa(bars + (BAR_EB + (lane >> 2)) * 8, paired ? lane & 1 : blockIdx.x & 1));
        }
        if (wq == 3) {
            bar_sync(7, 544);
            if (lane == 0) { flag_release(FL_C); TS(20); }
            __syncwarp();
            if (lane < 2) mbar_expect(bars + (lane ? BAR_Y2 : BAR_Y) * 8, lane ? 8192 : 12288);
            flag_wait(FL_C, ep1 * 128);
            fence_async_global();
            TSW(21);
            if (elect()) {
                bulk_g2s(sb + SM_Y, g_yv + rho * 5120, 12288, bars + BAR_Y * 8);
                bulk_g2s(sb + SM_Y + 12288, g_yv + rho * 5120 + 3072, 8192, bars + BAR_Y2 * 8);
            }
            __syncwarp();
        }
        if (elect()) {
            if (wq == 3) {
                mbar_expect(bars + BAR_XY * 8, 20480);
#pragma unroll 1
                for (int i = 0; i < 8; i++) {
                    bulk_g2s(sb + SM_YT + i * 2560, g_yv + (8 * rb + i) * 5120 + cm * 8, 2048, bars + BAR_XY * 8);
                    bulk_g2s(sb + SM_YT + i * 2560 + 2048, g_yv + (8 * rb + i) * 5120 + cr * 8, 512, bars + BAR_XY * 8);
                }
                mbar_wait(bars + BAR_FA * 8, 0);
                bulk_prefetch((const char*)p.w4 + cta * 17280, 17280);
                flag_wait(FL_CS, ep1 * 4);
                fence_async_global();
                mbar_expect(bars + BAR_CS * 8, 864);
                bulk_g2s(sb + SM_CS, g_cs + 64 * j, 256, bars + BAR_CS * 8);
                bulk_g2s(sb + SM_CS + 256, g_cs + 512 + RA3 * j, 4 * RA3, bars + BAR_CS * 8);
                bulk_g2s(sb + SM_CS + 256 + 4 * RA3, g_cs + HB0 + 64 * j, 256, bars + BAR_CS * 8);
                bulk_g2s(sb + SM_CS + 512 + 4 * RA3, g_cs + HB0 + 512 + RB3 * j, 4 * RB3, bars + BAR_CS * 8);
                mbar_wait(bars + BAR_ST * 8, 0);
#pragma unroll 1
                for (int i = 0; i < 3; i++) {
                    flag_wait(FL_G + 16 * i + rb, ep1 * 8);
                    mbar_expect(bars + (BAR_G + i) * 8, 0);
                    TS(35 + (i + 2) % 3);
                }
            } else if (wq == 1) {
                Ring<NB, SM_RB, BAR_FB, BAR_EB> r{sb, 0, 0};
#pragma unroll 1
                for (int ph = 0; ph < 7; ph++) {
                    const CUtensorMap* ma = ph == 0 ? &maps.w1a : ph == 1 ? &maps.w2a : ph == 6 ? &maps.w4a : &maps.w3a;
                    const bool b3b = ph == 2 || ph == 4 || ph == 5;
                    r.runw(paired, idx & 1, ma, ma + (b3b ? 2 : 1), ph == 3 ? 64 * j : b3b ? HB0 + 64 * j : cm,
                           ph == 3 ? 512 + RA3 * j : b3b ? HB0 + 512 + RB3 * j : cr, ph == 4 ? 10 - NA : ph == 5 ? 1 : 0,
                           ph == 6 ? 27 : ph == 5 ? 10 - NA : ph == 2 ? 1 : 10, ph == 0 ? 0 : ph == 6 ? OWNG * (HB0 / 64 + j) : cm >> 6,
                           ph == 3 ? 8192 + 128 * RA3 : b3b ? 8192 + 128 * RB3 : 10240,
                           ph == 1 ? GATE : ph == 3 ? GATE - 1 : -1, bars + (BAR_ST - (ph == 1)) * 8);
                }
            } else {
                Ring<NA, SM_RA, BAR_FA, BAR_EA> r{sb, 0, 0};
                if (cta >= 120) mbar_wait(bars + (BAR_K + 4) * 8, 0);
                mbar_expect(bars + BAR_XR * 8, 20480);
                bulk_g2s(sb + SM_XR, p.q + (size_t)rho * 16 * D_, 20480, bars + BAR_XR * 8);
                mbar_expect(bars + BAR_XY * 8, 20480);
                tma2d(sb + SM_XT, &maps.xa, cm, rb * 128, bars + BAR_XY * 8);
                tma2d(sb + SM_XT2, &maps.xb, cr, rb * 128, bars + BAR_XY * 8);
                const int grp = j >> 1;
                const int delta = (grp & 1 ? 1 : -1) * (1 + (grp >> 1));
                const int nb = min(max(rb + (delta > 0 ? 1 : -1), 0), 15);
                uint32_t fb = r.acquire(SLOT), dst = r.slot();
                flag_wait2(FL_R + nb, FL_R + rb, ep1 * 8);
                fence_async_global();
                tma2d(dst, &maps.hn, 0, rb * 128 + delta, fb);
                TS(24);
                r.next();
                r.run2d(&maps.hn, rb * 128 + delta);
#pragma unroll 1
                for (int i = 0; i < 2; i++) {
                    const char* src = (const char*)(i ? g_x1 : g_h1) + (size_t)rb * 163840;
                    r.acquire(0); r.next();
                    fb = r.acquire(SLOT); dst = r.slot();
                    const char* src1 = src + (cm == 0 ? SLOT : 0);
                    flag_wait(FL_B1 + 16 * i + rb, ep1 * 8);
                    fence_async_global();
                    bulk_g2s(dst, src1, SLOT, fb);
                    TS(28 + 4 * i);
                    mbar_expect(bars + (BAR_ST - 1 + i) * 8, 0);
                    r.next();
                    r.run1d(src, 2, 10, cm >> 6);
                }
                r.run1d((const char*)g_x1 + (size_t)rb * 163840, 1, 10 - NA, cm >> 6);
                if (OWNG) { r.acquire(0); r.next(); }
#pragma unroll 1
                for (int i = 0; i < 2; i++) {
                    mbar_wait(bars + (BAR_G + 1 + i) * 8, 0); fence_async_global();
                    r.run1d((const char*)g_g + (size_t)rb * 442368, OWNG + HB0 / 64 * i, i ? 27 : OWNG + HB0 / 64, OWNG * (HB0 / 64 + j));
                }
            }
        }
        return;
    }
    bar_arrive(13, 640);
    asm volatile("setmaxnreg.inc.sync.aligned.u32 112;");
    const int rrow = 16 * rho + (warp >> 1) + 8 * (warp & 1);

    fence_async_smem();
    bar_sync(1 + wg, 128);
#pragma unroll 1
    for (int cc = wg; cc < wg + 1 + (wg == 3); cc++) {
        mbar_wait(bars + (BAR_K + cc) * 8, 0);
        if (cc == 2 && wq == 0) TSW(40);
        uint32_t a = sb + sm_k(cc) + 32 + (tid & 127) * 32;
        uint32_t pw = lds32(a - 4);
        uint4 x = lds128(a), y = lds128(a + 16), o;
        if ((tid & 127) == 0) {
            uint16_t k0 = __bfloat16_as_ushort(__float2bfloat16_rn(blo(x.x) + __uint_as_float(lds32(sb + SM_GV + 520 + cc * 4))));
            x.x = (x.x & 0xffff0000u) | k0;
            sts16(a, k0);
        }
        o.x = prmt(pw, x.x, 0x5432); o.y = prmt(x.x, x.y, 0x5432); o.z = prmt(x.y, x.z, 0x5432); o.w = prmt(x.z, x.w, 0x5432);
        sts128(a + 4160, o);
        o.x = prmt(x.w, y.x, 0x5432); o.y = prmt(y.x, y.y, 0x5432); o.z = prmt(y.y, y.z, 0x5432); o.w = prmt(y.z, y.w, 0x5432);
        sts128(a + 4176, o);
    }
    bar_sync(1 + wg, 128);
    if (wg == 3) bar_arrive(11, 256);
#pragma unroll 1
    for (int cc = wg; cc < 5; cc += 3) {
        if (cc == 3 && wg == 0) break;
        if (cc == 4) bar_sync(11, 256);
        const uint32_t kaddr = sb + sm_k(cc) + ((g & 1) ? 32 : 4192) + 4 * ((g >> 1) - c) + 64 * wq;
        const AFrag f0 = ldA(kaddr), f1 = ldA(kaddr + 256);
        if (STAG && cc == 3) bar_sync(12, 256);
        mbar_wait(bars + (BAR_U + cc) * 8, 0);
        if (wq == 0) TSW(5 + cc);
        float d[64];
        conv_two<0>(d, f0, f1, kaddr, desc_lo(sb + sm_u(cc), U_PLANE), sb + sm_red(cc) + wq * 4352 + g * 544 + c * 8, cc == 1);
        if (wq == 0) TSW(10 + cc);
        if (cc == 1) bar_arrive(6, 256);
    }
#pragma unroll 1
    for (int cc = wg == 1 ? 4 : wg;; cc++) {
        if (cc == 1) bar_sync(6, 256); else bar_sync(1 + wg, 128);
        const int ch = cta * 5 + cc;
        uint32_t* dst = g_yv + ch * 8 + ((g + (ch >> 2)) & 7) + (126 - 32 * wq - 2 * c) * 5120;
        uint2 v[16];
#pragma unroll
        for (int i = 0; i < 16; i++) v[i] = lds64(sb + sm_red(cc) + g * 544 + wq * 128 + c * 8 + (i >> 2) * 32 + (i & 3) * 4360);
#pragma unroll
        for (int w = 1; w < 4; w++)
            if (wq == 3 && c > 3 - w) v[12 + w] = make_uint2(0, 0);
#pragma unroll
        for (int q = 0; q < 4; q++) {
            const uint2* u = v + 4 * q;
            dst[-8 * q * 5120] = badd2(u[0].x, badd2(u[1].x, badd2(u[2].x, u[3].x)));
            dst[(-8 * q + 1) * 5120] = badd2(u[0].y, badd2(u[1].y, badd2(u[2].y, u[3].y)));
        }
        if (wq == 0) TSW(15 + cc);
        if (cc != 0) break;
    }
    fence_async_smem();
    if (!(wg & 1)) bar_arrive(9, 288);
    bar_arrive(7, 544);

    const uint32_t one2 = 0x3f803f80u;
    const unsigned ones = p.ones;
    {
        uint32_t x[10], a[10], cb[10], sbv[10];
        if (RPRE_WAIT) bar_sync(10, 512);
        mbar_wait(bars + BAR_XR * 8, 0);
#pragma unroll
        for (int i = 0; i < 10; i++) x[i] = lds32(sb + SM_XR + (rrow & 15) * 1280 + lane * 4 + i * 128);
        const uint3 s1 = row_stats(x, lane);
        const int up = lane >> 4, gg = warp >> 1, e = warp & 1;
        const uint32_t ya = sb + SM_Y + lane * 64 + ((gg + (lane >> 1)) & 7) * 4;
        const uint32_t sel = (up ? 0x1054u : 0x5410u) + (e ? 0x2222u : 0u);
        const uint32_t ma = sb + SM_MOD + lane * 4;
        mbar_wait(bars + BAR_M * 8, 0);
        uint32_t pin = 0;
#pragma unroll
        for (int i = 0; i < 10; i++) {
            uint32_t h = bfma2(ln_apply(x[i], s1.x, s1.y, s1.z), badd2(lds32(ma + 1280 + i * 128), one2), lds32(ma + i * 128));
            a[i] = bmul2(h, lds32(ma + 2560 + i * 128));
            sbv[i] = lds32(ma + 3840 + i * 128);
            cb[i] = badd2(lds32(ma + 5120 + i * 128), one2);
            pin ^= a[i] ^ cb[i];
        }
        if (pin & ~ones) sts32(sb + SM_GV, pin);
        if (warp == 4) TSW(52);
        mbar_wait(bars + BAR_Y * 8, 0);
        if (warp == 0) TSW(22);
#pragma unroll
        for (int i = 0; i < 10; i++) {
            if (i == 6) mbar_wait(bars + BAR_Y2 * 8, 0);
            uint32_t y0 = lds32(ya + i * 2048 + up * 32), y1 = lds32(ya + i * 2048 + (up ^ 1) * 32);
            x[i] = bfma2(a[i], prmt(y0, y1, sel), x[i]);
        }
        const uint3 s2 = row_stats(x, lane);
#pragma unroll
        for (int i = 0; i < 10; i++) x[i] = bfma2(ln_apply(x[i], s2.x, s2.y, s2.z), cb[i], sbv[i]);
        const uint3 s3 = row_stats(x, lane);
        uint32_t* o = reinterpret_cast<uint32_t*>(g_hn + (size_t)rrow * D_) + lane;
#pragma unroll
        for (int i = 0; i < 10; i++) o[32 * i] = ln_apply(x[i], s3.x, s3.y, s3.z);
        if (lane < 2) g_rs[rrow * 2 + lane] = lane ? make_uint4(s2.x, s2.y, s2.z, 0) : make_uint4(s1.x, s1.y, s1.z, 0);
        if (warp == 0) TSW(34);
        bar_arrive(8, 544);
    }

    const int half = wg & 1;
    const int row = 64 * half + 16 * wq + g;
    const int tw0 = (rb * 80 + (cm >> 3)) * 512 + row * 4 + c, tw1 = (rb * 80 + (cr >> 3) - 8) * 512 + row * 4 + c;
    const uint32_t park = sb + SM_Y + (tid & 255) * 16;
    const uint32_t ms0 = sb + SM_MOD + (cm + 2 * c) * 2, ms1 = sb + SM_MOD + (cr - 64 + 2 * c) * 2;
    if (wg >= 2) {
        {
            float acc[40];
            gemm_loop<80, true, 10, 10, true>(acc, sb, half, 0, 0, 10, 0, 0, 25);
#pragma unroll
            for (int k = 0; k < 10; k += CH) CHUNK(k) {
#pragma unroll
                for (int q = k; q < k + CH && q < 10; q++) {
                    uint32_t* dst = reinterpret_cast<uint32_t*>(g_h1) + (q < 8 ? tw0 : tw1);
                    const uint32_t u = gelu2_h(bmul2(pack2(acc[4 * q], acc[4 * q + 1]), 0x3f003f00u));
                    const uint32_t v = gelu2_h(bmul2(pack2(acc[4 * q + 2], acc[4 * q + 3]), 0x3f003f00u));
                    dst[q * 512] = u;
                    dst[q * 512 + 32] = v;
                    acc[4 * q] = __uint_as_float(u); acc[4 * q + 1] = __uint_as_float(v);
                }
            }
            bar_arrive(15, 288);
            mbar_wait(bars + (BAR_FA + 10 % NA) * 8, (10 / NA) & 1);
#pragma unroll
            for (int q = 0; q < 8; q++) {
                sts32(sb + SM_RA + (10 % NA) * SLOT + q * 2048 + row * 16 + c * 4, __float_as_uint(acc[4 * q]));
                sts32(sb + SM_RA + (10 % NA) * SLOT + q * 2048 + row * 16 + c * 4 + 128, __float_as_uint(acc[4 * q + 1]));
            }
            fence_async_smem();
            bar_arrive(14, 512);
        }
        gemm3<0>(sb, rb, j, half, row, c, ones);
        {
            float acc[40];
            uint32_t gbv[10], base[20];
#pragma unroll
            for (int q = 0; q < 10; q++) gbv[q] = lds32((q < 8 ? ms0 : ms1) + 6400 + q * 16);
#pragma unroll
            for (int q = 0; q < 5; q++) { const uint4 t = lds128(park + q * 4096); base[4 * q] = t.x; base[4 * q + 1] = t.y; base[4 * q + 2] = t.z; base[4 * q + 3] = t.w; }
            gemm_loop<80, false, 27, 27 - NB, true>(acc, sb, half, 39 - NA, 40, 27 - NA, 11, 0, 42);
            auto fin = [&](int q, int r) {
                return bfma2(gbv[q], pack2(acc[4 * q + 2 * r], acc[4 * q + 2 * r + 1]), base[2 * q + r]);
            };
            auto tr4 = [&](uint32_t t0, uint32_t t1, uint32_t t2, uint32_t t3) {
                const bool o1 = c & 1, o2 = c & 2;
                uint32_t a = __shfl_xor_sync(0xffffffffu, o1 ? t0 : t1, 1), b = __shfl_xor_sync(0xffffffffu, o1 ? t2 : t3, 1);
                uint32_t u0 = o1 ? a : t0, u1 = o1 ? t1 : a, u2 = o1 ? b : t2, u3 = o1 ? t3 : b;
                a = __shfl_xor_sync(0xffffffffu, o2 ? u0 : u2, 2); b = __shfl_xor_sync(0xffffffffu, o2 ? u1 : u3, 2);
                return o2 ? make_uint4(a, b, u2, u3) : make_uint4(u0, u1, a, b);
            };
            bf16* go = p.out + (size_t)(rb * 128 + row) * D_;
#pragma unroll
            for (int k = 0; k < 2; k++) CHUNK(k) {
#pragma unroll
                for (int r = 0; r < 2; r++)
                    *reinterpret_cast<uint4*>(go + r * 8 * D_ + cm + 32 * k + 8 * c) = tr4(fin(4 * k, r), fin(4 * k + 1, r), fin(4 * k + 2, r), fin(4 * k + 3, r));
            }
            CHUNK(2) *reinterpret_cast<uint4*>(go + (c >> 1) * 8 * D_ + cr + 8 * (c & 1)) = tr4(fin(8, 0), fin(9, 0), fin(8, 1), fin(9, 1));
            if (tid == 256) TS(44);
            if (warp == 8) TSFLUSH();
        }
    } else {
        {
            float acc[40];
            uint32_t x2[20];
            {
                uint32_t y[20];
                mbar_wait(bars + BAR_XY * 8, 0);
                const uint32_t xa = sb + SM_XT + row * 128 + c * 4, xb = sb + SM_XT2 + row * 32 + c * 4;
                const uint32_t ya = sb + SM_YT + (4 * half + wq) * 2560 + c * 64;
#pragma unroll
                for (int q = 0; q < 10; q++) {
                    const uint32_t a = q < 8 ? xa + ((q ^ g) << 4) : xb + (q - 8) * 16;
                    x2[2 * q] = lds32(a); x2[2 * q + 1] = lds32(a + (q < 8 ? 1024 : 256));
                    const int pos = (g + ((q < 8 ? cm : cr) >> 2) + 2 * q + (c >> 1)) & 7;
                    y[2 * q] = lds32(ya + q * 256 + pos * 4); y[2 * q + 1] = lds32(ya + q * 256 + 32 + pos * 4);
                }
                fence_async_smem();
                bar_sync(1 + wg, 128);
                if ((tid & 127) < NA) mbar_arrive_cl(mapa(bars + (BAR_EA + (tid & 127)) * 8, blockIdx.x & 1));
                mbar_wait(bars + (BAR_FA + 1) * 8, 0);
                const uint4* rp = g_rs + (rb * 128 + row) * 2;
                const uint4 ra = ldcg128(rp), rb2 = ldcg128(rp + 1), rc = ldcg128(rp + 16), rd = ldcg128(rp + 17);
                bar_sync(14, 512);
#pragma unroll
                for (int q = 0; q < 10; q++) {
                    const uint32_t ms = q < 8 ? ms0 : ms1;
                    const uint32_t sa = lds32(ms + 16 * q), ca = badd2(lds32(ms + 1280 + 16 * q), one2), ga = lds32(ms + 2560 + 16 * q);
                    const uint32_t sbv = lds32(ms + 3840 + 16 * q), cb = badd2(lds32(ms + 5120 + 16 * q), one2);
                    uint32_t u = x2[2 * q], v = x2[2 * q + 1];
                    u = bfma2(bmul2(bfma2(ln_apply(u, ra.x, ra.y, ra.z), ca, sa), ga), prmt(y[2 * q], y[2 * q + 1], 0x5410), u);
                    v = bfma2(bmul2(bfma2(ln_apply(v, rc.x, rc.y, rc.z), ca, sa), ga), prmt(y[2 * q], y[2 * q + 1], 0x7632), v);
                    x2[2 * q] = u; x2[2 * q + 1] = v;
                    u = bfma2(ln_apply(u, rb2.x, rb2.y, rb2.z), cb, sbv);
                    v = bfma2(ln_apply(v, rd.x, rd.y, rd.z), cb, sbv);
                    acc[4 * q] = blo(u); acc[4 * q + 1] = bhi(u); acc[4 * q + 2] = blo(v); acc[4 * q + 3] = bhi(v);
                }
            }
            reg_fence<40>(acc);
            if (tid == 0) TS(45);
            gemm_loop<80, false, 10, 10, false>(acc, sb, half, 10, 10, 10, 0, 0, 29);
            uint32_t x1[20];
            float s0 = 0.f, q0 = 0.f, s1 = 0.f, q1 = 0.f;
#pragma unroll
            for (int q = 0; q < 10; q++) {
                uint32_t u = pack2(acc[4 * q], acc[4 * q + 1]);
                uint32_t v = pack2(acc[4 * q + 2], acc[4 * q + 3]);
                uint32_t* dst = reinterpret_cast<uint32_t*>(g_x1) + (q < 8 ? tw0 : tw1);
                dst[q * 512] = u;
                dst[q * 512 + 32] = v;
                x1[2 * q] = u; x1[2 * q + 1] = v;
            }
            bar_arrive(6, 288);
            CHUNK(0)
#pragma unroll
            for (int q = 0; q < 10; q++) {
                float a = blo(x1[2 * q]), b = bhi(x1[2 * q]), e = blo(x1[2 * q + 1]), f = bhi(x1[2 * q + 1]);
                s0 += a + b; q0 = fmaf(a, a, fmaf(b, b, q0));
                s1 += e + f; q1 = fmaf(e, e, fmaf(f, f, q1));
            }
#pragma unroll
            for (int m = 1; m <= 2; m <<= 1) {
                s0 += __shfl_xor_sync(0xffffffffu, s0, m); q0 += __shfl_xor_sync(0xffffffffu, q0, m);
                s1 += __shfl_xor_sync(0xffffffffu, s1, m); q1 += __shfl_xor_sync(0xffffffffu, q1, m);
            }
            if (c < 2) g_st[(rb * 8 + j) * 128 + row + 8 * c] = c ? make_float2(s1, q1) : make_float2(s0, q0);
            bar_arrive(8, 288);
            mbar_wait(bars + (BAR_FA + 20 % NA) * 8, (20 / NA) & 1);
#pragma unroll
            for (int q = 0; q < 8; q++) {
                sts32(sb + SM_RA + (20 % NA) * SLOT + q * 2048 + row * 16 + c * 4, x1[2 * q]);
                sts32(sb + SM_RA + (20 % NA) * SLOT + q * 2048 + row * 16 + c * 4 + 128, x1[2 * q + 1]);
            }
            fence_async_smem();
            bar_sync(3 + wg, 128);
#pragma unroll
            for (int q = 0; q < 5; q++) {
                const uint32_t ms = q < 4 ? ms0 : ms1;
                const uint32_t g0 = lds32(ms + 6400 + q * 32), g1 = lds32(ms + 6400 + q * 32 + 16);
                sts128(park + q * 4096, make_uint4(bfma2(g0, x1[4 * q], x2[4 * q]), bfma2(g0, x1[4 * q + 1], x2[4 * q + 1]),
                                                   bfma2(g1, x1[4 * q + 2], x2[4 * q + 2]), bfma2(g1, x1[4 * q + 3], x2[4 * q + 3])));
            }
        }
        gemm3<1>(sb, rb, j, half, row, c, ones);
    }
}

typedef CUresult (*EncFn)(CUtensorMap*, CUtensorMapDataType, cuuint32_t, void*, const cuuint64_t*, const cuuint64_t*,
                          const cuuint32_t*, const cuuint32_t*, CUtensorMapInterleave, CUtensorMapSwizzle,
                          CUtensorMapL2promotion, CUtensorMapFloatOOBfill);

void make_map(EncFn enc, CUtensorMap* m, const void* base, uint64_t inner, uint64_t outer, uint32_t bi, uint32_t bo,
              CUtensorMapSwizzle swz = CU_TENSOR_MAP_SWIZZLE_128B) {
    cuuint64_t dims[2] = {inner, outer};
    cuuint64_t st[1] = {inner * 2};
    cuuint32_t box[2] = {bi, bo};
    cuuint32_t es[2] = {1, 1};
    enc(m, CU_TENSOR_MAP_DATA_TYPE_BFLOAT16, 2, const_cast<void*>(base), dims, st, box, es, CU_TENSOR_MAP_INTERLEAVE_NONE,
        swz, CU_TENSOR_MAP_L2_PROMOTION_NONE, CU_TENSOR_MAP_FLOAT_OOB_FILL_NONE);
}

}

extern "C" void kernel_launch(void* const* d_in, const int* in_sizes, int n_in, void* d_out, int out_size) {
    (void)in_sizes; (void)n_in; (void)out_size;
    Params p;
    p.q = (const bf16*)d_in[0]; p.k = (const bf16*)d_in[1]; p.v = (const bf16*)d_in[2];
    p.shift = (const bf16*)d_in[3]; p.ssmk = (const bf16*)d_in[4]; p.ssmD = (const bf16*)d_in[5];
    p.w1 = (const bf16*)d_in[7]; p.w2 = (const bf16*)d_in[8]; p.w3 = (const bf16*)d_in[9]; p.w4 = (const bf16*)d_in[10];
    p.c = (const bf16*)d_in[11]; p.wmod = (const bf16*)d_in[12];
    p.out = (bf16*)d_out;
    p.ones = 0xffffffffu;

    void* fn = nullptr;
    cudaDriverEntryPointQueryResult qr;
    cudaGetDriverEntryPoint("cuTensorMapEncodeTiled", &fn, cudaEnableDefault, &qr);
    EncFn enc = (EncFn)fn;
    void* hn = nullptr;
    cudaGetSymbolAddress(&hn, g_hn);
    Maps maps;
    make_map(enc, &maps.w3s, p.w3, F_, D_, 216, 64, CU_TENSOR_MAP_SWIZZLE_NONE);
    make_map(enc, &maps.wm, p.wmod, 6 * D_, D_, 32, 128, CU_TENSOR_MAP_SWIZZLE_64B);
    make_map(enc, &maps.xa, p.q, D_, S_, 64, 128);
    make_map(enc, &maps.xb, p.q, D_, S_, 16, 128, CU_TENSOR_MAP_SWIZZLE_NONE);
    make_map(enc, &maps.hn, hn, D_, S_, 64, 128);
    make_map(enc, &maps.w1a, p.w1, D_, D_, 64, 64);
    make_map(enc, &maps.w1b, p.w1, D_, D_, 16, 64);
    make_map(enc, &maps.w2a, p.w2, D_, D_, 64, 64);
    make_map(enc, &maps.w2b, p.w2, D_, D_, 16, 64);
    make_map(enc, &maps.w3a, p.w3, F_, D_, 64, 64);
    make_map(enc, &maps.w3b, p.w3, F_, D_, RA3, 64);
    make_map(enc, &maps.w3c, p.w3, F_, D_, RB3, 64);
    make_map(enc, &maps.w4a, p.w4, D_, F_, 64, 64);
    make_map(enc, &maps.w4b, p.w4, D_, F_, 16, 64);
    cudaFuncSetAttribute(fused_kernel, cudaFuncAttributeMaxDynamicSharedMemorySize, SMEM_BYTES);
    fused_kernel<<<132, NTHREADS, SMEM_BYTES>>>(p, maps);
}
```

```cpp
#include <cuda_runtime.h>
#include <cuda_bf16.h>
#include <cuda.h>
#include <stdint.h>
#include <string.h>

#define SEED 0
#define RING_A 6
#define CH 2
#define FAST_LN 2
#define STAG 10
#define GATE 5
#define SSM_DELAY 0
#define B_DELAY 300
#define RPRE_WAIT 1
#define FASTW 1
#define PEEL 0
#define UU 1
#define US 1
#define UG 1
#define UA 1
#define UB 2
#define SSM_N 3
#define PF_EARLY 0

namespace {

typedef __nv_bfloat16 bf16;
typedef __nv_bfloat162 bf162;

constexpr int S_ = 2048, D_ = 640, F_ = 1728;
constexpr int NTHREADS = 640;
constexpr int NA = RING_A, NB = 12 - RING_A;
constexpr int SLOT = 16384;
constexpr int UNR_U = UU, UNR_S = US, UNR_G = UG, UNR_A = UA, UNR_B = UB;
constexpr int RA3 = 48, RB3 = 40, HB0 = 896;
constexpr int SM_RA = 0, SM_RB = NA * SLOT;

static_assert(NA == 6, "smem map");
constexpr int RED_STRIDE = 17536;
constexpr int K_STRIDE = 8320;
constexpr int U_PLANE = 2560, U_STRIDE = 5120;
constexpr int SM_Y = 12 * SLOT;
__device__ __forceinline__ int sm_red(int cc) { return cc * RED_STRIDE + (cc < 3 ? SM_RB : -3 * RED_STRIDE); }
__device__ __forceinline__ int sm_k(int cc) { return cc * K_STRIDE + (cc < 3 ? SM_RB + 3 * RED_STRIDE : 2 * RED_STRIDE - 3 * K_STRIDE); }
__device__ __forceinline__ int sm_u(int cc) { return cc * U_STRIDE + (cc < 3 ? SM_RB + 3 * RED_STRIDE + 3 * K_STRIDE : SM_Y + 8192 - 3 * U_STRIDE); }
constexpr int SM_PK = SM_RB;
constexpr int SM_PV = SM_RB + 24576;
constexpr int SM_WM = 57344;
constexpr int SM_XT = SM_WM, SM_XT2 = SM_WM + 16384, SM_XR = SM_WM + 20480;
constexpr int SM_YT = 0;
constexpr int SM_MOD = SM_Y + 20480;
constexpr int SM_GV = SM_MOD + 7680;
constexpr int SM_CS = SM_GV + 1024;
constexpr int SM_RP = SM_CS + 1024;
constexpr int SM_BAR = SM_RP + 1024;
constexpr int SM_PROF = SM_BAR + 512;
constexpr int SM_TOTAL = SM_PROF + 512;
constexpr int SMEM_BYTES = SM_TOTAL + 1024;
static_assert(SMEM_BYTES <= 232448, "smem");

constexpr int BAR_FA = 0, BAR_FB = NA, BAR_EA = 12, BAR_EB = 12 + NA, BAR_K = 24, BAR_U = 29, BAR_Y = 34, BAR_CS = 35, BAR_WM = 36, BAR_M = 37, BAR_XY = 38, BAR_Y2 = 39, BAR_G = 40, BAR_ST = 44, BAR_XR = 45, BAR_LR = 46, NBARS = 47;

__device__ __align__(1024) bf16 g_kvT[D_ * S_];
__device__ __align__(1024) uint32_t g_yv[128 * 5120];
__device__ __align__(1024) bf16 g_mod[6 * D_];
__device__ __align__(1024) bf16 g_hn[S_ * D_];
__device__ __align__(1024) uint4 g_rs[S_ * 2];
__device__ __align__(1024) bf16 g_h1[S_ * D_];
__device__ __align__(1024) bf16 g_x1[S_ * D_];
__device__ __align__(1024) bf16 g_g[S_ * F_];
__device__ __align__(1024) uint4 g_st[S_ * 8];
__device__ __align__(1024) float g_cs[F_];
__device__ __align__(1024) unsigned g_flags[128 * 32];
__device__ __align__(1024) unsigned g_epoch[160];
constexpr int FL_P = 0, FL_C = 8, FL_CS = 9, FL_M = 10, FL_R = 16, FL_B1 = 32, FL_B2 = 48, FL_G = 64;

#define TS(i) do {} while (0)
#define TSW(i) do {} while (0)
#define TSD(i, dep) do {} while (0)
#define TSD2(i, dep) do {} while (0)
#define TSFLUSH() do {} while (0)

struct Params {
    const bf16 *q, *k, *v, *shift, *ssmk, *ssmD, *w1, *w2, *w3, *w4, *c, *wmod;
    bf16* out;
    unsigned ones;
};
#define CHUNK(k) if (ones & (1u << (k)))
struct Maps { CUtensorMap hn, w1a, w1b, w2a, w2b, w3a, w3b, w3c, w4a, w4b, wm, xa, xb, w3s; };

template<int N> struct WgRs;
template<int N> struct WgSs;
template<> struct WgRs<32> { template<int OFF,int HI,int SC> static __device__ __forceinline__ void run(float* d,uint32_t a0,uint32_t a1,uint32_t a2,uint32_t a3,uint32_t blo){
 asm volatile("{.reg .b32 l; .reg .b64 db; add.u32 l,%20,%21; mov.b64 db,{l,%22}; wgmma.mma_async.sync.aligned.m64n32k16.f32.bf16.bf16 {%0,%1,%2,%3,%4,%5,%6,%7,%8,%9,%10,%11,%12,%13,%14,%15},{%16,%17,%18,%19},db,%23,1,1,0;}"
 :"+f"(d[0]),"+f"(d[1]),"+f"(d[2]),"+f"(d[3]),"+f"(d[4]),"+f"(d[5]),"+f"(d[6]),"+f"(d[7]),"+f"(d[8]),"+f"(d[9]),"+f"(d[10]),"+f"(d[11]),"+f"(d[12]),"+f"(d[13]),"+f"(d[14]),"+f"(d[15])
 :"r"(a0),"r"(a1),"r"(a2),"r"(a3),"r"(blo),"n"(OFF),"n"(HI),"n"(SC)); } };
template<> struct WgRs<48> { template<int OFF,int HI,int SC> static __device__ __forceinline__ void run(float* d,uint32_t a0,uint32_t a1,uint32_t a2,uint32_t a3,uint32_t blo){
 asm volatile("{.reg .b32 l; .reg .b64 db; add.u32 l,%28,%29; mov.b64 db,{l,%30}; wgmma.mma_async.sync.aligned.m64n48k16.f32.bf16.bf16 {%0,%1,%2,%3,%4,%5,%6,%7,%8,%9,%10,%11,%12,%13,%14,%15,%16,%17,%18,%19,%20,%21,%22,%23},{%24,%25,%26,%27},db,%31,1,1,0;}"
 :"+f"(d[0]),"+f"(d[1]),"+f"(d[2]),"+f"(d[3]),"+f"(d[4]),"+f"(d[5]),"+f"(d[6]),"+f"(d[7]),"+f"(d[8]),"+f"(d[9]),"+f"(d[10]),"+f"(d[11]),"+f"(d[12]),"+f"(d[13]),"+f"(d[14]),"+f"(d[15]),"+f"(d[16]),"+f"(d[17]),"+f"(d[18]),"+f"(d[19]),"+f"(d[20]),"+f"(d[21]),"+f"(d[22]),"+f"(d[23])
 :"r"(a0),"r"(a1),"r"(a2),"r"(a3),"r"(blo),"n"(OFF),"n"(HI),"n"(SC)); } };
template<> struct WgRs<64> { template<int OFF,int HI,int SC> static __device__ __forceinline__ void run(float* d,uint32_t a0,uint32_t a1,uint32_t a2,uint32_t a3,uint32_t blo){
 asm volatile("{.reg .b32 l; .reg .b64 db; add.u32 l,%36,%37; mov.b64 db,{l,%38}; wgmma.mma_async.sync.aligned.m64n64k16.f32.bf16.bf16 {%0,%1,%2,%3,%4,%5,%6,%7,%8,%9,%10,%11,%12,%13,%14,%15,%16,%17,%18,%19,%20,%21,%22,%23,%24,%25,%26,%27,%28,%29,%30,%31},{%32,%33,%34,%35},db,%39,1,1,0;}"
 :"+f"(d[0]),"+f"(d[1]),"+f"(d[2]),"+f"(d[3]),"+f"(d[4]),"+f"(d[5]),"+f"(d[6]),"+f"(d[7]),"+f"(d[8]),"+f"(d[9]),"+f"(d[10]),"+f"(d[11]),"+f"(d[12]),"+f"(d[13]),"+f"(d[14]),"+f"(d[15]),"+f"(d[16]),"+f"(d[17]),"+f"(d[18]),"+f"(d[19]),"+f"(d[20]),"+f"(d[21]),"+f"(d[22]),"+f"(d[23]),"+f"(d[24]),"+f"(d[25]),"+f"(d[26]),"+f"(d[27]),"+f"(d[28]),"+f"(d[29]),"+f"(d[30]),"+f"(d[31])
 :"r"(a0),"r"(a1),"r"(a2),"r"(a3),"r"(blo),"n"(OFF),"n"(HI),"n"(SC)); } };
template<> struct WgRs<80> { template<int OFF,int HI,int SC> static __device__ __forceinline__ void run(float* d,uint32_t a0,uint32_t a1,uint32_t a2,uint32_t a3,uint32_t blo){
 asm volatile("{.reg .b32 l; .reg .b64 db; add.u32 l,%44,%45; mov.b64 db,{l,%46}; wgmma.mma_async.sync.aligned.m64n80k16.f32.bf16.bf16 {%0,%1,%2,%3,%4,%5,%6,%7,%8,%9,%10,%11,%12,%13,%14,%15,%16,%17,%18,%19,%20,%21,%22,%23,%24,%25,%26,%27,%28,%29,%30,%31,%32,%33,%34,%35,%36,%37,%38,%39},{%40,%41,%42,%43},db,%47,1,1,0;}"
 :"+f"(d[0]),"+f"(d[1]),"+f"(d[2]),"+f"(d[3]),"+f"(d[4]),"+f"(d[5]),"+f"(d[6]),"+f"(d[7]),"+f"(d[8]),"+f"(d[9]),"+f"(d[10]),"+f"(d[11]),"+f"(d[12]),"+f"(d[13]),"+f"(d[14]),"+f"(d[15]),"+f"(d[16]),"+f"(d[17]),"+f"(d[18]),"+f"(d[19]),"+f"(d[20]),"+f"(d[21]),"+f"(d[22]),"+f"(d[23]),"+f"(d[24]),"+f"(d[25]),"+f"(d[26]),"+f"(d[27]),"+f"(d[28]),"+f"(d[29]),"+f"(d[30]),"+f"(d[31]),"+f"(d[32]),"+f"(d[33]),"+f"(d[34]),"+f"(d[35]),"+f"(d[36]),"+f"(d[37]),"+f"(d[38]),"+f"(d[39])
 :"r"(a0),"r"(a1),"r"(a2),"r"(a3),"r"(blo),"n"(OFF),"n"(HI),"n"(SC)); } };
template<> struct WgRs<96> { template<int OFF,int HI,int SC> static __device__ __forceinline__ void run(float* d,uint32_t a0,uint32_t a1,uint32_t a2,uint32_t a3,uint32_t blo){
 asm volatile("{.reg .b32 l; .reg .b64 db; add.u32 l,%52,%53; mov.b64 db,{l,%54}; wgmma.mma_async.sync.aligned.m64n96k16.f32.bf16.bf16 {%0,%1,%2,%3,%4,%5,%6,%7,%8,%9,%10,%11,%12,%13,%14,%15,%16,%17,%18,%19,%20,%21,%22,%23,%24,%25,%26,%27,%28,%29,%30,%31,%32,%33,%34,%35,%36,%37,%38,%39,%40,%41,%42,%43,%44,%45,%46,%47},{%48,%49,%50,%51},db,%55,1,1,0;}"
 :"+f"(d[0]),"+f"(d[1]),"+f"(d[2]),"+f"(d[3]),"+f"(d[4]),"+f"(d[5]),"+f"(d[6]),"+f"(d[7]),"+f"(d[8]),"+f"(d[9]),"+f"(d[10]),"+f"(d[11]),"+f"(d[12]),"+f"(d[13]),"+f"(d[14]),"+f"(d[15]),"+f"(d[16]),"+f"(d[17]),"+f"(d[18]),"+f"(d[19]),"+f"(d[20]),"+f"(d[21]),"+f"(d[22]),"+f"(d[23]),"+f"(d[24]),"+f"(d[25]),"+f"(d[26]),"+f"(d[27]),"+f"(d[28]),"+f"(d[29]),"+f"(d[30]),"+f"(d[31]),"+f"(d[32]),"+f"(d[33]),"+f"(d[34]),"+f"(d[35]),"+f"(d[36]),"+f"(d[37]),"+f"(d[38]),"+f"(d[39]),"+f"(d[40]),"+f"(d[41]),"+f"(d[42]),"+f"(d[43]),"+f"(d[44]),"+f"(d[45]),"+f"(d[46]),"+f"(d[47])
 :"r"(a0),"r"(a1),"r"(a2),"r"(a3),"r"(blo),"n"(OFF),"n"(HI),"n"(SC)); } };
template<> struct WgRs<112> { template<int OFF,int HI,int SC> static __device__ __forceinline__ void run(float* d,uint32_t a0,uint32_t a1,uint32_t a2,uint32_t a3,uint32_t blo){
 asm volatile("{.reg .b32 l; .reg .b64 db; add.u32 l,%60,%61; mov.b64 db,{l,%62}; wgmma.mma_async.sync.aligned.m64n112k16.f32.bf16.bf16 {%0,%1,%2,%3,%4,%5,%6,%7,%8,%9,%10,%11,%12,%13,%14,%15,%16,%17,%18,%19,%20,%21,%22,%23,%24,%25,%26,%27,%28,%29,%30,%31,%32,%33,%34,%35,%36,%37,%38,%39,%40,%41,%42,%43,%44,%45,%46,%47,%48,%49,%50,%51,%52,%53,%54,%55},{%56,%57,%58,%59},db,%63,1,1,0;}"
 :"+f"(d[0]),"+f"(d[1]),"+f"(d[2]),"+f"(d[3]),"+f"(d[4]),"+f"(d[5]),"+f"(d[6]),"+f"(d[7]),"+f"(d[8]),"+f"(d[9]),"+f"(d[10]),"+f"(d[11]),"+f"(d[12]),"+f"(d[13]),"+f"(d[14]),"+f"(d[15]),"+f"(d[16]),"+f"(d[17]),"+f"(d[18]),"+f"(d[19]),"+f"(d[20]),"+f"(d[21]),"+f"(d[22]),"+f"(d[23]),"+f"(d[24]),"+f"(d[25]),"+f"(d[26]),"+f"(d[27]),"+f"(d[28]),"+f"(d[29]),"+f"(d[30]),"+f"(d[31]),"+f"(d[32]),"+f"(d[33]),"+f"(d[34]),"+f"(d[35]),"+f"(d[36]),"+f"(d[37]),"+f"(d[38]),"+f"(d[39]),"+f"(d[40]),"+f"(d[41]),"+f"(d[42]),"+f"(d[43]),"+f"(d[44]),"+f"(d[45]),"+f"(d[46]),"+f"(d[47]),"+f"(d[48]),"+f"(d[49]),"+f"(d[50]),"+f"(d[51]),"+f"(d[52]),"+f"(d[53]),"+f"(d[54]),"+f"(d[55])
 :"r"(a0),"r"(a1),"r"(a2),"r"(a3),"r"(blo),"n"(OFF),"n"(HI),"n"(SC)); } };
template<> struct WgRs<128> { template<int OFF,int HI,int SC> static __device__ __forceinline__ void run(float* d,uint32_t a0,uint32_t a1,uint32_t a2,uint32_t a3,uint32_t blo){
 asm volatile("{.reg .b32 l; .reg .b64 db; add.u32 l,%68,%69; mov.b64 db,{l,%70}; wgmma.mma_async.sync.aligned.m64n128k16.f32.bf16.bf16 {%0,%1,%2,%3,%4,%5,%6,%7,%8,%9,%10,%11,%12,%13,%14,%15,%16,%17,%18,%19,%20,%21,%22,%23,%24,%25,%26,%27,%28,%29,%30,%31,%32,%33,%34,%35,%36,%37,%38,%39,%40,%41,%42,%43,%44,%45,%46,%47,%48,%49,%50,%51,%52,%53,%54,%55,%56,%57,%58,%59,%60,%61,%62,%63},{%64,%65,%66,%67},db,%71,1,1,0;}"
 :"+f"(d[0]),"+f"(d[1]),"+f"(d[2]),"+f"(d[3]),"+f"(d[4]),"+f"(d[5]),"+f"(d[6]),"+f"(d[7]),"+f"(d[8]),"+f"(d[9]),"+f"(d[10]),"+f"(d[11]),"+f"(d[12]),"+f"(d[13]),"+f"(d[14]),"+f"(d[15]),"+f"(d[16]),"+f"(d[17]),"+f"(d[18]),"+f"(d[19]),"+f"(d[20]),"+f"(d[21]),"+f"(d[22]),"+f"(d[23]),"+f"(d[24]),"+f"(d[25]),"+f"(d[26]),"+f"(d[27]),"+f"(d[28]),"+f"(d[29]),"+f"(d[30]),"+f"(d[31]),"+f"(d[32]),"+f"(d[33]),"+f"(d[34]),"+f"(d[35]),"+f"(d[36]),"+f"(d[37]),"+f"(d[38]),"+f"(d[39]),"+f"(d[40]),"+f"(d[41]),"+f"(d[42]),"+f"(d[43]),"+f"(d[44]),"+f"(d[45]),"+f"(d[46]),"+f"(d[47]),"+f"(d[48]),"+f"(d[49]),"+f"(d[50]),"+f"(d[51]),"+f"(d[52]),"+f"(d[53]),"+f"(d[54]),"+f"(d[55]),"+f"(d[56]),"+f"(d[57]),"+f"(d[58]),"+f"(d[59]),"+f"(d[60]),"+f"(d[61]),"+f"(d[62]),"+f"(d[63])
 :"r"(a0),"r"(a1),"r"(a2),"r"(a3),"r"(blo),"n"(OFF),"n"(HI),"n"(SC)); } };
template<> struct WgSs<80> { template<int AOFF,int AHI,int BOFF,int BHI> static __device__ __forceinline__ void run(float* d,uint32_t alo,uint32_t blo,int sc){
 asm volatile("{.reg .pred p; .reg .b32 l,m; .reg .b64 da,db; setp.ne.b32 p,%46,0; add.u32 l,%40,%42; mov.b64 da,{l,%43}; add.u32 m,%41,%44; mov.b64 db,{m,%45}; wgmma.mma_async.sync.aligned.m64n80k16.f32.bf16.bf16 {%0,%1,%2,%3,%4,%5,%6,%7,%8,%9,%10,%11,%12,%13,%14,%15,%16,%17,%18,%19,%20,%21,%22,%23,%24,%25,%26,%27,%28,%29,%30,%31,%32,%33,%34,%35,%36,%37,%38,%39},da,db,p,1,1,0,1;}"
 :"+f"(d[0]),"+f"(d[1]),"+f"(d[2]),"+f"(d[3]),"+f"(d[4]),"+f"(d[5]),"+f"(d[6]),"+f"(d[7]),"+f"(d[8]),"+f"(d[9]),"+f"(d[10]),"+f"(d[11]),"+f"(d[12]),"+f"(d[13]),"+f"(d[14]),"+f"(d[15]),"+f"(d[16]),"+f"(d[17]),"+f"(d[18]),"+f"(d[19]),"+f"(d[20]),"+f"(d[21]),"+f"(d[22]),"+f"(d[23]),"+f"(d[24]),"+f"(d[25]),"+f"(d[26]),"+f"(d[27]),"+f"(d[28]),"+f"(d[29]),"+f"(d[30]),"+f"(d[31]),"+f"(d[32]),"+f"(d[33]),"+f"(d[34]),"+f"(d[35]),"+f"(d[36]),"+f"(d[37]),"+f"(d[38]),"+f"(d[39])
 :"r"(alo),"r"(blo),"n"(AOFF),"n"(AHI),"n"(BOFF),"n"(BHI),"r"(sc)); } };
template<> struct WgSs<104> { template<int AOFF,int AHI,int BOFF,int BHI> static __device__ __forceinline__ void run(float* d,uint32_t alo,uint32_t blo,int sc){
 asm volatile("{.reg .pred p; .reg .b32 l,m; .reg .b64 da,db; setp.ne.b32 p,%58,0; add.u32 l,%52,%54; mov.b64 da,{l,%55}; add.u32 m,%53,%56; mov.b64 db,{m,%57}; wgmma.mma_async.sync.aligned.m64n104k16.f32.bf16.bf16 {%0,%1,%2,%3,%4,%5,%6,%7,%8,%9,%10,%11,%12,%13,%14,%15,%16,%17,%18,%19,%20,%21,%22,%23,%24,%25,%26,%27,%28,%29,%30,%31,%32,%33,%34,%35,%36,%37,%38,%39,%40,%41,%42,%43,%44,%45,%46,%47,%48,%49,%50,%51},da,db,p,1,1,0,1;}"
 :"+f"(d[0]),"+f"(d[1]),"+f"(d[2]),"+f"(d[3]),"+f"(d[4]),"+f"(d[5]),"+f"(d[6]),"+f"(d[7]),"+f"(d[8]),"+f"(d[9]),"+f"(d[10]),"+f"(d[11]),"+f"(d[12]),"+f"(d[13]),"+f"(d[14]),"+f"(d[15]),"+f"(d[16]),"+f"(d[17]),"+f"(d[18]),"+f"(d[19]),"+f"(d[20]),"+f"(d[21]),"+f"(d[22]),"+f"(d[23]),"+f"(d[24]),"+f"(d[25]),"+f"(d[26]),"+f"(d[27]),"+f"(d[28]),"+f"(d[29]),"+f"(d[30]),"+f"(d[31]),"+f"(d[32]),"+f"(d[33]),"+f"(d[34]),"+f"(d[35]),"+f"(d[36]),"+f"(d[37]),"+f"(d[38]),"+f"(d[39]),"+f"(d[40]),"+f"(d[41]),"+f"(d[42]),"+f"(d[43]),"+f"(d[44]),"+f"(d[45]),"+f"(d[46]),"+f"(d[47]),"+f"(d[48]),"+f"(d[49]),"+f"(d[50]),"+f"(d[51])
 :"r"(alo),"r"(blo),"n"(AOFF),"n"(AHI),"n"(BOFF),"n"(BHI),"r"(sc)); } };
template<> struct WgSs<112> { template<int AOFF,int AHI,int BOFF,int BHI> static __device__ __forceinline__ void run(float* d,uint32_t alo,uint32_t blo,int sc){
 asm volatile("{.reg .pred p; .reg .b32 l,m; .reg .b64 da,db; setp.ne.b32 p,%62,0; add.u32 l,%56,%58; mov.b64 da,{l,%59}; add.u32 m,%57,%60; mov.b64 db,{m,%61}; wgmma.mma_async.sync.aligned.m64n112k16.f32.bf16.bf16 {%0,%1,%2,%3,%4,%5,%6,%7,%8,%9,%10,%11,%12,%13,%14,%15,%16,%17,%18,%19,%20,%21,%22,%23,%24,%25,%26,%27,%28,%29,%30,%31,%32,%33,%34,%35,%36,%37,%38,%39,%40,%41,%42,%43,%44,%45,%46,%47,%48,%49,%50,%51,%52,%53,%54,%55},da,db,p,1,1,0,1;}"
 :"+f"(d[0]),"+f"(d[1]),"+f"(d[2]),"+f"(d[3]),"+f"(d[4]),"+f"(d[5]),"+f"(d[6]),"+f"(d[7]),"+f"(d[8]),"+f"(d[9]),"+f"(d[10]),"+f"(d[11]),"+f"(d[12]),"+f"(d[13]),"+f"(d[14]),"+f"(d[15]),"+f"(d[16]),"+f"(d[17]),"+f"(d[18]),"+f"(d[19]),"+f"(d[20]),"+f"(d[21]),"+f"(d[22]),"+f"(d[23]),"+f"(d[24]),"+f"(d[25]),"+f"(d[26]),"+f"(d[27]),"+f"(d[28]),"+f"(d[29]),"+f"(d[30]),"+f"(d[31]),"+f"(d[32]),"+f"(d[33]),"+f"(d[34]),"+f"(d[35]),"+f"(d[36]),"+f"(d[37]),"+f"(d[38]),"+f"(d[39]),"+f"(d[40]),"+f"(d[41]),"+f"(d[42]),"+f"(d[43]),"+f"(d[44]),"+f"(d[45]),"+f"(d[46]),"+f"(d[47]),"+f"(d[48]),"+f"(d[49]),"+f"(d[50]),"+f"(d[51]),"+f"(d[52]),"+f"(d[53]),"+f"(d[54]),"+f"(d[55])
 :"r"(alo),"r"(blo),"n"(AOFF),"n"(AHI),"n"(BOFF),"n"(BHI),"r"(sc)); } };

__device__ __forceinline__ void wg_fence() { asm volatile("wgmma.fence.sync.aligned;" ::: "memory"); }
__device__ __forceinline__ void wg_commit() { asm volatile("wgmma.commit_group.sync.aligned;" ::: "memory"); }
template <int N> __device__ __forceinline__ void wg_wait() { asm volatile("wgmma.wait_group.sync.aligned %0;" ::"n"(N) : "memory"); }
template <int N> __device__ __forceinline__ void reg_fence(float* d) {
#pragma unroll
    for (int i = 0; i < N; i++) asm volatile("" : "+f"(d[i])::"memory");
}
__device__ __forceinline__ uint32_t desc_lo(uint32_t addr, uint32_t lbo) { return ((addr & 0x3FFFF) >> 4) | ((lbo >> 4) << 16); }
#define desc_hi(sbo, sw) (((sbo) >> 4) | ((sw) << 30))
__device__ __forceinline__ uint32_t smem_u32(const void* p) { return (uint32_t)__cvta_generic_to_shared(p); }
__device__ __forceinline__ bool elect() {
    uint32_t p;
    asm volatile("{.reg .pred P; elect.sync _|P, 0xffffffff; selp.u32 %0,1,0,P;}" : "=r"(p));
    return p;
}
__device__ __forceinline__ void mbar_init(uint32_t bar, uint32_t cnt) { asm volatile("mbarrier.init.shared::cta.b64 [%0], %1;" ::"r"(bar), "r"(cnt) : "memory"); }
__device__ __forceinline__ void mbar_expect(uint32_t bar, uint32_t bytes) { asm volatile("mbarrier.arrive.expect_tx.shared::cta.b64 _, [%0], %1;" ::"r"(bar), "r"(bytes) : "memory"); }
__device__ __forceinline__ bool mbar_try(uint32_t bar, uint32_t par) {
    uint32_t ok;
    asm volatile("{.reg .pred p; mbarrier.try_wait.parity.shared::cta.b64 p, [%1], %2; selp.u32 %0,1,0,p;}" : "=r"(ok) : "r"(bar), "r"(par) : "memory");
    return ok;
}
constexpr int SPIN_LIMIT = 1 << 18;
__device__ __forceinline__ void mbar_wait(uint32_t bar, uint32_t par) {
    if (mbar_try(bar, par)) return;
    asm volatile("{.reg .pred p, q; .reg .b32 n; mov.u32 n, 0;\n"
                 "W%=: mbarrier.try_wait.parity.shared::cta.b64 p, [%0], %1; add.u32 n, n, 1; setp.lt.and.u32 q, n, %2, !p; @q bra W%=;}"
                 ::"r"(bar), "r"(par), "n"(SPIN_LIMIT) : "memory");
}
__device__ __forceinline__ void bulk_g2s(uint32_t dst, const void* src, uint32_t bytes, uint32_t bar) {
    asm volatile("cp.async.bulk.shared::cluster.global.mbarrier::complete_tx::bytes [%0], [%1], %2, [%3];" ::"r"(dst), "l"(src), "r"(bytes), "r"(bar) : "memory");
}
__device__ __forceinline__ void bulk_s2g(void* dst, uint32_t src, uint32_t bytes) {
    asm volatile("cp.async.bulk.global.shared::cta.bulk_group [%0], [%1], %2;" ::"l"(dst), "r"(src), "r"(bytes) : "memory");
}
__device__ __forceinline__ void bulk_prefetch(const void* src, uint32_t bytes) {
    asm volatile("cp.async.bulk.prefetch.L2.global [%0], %1;" ::"l"(src), "r"(bytes) : "memory");
}
__device__ __forceinline__ void tma2d(uint32_t dst, const CUtensorMap* m, int c0, int c1, uint32_t bar) {
    asm volatile("cp.async.bulk.tensor.2d.shared::cluster.global.mbarrier::complete_tx::bytes [%0], [%1, {%3, %4}], [%2];" ::"r"(dst), "l"(m), "r"(bar), "r"(c0), "r"(c1) : "memory");
}
__device__ __forceinline__ void tma2d_mc(uint32_t dst, const CUtensorMap* m, int c0, int c1, uint32_t bar) {
    asm volatile("cp.async.bulk.tensor.2d.shared::cluster.global.mbarrier::complete_tx::bytes.multicast::cluster [%0], [%1, {%3, %4}], [%2], %5;" ::"r"(dst), "l"(m), "r"(bar), "r"(c0), "r"(c1), "h"((uint16_t)3) : "memory");
}
__device__ __forceinline__ uint32_t mapa(uint32_t a, uint32_t rank) { uint32_t r; asm("mapa.shared::cluster.u32 %0, %1, %2;" : "=r"(r) : "r"(a), "r"(rank)); return r; }
__device__ __forceinline__ void mbar_arrive_cl(uint32_t bar) { asm volatile("mbarrier.arrive.shared::cluster.b64 _, [%0];" ::"r"(bar) : "memory"); }
__device__ __forceinline__ void prefetch_map(const CUtensorMap* m) { asm volatile("prefetch.tensormap [%0];" ::"l"(m) : "memory"); }
__device__ __forceinline__ void cpasync16(uint32_t dst, const void* src, uint32_t srcsz) {
    asm volatile("cp.async.cg.shared.global [%0], [%1], 16, %2;" ::"r"(dst), "l"(src), "r"(srcsz) : "memory");
}
__device__ __forceinline__ void bar_sync(int id, int n) { asm volatile("bar.sync %0, %1;" ::"r"(id), "r"(n) : "memory"); }
__device__ __forceinline__ void bar_arrive(int id, int n) { asm volatile("bar.arrive %0, %1;" ::"r"(id), "r"(n) : "memory"); }
__device__ __forceinline__ void fence_async_smem() { asm volatile("fence.proxy.async.shared::cta;" ::: "memory"); }
__device__ __forceinline__ void fence_async_global() { asm volatile("fence.proxy.async.global;" ::: "memory"); }
__device__ __forceinline__ void flag_release(int f) { asm volatile("red.release.gpu.global.add.u32 [%0], 1;" ::"l"(&g_flags[f * 32]) : "memory"); }
__device__ __forceinline__ void flag_wait(int f, unsigned target) {
    const unsigned* p = &g_flags[f * 32];
    unsigned v; int n = 0;
    do {
        asm volatile("ld.relaxed.gpu.global.u32 %0, [%1];" : "=r"(v) : "l"(p) : "memory");
    } while ((int)(v - target) < 0 && ++n < SPIN_LIMIT);
    asm volatile("fence.acquire.gpu;" ::: "memory");
}
__device__ __forceinline__ unsigned ld_flag(const unsigned* p) { unsigned v; asm volatile("ld.relaxed.gpu.global.u32 %0, [%1];" : "=r"(v) : "l"(p) : "memory"); return v; }
__device__ __forceinline__ void spin(unsigned n) { unsigned t0, t1; asm volatile("mov.u32 %0, %%clock;" : "=r"(t0)); do { asm volatile("mov.u32 %0, %%clock;" : "=r"(t1)); } while (t1 - t0 < n); }
__device__ __forceinline__ void flag_wait2(int f0, int f1, unsigned target) {
    const unsigned *p = &g_flags[f0 * 32], *q = &g_flags[f1 * 32];
    unsigned v, w; int n = 0;
    do { v = ld_flag(p); w = ld_flag(q); } while ((int)((v - target) | (w - target)) < 0 && ++n < SPIN_LIMIT);
    asm volatile("fence.acquire.gpu;" ::: "memory");
}
__device__ __forceinline__ uint32_t lds32(uint32_t a) { uint32_t v; asm volatile("ld.shared.u32 %0, [%1];" : "=r"(v) : "r"(a)); return v; }
__device__ __forceinline__ float2 lds64f(uint32_t a) { float2 v; asm volatile("ld.shared.v2.f32 {%0,%1}, [%2];" : "=f"(v.x), "=f"(v.y) : "r"(a)); return v; }
__device__ __forceinline__ uint2 lds64(uint32_t a) { uint2 v; asm volatile("ld.shared.v2.u32 {%0,%1}, [%2];" : "=r"(v.x), "=r"(v.y) : "r"(a)); return v; }
__device__ __forceinline__ void sts64f(uint32_t a, float2 v) { asm volatile("st.shared.v2.f32 [%0], {%1,%2};" ::"r"(a), "f"(v.x), "f"(v.y) : "memory"); }
__device__ __forceinline__ void sts32(uint32_t a, uint32_t v) { asm volatile("st.shared.u32 [%0], %1;" ::"r"(a), "r"(v) : "memory"); }
__device__ __forceinline__ void sts64(uint32_t a, uint32_t x, uint32_t y) { asm volatile("st.shared.v2.u32 [%0], {%1,%2};" ::"r"(a), "r"(x), "r"(y) : "memory"); }
__device__ __forceinline__ void sts16(uint32_t a, uint16_t v) { asm volatile("st.shared.u16 [%0], %1;" ::"r"(a), "h"(v) : "memory"); }
__device__ __forceinline__ uint4 lds128(uint32_t a) { uint4 v; asm volatile("ld.shared.v4.u32 {%0,%1,%2,%3}, [%4];" : "=r"(v.x), "=r"(v.y), "=r"(v.z), "=r"(v.w) : "r"(a)); return v; }
__device__ __forceinline__ void sts128(uint32_t a, uint4 v) { asm volatile("st.shared.v4.u32 [%0], {%1,%2,%3,%4};" ::"r"(a), "r"(v.x), "r"(v.y), "r"(v.z), "r"(v.w) : "memory"); }
__device__ __forceinline__ void sts128f(uint32_t a, float x, float y, float z, float w) { asm volatile("st.shared.v4.f32 [%0], {%1,%2,%3,%4};" ::"r"(a), "f"(x), "f"(y), "f"(z), "f"(w) : "memory"); }
__device__ __forceinline__ uint32_t prmt(uint32_t a, uint32_t b, uint32_t s) { uint32_t r; asm("prmt.b32 %0,%1,%2,%3;" : "=r"(r) : "r"(a), "r"(b), "r"(s)); return r; }
__device__ __forceinline__ uint32_t pack2(float lo, float hi) { uint32_t r; asm("cvt.rn.bf16x2.f32 %0, %1, %2;" : "=r"(r) : "f"(hi), "f"(lo)); return r; }
__device__ __forceinline__ float blo(uint32_t v) { return __uint_as_float(v << 16); }
__device__ __forceinline__ float bhi(uint32_t v) { return __uint_as_float(v & 0xffff0000u); }
__device__ __forceinline__ uint32_t bmul2(uint32_t a, uint32_t b) { uint32_t r; asm("mul.rn.bf16x2 %0,%1,%2;" : "=r"(r) : "r"(a), "r"(b)); return r; }
__device__ __forceinline__ uint32_t badd2(uint32_t a, uint32_t b) { uint32_t r; asm("add.rn.bf16x2 %0,%1,%2;" : "=r"(r) : "r"(a), "r"(b)); return r; }
__device__ __forceinline__ float rbf(float x) { return __bfloat162float(__float2bfloat16_rn(x)); }
__device__ __forceinline__ uint32_t ldcg32(const void* p) { uint32_t v; asm volatile("ld.global.cg.u32 %0, [%1];" : "=r"(v) : "l"(p) : "memory"); return v; }
__device__ __forceinline__ uint4 ldcg128(const void* p) { uint4 v; asm volatile("ld.global.cg.v4.u32 {%0,%1,%2,%3}, [%4];" : "=r"(v.x), "=r"(v.y), "=r"(v.z), "=r"(v.w) : "l"(p) : "memory"); return v; }
__device__ __forceinline__ void stg32_if(void* p, uint32_t v, int on) { asm volatile("{.reg .pred q; setp.ne.b32 q, %2, 0; @q st.global.u32 [%0], %1;}" ::"l"(p), "r"(v), "r"(on) : "memory"); }
__device__ __forceinline__ uint4 ld_tagged(const void* p) {
    uint4 v;
    asm volatile("{.reg .b64 a, b; ld.relaxed.gpu.global.v2.b64 {a, b}, [%4]; mov.b64 {%0, %1}, a; mov.b64 {%2, %3}, b;}" : "=r"(v.x), "=r"(v.y), "=r"(v.z), "=r"(v.w) : "l"(p) : "memory");
    return v;
}
__device__ __forceinline__ uint2 ldcg64(const void* p) { uint2 v; asm volatile("ld.global.cg.v2.u32 {%0,%1}, [%2];" : "=r"(v.x), "=r"(v.y) : "l"(p) : "memory"); return v; }
__device__ __forceinline__ float half_rstd(float sum, float sq) {
    float mean = sum * (1.0f / D_), inv;
    asm("rsqrt.approx.ftz.f32 %0, %1;" : "=f"(inv) : "f"(fmaxf(fmaf(-mean, mean, fmaf(sq, 1.0f / D_, 1e-5f)), 1e-5f)));
    return 0.5f * inv;
}
__device__ __forceinline__ uint32_t bsub2(uint32_t a, uint32_t b) { uint32_t r; asm("sub.rn.bf16x2 %0,%1,%2;" : "=r"(r) : "r"(a), "r"(b)); return r; }
__device__ __forceinline__ uint32_t bfma2(uint32_t a, uint32_t b, uint32_t c) { uint32_t r; asm("fma.rn.bf16x2 %0,%1,%2,%3;" : "=r"(r) : "r"(a), "r"(b), "r"(c)); return r; }
__device__ __forceinline__ uint32_t gelu2_h(uint32_t h) {
    uint32_t u = bmul2(h, bfma2(bmul2(h, h), 0x3e923e92u, 0x3fcc3fccu)), th;
    asm("tanh.approx.bf16x2 %0, %1;" : "=r"(th) : "r"(u));
    return bfma2(h, th, h);
}
__device__ __forceinline__ uint3 row_stats(const uint32_t* v, int lane) {
    float s = 0.f, q = 0.f, s_ = 0.f, q_ = 0.f;
#pragma unroll
    for (int i = 0; i < 10; i++) { float a = blo(v[i]), b = bhi(v[i]); s += a; s_ += b; q = fmaf(a, a, q); q_ = fmaf(b, b, q_); }
    s += s_; q += q_;
    {
        float t = __shfl_xor_sync(0xffffffffu, (lane & 16) ? s : q, 16);
        t += (lane & 16) ? q : s;
#pragma unroll
        for (int m = 8; m; m >>= 1) t += __shfl_xor_sync(0xffffffffu, t, m);
        float o = __shfl_xor_sync(0xffffffffu, t, 16);
        s = (lane & 16) ? o : t; q = (lane & 16) ? t : o;
    }
    float mean = s * (1.0f / D_), inv;
    asm("rsqrt.approx.ftz.f32 %0, %1;" : "=f"(inv) : "f"(fmaxf(fmaf(-mean, mean, fmaf(q, 1.0f / D_, 1e-5f)), 1e-5f)));
    uint3 r;
    r.x = pack2(mean, mean);
    r.y = pack2(inv, inv);
    inv -= blo(r.y);
    r.z = pack2(inv, inv);
    return r;
}
__device__ __forceinline__ uint32_t ln_apply(uint32_t x, uint32_t m, uint32_t hi, uint32_t lo) {
    uint32_t xc = bsub2(x, m);
    return bmul2(xc, hi);
}

struct AFrag { uint32_t m, a, b, c, d; };
__device__ __forceinline__ AFrag ldA(uint32_t a) { AFrag f; f.m = lds32(a - 16); f.a = lds32(a); f.b = lds32(a + 16); f.c = lds32(a + 32); f.d = lds32(a + 48); return f; }
template <int N, int M> __device__ __forceinline__ void conv_pair(float* d, const AFrag& f, uint32_t descU) {
    WgRs<N>::template run<8 * M, desc_hi(128, 0), M ? 1 : 0>(d, f.a, f.b, f.m, f.a, descU);
    WgRs<N>::template run<8 * M + 1, desc_hi(128, 0), 1>(d, f.c, f.d, f.b, f.c, descU);
}
template <int Q> __device__ __forceinline__ void conv_put(float* d, uint32_t r0) {
    sts64(r0 + Q * 32, pack2(d[4 * Q + 1], d[4 * Q + 3]), pack2(d[4 * Q], d[4 * Q + 2]));
}
template <int M> __device__ __forceinline__ void conv_two(float* d, AFrag f0, AFrag f1, uint32_t kaddr, uint32_t descU, uint32_t r0, bool handoff) {
    constexpr int N = M < 14 ? 128 - 8 * M : 32;
    wg_fence();
    conv_pair<N, M>(d, f0, descU);
    wg_commit();
    if constexpr (M > 0) f1 = ldA(kaddr + 256 * (M + 1));
    wg_fence();
    conv_pair<N, M + 1>(d, f1, descU);
    wg_commit();
    if (STAG && M == STAG && handoff) bar_arrive(12, 256);
    if constexpr (M < 14) {
        if constexpr (M > 0) { conv_put<17 - M>(d, r0); conv_put<16 - M>(d, r0); }
        wg_wait<1>();
        f0 = ldA(kaddr + 256 * (M + 2));
        if constexpr (M < 12) wg_wait<0>();
        conv_two<M + 2>(d, f0, f1, kaddr, descU, r0, handoff);
    } else {
        wg_wait<0>();
        conv_put<3>(d, r0); conv_put<2>(d, r0); conv_put<1>(d, r0); conv_put<0>(d, r0);
    }
}
template <int N, bool ASWZ>
__device__ __forceinline__ void gemm_loop(float* acc, uint32_t sb, int half, int nkb, int keep, int ia0, int ib0, int rela, int relb, int wait_bar, int tsid) {
    int sa = ia0 % NA, pa = (ia0 / NA) & 1, sw = ib0 % NB, pw = (ib0 / NB) & 1;
    const uint32_t bars = sb + SM_BAR;
    const int t = threadIdx.x & 127;
    uint32_t ebar = mapa(bars + (t < 2 ? BAR_EB : BAR_EA) * 8, (t < 2 && lds32(sb + SM_GV + 516)) ? t : blockIdx.x & 1);
    const int nrel = t < 2 ? relb : t == 2 ? rela : 0;
    const uint32_t da0 = ASWZ ? desc_lo(sb + SM_RA + half * 8192, 16) : desc_lo(sb + SM_RA + half * 1024, 2048), db0 = desc_lo(sb + SM_RB, 8192);
    asm volatile("" : "+r"(ebar));
    if (wait_bar) bar_sync(wait_bar, 512);
    constexpr int AK = ASWZ ? 2 : 256, AH = ASWZ ? desc_hi(1024, 1) : desc_hi(128, 0), BH = desc_hi(1024, 1);
    int prev = 0;
    auto step = [&](int kb) {
        mbar_wait(bars + (BAR_FB + sw) * 8, pw);
        mbar_wait(bars + (BAR_FA + sa) * 8, pa);
        const uint32_t da = da0 + sa * (SLOT >> 4), db = db0 + sw * (SLOT >> 4);
        wg_fence();
        WgSs<N>::template run<0, AH, 0, BH>(acc, da, db, kb | keep);
        WgSs<N>::template run<AK, AH, 128, BH>(acc, da, db, 1);
        WgSs<N>::template run<2 * AK, AH, 256, BH>(acc, da, db, 1);
        WgSs<N>::template run<3 * AK, AH, 384, BH>(acc, da, db, 1);
        wg_commit();
        wg_wait<1>();
        if ((unsigned)(kb - 1) < (unsigned)nrel) mbar_arrive_cl(ebar + prev * 8);
        prev = t < 2 ? sw : sa;
        if (++sa == NA) { sa = 0; pa ^= 1; }
        if (++sw == NB) { sw = 0; pw ^= 1; }
    };
    if (PEEL) step(0);
#pragma unroll 1
    for (int kb = PEEL; kb < nkb; kb++) step(kb);
    wg_wait<0>();
    if (nrel == nkb) mbar_arrive_cl(ebar + prev * 8);
    reg_fence<N / 2>(acc);
    if ((threadIdx.x & 255) == 0) TS(tsid + 1);
}

template <int NS, int BASE, int BF, int BE> struct Ring {
    uint32_t sb, st, ph;
    __device__ __forceinline__ uint32_t acquire(uint32_t bytes) {
        mbar_wait(sb + SM_BAR + BE * 8 + st * 8, ph);
        uint32_t fb = sb + SM_BAR + BF * 8 + st * 8;
        mbar_expect(fb, bytes);
        return fb;
    }
    __device__ __forceinline__ uint32_t slot() { return sb + BASE + st * SLOT; }
    __device__ __forceinline__ void next() { if (++st == NS) { st = 0; ph ^= 1; } }
    __device__ __forceinline__ void run2d(const CUtensorMap* m, int c1) {
#pragma unroll 1
        for (int c0 = 64; c0 < D_; c0 += 64) {
            uint32_t fb = acquire(SLOT);
            tma2d(slot(), m, c0, c1, fb);
            next();
        }
    }
    static __device__ __forceinline__ int korder(int i, int own) { return i == 0 ? own : i > own ? i : i - 1; }
    __device__ __forceinline__ void runw(bool paired, int rk, const CUtensorMap* ma, const CUtensorMap* mb, int ca, int cb, int i0, int i1, int own, uint32_t bytes, int gate_at, uint32_t gate) {
        const CUtensorMap* m = rk ? mb : ma;
        const int c0 = rk ? cb : ca;
#pragma unroll 1
        for (int i = i0; i < i1; i++) {
            const int c1 = korder(i, own) * 64;
            if (i == gate_at) mbar_wait(gate, 0);
            uint32_t fb = acquire(bytes);
            if (paired) tma2d_mc(slot() + 8192 * rk, m, c0, c1, fb);
            else { tma2d(slot(), ma, ca, c1, fb); tma2d(slot() + 8192, mb, cb, c1, fb); }
            next();
        }
    }
    __device__ __forceinline__ void run1d(const char* src, int i0, int i1, int own) {
#pragma unroll 1
        for (int i = i0; i < i1; i++) {
            const char* s = src + korder(i, own) * SLOT;
            uint32_t fb = acquire(SLOT);
            bulk_g2s(slot(), s, SLOT, fb);
            next();
        }
    }
};

__global__ void __cluster_dims__(2, 1, 1) __launch_bounds__(NTHREADS, 1) fused_kernel(const Params p, const __grid_constant__ Maps maps) {
    extern __shared__ __align__(1024) unsigned char smem_raw[];
    const uint32_t sb = (smem_u32(smem_raw) + 1023u) & ~1023u;
#pragma unroll
    for (int i = 0; i < SEED; i++) asm volatile("{.reg .b32 t; mov.u32 t, %laneid;}");
    const uint32_t bars = sb + SM_BAR;
    const int tid = threadIdx.x, lane = tid & 31;
    unsigned smid;
    asm volatile("mov.u32 %0, %%smid;" : "=r"(smid));
    const bool spare = (smid >> 2) == 30;
    const int cta = smid < 120 ? smid : smid - 4;
    const int pg = cta >> 4, pi = cta & 15;
    const int hb = tid >= 320;
    if (!spare) {
        const unsigned t = tid - 320 * hb, r32 = t / 10u, cc = t - r32 * 10u, row = r32 + 64 * hb;
        const unsigned go = (unsigned)(pi * 128 * 1280 + pg * 160) + row * 1280u + cc * 16u;
        const uint32_t so = sb + (row >> 4) * 32u + row * 160u + cc * 16u;
        const char* kb = (const char*)p.k + go;
        const char* vb = (const char*)p.v + go;
        if (hb) {
            if (tid >= 640 - NBARS) {
                const int i = 639 - tid;
                mbar_init(bars + i * 8, (i >= BAR_EB && i < BAR_K) ? 4 : ((i >= BAR_EA && i < BAR_EB) || i == BAR_XY) ? 2 : 1);
                asm volatile("fence.mbarrier_init.release.cluster;" ::: "memory");
            }
            bar_arrive(14, 640);
            if (B_DELAY) spin(B_DELAY);
        }
        cpasync16(so + SM_PK + 2592, kb, 16);
        cpasync16(so + SM_PV, vb, 16);
        cpasync16(so + SM_PK + 3 * 2592, kb + 32 * 1280, 16);
        cpasync16(so + SM_PV + 2 * 2592, vb + 32 * 1280, 16);
        if (tid < 30) cpasync16(so + SM_PK + 13 * 160, pi ? kb - 3 * 1280 : kb, pi ? 16 : 0);
        asm volatile("cp.async.commit_group;" ::: "memory");
    }
    const int warp = __shfl_sync(0xffffffffu, tid >> 5, 0);
    const int wg = warp >> 2, wq = warp & 3;
    unsigned ep0 = 0;
    if (wg == 4 || spare) ep0 = *(volatile unsigned*)&g_epoch[smid];
#define ep1 (ep0 + 1)

    if (spare) {
        const int sp = smid & 3;
        if (tid == 32) { sts32(sb + SM_GV + 512, smid); asm volatile("fence.release.sync_restrict::shared::cta.cluster;" ::: "memory"); }
        asm volatile("barrier.cluster.arrive.relaxed.aligned;" ::: "memory");
        asm volatile("barrier.cluster.wait.aligned;" ::: "memory");
        if (tid == 0) {
            for (int i = 0; i < 4; i++) mbar_init(bars + i * 8, 1);
            asm volatile("fence.mbarrier_init.release.cluster;" ::: "memory");
        }
        if (warp == 0) { if (lane < 8) flag_wait(FL_P + lane, ep1 * 16); __syncwarp(); }
        __syncthreads();
        const int cq = tid % 54, rg = tid / 54;
        float a[8];
#pragma unroll
        for (int i = 0; i < 8; i++) a[i] = 0.f;
#pragma unroll 1
        for (int it = -4; it < 10; it++) {
            const uint32_t st = sb + (it & 3) * 55296, fb = bars + (it & 3) * 8;
            if (it >= 0) {
                mbar_wait(fb, (it >> 2) & 1);
                if (tid < 432) {
#pragma unroll 2
                    for (int i = 0; i < 8; i++) {
                        uint4 w = lds128(st + (cq >= 27 ? 27648 - 432 : 0) + (rg * 8 + i) * 432 + cq * 16);
                        a[0] += blo(w.x); a[1] += bhi(w.x); a[2] += blo(w.y); a[3] += bhi(w.y);
                        a[4] += blo(w.z); a[5] += bhi(w.z); a[6] += blo(w.w); a[7] += bhi(w.w);
                    }
                }
                __syncthreads();
            }
            if (it < 6 && warp == 19 && elect()) {
                mbar_expect(fb, 55296);
                tma2d(st, &maps.w3s, sp * 432, (it + 4) * 64, fb);
                tma2d(st + 27648, &maps.w3s, sp * 432 + 216, (it + 4) * 64, fb);
            }
        }
        if (tid < 432) {
            sts128f(sb + rg * 1728 + cq * 32, a[0], a[1], a[2], a[3]);
            sts128f(sb + rg * 1728 + cq * 32 + 16, a[4], a[5], a[6], a[7]);
        }
        __syncthreads();
        if (tid < 432) {
            float s = 0.f;
#pragma unroll
            for (int i = 0; i < 8; i++) s += __uint_as_float(lds32(sb + i * 1728 + tid * 4));
            g_cs[sp * 432 + tid] = s;
        }
        __syncthreads();
        if (tid == 0) { flag_release(FL_CS); g_epoch[smid] = ep1; TS(0); }
        if (warp == 0) TSFLUSH();
        return;
    }

    int gpc, idx;
    if (smid < 64) { gpc = (smid & 15) >> 1; idx = (smid >> 4) * 2 + (smid & 1); }
    else if (smid < 120) { int t = smid - 64; gpc = 1 + (t % 14) / 2; idx = 8 + (t / 14) * 2 + (smid & 1); }
    else { gpc = 0; idx = 8 + (smid - 124); }
    const int rb = 2 * gpc + (idx & 1), j = idx >> 1;
    const int g = lane >> 2, c = lane & 3;
    const int cm = 160 * (j >> 1) + 64 * (j & 1) + ((j & 2) ? 32 : 0), cr = 160 * (j >> 1) + 16 * (j & 1) + ((j & 2) ? 0 : 128);

    {
        if (warp == 5) TSW(61);
        const int w10 = warp - 10 * hb, h = w10 >= 5;
        const int pr = (w10 - 5 * h) * 8 + (lane >> 2), blk = 4 * hb + (lane & 3);
        const int ch = 80 * pg + 2 * pr;
        const uint4 sw = __ldg(reinterpret_cast<const uint4*>(p.shift + ch * 4));
        uint32_t dv = 0;
        if (warp == 9 && lane < 5) dv = __bfloat16_as_ushort(p.ssmD[cta * 5 + lane]);
        if (tid == 512) { sts32(sb + SM_GV + 512, smid); asm volatile("fence.release.sync_restrict::shared::cta.cluster;" ::: "memory"); }
        asm volatile("barrier.cluster.arrive.relaxed.aligned;" ::: "memory");
        if (warp == 11 && lane < 13) prefetch_map(&maps.hn + lane);
        if (wg < 4) {
            const int t = tid & 127, cc = (wg == 3 && t >= 64) ? 4 : wg;
            if (t < 64 || wg == 3) sts128(sb + sm_u(cc) + ((t >> 5) & 1) * U_PLANE + 2048 + lane * 16, make_uint4(0, 0, 0, 0));
            if ((t & 63) < 4 && (t < 64 || wg == 3)) sts128(sb + sm_k(cc) + ((t >> 1) & 1) * 4160 + (t & 1) * 16, make_uint4(0, 0, 0, 0));
        }
        if (warp == 9 && lane < 5) sts32(sb + SM_GV + 520 + lane * 4, dv << 16);
        asm volatile("cp.async.wait_group 0;" ::: "memory");
        if (!hb) bar_arrive(12, 640);
        bar_sync(hb ? 12 : 14, 640);
        if (warp == 9) {
            if (SSM_DELAY) spin(SSM_DELAY);
            if (elect()) {
#pragma unroll
                for (int i = 0; i < SSM_N; i++) {
                    mbar_expect(bars + (BAR_K + i) * 8, 4096);
                    bulk_g2s(sb + sm_k(i) + 32, p.ssmk + (size_t)(cta * 5 + i) * S_, 4096, bars + (BAR_K + i) * 8);
                }
            }
        }
        const uint32_t w0 = prmt(sw.x, sw.z, 0x5410), w1 = prmt(sw.x, sw.z, 0x7632), w2 = prmt(sw.y, sw.w, 0x5410), w3 = prmt(sw.y, sw.w, 0x7632);
        const uint32_t ka = sb + SM_PK + 2592 + blk * 2592 + h * 1280 + pr * 4;
        const uint32_t va = sb + SM_PV + blk * 2592 + h * 1280 + pr * 4;
        uint32_t kk[11], kv[8];
#pragma unroll
        for (int i = 0; i < 11; i++) kk[i] = lds32(ka + (i - 3) * 160 - ((i < 3 && h == 0) ? 32 : 0));
#pragma unroll
        for (int i = 0; i < 8; i++) {
            uint32_t t = badd2(badd2(badd2(bmul2(kk[i], w3), bmul2(kk[i + 1], w2)), bmul2(kk[i + 2], w1)), bmul2(kk[i + 3], w0));
            kv[i] = bmul2(t, lds32(va + i * 160));
        }
        uint4 o0, o1;
        o0.x = prmt(kv[1], kv[0], 0x5410); o0.y = prmt(kv[3], kv[2], 0x5410); o0.z = prmt(kv[5], kv[4], 0x5410); o0.w = prmt(kv[7], kv[6], 0x5410);
        o1.x = prmt(kv[1], kv[0], 0x7632); o1.y = prmt(kv[3], kv[2], 0x7632); o1.z = prmt(kv[5], kv[4], 0x7632); o1.w = prmt(kv[7], kv[6], 0x7632);
        uint4* dst = reinterpret_cast<uint4*>(g_kvT) + ch * 256 + h * 128 + (127 - (8 * pi + blk));
        dst[0] = o0;
        dst[256] = o1;
    }

    const int rho = 8 * rb + j;

    if (wg == 4) {
        asm volatile("setmaxnreg.dec.sync.aligned.u32 32;");
        if (wq == 0) {
            bar_sync(13, 640);
            TSW(39);
            if (lane == 0) flag_release(FL_P + pg);
            __syncwarp();
            TSW(2);
            if (lane < 5) mbar_expect(bars + (BAR_U + lane) * 8, 4096);
            flag_wait(FL_P + pg, ep1 * 16);
            fence_async_global();
            TSW(3);
            if (elect()) {
#pragma unroll UNR_U
                for (int i = 0; i < 5; i++) {
                    const char* us = (const char*)g_kvT + (size_t)(cta * 5 + i) * 4096;
                    bulk_g2s(sb + sm_u(i), us, 2048, bars + (BAR_U + i) * 8);
                    bulk_g2s(sb + sm_u(i) + U_PLANE, us + 2048, 2048, bars + (BAR_U + i) * 8);
                }
            }
            __syncwarp();
            if (elect()) {
#pragma unroll
                for (int i = SSM_N; i < 5; i++) {
                    mbar_expect(bars + (BAR_K + i) * 8, 4096);
                    bulk_g2s(sb + sm_k(i) + 32, p.ssmk + (size_t)(cta * 5 + i) * S_, 4096, bars + (BAR_K + i) * 8);
                }
                if (cta < 120) {
                    mbar_expect(bars + BAR_WM * 8, 40960);
#pragma unroll 1
                    for (int i = 0; i < 5; i++) tma2d(sb + SM_WM + i * 8192, &maps.wm, cta * 32, i * 128, bars + BAR_WM * 8);
                }
                bulk_prefetch((const char*)p.q + cta * 20480, 20480);
                bulk_prefetch((const char*)p.w1 + cta * 6400, 6400);
                bulk_prefetch((const char*)p.w2 + cta * 6400, 6400);
            }
            __syncwarp();
        } else {
            bar_arrive(13, 640);
        }
        asm volatile("barrier.cluster.wait.aligned;" ::: "memory");
        uint32_t peer;
        asm volatile("ld.shared::cluster.u32 %0, [%1];" : "=r"(peer) : "r"(mapa(sb + SM_GV + 512, (blockIdx.x & 1) ^ 1)) : "memory");
        const bool paired = peer == (smid ^ 1);
        if (tid == 639) { sts32(sb + SM_GV + 516, paired); sts32(sb + SM_GV + 540, ep1); }
        if (cta < 120) {
            float d[4];
            if (tid < 592) {
                const int t = tid - 512;
                mbar_wait(bars + BAR_U * 8, 0);
                uint4 cv = __ldg(reinterpret_cast<const uint4*>(p.c) + t);
                auto silu2 = [](uint32_t v) { float a = blo(v), b = bhi(v); return pack2(__fdividef(a, 1.0f + __expf(-a)), __fdividef(b, 1.0f + __expf(-b))); };
#pragma unroll UNR_G
                for (int i = 0; i < 4; i++) { const uint32_t r = silu2(cv.x); cv.x = cv.y; cv.y = cv.z; cv.z = cv.w; cv.w = r; }
                sts128(sb + SM_Y + (t % 40) * 32 + (t / 40) * 16, cv);
                fence_async_smem();
            }
            bar_sync(5, 128);
            mbar_wait(bars + BAR_WM * 8, 0);
            if (wq == 3) TSW(56);
            const uint32_t da = desc_lo(sb + SM_WM, 20480), db = desc_lo(sb + SM_Y, 32);
#pragma unroll UNR_G
            for (int k0 = 0; k0 < 20; k0 += 4) {
                wg_fence();
#pragma unroll
                for (int k = k0; k < k0 + 4; k++) asm volatile("{.reg .pred p; .reg .b32 l,m; .reg .b64 da,db; setp.ne.b32 p,%10,0; add.u32 l,%4,%6; mov.b64 da,{l,%8}; add.u32 m,%5,%7; mov.b64 db,{m,%9};"
                             " wgmma.mma_async.sync.aligned.m64n8k16.f32.bf16.bf16 {%0,%1,%2,%3},da,db,p,1,1,1,0;}"
                             : "+f"(d[0]), "+f"(d[1]), "+f"(d[2]), "+f"(d[3])
                             : "r"(da), "r"(db), "r"(64 * k), "r"(4 * k), "n"(desc_hi(512, 2u)), "n"(desc_hi(128, 0)), "r"(k));
                wg_commit();
            }
            wg_wait<0>();
            reg_fence<4>(d);
            if (c == 0) {
                sts32(sb + SM_GV + (16 * wq + g) * 4, __float_as_uint(wq < 2 ? d[0] : d[1]));
                sts32(sb + SM_GV + (16 * wq + g + 8) * 4, __float_as_uint(wq < 2 ? d[2] : d[3]));
            }
            bar_sync(5, 128);
            if (wq == 2) {
                g_mod[cta * 32 + lane] = __float2bfloat16_rn(__uint_as_float(lds32(sb + SM_GV + lane * 4)) + __uint_as_float(lds32(sb + SM_GV + 128 + lane * 4)));
                __syncwarp();
                if (lane == 0) flag_release(FL_M);
                __syncwarp();
                TSW(4);
            }

        }
        if (wq == 2) {
            flag_wait(FL_M, ep1 * 120);
            fence_async_global();
            if (elect()) {
                mbar_expect(bars + BAR_M * 8, 7680);
                bulk_g2s(sb + SM_MOD, g_mod, 7680, bars + BAR_M * 8);
            }
            __syncwarp();
            TSW(60);
#pragma unroll UNR_S
            for (int i = 0; i < 5; i++) {
                bar_sync((0x216f8 >> (4 * i)) & 15, i ? 288 : 544);
                if (lane == 0) {
                    if (i > 2) TS(50 + i);
                    flag_release(FL_R + 16 * i + rb);
                    if (i > 2) mbar_expect(bars + BAR_LR * 8, 0);
                    TS(i < 3 ? 23 + 4 * i : 54 + i);
                }
                __syncwarp();
            }
            if (lane == 0) g_epoch[smid] = ep1;
            return;
        }
        if (wq == 1) {
            bar_sync(9, 288);
            if (lane < 4 * NB) mbar_arrive_cl(mapa(bars + (BAR_EB + (lane >> 2)) * 8, paired ? lane & 1 : blockIdx.x & 1));
        }
        if (wq == 3) {
            bar_sync(7, 544);
            if (lane == 0) { flag_release(FL_C); TS(20); }
            __syncwarp();
            if (lane < 2) mbar_expect(bars + (lane ? BAR_Y2 : BAR_Y) * 8, lane ? 8192 : 12288);
            flag_wait(FL_C, ep1 * 128);
            fence_async_global();
            TSW(21);
            if (elect()) {
                bulk_g2s(sb + SM_Y, g_yv + rho * 5120, 12288, bars + BAR_Y * 8);
                bulk_g2s(sb + SM_Y + 12288, g_yv + rho * 5120 + 3072, 8192, bars + BAR_Y2 * 8);
            }
            __syncwarp();
        }
        if (elect()) {
            if (wq == 3) {
                mbar_expect(bars + BAR_XY * 8, 20480);
#pragma unroll 1
                for (int i = 0; i < 8; i++) {
                    bulk_g2s(sb + SM_YT + i * 2560, g_yv + (8 * rb + i) * 5120 + cm * 8, 2048, bars + BAR_XY * 8);
                    bulk_g2s(sb + SM_YT + i * 2560 + 2048, g_yv + (8 * rb + i) * 5120 + cr * 8, 512, bars + BAR_XY * 8);
                }
                mbar_wait(bars + BAR_FA * 8, 0);
                bulk_prefetch((const char*)p.w4 + cta * 17280, 17280);
                flag_wait(FL_CS, ep1 * 4);
                fence_async_global();
                mbar_expect(bars + BAR_CS * 8, 864);
                bulk_g2s(sb + SM_CS, g_cs + 64 * j, 256, bars + BAR_CS * 8);
                bulk_g2s(sb + SM_CS + 256, g_cs + 512 + RA3 * j, 4 * RA3, bars + BAR_CS * 8);
                bulk_g2s(sb + SM_CS + 256 + 4 * RA3, g_cs + HB0 + 64 * j, 256, bars + BAR_CS * 8);
                bulk_g2s(sb + SM_CS + 512 + 4 * RA3, g_cs + HB0 + 512 + RB3 * j, 4 * RB3, bars + BAR_CS * 8);
#pragma unroll 1
                for (int i = 0; i < 2; i++) {
                    mbar_wait(bars + BAR_LR * 8, i);
                    flag_wait(FL_G + 16 * i + rb, ep1 * 8);
                    mbar_expect(bars + (BAR_G + i) * 8, 0);
                    TS(35 + i);
                }
            } else if (wq == 1) {
                Ring<NB, SM_RB, BAR_FB, BAR_EB> r{sb, 0, 0};
#pragma unroll 1
                for (int ph = 0; ph < 7; ph++) {
                    const CUtensorMap* ma = ph == 0 ? &maps.w1a : ph == 1 ? &maps.w2a : ph == 6 ? &maps.w4a : &maps.w3a;
                    const bool b3b = ph == 2 || ph == 4 || ph == 5;
                    r.runw(paired, idx & 1, ma, ma + (b3b ? 2 : 1), ph == 3 ? 64 * j : b3b ? HB0 + 64 * j : cm,
                           ph == 3 ? 512 + RA3 * j : b3b ? HB0 + 512 + RB3 * j : cr, ph == 4 ? 10 - NA : ph == 5 ? 1 : 0,
                           ph == 6 ? 27 : ph == 5 ? 10 - NA : ph == 2 ? 1 : 10, ph == 0 ? 0 : ph == 6 ? HB0 / 64 + j : cm >> 6,
                           ph == 3 ? 8192 + 128 * RA3 : b3b ? 8192 + 128 * RB3 : 10240,
                           ph == 1 ? GATE : ph == 3 ? GATE - 1 : -1, bars + (BAR_ST - (ph == 1)) * 8);
                }
            } else {
                Ring<NA, SM_RA, BAR_FA, BAR_EA> r{sb, 0, 0};
                if (cta >= 120) mbar_wait(bars + (BAR_K + 4) * 8, 0);
                mbar_expect(bars + BAR_XR * 8, 20480);
                bulk_g2s(sb + SM_XR, p.q + (size_t)rho * 16 * D_, 20480, bars + BAR_XR * 8);
                mbar_expect(bars + BAR_XY * 8, 20480);
                tma2d(sb + SM_XT, &maps.xa, cm, rb * 128, bars + BAR_XY * 8);
                tma2d(sb + SM_XT2, &maps.xb, cr, rb * 128, bars + BAR_XY * 8);
                const int grp = j >> 1;
                const int delta = (grp & 1 ? 1 : -1) * (1 + (grp >> 1));
                const int nb = min(max(rb + (delta > 0 ? 1 : -1), 0), 15);
                const uint32_t fb0 = r.acquire(SLOT);
                flag_wait2(FL_R + nb, FL_R + rb, ep1 * 8);
                fence_async_global();
                tma2d(sb + SM_RA, &maps.hn, 0, rb * 128 + delta, fb0);
                TS(24);
                r.next();
                r.run2d(&maps.hn, rb * 128 + delta);
#pragma unroll UNR_A
                for (int ph = 0; ph < 5; ph++) {
                    const char* src = ph == 0 ? (const char*)g_h1 + rb * 163840 : ph < 3 ? (const char*)g_x1 + rb * 163840 : (const char*)g_g + rb * 442368;
                    const int own = ph < 3 ? cm >> 6 : HB0 / 64 + j;
                    if (ph != 2 && ph != 4) { r.acquire(0); r.next(); }
                    const int i0 = ph == 4 ? 1 + HB0 / 64 : 1;
                    const char* src1 = src + r.korder(i0, own) * SLOT;
                    const uint32_t fb = r.acquire(SLOT), dst = r.slot();
                    if (ph < 2) flag_wait(FL_B1 + 16 * ph + rb, ep1 * 8);
                    if (ph > 2) mbar_wait(bars + (BAR_G - 3 + ph) * 8, 0);
                    fence_async_global();
                    bulk_g2s(dst, src1, SLOT, fb);
                    if (ph < 2) { TS(28 + 4 * ph); mbar_expect(bars + (BAR_ST - 1 + ph) * 8, 0); }
                    r.next();
                    r.run1d(src, i0 + 1, ph < 2 ? 10 : ph == 2 ? 10 - NA : ph == 3 ? 1 + HB0 / 64 : 27, own);
                }
            }
        }
        return;
    }
    bar_arrive(13, 640);
    asm volatile("setmaxnreg.inc.sync.aligned.u32 112;");
    const int rrow = 16 * rho + (warp >> 1) + 8 * (warp & 1);

    fence_async_smem();
    bar_sync(1 + wg, 128);
#pragma unroll 1
    for (int cc = wg; cc < wg + 1 + (wg == 3); cc++) {
        mbar_wait(bars + (BAR_K + cc) * 8, 0);
        if (cc == 2 && wq == 0) TSW(40);
        uint32_t a = sb + sm_k(cc) + 32 + (tid & 127) * 32;
        uint32_t pw = lds32(a - 4);
        uint4 x = lds128(a), y = lds128(a + 16), o;
        if ((tid & 127) == 0) {
            uint16_t k0 = __bfloat16_as_ushort(__float2bfloat16_rn(blo(x.x) + __uint_as_float(lds32(sb + SM_GV + 520 + cc * 4))));
            x.x = (x.x & 0xffff0000u) | k0;
            sts16(a, k0);
        }
        o.x = prmt(pw, x.x, 0x5432); o.y = prmt(x.x, x.y, 0x5432); o.z = prmt(x.y, x.z, 0x5432); o.w = prmt(x.z, x.w, 0x5432);
        sts128(a + 4160, o);
        o.x = prmt(x.w, y.x, 0x5432); o.y = prmt(y.x, y.y, 0x5432); o.z = prmt(y.y, y.z, 0x5432); o.w = prmt(y.z, y.w, 0x5432);
        sts128(a + 4176, o);
    }
    bar_sync(1 + wg, 128);
    if (wg == 3) bar_arrive(11, 256);
#pragma unroll 1
    for (int cc = wg; cc < 5; cc += 3) {
        if (cc == 3 && wg == 0) break;
        if (cc == 4) bar_sync(11, 256);
        const uint32_t kaddr = sb + sm_k(cc) + ((g & 1) ? 32 : 4192) + 4 * ((g >> 1) - c) + 64 * wq;
        const AFrag f0 = ldA(kaddr), f1 = ldA(kaddr + 256);
        if (STAG && cc == 3) bar_sync(12, 256);
        mbar_wait(bars + (BAR_U + cc) * 8, 0);
        if (wq == 0) TSW(5 + cc);
        float d[64];
        conv_two<0>(d, f0, f1, kaddr, desc_lo(sb + sm_u(cc), U_PLANE), sb + sm_red(cc) + wq * 4352 + g * 544 + c * 8, cc == 1);
        if (wq == 0) TSW(10 + cc);
        if (cc == 1) bar_arrive(6, 256);
    }
#pragma unroll 1
    for (int cc = wg == 1 ? 4 : wg;; cc++) {
        if (cc == 1) bar_sync(6, 256); else bar_sync(1 + wg, 128);
        const int ch = cta * 5 + cc;
        uint32_t* dst = g_yv + ch * 8 + ((g + (ch >> 2)) & 7) + (126 - 32 * wq - 2 * c) * 5120;
        uint2 v[16];
#pragma unroll
        for (int i = 0; i < 16; i++) v[i] = lds64(sb + sm_red(cc) + g * 544 + wq * 128 + c * 8 + (i >> 2) * 32 + (i & 3) * 4360);
#pragma unroll
        for (int w = 1; w < 4; w++)
            if (wq == 3 && c > 3 - w) v[12 + w] = make_uint2(0, 0);
#pragma unroll
        for (int q = 0; q < 4; q++) {
            const uint2* u = v + 4 * q;
            dst[-8 * q * 5120] = badd2(u[0].x, badd2(u[1].x, badd2(u[2].x, u[3].x)));
            dst[(-8 * q + 1) * 5120] = badd2(u[0].y, badd2(u[1].y, badd2(u[2].y, u[3].y)));
        }
        if (wq == 0) TSW(15 + cc);
        if (cc != 0) break;
    }
    fence_async_smem();
    if (!(wg & 1)) bar_arrive(9, 288);
    bar_arrive(7, 544);

    const uint32_t one2 = 0x3f803f80u;
    const unsigned ones = p.ones;
    {
        uint32_t x[10], a[10], cb[10], sbv[10];
        if (RPRE_WAIT) bar_sync(10, 512);
        mbar_wait(bars + BAR_XR * 8, 0);
#pragma unroll
        for (int i = 0; i < 10; i++) x[i] = lds32(sb + SM_XR + (rrow & 15) * 1280 + lane * 4 + i * 128);
        const uint3 s1 = row_stats(x, lane);
        const int up = lane >> 4, gg = warp >> 1, e = warp & 1;
        const uint32_t ya = sb + SM_Y + lane * 64 + ((gg + (lane >> 1)) & 7) * 4;
        const uint32_t sel = (up ? 0x1054u : 0x5410u) + (e ? 0x2222u : 0u);
        const uint32_t ma = sb + SM_MOD + lane * 4;
        mbar_wait(bars + BAR_M * 8, 0);
        uint32_t pin = 0;
#pragma unroll
        for (int i = 0; i < 10; i++) {
            uint32_t h = bfma2(ln_apply(x[i], s1.x, s1.y, s1.z), badd2(lds32(ma + 1280 + i * 128), one2), lds32(ma + i * 128));
            a[i] = bmul2(h, lds32(ma + 2560 + i * 128));
            sbv[i] = lds32(ma + 3840 + i * 128);
            cb[i] = badd2(lds32(ma + 5120 + i * 128), one2);
            pin ^= a[i] ^ cb[i];
        }
        if (pin & ~ones) sts32(sb + SM_GV, pin);
        if (warp == 4) TSW(52);
        mbar_wait(bars + BAR_Y * 8, 0);
        if (warp == 0) TSW(22);
#pragma unroll
        for (int i = 0; i < 10; i++) {
            if (i == 6) mbar_wait(bars + BAR_Y2 * 8, 0);
            uint32_t y0 = lds32(ya + i * 2048 + up * 32), y1 = lds32(ya + i * 2048 + (up ^ 1) * 32);
            x[i] = bfma2(a[i], prmt(y0, y1, sel), x[i]);
        }
        const uint3 s2 = row_stats(x, lane);
#pragma unroll
        for (int i = 0; i < 10; i++) x[i] = bfma2(ln_apply(x[i], s2.x, s2.y, s2.z), cb[i], sbv[i]);
        const uint3 s3 = row_stats(x, lane);
        uint32_t* o = reinterpret_cast<uint32_t*>(g_hn + (size_t)rrow * D_) + lane;
#pragma unroll
        for (int i = 0; i < 10; i++) o[32 * i] = ln_apply(x[i], s3.x, s3.y, s3.z);
        if (lane < 2) g_rs[rrow * 2 + lane] = lane ? make_uint4(s2.x, s2.y, s2.z, 0) : make_uint4(s1.x, s1.y, s1.z, 0);
        if (warp == 0) TSW(34);
        bar_arrive(8, 544);
    }

    const int half = wg & 1;
    const int row = 64 * half + 16 * wq + g;
    const int tw0 = (rb * 80 + (cm >> 3)) * 512 + row * 4 + c, tw1 = (rb * 80 + (cr >> 3) - 8) * 512 + row * 4 + c;
    const uint32_t park = sb + SM_Y + (tid & 255) * 16;
    const uint32_t ms0 = sb + SM_MOD + (cm + 2 * c) * 2, ms1 = sb + SM_MOD + (cr - 64 + 2 * c) * 2;
    float ac3[56];
    float2 cs[14];
    unsigned goff0, goff1;
    auto load_cs = [&](int part) {
        mbar_wait(bars + BAR_CS * 8, 0);
#pragma unroll
        for (int q = 0; q < 14; q++) cs[q] = lds64f(sb + SM_CS + part * 448 + 8 * c + 32 * q);
        goff0 = (rb * 216 + 112 * part + 8 * j) * 512 + row * 4 + c;
        goff1 = goff0 + (56 - (2 + part) * j) * 512;
    };
    auto epi3 = [&](const int part) {
        const uint4 rp = lds128(sb + SM_RP + ((tid & 255) >> 2) * 16);
        const float nb0 = __uint_as_float(rp.y), nb1 = __uint_as_float(rp.w);
        const uint32_t own = sb + SM_RA + ((39 - NA) % NA) * SLOT + row * 16 + c * 4;
        uint32_t* dst = reinterpret_cast<uint32_t*>(g_g) + goff0;
        uint32_t* dst1 = reinterpret_cast<uint32_t*>(g_g) + goff1;
#pragma unroll
        for (int k = 0; k < 14; k += 4) CHUNK(k) {
#pragma unroll
            for (int q = k; q < k + 4 && q < 14 - part; q++) {
                const uint32_t u = gelu2_h(bmul2(pack2(fmaf(nb0, cs[q].x, ac3[4 * q]), fmaf(nb0, cs[q].y, ac3[4 * q + 1])), rp.x));
                const uint32_t v = gelu2_h(bmul2(pack2(fmaf(nb1, cs[q].x, ac3[4 * q + 2]), fmaf(nb1, cs[q].y, ac3[4 * q + 3])), rp.z));
                (q < 8 ? dst : dst1)[q * 512] = u;
                (q < 8 ? dst : dst1)[q * 512 + 32] = v;
                if (q < 8 && part) { sts32(own + q * 2048, u); sts32(own + q * 2048 + 128, v); }
            }
            if (k == 4 && part) fence_async_smem();
        }
        bar_arrive(1 + part, 288);
        bar_arrive(10 + part, 512);
    };
    if (wg >= 2) {
        {
            float acc[40];
            gemm_loop<80, true>(acc, sb, half, 10, 0, 0, 0, 10, 10, 0, 25);
#pragma unroll
            for (int k = 0; k < 10; k += CH) CHUNK(k) {
#pragma unroll
                for (int q = k; q < k + CH && q < 10; q++) {
                    uint32_t* dst = reinterpret_cast<uint32_t*>(g_h1) + (q < 8 ? tw0 : tw1);
                    const uint32_t u = gelu2_h(bmul2(pack2(acc[4 * q], acc[4 * q + 1]), 0x3f003f00u));
                    const uint32_t v = gelu2_h(bmul2(pack2(acc[4 * q + 2], acc[4 * q + 3]), 0x3f003f00u));
                    dst[q * 512] = u;
                    dst[q * 512 + 32] = v;
                    acc[4 * q] = __uint_as_float(u); acc[4 * q + 1] = __uint_as_float(v);
                }
            }
            bar_arrive(15, 288);
            mbar_wait(bars + (BAR_FA + 10 % NA) * 8, (10 / NA) & 1);
#pragma unroll
            for (int q = 0; q < 8; q++) {
                sts32(sb + SM_RA + (10 % NA) * SLOT + q * 2048 + row * 16 + c * 4, __float_as_uint(acc[4 * q]));
                sts32(sb + SM_RA + (10 % NA) * SLOT + q * 2048 + row * 16 + c * 4 + 128, __float_as_uint(acc[4 * q + 1]));
            }
            fence_async_smem();
            bar_arrive(14, 512);
        }
        load_cs(0);
        gemm_loop<112, false>(ac3, sb, half, 10, 0, 20, 21, 10 - NA, 10, 9, 46);
        bar_sync(13, 512);
        epi3(0);
    } else {
        {
            float acc[40];
            uint32_t x2[20];
            {
                uint32_t y[20];
                mbar_wait(bars + BAR_XY * 8, 0);
                const uint32_t xa = sb + SM_XT + row * 128 + c * 4, xb = sb + SM_XT2 + row * 32 + c * 4;
                const uint32_t ya = sb + SM_YT + (4 * half + wq) * 2560 + c * 64;
#pragma unroll
                for (int q = 0; q < 10; q++) {
                    const uint32_t a = q < 8 ? xa + ((q ^ g) << 4) : xb + (q - 8) * 16;
                    x2[2 * q] = lds32(a); x2[2 * q + 1] = lds32(a + (q < 8 ? 1024 : 256));
                    const int pos = (g + ((q < 8 ? cm : cr) >> 2) + 2 * q + (c >> 1)) & 7;
                    y[2 * q] = lds32(ya + q * 256 + pos * 4); y[2 * q + 1] = lds32(ya + q * 256 + 32 + pos * 4);
                }
                fence_async_smem();
                bar_sync(1 + wg, 128);
                if ((tid & 127) < NA) mbar_arrive_cl(mapa(bars + (BAR_EA + (tid & 127)) * 8, blockIdx.x & 1));
                mbar_wait(bars + (BAR_FA + 1) * 8, 0);
                const uint4* rp = g_rs + (rb * 128 + row) * 2;
                const uint4 ra = ldcg128(rp), rb2 = ldcg128(rp + 1), rc = ldcg128(rp + 16), rd = ldcg128(rp + 17);
                bar_sync(14, 512);
#pragma unroll
                for (int q = 0; q < 10; q++) {
                    const uint32_t ms = q < 8 ? ms0 : ms1;
                    const uint32_t sa = lds32(ms + 16 * q), ca = badd2(lds32(ms + 1280 + 16 * q), one2), ga = lds32(ms + 2560 + 16 * q);
                    const uint32_t sbv = lds32(ms + 3840 + 16 * q), cb = badd2(lds32(ms + 5120 + 16 * q), one2);
                    uint32_t u = x2[2 * q], v = x2[2 * q + 1];
                    u = bfma2(bmul2(bfma2(ln_apply(u, ra.x, ra.y, ra.z), ca, sa), ga), prmt(y[2 * q], y[2 * q + 1], 0x5410), u);
                    v = bfma2(bmul2(bfma2(ln_apply(v, rc.x, rc.y, rc.z), ca, sa), ga), prmt(y[2 * q], y[2 * q + 1], 0x7632), v);
                    x2[2 * q] = u; x2[2 * q + 1] = v;
                    u = bfma2(ln_apply(u, rb2.x, rb2.y, rb2.z), cb, sbv);
                    v = bfma2(ln_apply(v, rd.x, rd.y, rd.z), cb, sbv);
                    acc[4 * q] = blo(u); acc[4 * q + 1] = bhi(u); acc[4 * q + 2] = blo(v); acc[4 * q + 3] = bhi(v);
                }
            }
            reg_fence<40>(acc);
            if (tid == 0) TS(45);
            gemm_loop<80, false>(acc, sb, half, 10, 1, 10, 10, 10, 10, 0, 29);
            uint32_t x1[20];
            float s0 = 0.f, q0 = 0.f, s1 = 0.f, q1 = 0.f;
#pragma unroll
            for (int q = 0; q < 10; q++) {
                uint32_t u = pack2(acc[4 * q], acc[4 * q + 1]);
                uint32_t v = pack2(acc[4 * q + 2], acc[4 * q + 3]);
                uint32_t* dst = reinterpret_cast<uint32_t*>(g_x1) + (q < 8 ? tw0 : tw1);
                dst[q * 512] = u;
                dst[q * 512 + 32] = v;
                x1[2 * q] = u; x1[2 * q + 1] = v;
            }
            bar_arrive(6, 288);
            CHUNK(0)
#pragma unroll
            for (int q = 0; q < 10; q++) {
                float a = blo(x1[2 * q]), b = bhi(x1[2 * q]), e = blo(x1[2 * q + 1]), f = bhi(x1[2 * q + 1]);
                s0 += a + b; q0 = fmaf(a, a, fmaf(b, b, q0));
                s1 += e + f; q1 = fmaf(e, e, fmaf(f, f, q1));
            }
#pragma unroll
            for (int m = 1; m <= 2; m <<= 1) {
                s0 += __shfl_xor_sync(0xffffffffu, s0, m); q0 += __shfl_xor_sync(0xffffffffu, q0, m);
                s1 += __shfl_xor_sync(0xffffffffu, s1, m); q1 += __shfl_xor_sync(0xffffffffu, q1, m);
            }
            if (c < 2) asm volatile("{.reg .b64 a, b; mov.b64 a, {%1, %3}; mov.b64 b, {%2, %3}; st.relaxed.gpu.global.v2.b64 [%0], {a, b};}"
                                    ::"l"(&g_st[(rb * 8 + j) * 128 + row + 8 * c]), "r"(__float_as_uint(c ? s1 : s0)), "r"(__float_as_uint(c ? q1 : q0)), "r"(lds32(sb + SM_GV + 540)) : "memory");
            mbar_wait(bars + (BAR_FA + 20 % NA) * 8, (20 / NA) & 1);
#pragma unroll
            for (int q = 0; q < 8; q++) {
                sts32(sb + SM_RA + (20 % NA) * SLOT + q * 2048 + row * 16 + c * 4, x1[2 * q]);
                sts32(sb + SM_RA + (20 % NA) * SLOT + q * 2048 + row * 16 + c * 4 + 128, x1[2 * q + 1]);
            }
            fence_async_smem();
            bar_sync(3 + wg, 128);
#pragma unroll
            for (int q = 0; q < 5; q++) {
                const uint32_t ms = q < 4 ? ms0 : ms1;
                const uint32_t g0 = lds32(ms + 6400 + q * 32), g1 = lds32(ms + 6400 + q * 32 + 16);
                sts128(park + q * 4096, make_uint4(bfma2(g0, x1[4 * q], x2[4 * q]), bfma2(g0, x1[4 * q + 1], x2[4 * q + 1]),
                                                   bfma2(g1, x1[4 * q + 2], x2[4 * q + 2]), bfma2(g1, x1[4 * q + 3], x2[4 * q + 3])));
            }
        }
#pragma unroll UNR_B
        for (int it = 0; it < 2; it++) {
            gemm_loop<104, false>(ac3, sb, half, it ? 9 : 1, it, it ? 30 - NA : 20, it ? 31 : 20, it ? 9 : 0, it ? 9 : 1, it ? 10 : 0, it ? 48 : 50);
            if (it) break;
            bar_arrive(9, 512);
            load_cs(1);
            mbar_wait(bars + BAR_ST * 8, 0);
            const uint4* sp = &g_st[(rb * 8 + 2 * c) * 128 + row];
            const uint32_t tag = lds32(sb + SM_GV + 540);
            uint4 s0, s1, s2, s3;
            for (int n = 0; n < SPIN_LIMIT; n++) {
                s0 = ld_tagged(sp); s1 = ld_tagged(sp + 128); s2 = ld_tagged(sp + 8); s3 = ld_tagged(sp + 136);
                if (!(((s0.y ^ tag) | (s0.w ^ tag) | (s1.y ^ tag) | (s1.w ^ tag)) | ((s2.y ^ tag) | (s2.w ^ tag) | (s3.y ^ tag) | (s3.w ^ tag)))) break;
            }
            __syncwarp();
            float a0 = __uint_as_float(s0.x) + __uint_as_float(s1.x), b0 = __uint_as_float(s0.z) + __uint_as_float(s1.z);
            float a1 = __uint_as_float(s2.x) + __uint_as_float(s3.x), b1 = __uint_as_float(s2.z) + __uint_as_float(s3.z);
#pragma unroll
            for (int m = 1; m <= 2; m <<= 1) {
                a0 += __shfl_xor_sync(0xffffffffu, a0, m); b0 += __shfl_xor_sync(0xffffffffu, b0, m);
                a1 += __shfl_xor_sync(0xffffffffu, a1, m); b1 += __shfl_xor_sync(0xffffffffu, b1, m);
            }
            const float inv0 = half_rstd(a0, b0), inv1 = half_rstd(a1, b1);
            if (c == 0) sts128(sb + SM_RP + (tid >> 2) * 16, make_uint4(pack2(inv0, inv0), __float_as_uint(a0 * (-1.0f / D_)), pack2(inv1, inv1), __float_as_uint(a1 * (-1.0f / D_))));
            bar_arrive(13, 512);
        }
        mbar_wait(bars + (BAR_FA + (39 - NA) % NA) * 8, ((39 - NA) / NA) & 1);
        epi3(1);
    }
    if (wg >= 2) {
        {
            float acc[40];
            uint32_t gbv[10], base[20];
#pragma unroll
            for (int q = 0; q < 10; q++) gbv[q] = lds32((q < 8 ? ms0 : ms1) + 6400 + q * 16);
#pragma unroll
            for (int q = 0; q < 5; q++) { const uint4 t = lds128(park + q * 4096); base[4 * q] = t.x; base[4 * q + 1] = t.y; base[4 * q + 2] = t.z; base[4 * q + 3] = t.w; }
            gemm_loop<80, false>(acc, sb, half, 27, 0, 39 - NA, 40, 27 - NA, 27 - NB, 11, 42);
            auto fin = [&](int q, int r) {
                return bfma2(gbv[q], pack2(acc[4 * q + 2 * r], acc[4 * q + 2 * r + 1]), base[2 * q + r]);
            };
            auto tr4 = [&](uint32_t t0, uint32_t t1, uint32_t t2, uint32_t t3) {
                const bool o1 = c & 1, o2 = c & 2;
                uint32_t a = __shfl_xor_sync(0xffffffffu, o1 ? t0 : t1, 1), b = __shfl_xor_sync(0xffffffffu, o1 ? t2 : t3, 1);
                uint32_t u0 = o1 ? a : t0, u1 = o1 ? t1 : a, u2 = o1 ? b : t2, u3 = o1 ? t3 : b;
                a = __shfl_xor_sync(0xffffffffu, o2 ? u0 : u2, 2); b = __shfl_xor_sync(0xffffffffu, o2 ? u1 : u3, 2);
                return o2 ? make_uint4(a, b, u2, u3) : make_uint4(u0, u1, a, b);
            };
            bf16* go = p.out + (size_t)(rb * 128 + row) * D_;
#pragma unroll
            for (int k = 0; k < 2; k++) CHUNK(k) {
#pragma unroll
                for (int r = 0; r < 2; r++)
                    *reinterpret_cast<uint4*>(go + r * 8 * D_ + cm + 32 * k + 8 * c) = tr4(fin(4 * k, r), fin(4 * k + 1, r), fin(4 * k + 2, r), fin(4 * k + 3, r));
            }
            CHUNK(2) *reinterpret_cast<uint4*>(go + (c >> 1) * 8 * D_ + cr + 8 * (c & 1)) = tr4(fin(8, 0), fin(9, 0), fin(8, 1), fin(9, 1));
            if (tid == 256) TS(44);
            if (warp == 8) TSFLUSH();
        }
    }
}

typedef CUresult (*EncFn)(CUtensorMap*, CUtensorMapDataType, cuuint32_t, void*, const cuuint64_t*, const cuuint64_t*,
                          const cuuint32_t*, const cuuint32_t*, CUtensorMapInterleave, CUtensorMapSwizzle,
                          CUtensorMapL2promotion, CUtensorMapFloatOOBfill);

void make_map(EncFn enc, CUtensorMap* m, const void* base, uint64_t inner, uint64_t outer, uint32_t bi, uint32_t bo,
              CUtensorMapSwizzle swz = CU_TENSOR_MAP_SWIZZLE_128B) {
    cuuint64_t dims[2] = {inner, outer};
    cuuint64_t st[1] = {inner * 2};
    cuuint32_t box[2] = {bi, bo};
    cuuint32_t es[2] = {1, 1};
    enc(m, CU_TENSOR_MAP_DATA_TYPE_BFLOAT16, 2, const_cast<void*>(base), dims, st, box, es, CU_TENSOR_MAP_INTERLEAVE_NONE,
        swz, CU_TENSOR_MAP_L2_PROMOTION_NONE, CU_TENSOR_MAP_FLOAT_OOB_FILL_NONE);
}

}

extern "C" void kernel_launch(void* const* d_in, const int* in_sizes, int n_in, void* d_out, int out_size) {
    (void)in_sizes; (void)n_in; (void)out_size;
    Params p;
    p.q = (const bf16*)d_in[0]; p.k = (const bf16*)d_in[1]; p.v = (const bf16*)d_in[2];
    p.shift = (const bf16*)d_in[3]; p.ssmk = (const bf16*)d_in[4]; p.ssmD = (const bf16*)d_in[5];
    p.w1 = (const bf16*)d_in[7]; p.w2 = (const bf16*)d_in[8]; p.w3 = (const bf16*)d_in[9]; p.w4 = (const bf16*)d_in[10];
    p.c = (const bf16*)d_in[11]; p.wmod = (const bf16*)d_in[12];
    p.out = (bf16*)d_out;
    p.ones = 0xffffffffu;

    void* fn = nullptr;
    cudaDriverEntryPointQueryResult qr;
    cudaGetDriverEntryPoint("cuTensorMapEncodeTiled", &fn, cudaEnableDefault, &qr);
    EncFn enc = (EncFn)fn;
    void* hn = nullptr;
    cudaGetSymbolAddress(&hn, g_hn);
    Maps maps;
    make_map(enc, &maps.w3s, p.w3, F_, D_, 216, 64, CU_TENSOR_MAP_SWIZZLE_NONE);
    make_map(enc, &maps.wm, p.wmod, 6 * D_, D_, 32, 128, CU_TENSOR_MAP_SWIZZLE_64B);
    make_map(enc, &maps.xa, p.q, D_, S_, 64, 128);
    make_map(enc, &maps.xb, p.q, D_, S_, 16, 128, CU_TENSOR_MAP_SWIZZLE_NONE);
    make_map(enc, &maps.hn, hn, D_, S_, 64, 128);
    make_map(enc, &maps.w1a, p.w1, D_, D_, 64, 64);
    make_map(enc, &maps.w1b, p.w1, D_, D_, 16, 64);
    make_map(enc, &maps.w2a, p.w2, D_, D_, 64, 64);
    make_map(enc, &maps.w2b, p.w2, D_, D_, 16, 64);
    make_map(enc, &maps.w3a, p.w3, F_, D_, 64, 64);
    make_map(enc, &maps.w3b, p.w3, F_, D_, RA3, 64);
    make_map(enc, &maps.w3c, p.w3, F_, D_, RB3, 64);
    make_map(enc, &maps.w4a, p.w4, D_, F_, 64, 64);
    make_map(enc, &maps.w4b, p.w4, D_, F_, 16, 64);
    cudaFuncSetAttribute(fused_kernel, cudaFuncAttributeMaxDynamicSharedMemorySize, SMEM_BYTES);
    fused_kernel<<<132, NTHREADS, SMEM_BYTES>>>(p, maps);
}
```

```cpp
#include <cuda_runtime.h>
#include <cuda_bf16.h>
#include <cuda.h>
#include <stdint.h>
#include <string.h>

#define SEED 2
#define RING_A 6
#define CH 2
#define FAST_LN 2
#define STAG 12
#define PGELU 2
#define CH3 4
#define HO_A 16
#define HO_B 16
#define RA3 48
#define CSP 16
#define OWNG 1
#define GATE 5
#define SSM_DELAY 0
#define B_DELAY 300
#define RPRE_WAIT 1
#define SSM_N 3

namespace {

typedef __nv_bfloat16 bf16;
typedef __nv_bfloat162 bf162;

constexpr int S_ = 2048, D_ = 640, F_ = 1728;
constexpr int NTHREADS = 640;
constexpr int NA = RING_A, NB = 12 - RING_A;
constexpr int SLOT = 16384;
constexpr int RB3 = 88 - RA3, HB0 = 512 + 8 * RA3;
constexpr int SM_RA = 0, SM_RB = NA * SLOT;

static_assert(NA == 6, "smem map");
constexpr int RED_STRIDE = 17536;
constexpr int K_STRIDE = 8320;
constexpr int U_PLANE = 2560, U_STRIDE = 5120;
constexpr int SM_Y = 12 * SLOT;
__device__ __forceinline__ int sm_red(int cc) { return cc * RED_STRIDE + (cc < 3 ? SM_RB : -3 * RED_STRIDE); }
__device__ __forceinline__ int sm_k(int cc) { return cc * K_STRIDE + (cc < 3 ? SM_RB + 3 * RED_STRIDE : 2 * RED_STRIDE - 3 * K_STRIDE); }
__device__ __forceinline__ int sm_u(int cc) { return cc * U_STRIDE + (cc < 3 ? SM_RB + 3 * RED_STRIDE + 3 * K_STRIDE : SM_Y + 8192 - 3 * U_STRIDE); }
constexpr int SM_PK = SM_RB;
constexpr int SM_PV = SM_RB + 24576;
constexpr int SM_WM = 57344;
constexpr int SM_XT = SM_WM, SM_XT2 = SM_WM + 16384, SM_XR = SM_WM + 20480;
constexpr int SM_YT = 0;
constexpr int SM_MOD = SM_Y + 20480;
constexpr int SM_GV = SM_MOD + 7680;
constexpr int SM_CS = SM_GV + 1024;
constexpr int SM_RP = SM_CS + 1024;
constexpr int SM_BAR = SM_RP + 1024;
constexpr int SM_PROF = SM_BAR + 512;
constexpr int SM_TOTAL = SM_PROF + 512;
constexpr int SMEM_BYTES = SM_TOTAL + 1024;
static_assert(SMEM_BYTES <= 232448, "smem");

constexpr int BAR_FA = 0, BAR_FB = NA, BAR_EA = 12, BAR_EB = 12 + NA, BAR_K = 24, BAR_U = 29, BAR_Y = 34, BAR_CS = 35, BAR_WM = 36, BAR_M = 37, BAR_XY = 38, BAR_Y2 = 39, BAR_G = 40, BAR_ST = 44, BAR_XR = 45, NBARS = 46;

__device__ __align__(1024) bf16 g_kvT[D_ * S_];
__device__ __align__(1024) uint32_t g_yv[128 * 5120];
__device__ __align__(1024) bf16 g_mod[6 * D_];
__device__ __align__(1024) bf16 g_hn[S_ * D_];
__device__ __align__(1024) uint4 g_rs[S_ * 2];
__device__ __align__(1024) bf16 g_h1[S_ * D_];
__device__ __align__(1024) bf16 g_x1[S_ * D_];
__device__ __align__(1024) bf16 g_g[S_ * F_];
__device__ __align__(1024) float2 g_st[S_ * 8];
__device__ __align__(1024) float g_cs[F_];
__device__ __align__(1024) unsigned g_flags[128 * 32];
__device__ __align__(1024) unsigned g_epoch[160];
constexpr int FL_P = 0, FL_C = 8, FL_CS = 9, FL_M = 10, FL_R = 16, FL_B1 = 32, FL_B2 = 48, FL_G = 64;

#define TS(i) do {} while (0)
#define TSW(i) do {} while (0)
#define TSD(i, dep) do {} while (0)
#define TSD2(i, dep) do {} while (0)
#define TSFLUSH() do {} while (0)

struct Params {
    const bf16 *q, *k, *v, *shift, *ssmk, *ssmD, *w1, *w2, *w3, *w4, *c, *wmod;
    bf16* out;
    unsigned ones;
};
#define CHUNK(k) if (ones & (1u << (k)))
struct Maps { CUtensorMap hn, w1a, w1b, w2a, w2b, w3a, w3b, w3c, w4a, w4b, wm, xa, xb, w3s; };

template<int N> struct WgRs;
template<int N> struct WgSs;
template<> struct WgRs<32> { template<int OFF,int HI,int SC> static __device__ __forceinline__ void run(float* d,uint32_t a0,uint32_t a1,uint32_t a2,uint32_t a3,uint32_t blo){
 asm volatile("{.reg .b32 l; .reg .b64 db; add.u32 l,%20,%21; mov.b64 db,{l,%22}; wgmma.mma_async.sync.aligned.m64n32k16.f32.bf16.bf16 {%0,%1,%2,%3,%4,%5,%6,%7,%8,%9,%10,%11,%12,%13,%14,%15},{%16,%17,%18,%19},db,%23,1,1,0;}"
 :"+f"(d[0]),"+f"(d[1]),"+f"(d[2]),"+f"(d[3]),"+f"(d[4]),"+f"(d[5]),"+f"(d[6]),"+f"(d[7]),"+f"(d[8]),"+f"(d[9]),"+f"(d[10]),"+f"(d[11]),"+f"(d[12]),"+f"(d[13]),"+f"(d[14]),"+f"(d[15])
 :"r"(a0),"r"(a1),"r"(a2),"r"(a3),"r"(blo),"n"(OFF),"n"(HI),"n"(SC)); } };
template<> struct WgRs<48> { template<int OFF,int HI,int SC> static __device__ __forceinline__ void run(float* d,uint32_t a0,uint32_t a1,uint32_t a2,uint32_t a3,uint32_t blo){
 asm volatile("{.reg .b32 l; .reg .b64 db; add.u32 l,%28,%29; mov.b64 db,{l,%30}; wgmma.mma_async.sync.aligned.m64n48k16.f32.bf16.bf16 {%0,%1,%2,%3,%4,%5,%6,%7,%8,%9,%10,%11,%12,%13,%14,%15,%16,%17,%18,%19,%20,%21,%22,%23},{%24,%25,%26,%27},db,%31,1,1,0;}"
 :"+f"(d[0]),"+f"(d[1]),"+f"(d[2]),"+f"(d[3]),"+f"(d[4]),"+f"(d[5]),"+f"(d[6]),"+f"(d[7]),"+f"(d[8]),"+f"(d[9]),"+f"(d[10]),"+f"(d[11]),"+f"(d[12]),"+f"(d[13]),"+f"(d[14]),"+f"(d[15]),"+f"(d[16]),"+f"(d[17]),"+f"(d[18]),"+f"(d[19]),"+f"(d[20]),"+f"(d[21]),"+f"(d[22]),"+f"(d[23])
 :"r"(a0),"r"(a1),"r"(a2),"r"(a3),"r"(blo),"n"(OFF),"n"(HI),"n"(SC)); } };
template<> struct WgRs<64> { template<int OFF,int HI,int SC> static __device__ __forceinline__ void run(float* d,uint32_t a0,uint32_t a1,uint32_t a2,uint32_t a3,uint32_t blo){
 asm volatile("{.reg .b32 l; .reg .b64 db; add.u32 l,%36,%37; mov.b64 db,{l,%38}; wgmma.mma_async.sync.aligned.m64n64k16.f32.bf16.bf16 {%0,%1,%2,%3,%4,%5,%6,%7,%8,%9,%10,%11,%12,%13,%14,%15,%16,%17,%18,%19,%20,%21,%22,%23,%24,%25,%26,%27,%28,%29,%30,%31},{%32,%33,%34,%35},db,%39,1,1,0;}"
 :"+f"(d[0]),"+f"(d[1]),"+f"(d[2]),"+f"(d[3]),"+f"(d[4]),"+f"(d[5]),"+f"(d[6]),"+f"(d[7]),"+f"(d[8]),"+f"(d[9]),"+f"(d[10]),"+f"(d[11]),"+f"(d[12]),"+f"(d[13]),"+f"(d[14]),"+f"(d[15]),"+f"(d[16]),"+f"(d[17]),"+f"(d[18]),"+f"(d[19]),"+f"(d[20]),"+f"(d[21]),"+f"(d[22]),"+f"(d[23]),"+f"(d[24]),"+f"(d[25]),"+f"(d[26]),"+f"(d[27]),"+f"(d[28]),"+f"(d[29]),"+f"(d[30]),"+f"(d[31])
 :"r"(a0),"r"(a1),"r"(a2),"r"(a3),"r"(blo),"n"(OFF),"n"(HI),"n"(SC)); } };
template<> struct WgRs<80> { template<int OFF,int HI,int SC> static __device__ __forceinline__ void run(float* d,uint32_t a0,uint32_t a1,uint32_t a2,uint32_t a3,uint32_t blo){
 asm volatile("{.reg .b32 l; .reg .b64 db; add.u32 l,%44,%45; mov.b64 db,{l,%46}; wgmma.mma_async.sync.aligned.m64n80k16.f32.bf16.bf16 {%0,%1,%2,%3,%4,%5,%6,%7,%8,%9,%10,%11,%12,%13,%14,%15,%16,%17,%18,%19,%20,%21,%22,%23,%24,%25,%26,%27,%28,%29,%30,%31,%32,%33,%34,%35,%36,%37,%38,%39},{%40,%41,%42,%43},db,%47,1,1,0;}"
 :"+f"(d[0]),"+f"(d[1]),"+f"(d[2]),"+f"(d[3]),"+f"(d[4]),"+f"(d[5]),"+f"(d[6]),"+f"(d[7]),"+f"(d[8]),"+f"(d[9]),"+f"(d[10]),"+f"(d[11]),"+f"(d[12]),"+f"(d[13]),"+f"(d[14]),"+f"(d[15]),"+f"(d[16]),"+f"(d[17]),"+f"(d[18]),"+f"(d[19]),"+f"(d[20]),"+f"(d[21]),"+f"(d[22]),"+f"(d[23]),"+f"(d[24]),"+f"(d[25]),"+f"(d[26]),"+f"(d[27]),"+f"(d[28]),"+f"(d[29]),"+f"(d[30]),"+f"(d[31]),"+f"(d[32]),"+f"(d[33]),"+f"(d[34]),"+f"(d[35]),"+f"(d[36]),"+f"(d[37]),"+f"(d[38]),"+f"(d[39])
 :"r"(a0),"r"(a1),"r"(a2),"r"(a3),"r"(blo),"n"(OFF),"n"(HI),"n"(SC)); } };
template<> struct WgRs<96> { template<int OFF,int HI,int SC> static __device__ __forceinline__ void run(float* d,uint32_t a0,uint32_t a1,uint32_t a2,uint32_t a3,uint32_t blo){
 asm volatile("{.reg .b32 l; .reg .b64 db; add.u32 l,%52,%53; mov.b64 db,{l,%54}; wgmma.mma_async.sync.aligned.m64n96k16.f32.bf16.bf16 {%0,%1,%2,%3,%4,%5,%6,%7,%8,%9,%10,%11,%12,%13,%14,%15,%16,%17,%18,%19,%20,%21,%22,%23,%24,%25,%26,%27,%28,%29,%30,%31,%32,%33,%34,%35,%36,%37,%38,%39,%40,%41,%42,%43,%44,%45,%46,%47},{%48,%49,%50,%51},db,%55,1,1,0;}"
 :"+f"(d[0]),"+f"(d[1]),"+f"(d[2]),"+f"(d[3]),"+f"(d[4]),"+f"(d[5]),"+f"(d[6]),"+f"(d[7]),"+f"(d[8]),"+f"(d[9]),"+f"(d[10]),"+f"(d[11]),"+f"(d[12]),"+f"(d[13]),"+f"(d[14]),"+f"(d[15]),"+f"(d[16]),"+f"(d[17]),"+f"(d[18]),"+f"(d[19]),"+f"(d[20]),"+f"(d[21]),"+f"(d[22]),"+f"(d[23]),"+f"(d[24]),"+f"(d[25]),"+f"(d[26]),"+f"(d[27]),"+f"(d[28]),"+f"(d[29]),"+f"(d[30]),"+f"(d[31]),"+f"(d[32]),"+f"(d[33]),"+f"(d[34]),"+f"(d[35]),"+f"(d[36]),"+f"(d[37]),"+f"(d[38]),"+f"(d[39]),"+f"(d[40]),"+f"(d[41]),"+f"(d[42]),"+f"(d[43]),"+f"(d[44]),"+f"(d[45]),"+f"(d[46]),"+f"(d[47])
 :"r"(a0),"r"(a1),"r"(a2),"r"(a3),"r"(blo),"n"(OFF),"n"(HI),"n"(SC)); } };
template<> struct WgRs<112> { template<int OFF,int HI,int SC> static __device__ __forceinline__ void run(float* d,uint32_t a0,uint32_t a1,uint32_t a2,uint32_t a3,uint32_t blo){
 asm volatile("{.reg .b32 l; .reg .b64 db; add.u32 l,%60,%61; mov.b64 db,{l,%62}; wgmma.mma_async.sync.aligned.m64n112k16.f32.bf16.bf16 {%0,%1,%2,%3,%4,%5,%6,%7,%8,%9,%10,%11,%12,%13,%14,%15,%16,%17,%18,%19,%20,%21,%22,%23,%24,%25,%26,%27,%28,%29,%30,%31,%32,%33,%34,%35,%36,%37,%38,%39,%40,%41,%42,%43,%44,%45,%46,%47,%48,%49,%50,%51,%52,%53,%54,%55},{%56,%57,%58,%59},db,%63,1,1,0;}"
 :"+f"(d[0]),"+f"(d[1]),"+f"(d[2]),"+f"(d[3]),"+f"(d[4]),"+f"(d[5]),"+f"(d[6]),"+f"(d[7]),"+f"(d[8]),"+f"(d[9]),"+f"(d[10]),"+f"(d[11]),"+f"(d[12]),"+f"(d[13]),"+f"(d[14]),"+f"(d[15]),"+f"(d[16]),"+f"(d[17]),"+f"(d[18]),"+f"(d[19]),"+f"(d[20]),"+f"(d[21]),"+f"(d[22]),"+f"(d[23]),"+f"(d[24]),"+f"(d[25]),"+f"(d[26]),"+f"(d[27]),"+f"(d[28]),"+f"(d[29]),"+f"(d[30]),"+f"(d[31]),"+f"(d[32]),"+f"(d[33]),"+f"(d[34]),"+f"(d[35]),"+f"(d[36]),"+f"(d[37]),"+f"(d[38]),"+f"(d[39]),"+f"(d[40]),"+f"(d[41]),"+f"(d[42]),"+f"(d[43]),"+f"(d[44]),"+f"(d[45]),"+f"(d[46]),"+f"(d[47]),"+f"(d[48]),"+f"(d[49]),"+f"(d[50]),"+f"(d[51]),"+f"(d[52]),"+f"(d[53]),"+f"(d[54]),"+f"(d[55])
 :"r"(a0),"r"(a1),"r"(a2),"r"(a3),"r"(blo),"n"(OFF),"n"(HI),"n"(SC)); } };
template<> struct WgRs<128> { template<int OFF,int HI,int SC> static __device__ __forceinline__ void run(float* d,uint32_t a0,uint32_t a1,uint32_t a2,uint32_t a3,uint32_t blo){
 asm volatile("{.reg .b32 l; .reg .b64 db; add.u32 l,%68,%69; mov.b64 db,{l,%70}; wgmma.mma_async.sync.aligned.m64n128k16.f32.bf16.bf16 {%0,%1,%2,%3,%4,%5,%6,%7,%8,%9,%10,%11,%12,%13,%14,%15,%16,%17,%18,%19,%20,%21,%22,%23,%24,%25,%26,%27,%28,%29,%30,%31,%32,%33,%34,%35,%36,%37,%38,%39,%40,%41,%42,%43,%44,%45,%46,%47,%48,%49,%50,%51,%52,%53,%54,%55,%56,%57,%58,%59,%60,%61,%62,%63},{%64,%65,%66,%67},db,%71,1,1,0;}"
 :"+f"(d[0]),"+f"(d[1]),"+f"(d[2]),"+f"(d[3]),"+f"(d[4]),"+f"(d[5]),"+f"(d[6]),"+f"(d[7]),"+f"(d[8]),"+f"(d[9]),"+f"(d[10]),"+f"(d[11]),"+f"(d[12]),"+f"(d[13]),"+f"(d[14]),"+f"(d[15]),"+f"(d[16]),"+f"(d[17]),"+f"(d[18]),"+f"(d[19]),"+f"(d[20]),"+f"(d[21]),"+f"(d[22]),"+f"(d[23]),"+f"(d[24]),"+f"(d[25]),"+f"(d[26]),"+f"(d[27]),"+f"(d[28]),"+f"(d[29]),"+f"(d[30]),"+f"(d[31]),"+f"(d[32]),"+f"(d[33]),"+f"(d[34]),"+f"(d[35]),"+f"(d[36]),"+f"(d[37]),"+f"(d[38]),"+f"(d[39]),"+f"(d[40]),"+f"(d[41]),"+f"(d[42]),"+f"(d[43]),"+f"(d[44]),"+f"(d[45]),"+f"(d[46]),"+f"(d[47]),"+f"(d[48]),"+f"(d[49]),"+f"(d[50]),"+f"(d[51]),"+f"(d[52]),"+f"(d[53]),"+f"(d[54]),"+f"(d[55]),"+f"(d[56]),"+f"(d[57]),"+f"(d[58]),"+f"(d[59]),"+f"(d[60]),"+f"(d[61]),"+f"(d[62]),"+f"(d[63])
 :"r"(a0),"r"(a1),"r"(a2),"r"(a3),"r"(blo),"n"(OFF),"n"(HI),"n"(SC)); } };
template<> struct WgSs<80> { template<int AOFF,int AHI,int BOFF,int BHI,int SC> static __device__ __forceinline__ void run(float* d,uint32_t alo,uint32_t blo){
 asm volatile("{.reg .b32 l,m; .reg .b64 da,db; add.u32 l,%40,%42; mov.b64 da,{l,%43}; add.u32 m,%41,%44; mov.b64 db,{m,%45}; wgmma.mma_async.sync.aligned.m64n80k16.f32.bf16.bf16 {%0,%1,%2,%3,%4,%5,%6,%7,%8,%9,%10,%11,%12,%13,%14,%15,%16,%17,%18,%19,%20,%21,%22,%23,%24,%25,%26,%27,%28,%29,%30,%31,%32,%33,%34,%35,%36,%37,%38,%39},da,db,%46,1,1,0,1;}"
 :"+f"(d[0]),"+f"(d[1]),"+f"(d[2]),"+f"(d[3]),"+f"(d[4]),"+f"(d[5]),"+f"(d[6]),"+f"(d[7]),"+f"(d[8]),"+f"(d[9]),"+f"(d[10]),"+f"(d[11]),"+f"(d[12]),"+f"(d[13]),"+f"(d[14]),"+f"(d[15]),"+f"(d[16]),"+f"(d[17]),"+f"(d[18]),"+f"(d[19]),"+f"(d[20]),"+f"(d[21]),"+f"(d[22]),"+f"(d[23]),"+f"(d[24]),"+f"(d[25]),"+f"(d[26]),"+f"(d[27]),"+f"(d[28]),"+f"(d[29]),"+f"(d[30]),"+f"(d[31]),"+f"(d[32]),"+f"(d[33]),"+f"(d[34]),"+f"(d[35]),"+f"(d[36]),"+f"(d[37]),"+f"(d[38]),"+f"(d[39])
 :"r"(alo),"r"(blo),"n"(AOFF),"n"(AHI),"n"(BOFF),"n"(BHI),"n"(SC)); } };
template<> struct WgSs<104> { template<int AOFF,int AHI,int BOFF,int BHI,int SC> static __device__ __forceinline__ void run(float* d,uint32_t alo,uint32_t blo){
 asm volatile("{.reg .b32 l,m; .reg .b64 da,db; add.u32 l,%52,%54; mov.b64 da,{l,%55}; add.u32 m,%53,%56; mov.b64 db,{m,%57}; wgmma.mma_async.sync.aligned.m64n104k16.f32.bf16.bf16 {%0,%1,%2,%3,%4,%5,%6,%7,%8,%9,%10,%11,%12,%13,%14,%15,%16,%17,%18,%19,%20,%21,%22,%23,%24,%25,%26,%27,%28,%29,%30,%31,%32,%33,%34,%35,%36,%37,%38,%39,%40,%41,%42,%43,%44,%45,%46,%47,%48,%49,%50,%51},da,db,%58,1,1,0,1;}"
 :"+f"(d[0]),"+f"(d[1]),"+f"(d[2]),"+f"(d[3]),"+f"(d[4]),"+f"(d[5]),"+f"(d[6]),"+f"(d[7]),"+f"(d[8]),"+f"(d[9]),"+f"(d[10]),"+f"(d[11]),"+f"(d[12]),"+f"(d[13]),"+f"(d[14]),"+f"(d[15]),"+f"(d[16]),"+f"(d[17]),"+f"(d[18]),"+f"(d[19]),"+f"(d[20]),"+f"(d[21]),"+f"(d[22]),"+f"(d[23]),"+f"(d[24]),"+f"(d[25]),"+f"(d[26]),"+f"(d[27]),"+f"(d[28]),"+f"(d[29]),"+f"(d[30]),"+f"(d[31]),"+f"(d[32]),"+f"(d[33]),"+f"(d[34]),"+f"(d[35]),"+f"(d[36]),"+f"(d[37]),"+f"(d[38]),"+f"(d[39]),"+f"(d[40]),"+f"(d[41]),"+f"(d[42]),"+f"(d[43]),"+f"(d[44]),"+f"(d[45]),"+f"(d[46]),"+f"(d[47]),"+f"(d[48]),"+f"(d[49]),"+f"(d[50]),"+f"(d[51])
 :"r"(alo),"r"(blo),"n"(AOFF),"n"(AHI),"n"(BOFF),"n"(BHI),"n"(SC)); } };
template<> struct WgSs<112> { template<int AOFF,int AHI,int BOFF,int BHI,int SC> static __device__ __forceinline__ void run(float* d,uint32_t alo,uint32_t blo){
 asm volatile("{.reg .b32 l,m; .reg .b64 da,db; add.u32 l,%56,%58; mov.b64 da,{l,%59}; add.u32 m,%57,%60; mov.b64 db,{m,%61}; wgmma.mma_async.sync.aligned.m64n112k16.f32.bf16.bf16 {%0,%1,%2,%3,%4,%5,%6,%7,%8,%9,%10,%11,%12,%13,%14,%15,%16,%17,%18,%19,%20,%21,%22,%23,%24,%25,%26,%27,%28,%29,%30,%31,%32,%33,%34,%35,%36,%37,%38,%39,%40,%41,%42,%43,%44,%45,%46,%47,%48,%49,%50,%51,%52,%53,%54,%55},da,db,%62,1,1,0,1;}"
 :"+f"(d[0]),"+f"(d[1]),"+f"(d[2]),"+f"(d[3]),"+f"(d[4]),"+f"(d[5]),"+f"(d[6]),"+f"(d[7]),"+f"(d[8]),"+f"(d[9]),"+f"(d[10]),"+f"(d[11]),"+f"(d[12]),"+f"(d[13]),"+f"(d[14]),"+f"(d[15]),"+f"(d[16]),"+f"(d[17]),"+f"(d[18]),"+f"(d[19]),"+f"(d[20]),"+f"(d[21]),"+f"(d[22]),"+f"(d[23]),"+f"(d[24]),"+f"(d[25]),"+f"(d[26]),"+f"(d[27]),"+f"(d[28]),"+f"(d[29]),"+f"(d[30]),"+f"(d[31]),"+f"(d[32]),"+f"(d[33]),"+f"(d[34]),"+f"(d[35]),"+f"(d[36]),"+f"(d[37]),"+f"(d[38]),"+f"(d[39]),"+f"(d[40]),"+f"(d[41]),"+f"(d[42]),"+f"(d[43]),"+f"(d[44]),"+f"(d[45]),"+f"(d[46]),"+f"(d[47]),"+f"(d[48]),"+f"(d[49]),"+f"(d[50]),"+f"(d[51]),"+f"(d[52]),"+f"(d[53]),"+f"(d[54]),"+f"(d[55])
 :"r"(alo),"r"(blo),"n"(AOFF),"n"(AHI),"n"(BOFF),"n"(BHI),"n"(SC)); } };

__device__ __forceinline__ void wg_fence() { asm volatile("wgmma.fence.sync.aligned;" ::: "memory"); }
__device__ __forceinline__ void wg_commit() { asm volatile("wgmma.commit_group.sync.aligned;" ::: "memory"); }
template <int N> __device__ __forceinline__ void wg_wait() { asm volatile("wgmma.wait_group.sync.aligned %0;" ::"n"(N) : "memory"); }
template <int N> __device__ __forceinline__ void reg_fence(float* d) {
#pragma unroll
    for (int i = 0; i < N; i++) asm volatile("" : "+f"(d[i])::"memory");
}
__device__ __forceinline__ uint32_t desc_lo(uint32_t addr, uint32_t lbo) { return ((addr & 0x3FFFF) >> 4) | ((lbo >> 4) << 16); }
#define desc_hi(sbo, sw) (((sbo) >> 4) | ((sw) << 30))
__device__ __forceinline__ uint32_t smem_u32(const void* p) { return (uint32_t)__cvta_generic_to_shared(p); }
__device__ __forceinline__ bool elect() {
    uint32_t p;
    asm volatile("{.reg .pred P; elect.sync _|P, 0xffffffff; selp.u32 %0,1,0,P;}" : "=r"(p));
    return p;
}
__device__ __forceinline__ void mbar_init(uint32_t bar, uint32_t cnt) { asm volatile("mbarrier.init.shared::cta.b64 [%0], %1;" ::"r"(bar), "r"(cnt) : "memory"); }
__device__ __forceinline__ void mbar_expect(uint32_t bar, uint32_t bytes) { asm volatile("mbarrier.arrive.expect_tx.shared::cta.b64 _, [%0], %1;" ::"r"(bar), "r"(bytes) : "memory"); }
__device__ __forceinline__ bool mbar_try(uint32_t bar, uint32_t par) {
    uint32_t ok;
    asm volatile("{.reg .pred p; mbarrier.try_wait.parity.shared::cta.b64 p, [%1], %2; selp.u32 %0,1,0,p;}" : "=r"(ok) : "r"(bar), "r"(par) : "memory");
    return ok;
}
constexpr int SPIN_LIMIT = 1 << 18;
__device__ __forceinline__ void mbar_wait(uint32_t bar, uint32_t par) {
    if (mbar_try(bar, par)) return;
    asm volatile("{.reg .pred p, q; .reg .b32 n; mov.u32 n, 0;\n"
                 "W%=: mbarrier.try_wait.parity.shared::cta.b64 p, [%0], %1; add.u32 n, n, 1; setp.lt.and.u32 q, n, %2, !p; @q bra W%=;}"
                 ::"r"(bar), "r"(par), "n"(SPIN_LIMIT) : "memory");
}
__device__ __forceinline__ void bulk_g2s(uint32_t dst, const void* src, uint32_t bytes, uint32_t bar) {
    asm volatile("cp.async.bulk.shared::cluster.global.mbarrier::complete_tx::bytes [%0], [%1], %2, [%3];" ::"r"(dst), "l"(src), "r"(bytes), "r"(bar) : "memory");
}
__device__ __forceinline__ void bulk_s2g(void* dst, uint32_t src, uint32_t bytes) {
    asm volatile("cp.async.bulk.global.shared::cta.bulk_group [%0], [%1], %2;" ::"l"(dst), "r"(src), "r"(bytes) : "memory");
}
__device__ __forceinline__ void bulk_prefetch(const void* src, uint32_t bytes) {
    asm volatile("cp.async.bulk.prefetch.L2.global [%0], %1;" ::"l"(src), "r"(bytes) : "memory");
}
__device__ __forceinline__ void tma2d(uint32_t dst, const CUtensorMap* m, int c0, int c1, uint32_t bar) {
    asm volatile("cp.async.bulk.tensor.2d.shared::cluster.global.mbarrier::complete_tx::bytes [%0], [%1, {%3, %4}], [%2];" ::"r"(dst), "l"(m), "r"(bar), "r"(c0), "r"(c1) : "memory");
}
__device__ __forceinline__ void tma2d_mc(uint32_t dst, const CUtensorMap* m, int c0, int c1, uint32_t bar) {
    asm volatile("cp.async.bulk.tensor.2d.shared::cluster.global.mbarrier::complete_tx::bytes.multicast::cluster [%0], [%1, {%3, %4}], [%2], %5;" ::"r"(dst), "l"(m), "r"(bar), "r"(c0), "r"(c1), "h"((uint16_t)3) : "memory");
}
__device__ __forceinline__ uint32_t mapa(uint32_t a, uint32_t rank) { uint32_t r; asm("mapa.shared::cluster.u32 %0, %1, %2;" : "=r"(r) : "r"(a), "r"(rank)); return r; }
__device__ __forceinline__ void mbar_arrive_cl(uint32_t bar) { asm volatile("mbarrier.arrive.shared::cluster.b64 _, [%0];" ::"r"(bar) : "memory"); }
__device__ __forceinline__ void prefetch_map(const CUtensorMap* m) { asm volatile("prefetch.tensormap [%0];" ::"l"(m) : "memory"); }
__device__ __forceinline__ void cpasync16(uint32_t dst, const void* src, uint32_t srcsz) {
    asm volatile("cp.async.cg.shared.global [%0], [%1], 16, %2;" ::"r"(dst), "l"(src), "r"(srcsz) : "memory");
}
__device__ __forceinline__ void bar_sync(int id, int n) { asm volatile("bar.sync %0, %1;" ::"r"(id), "r"(n) : "memory"); }
__device__ __forceinline__ void bar_arrive(int id, int n) { asm volatile("bar.arrive %0, %1;" ::"r"(id), "r"(n) : "memory"); }
__device__ __forceinline__ void fence_async_smem() { asm volatile("fence.proxy.async.shared::cta;" ::: "memory"); }
__device__ __forceinline__ void fence_async_global() { asm volatile("fence.proxy.async.global;" ::: "memory"); }
__device__ __forceinline__ void flag_release(int f) { asm volatile("red.release.gpu.global.add.u32 [%0], 1;" ::"l"(&g_flags[f * 32]) : "memory"); }
__device__ __forceinline__ void flag_wait(int f, unsigned target) {
    const unsigned* p = &g_flags[f * 32];
    unsigned v; int n = 0;
    do {
        asm volatile("ld.relaxed.gpu.global.u32 %0, [%1];" : "=r"(v) : "l"(p) : "memory");
    } while ((int)(v - target) < 0 && ++n < SPIN_LIMIT);
    asm volatile("fence.acquire.gpu;" ::: "memory");
}
__device__ __forceinline__ unsigned ld_flag(const unsigned* p) { unsigned v; asm volatile("ld.relaxed.gpu.global.u32 %0, [%1];" : "=r"(v) : "l"(p) : "memory"); return v; }
__device__ __forceinline__ void spin(unsigned n) { unsigned t0, t1; asm volatile("mov.u32 %0, %%clock;" : "=r"(t0)); do { asm volatile("mov.u32 %0, %%clock;" : "=r"(t1)); } while (t1 - t0 < n); }
__device__ __forceinline__ void flag_wait2(int f0, int f1, unsigned target) {
    const unsigned *p = &g_flags[f0 * 32], *q = &g_flags[f1 * 32];
    unsigned v, w; int n = 0;
    do { v = ld_flag(p); w = ld_flag(q); } while ((int)((v - target) | (w - target)) < 0 && ++n < SPIN_LIMIT);
    asm volatile("fence.acquire.gpu;" ::: "memory");
}
__device__ __forceinline__ uint32_t lds32(uint32_t a) { uint32_t v; asm volatile("ld.shared.u32 %0, [%1];" : "=r"(v) : "r"(a)); return v; }
__device__ __forceinline__ float2 lds64f(uint32_t a) { float2 v; asm volatile("ld.shared.v2.f32 {%0,%1}, [%2];" : "=f"(v.x), "=f"(v.y) : "r"(a)); return v; }
__device__ __forceinline__ uint2 lds64(uint32_t a) { uint2 v; asm volatile("ld.shared.v2.u32 {%0,%1}, [%2];" : "=r"(v.x), "=r"(v.y) : "r"(a)); return v; }
__device__ __forceinline__ void sts64f(uint32_t a, float2 v) { asm volatile("st.shared.v2.f32 [%0], {%1,%2};" ::"r"(a), "f"(v.x), "f"(v.y) : "memory"); }
__device__ __forceinline__ void sts32(uint32_t a, uint32_t v) { asm volatile("st.shared.u32 [%0], %1;" ::"r"(a), "r"(v) : "memory"); }
__device__ __forceinline__ void sts64(uint32_t a, uint32_t x, uint32_t y) { asm volatile("st.shared.v2.u32 [%0], {%1,%2};" ::"r"(a), "r"(x), "r"(y) : "memory"); }
__device__ __forceinline__ void sts16(uint32_t a, uint16_t v) { asm volatile("st.shared.u16 [%0], %1;" ::"r"(a), "h"(v) : "memory"); }
__device__ __forceinline__ uint4 lds128(uint32_t a) { uint4 v; asm volatile("ld.shared.v4.u32 {%0,%1,%2,%3}, [%4];" : "=r"(v.x), "=r"(v.y), "=r"(v.z), "=r"(v.w) : "r"(a)); return v; }
__device__ __forceinline__ void sts128(uint32_t a, uint4 v) { asm volatile("st.shared.v4.u32 [%0], {%1,%2,%3,%4};" ::"r"(a), "r"(v.x), "r"(v.y), "r"(v.z), "r"(v.w) : "memory"); }
__device__ __forceinline__ void sts128f(uint32_t a, float x, float y, float z, float w) { asm volatile("st.shared.v4.f32 [%0], {%1,%2,%3,%4};" ::"r"(a), "f"(x), "f"(y), "f"(z), "f"(w) : "memory"); }
__device__ __forceinline__ uint32_t prmt(uint32_t a, uint32_t b, uint32_t s) { uint32_t r; asm("prmt.b32 %0,%1,%2,%3;" : "=r"(r) : "r"(a), "r"(b), "r"(s)); return r; }
__device__ __forceinline__ uint32_t pack2(float lo, float hi) { uint32_t r; asm("cvt.rn.bf16x2.f32 %0, %1, %2;" : "=r"(r) : "f"(hi), "f"(lo)); return r; }
__device__ __forceinline__ float blo(uint32_t v) { return __uint_as_float(v << 16); }
__device__ __forceinline__ float bhi(uint32_t v) { return __uint_as_float(v & 0xffff0000u); }
__device__ __forceinline__ uint32_t bmul2(uint32_t a, uint32_t b) { uint32_t r; asm("mul.rn.bf16x2 %0,%1,%2;" : "=r"(r) : "r"(a), "r"(b)); return r; }
__device__ __forceinline__ uint32_t badd2(uint32_t a, uint32_t b) { uint32_t r; asm("add.rn.bf16x2 %0,%1,%2;" : "=r"(r) : "r"(a), "r"(b)); return r; }
__device__ __forceinline__ float rbf(float x) { return __bfloat162float(__float2bfloat16_rn(x)); }
__device__ __forceinline__ uint32_t ldcg32(const void* p) { uint32_t v; asm volatile("ld.global.cg.u32 %0, [%1];" : "=r"(v) : "l"(p) : "memory"); return v; }
__device__ __forceinline__ uint4 ldcg128(const void* p) { uint4 v; asm volatile("ld.global.cg.v4.u32 {%0,%1,%2,%3}, [%4];" : "=r"(v.x), "=r"(v.y), "=r"(v.z), "=r"(v.w) : "l"(p) : "memory"); return v; }
__device__ __forceinline__ void stg32_if(void* p, uint32_t v, int on) { asm volatile("{.reg .pred q; setp.ne.b32 q, %2, 0; @q st.global.u32 [%0], %1;}" ::"l"(p), "r"(v), "r"(on) : "memory"); }
__device__ __forceinline__ uint2 ldcg64(const void* p) { uint2 v; asm volatile("ld.global.cg.v2.u32 {%0,%1}, [%2];" : "=r"(v.x), "=r"(v.y) : "l"(p) : "memory"); return v; }
__device__ __forceinline__ float gelu_h(float h) {
    float u = h * fmaf(h * h, 8.0f * 0.044715f * 0.7978845608028654f, 2.0f * 0.7978845608028654f);
    float th;
    asm("tanh.approx.f32 %0, %1;" : "=f"(th) : "f"(u));
    return fmaf(h, th, h);
}
__device__ __forceinline__ float gelu(float x) { return gelu_h(0.5f * x); }
__device__ __forceinline__ float half_rstd(float sum, float sq) {
    float mean = sum * (1.0f / D_), inv;
    asm("rsqrt.approx.ftz.f32 %0, %1;" : "=f"(inv) : "f"(fmaxf(fmaf(-mean, mean, fmaf(sq, 1.0f / D_, 1e-5f)), 1e-5f)));
    return 0.5f * inv;
}
__device__ __forceinline__ uint32_t bsub2(uint32_t a, uint32_t b) { uint32_t r; asm("sub.rn.bf16x2 %0,%1,%2;" : "=r"(r) : "r"(a), "r"(b)); return r; }
__device__ __forceinline__ uint32_t bfma2(uint32_t a, uint32_t b, uint32_t c) { uint32_t r; asm("fma.rn.bf16x2 %0,%1,%2,%3;" : "=r"(r) : "r"(a), "r"(b), "r"(c)); return r; }
__device__ __forceinline__ uint32_t gelu2_h(uint32_t h) {
    uint32_t u = bmul2(h, bfma2(bmul2(h, h), 0x3e923e92u, 0x3fcc3fccu)), th;
    asm("tanh.approx.bf16x2 %0, %1;" : "=r"(th) : "r"(u));
    return bfma2(h, th, h);
}
__device__ __forceinline__ uint3 row_stats(const uint32_t* v, int lane) {
    float s = 0.f, q = 0.f, s_ = 0.f, q_ = 0.f;
#pragma unroll
    for (int i = 0; i < 10; i++) { float a = blo(v[i]), b = bhi(v[i]); s += a; s_ += b; q = fmaf(a, a, q); q_ = fmaf(b, b, q_); }
    s += s_; q += q_;
    {
        float t = __shfl_xor_sync(0xffffffffu, (lane & 16) ? s : q, 16);
        t += (lane & 16) ? q : s;
#pragma unroll
        for (int m = 8; m; m >>= 1) t += __shfl_xor_sync(0xffffffffu, t, m);
        float o = __shfl_xor_sync(0xffffffffu, t, 16);
        s = (lane & 16) ? o : t; q = (lane & 16) ? t : o;
    }
    float mean = s * (1.0f / D_), inv;
    asm("rsqrt.approx.ftz.f32 %0, %1;" : "=f"(inv) : "f"(fmaxf(fmaf(-mean, mean, fmaf(q, 1.0f / D_, 1e-5f)), 1e-5f)));
    uint3 r;
    r.x = pack2(mean, mean);
    r.y = pack2(inv, inv);
    inv -= blo(r.y);
    r.z = pack2(inv, inv);
    return r;
}
__device__ __forceinline__ uint32_t ln_apply(uint32_t x, uint32_t m, uint32_t hi, uint32_t lo) {
    uint32_t xc = bsub2(x, m);
    return bmul2(xc, hi);
}

struct AFrag { uint32_t m, a, b, c, d; };
__device__ __forceinline__ AFrag ldA(uint32_t a) { AFrag f; f.m = lds32(a - 16); f.a = lds32(a); f.b = lds32(a + 16); f.c = lds32(a + 32); f.d = lds32(a + 48); return f; }
template <int N, int M> __device__ __forceinline__ void conv_pair(float* d, const AFrag& f, uint32_t descU) {
    WgRs<N>::template run<8 * M, desc_hi(128, 0), M ? 1 : 0>(d, f.a, f.b, f.m, f.a, descU);
    WgRs<N>::template run<8 * M + 1, desc_hi(128, 0), 1>(d, f.c, f.d, f.b, f.c, descU);
}
template <int Q> __device__ __forceinline__ void conv_put(float* d, uint32_t r0) {
    sts64(r0 + Q * 32, pack2(d[4 * Q + 1], d[4 * Q + 3]), pack2(d[4 * Q], d[4 * Q + 2]));
}
template <int M> __device__ __forceinline__ void conv_two(float* d, AFrag f0, AFrag f1, uint32_t kaddr, uint32_t descU, uint32_t r0, bool handoff) {
    constexpr int N = M < 14 ? 128 - 8 * M : 32;
    wg_fence();
    conv_pair<N, M>(d, f0, descU);
    wg_commit();
    if constexpr (M > 0) f1 = ldA(kaddr + 256 * (M + 1));
    wg_fence();
    conv_pair<N, M + 1>(d, f1, descU);
    wg_commit();
    if (STAG && M == STAG && handoff) bar_arrive(12, 256);
    if constexpr (M < 14) {
        if constexpr (M > 0) { conv_put<17 - M>(d, r0); conv_put<16 - M>(d, r0); }
        wg_wait<1>();
        f0 = ldA(kaddr + 256 * (M + 2));
        if constexpr (M < 12) wg_wait<0>();
        conv_two<M + 2>(d, f0, f1, kaddr, descU, r0, handoff);
    } else {
        wg_wait<0>();
        conv_put<3>(d, r0); conv_put<2>(d, r0); conv_put<1>(d, r0); conv_put<0>(d, r0);
    }
}
template <int N, bool ASWZ, int SC0>
__device__ __forceinline__ void gemm_issue(float* acc, uint32_t bars, int sa, int pa, int sw, int pw, uint32_t da0, uint32_t db0) {
    mbar_wait(bars + (BAR_FB + sw) * 8, pw);
    mbar_wait(bars + (BAR_FA + sa) * 8, pa);
    const uint32_t da = da0 + sa * (SLOT >> 4), db = db0 + sw * (SLOT >> 4);
    constexpr int AK = ASWZ ? 2 : 256, AH = ASWZ ? desc_hi(1024, 1) : desc_hi(128, 0), BH = desc_hi(1024, 1);
    wg_fence();
    WgSs<N>::template run<0, AH, 0, BH, SC0>(acc, da, db);
    WgSs<N>::template run<AK, AH, 128, BH, 1>(acc, da, db);
    WgSs<N>::template run<2 * AK, AH, 256, BH, 1>(acc, da, db);
    WgSs<N>::template run<3 * AK, AH, 384, BH, 1>(acc, da, db);
    wg_commit();
}
template <int N, bool ASWZ, int NKB, int RELB, bool ZERO>
__device__ __forceinline__ void gemm_loop(float* acc, uint32_t sb, int half, int ia0, int ib0, int rela, int wait_bar, int order_bar, int tsid) {
    int sa = ia0 % NA, pa = (ia0 / NA) & 1, sw = ib0 % NB, pw = (ib0 / NB) & 1;
    const uint32_t bars = sb + SM_BAR;
    const int t = threadIdx.x & 127;
    uint32_t ebar = mapa(bars + (t < 2 ? BAR_EB : BAR_EA) * 8, (t < 2 && lds32(sb + SM_GV + 516)) ? t : blockIdx.x & 1);
    const int nrel = t < 2 ? RELB : t == 2 ? rela : 0;
    const uint32_t da0 = ASWZ ? desc_lo(sb + SM_RA + half * 8192, 16) : desc_lo(sb + SM_RA + half * 1024, 2048), db0 = desc_lo(sb + SM_RB, 8192);
    asm volatile("" : "+r"(ebar));
    if (wait_bar) bar_sync(wait_bar, 512);
    gemm_issue<N, ASWZ, ZERO ? 0 : 1>(acc, bars, sa, pa, sw, pw, da0, db0);
    if ((threadIdx.x & 255) == 0) TS(tsid);
#pragma unroll 1
    for (int kb = 1; kb < NKB; kb++) {
        const int prev = t < 2 ? sw : sa;
        if (++sa == NA) { sa = 0; pa ^= 1; }
        if (++sw == NB) { sw = 0; pw ^= 1; }
        gemm_issue<N, ASWZ, 1>(acc, bars, sa, pa, sw, pw, da0, db0);
        if (order_bar && kb == NKB - 1) bar_arrive(order_bar, 512);
        wg_wait<1>();
        if (kb <= nrel) mbar_arrive_cl(ebar + prev * 8);
    }
    wg_wait<0>();
    if (nrel == NKB) mbar_arrive_cl(ebar + (t < 2 ? sw : sa) * 8);
    reg_fence<N / 2>(acc);
    if ((threadIdx.x & 255) == 0) TS(tsid + 1);
}

template <int PART>
__device__ __forceinline__ void gemm3(uint32_t sb, int rb, int j, int half, int row, int c, unsigned ones) {
    constexpr int N = 64 + (PART ? RB3 : RA3), NQ = N / 8;
    constexpr int HO = PART ? HO_B : HO_A;
    float acc[N / 2];
    float2 cr[NQ];
    if (PART) {
        gemm_loop<N, false, 1, 1, true>(acc, sb, half, 20, 20, 0, 0, 0, 50);
        bar_arrive(9, 512);
    }
    mbar_wait(sb + SM_BAR + BAR_CS * 8, 0);
    const uint32_t csa = sb + SM_CS + PART * (256 + 4 * RA3) + 8 * c;
#pragma unroll
    for (int q = 0; q < NQ; q++) if (q < CSP) cr[q] = lds64f(csa + 32 * q);
    uint4 rp;
    if (PART) {
        mbar_wait(sb + SM_BAR + BAR_G * 8, 0);
        const float2* sp = &g_st[(rb * 8 + 2 * c) * 128 + row];
        const uint2 s0 = ldcg64(sp), s1 = ldcg64(sp + 128), s2 = ldcg64(sp + 8), s3 = ldcg64(sp + 136);
        float a0 = __uint_as_float(s0.x) + __uint_as_float(s1.x), b0 = __uint_as_float(s0.y) + __uint_as_float(s1.y);
        float a1 = __uint_as_float(s2.x) + __uint_as_float(s3.x), b1 = __uint_as_float(s2.y) + __uint_as_float(s3.y);
#pragma unroll
        for (int m = 1; m <= 2; m <<= 1) {
            a0 += __shfl_xor_sync(0xffffffffu, a0, m); b0 += __shfl_xor_sync(0xffffffffu, b0, m);
            a1 += __shfl_xor_sync(0xffffffffu, a1, m); b1 += __shfl_xor_sync(0xffffffffu, b1, m);
        }
        const float inv0 = half_rstd(a0, b0), inv1 = half_rstd(a1, b1);
        rp = make_uint4(PGELU ? pack2(inv0, inv0) : __float_as_uint(inv0), __float_as_uint(a0 * (-1.0f / D_)),
                        PGELU ? pack2(inv1, inv1) : __float_as_uint(inv1), __float_as_uint(a1 * (-1.0f / D_)));
        if (c == 0) sts128(sb + SM_RP + ((threadIdx.x & 255) >> 2) * 16, rp);
        bar_arrive(13, 512);
    }
    gemm_loop<N, false, 10 - PART, 10 - PART, !PART>(acc, sb, half, 20 + (10 - NA) * PART, 21 + 10 * PART, PART ? 9 : 10 - NA, 9 + PART, HO < 0 ? 10 + PART : 0, 46 + 2 * PART);
    if (!PART) {
        bar_sync(13, 512);
        rp = lds128(sb + SM_RP + ((threadIdx.x & 255) >> 2) * 16);
    }
    const float nb0 = __uint_as_float(rp.y), nb1 = __uint_as_float(rp.w);
    const uint32_t own = sb + SM_RA + ((39 - NA) % NA) * SLOT + row * 16 + c * 4;
    if (PART && OWNG) mbar_wait(sb + SM_BAR + (BAR_FA + (39 - NA) % NA) * 8, ((39 - NA) / NA) & 1);
    uint32_t* dst = reinterpret_cast<uint32_t*>(g_g) + (rb * 216 + HB0 / 8 * PART + 8 * j) * 512 + row * 4 + c;
    auto act = [&](int q, int r) {
        const float nb = r ? nb1 : nb0;
        const uint32_t inv = r ? rp.z : rp.x;
        const float t0 = fmaf(nb, cr[q].x, acc[4 * q + 2 * r]), t1 = fmaf(nb, cr[q].y, acc[4 * q + 2 * r + 1]);
        return gelu2_h(bmul2(pack2(t0, t1), inv));
    };
    uint32_t* dst1 = dst + (56 - (16 - NQ) * j) * 512;
#pragma unroll
    for (int k = 0; k < NQ; k += CH3) {
        if (k == HO) bar_arrive(10 + PART, 512);
        CHUNK(k) {
#pragma unroll
            for (int q = k; q < k + CH3 && q < NQ; q++) {
                if (q + CSP < NQ) cr[q + CSP] = lds64f(csa + 32 * (q + CSP));
                const uint32_t u = act(q, 0), v = act(q, 1);
                (q < 8 ? dst : dst1)[q * 512] = u;
                (q < 8 ? dst : dst1)[q * 512 + 32] = v;
                if (PART && OWNG && q < 8) { sts32(own + q * 2048, u); sts32(own + q * 2048 + 128, v); }
            }
            if (PART && OWNG && k < 8 && k + CH3 >= 8) fence_async_smem();
        }
    }
    bar_arrive(1 + PART, 288);
    if (HO >= NQ) bar_arrive(10 + PART, 512);
}

template <int NS, int BASE, int BF, int BE> struct Ring {
    uint32_t sb, st, ph;
    __device__ __forceinline__ uint32_t acquire(uint32_t bytes) {
        mbar_wait(sb + SM_BAR + BE * 8 + st * 8, ph);
        uint32_t fb = sb + SM_BAR + BF * 8 + st * 8;
        mbar_expect(fb, bytes);
        return fb;
    }
    __device__ __forceinline__ uint32_t slot() { return sb + BASE + st * SLOT; }
    __device__ __forceinline__ void next() { if (++st == NS) { st = 0; ph ^= 1; } }
    __device__ __forceinline__ void run2d(const CUtensorMap* m, int c1) {
#pragma unroll 1
        for (int c0 = 64; c0 < D_; c0 += 64) {
            uint32_t fb = acquire(SLOT);
            tma2d(slot(), m, c0, c1, fb);
            next();
        }
    }
    static __device__ __forceinline__ int korder(int i, int own) { return i == 0 ? own : i > own ? i : i - 1; }
    __device__ __forceinline__ void runw(bool paired, int rk, const CUtensorMap* ma, const CUtensorMap* mb, int ca, int cb, int i0, int i1, int own, uint32_t bytes, int gate_at, uint32_t gate) {
        if (paired) {
            const CUtensorMap* m = rk ? mb : ma;
            const int c0 = rk ? cb : ca;
#pragma unroll 1
            for (int i = i0; i < i1; i++) {
                const int c1 = korder(i, own) * 64;
                if (i == gate_at) mbar_wait(gate, 0);
                uint32_t fb = acquire(bytes);
                tma2d_mc(slot() + 8192 * rk, m, c0, c1, fb);
                next();
            }
        } else {
#pragma unroll 1
            for (int i = i0; i < i1; i++) {
                const int c1 = korder(i, own) * 64;
                uint32_t fb = acquire(bytes);
                tma2d(slot(), ma, ca, c1, fb);
                tma2d(slot() + 8192, mb, cb, c1, fb);
                next();
            }
        }
    }
    __device__ __forceinline__ void run1d(const char* src, int i0, int i1, int own) {
#pragma unroll 1
        for (int i = i0; i < i1; i++) {
            const char* s = src + korder(i, own) * SLOT;
            uint32_t fb = acquire(SLOT);
            bulk_g2s(slot(), s, SLOT, fb);
            next();
        }
    }
};

__global__ void __cluster_dims__(2, 1, 1) __launch_bounds__(NTHREADS, 1) fused_kernel(const Params p, const __grid_constant__ Maps maps) {
    extern __shared__ __align__(1024) unsigned char smem_raw[];
    const uint32_t sb = (smem_u32(smem_raw) + 1023u) & ~1023u;
#pragma unroll
    for (int i = 0; i < SEED; i++) asm volatile("{.reg .b32 t; mov.u32 t, %laneid;}");
    const uint32_t bars = sb + SM_BAR;
    const int tid = threadIdx.x, lane = tid & 31;
    unsigned smid;
    asm volatile("mov.u32 %0, %%smid;" : "=r"(smid));
    const bool spare = (smid >> 2) == 30;
    const int cta = smid < 120 ? smid : smid - 4;
    const int pg = cta >> 4, pi = cta & 15;
    const int hb = tid >= 320;
    if (!spare) {
        const unsigned t = tid - 320 * hb, r32 = t / 10u, cc = t - r32 * 10u, row = r32 + 64 * hb;
        const unsigned go = (unsigned)(pi * 128 * 1280 + pg * 160) + row * 1280u + cc * 16u;
        const uint32_t so = sb + (row >> 4) * 32u + row * 160u + cc * 16u;
        const char* kb = (const char*)p.k + go;
        const char* vb = (const char*)p.v + go;
        if (hb) {
            if (tid >= 640 - NBARS) {
                const int i = 639 - tid;
                mbar_init(bars + i * 8, (i >= BAR_EB && i < BAR_K) ? 4 : ((i >= BAR_EA && i < BAR_EB) || i == BAR_XY) ? 2 : 1);
                asm volatile("fence.mbarrier_init.release.cluster;" ::: "memory");
            }
            bar_arrive(14, 640);
            if (B_DELAY) spin(B_DELAY);
        }
        cpasync16(so + SM_PK + 2592, kb, 16);
        cpasync16(so + SM_PV, vb, 16);
        cpasync16(so + SM_PK + 3 * 2592, kb + 32 * 1280, 16);
        cpasync16(so + SM_PV + 2 * 2592, vb + 32 * 1280, 16);
        if (tid < 30) cpasync16(so + SM_PK + 13 * 160, pi ? kb - 3 * 1280 : kb, pi ? 16 : 0);
        asm volatile("cp.async.commit_group;" ::: "memory");
    }
    const int warp = __shfl_sync(0xffffffffu, tid >> 5, 0);
    const int wg = warp >> 2, wq = warp & 3;
    unsigned ep0 = 0;
    if (wg == 4 || spare) ep0 = *(volatile unsigned*)&g_epoch[smid];
#define ep1 (ep0 + 1)

    if (spare) {
        const int sp = smid & 3;
        if (tid == 32) { sts32(sb + SM_GV + 512, smid); asm volatile("fence.release.sync_restrict::shared::cta.cluster;" ::: "memory"); }
        asm volatile("barrier.cluster.arrive.relaxed.aligned;" ::: "memory");
        asm volatile("barrier.cluster.wait.aligned;" ::: "memory");
        if (tid == 0) {
            for (int i = 0; i < 4; i++) mbar_init(bars + i * 8, 1);
            asm volatile("fence.mbarrier_init.release.cluster;" ::: "memory");
        }
        if (warp == 0) { if (lane < 8) flag_wait(FL_P + lane, ep1 * 16); __syncwarp(); }
        __syncthreads();
        const int cq = tid % 54, rg = tid / 54;
        float a[8];
#pragma unroll
        for (int i = 0; i < 8; i++) a[i] = 0.f;
#pragma unroll 1
        for (int it = -4; it < 10; it++) {
            const uint32_t st = sb + (it & 3) * 55296, fb = bars + (it & 3) * 8;
            if (it >= 0) {
                mbar_wait(fb, (it >> 2) & 1);
                if (tid < 432) {
#pragma unroll 2
                    for (int i = 0; i < 8; i++) {
                        uint4 w = lds128(st + (cq >= 27 ? 27648 - 432 : 0) + (rg * 8 + i) * 432 + cq * 16);
                        a[0] += blo(w.x); a[1] += bhi(w.x); a[2] += blo(w.y); a[3] += bhi(w.y);
                        a[4] += blo(w.z); a[5] += bhi(w.z); a[6] += blo(w.w); a[7] += bhi(w.w);
                    }
                }
                __syncthreads();
            }
            if (it < 6 && warp == 19 && elect()) {
                mbar_expect(fb, 55296);
                tma2d(st, &maps.w3s, sp * 432, (it + 4) * 64, fb);
                tma2d(st + 27648, &maps.w3s, sp * 432 + 216, (it + 4) * 64, fb);
            }
        }
        if (warp == 19 && elect()) {
#pragma unroll 1
            for (int i = 0; i < 27; i++) bulk_prefetch((const char*)p.w4 + sp * 552960 + i * 20480, 20480);
        }
        if (tid < 432) {
            sts128f(sb + rg * 1728 + cq * 32, a[0], a[1], a[2], a[3]);
            sts128f(sb + rg * 1728 + cq * 32 + 16, a[4], a[5], a[6], a[7]);
        }
        __syncthreads();
        if (tid < 432) {
            float s = 0.f;
#pragma unroll
            for (int i = 0; i < 8; i++) s += __uint_as_float(lds32(sb + i * 1728 + tid * 4));
            g_cs[sp * 432 + tid] = s;
        }
        __syncthreads();
        if (tid == 0) { flag_release(FL_CS); g_epoch[smid] = ep1; TS(0); }
        if (warp == 0) TSFLUSH();
        return;
    }

    int gpc, idx;
    if (smid < 64) { gpc = (smid & 15) >> 1; idx = (smid >> 4) * 2 + (smid & 1); }
    else if (smid < 120) { int t = smid - 64; gpc = 1 + (t % 14) / 2; idx = 8 + (t / 14) * 2 + (smid & 1); }
    else { gpc = 0; idx = 8 + (smid - 124); }
    const int rb = 2 * gpc + (idx & 1), j = idx >> 1;
    const int g = lane >> 2, c = lane & 3;
    const int cm = 160 * (j >> 1) + 64 * (j & 1) + ((j & 2) ? 32 : 0), cr = 160 * (j >> 1) + 16 * (j & 1) + ((j & 2) ? 0 : 128);

    {
        if (warp == 5) TSW(61);
        const int w10 = warp - 10 * hb, h = w10 >= 5;
        const int pr = (w10 - 5 * h) * 8 + (lane >> 2), blk = 4 * hb + (lane & 3);
        const int ch = 80 * pg + 2 * pr;
        const uint4 sw = __ldg(reinterpret_cast<const uint4*>(p.shift + ch * 4));
        uint32_t dv = 0;
        if (warp == 9 && lane < 5) dv = __bfloat16_as_ushort(p.ssmD[cta * 5 + lane]);
        if (tid == 512) { sts32(sb + SM_GV + 512, smid); asm volatile("fence.release.sync_restrict::shared::cta.cluster;" ::: "memory"); }
        asm volatile("barrier.cluster.arrive.relaxed.aligned;" ::: "memory");
        if (warp == 11 && lane < 13) prefetch_map(&maps.hn + lane);
        if (wg < 4) {
            const int t = tid & 127, cc = (wg == 3 && t >= 64) ? 4 : wg;
            if (t < 64 || wg == 3) sts128(sb + sm_u(cc) + ((t >> 5) & 1) * U_PLANE + 2048 + lane * 16, make_uint4(0, 0, 0, 0));
            if ((t & 63) < 4 && (t < 64 || wg == 3)) sts128(sb + sm_k(cc) + ((t >> 1) & 1) * 4160 + (t & 1) * 16, make_uint4(0, 0, 0, 0));
        }
        if (warp == 9 && lane < 5) sts32(sb + SM_GV + 520 + lane * 4, dv << 16);
        asm volatile("cp.async.wait_group 0;" ::: "memory");
        if (!hb) bar_arrive(12, 640);
        bar_sync(hb ? 12 : 14, 640);
        if (warp == 9) {
            if (SSM_DELAY) spin(SSM_DELAY);
            if (elect()) {
#pragma unroll
                for (int i = 0; i < SSM_N; i++) {
                    mbar_expect(bars + (BAR_K + i) * 8, 4096);
                    bulk_g2s(sb + sm_k(i) + 32, p.ssmk + (size_t)(cta * 5 + i) * S_, 4096, bars + (BAR_K + i) * 8);
                }
            }
        }
        const uint32_t w0 = prmt(sw.x, sw.z, 0x5410), w1 = prmt(sw.x, sw.z, 0x7632), w2 = prmt(sw.y, sw.w, 0x5410), w3 = prmt(sw.y, sw.w, 0x7632);
        const uint32_t ka = sb + SM_PK + 2592 + blk * 2592 + h * 1280 + pr * 4;
        const uint32_t va = sb + SM_PV + blk * 2592 + h * 1280 + pr * 4;
        uint32_t kk[11], kv[8];
#pragma unroll
        for (int i = 0; i < 11; i++) kk[i] = lds32(ka + (i - 3) * 160 - ((i < 3 && h == 0) ? 32 : 0));
#pragma unroll
        for (int i = 0; i < 8; i++) {
            uint32_t t = badd2(badd2(badd2(bmul2(kk[i], w3), bmul2(kk[i + 1], w2)), bmul2(kk[i + 2], w1)), bmul2(kk[i + 3], w0));
            kv[i] = bmul2(t, lds32(va + i * 160));
        }
        uint4 o0, o1;
        o0.x = prmt(kv[1], kv[0], 0x5410); o0.y = prmt(kv[3], kv[2], 0x5410); o0.z = prmt(kv[5], kv[4], 0x5410); o0.w = prmt(kv[7], kv[6], 0x5410);
        o1.x = prmt(kv[1], kv[0], 0x7632); o1.y = prmt(kv[3], kv[2], 0x7632); o1.z = prmt(kv[5], kv[4], 0x7632); o1.w = prmt(kv[7], kv[6], 0x7632);
        uint4* dst = reinterpret_cast<uint4*>(g_kvT) + ch * 256 + h * 128 + (127 - (8 * pi + blk));
        dst[0] = o0;
        dst[256] = o1;
    }

    const int rho = 8 * rb + j;

    if (wg == 4) {
        asm volatile("setmaxnreg.dec.sync.aligned.u32 32;");
        if (wq == 0) {
            bar_sync(13, 640);
            TSW(39);
            if (lane == 0) flag_release(FL_P + pg);
            __syncwarp();
            TSW(2);
            if (lane < 5) mbar_expect(bars + (BAR_U + lane) * 8, 4096);
            flag_wait(FL_P + pg, ep1 * 16);
            fence_async_global();
            TSW(3);
            if (elect()) {
#pragma unroll
                for (int i = 0; i < 5; i++) {
                    const char* us = (const char*)g_kvT + (size_t)(cta * 5 + i) * 4096;
                    bulk_g2s(sb + sm_u(i), us, 2048, bars + (BAR_U + i) * 8);
                    bulk_g2s(sb + sm_u(i) + U_PLANE, us + 2048, 2048, bars + (BAR_U + i) * 8);
                }
            }
            __syncwarp();
            if (elect()) {
#pragma unroll
                for (int i = SSM_N; i < 5; i++) {
                    mbar_expect(bars + (BAR_K + i) * 8, 4096);
                    bulk_g2s(sb + sm_k(i) + 32, p.ssmk + (size_t)(cta * 5 + i) * S_, 4096, bars + (BAR_K + i) * 8);
                }
                if (cta < 120) {
                    mbar_expect(bars + BAR_WM * 8, 40960);
#pragma unroll 1
                    for (int i = 0; i < 5; i++) tma2d(sb + SM_WM + i * 8192, &maps.wm, cta * 32, i * 128, bars + BAR_WM * 8);
                }
                bulk_prefetch((const char*)p.q + cta * 20480, 20480);
                bulk_prefetch((const char*)p.w1 + cta * 6400, 6400);
                bulk_prefetch((const char*)p.w2 + cta * 6400, 6400);
            }
            __syncwarp();
        } else {
            bar_arrive(13, 640);
        }
        asm volatile("barrier.cluster.wait.aligned;" ::: "memory");
        uint32_t peer;
        asm volatile("ld.shared::cluster.u32 %0, [%1];" : "=r"(peer) : "r"(mapa(sb + SM_GV + 512, (blockIdx.x & 1) ^ 1)) : "memory");
        const bool paired = peer == (smid ^ 1);
        if (tid == 639) sts32(sb + SM_GV + 516, paired);
        if (cta < 120) {
            float d[4];
            if (tid < 592) {
                const int t = tid - 512;
                mbar_wait(bars + BAR_U * 8, 0);
                uint4 cv = __ldg(reinterpret_cast<const uint4*>(p.c) + t);
                auto silu2 = [](uint32_t v) { float a = blo(v), b = bhi(v); return pack2(__fdividef(a, 1.0f + __expf(-a)), __fdividef(b, 1.0f + __expf(-b))); };
#pragma unroll 1
                for (int i = 0; i < 4; i++) { const uint32_t r = silu2(cv.x); cv.x = cv.y; cv.y = cv.z; cv.z = cv.w; cv.w = r; }
                sts128(sb + SM_Y + (t % 40) * 32 + (t / 40) * 16, cv);
                fence_async_smem();
            }
            bar_sync(5, 128);
            mbar_wait(bars + BAR_WM * 8, 0);
            if (wq == 3) TSW(56);
            const uint32_t da = desc_lo(sb + SM_WM, 20480), db = desc_lo(sb + SM_Y, 32);
#pragma unroll 1
            for (int k0 = 0; k0 < 20; k0 += 4) {
                wg_fence();
#pragma unroll
                for (int k = k0; k < k0 + 4; k++) asm volatile("{.reg .pred p; .reg .b32 l,m; .reg .b64 da,db; setp.ne.b32 p,%10,0; add.u32 l,%4,%6; mov.b64 da,{l,%8}; add.u32 m,%5,%7; mov.b64 db,{m,%9};"
                             " wgmma.mma_async.sync.aligned.m64n8k16.f32.bf16.bf16 {%0,%1,%2,%3},da,db,p,1,1,1,0;}"
                             : "+f"(d[0]), "+f"(d[1]), "+f"(d[2]), "+f"(d[3])
                             : "r"(da), "r"(db), "r"(64 * k), "r"(4 * k), "n"(desc_hi(512, 2u)), "n"(desc_hi(128, 0)), "r"(k));
                wg_commit();
            }
            wg_wait<0>();
            reg_fence<4>(d);
            if (c == 0) {
                sts32(sb + SM_GV + (16 * wq + g) * 4, __float_as_uint(wq < 2 ? d[0] : d[1]));
                sts32(sb + SM_GV + (16 * wq + g + 8) * 4, __float_as_uint(wq < 2 ? d[2] : d[3]));
            }
            bar_sync(5, 128);
            if (wq == 2) {
                g_mod[cta * 32 + lane] = __float2bfloat16_rn(__uint_as_float(lds32(sb + SM_GV + lane * 4)) + __uint_as_float(lds32(sb + SM_GV + 128 + lane * 4)));
                __syncwarp();
                if (lane == 0) flag_release(FL_M);
                __syncwarp();
                TSW(4);
            }

        }
        if (wq == 2) {
            flag_wait(FL_M, ep1 * 120);
            fence_async_global();
            if (elect()) {
                mbar_expect(bars + BAR_M * 8, 7680);
                bulk_g2s(sb + SM_MOD, g_mod, 7680, bars + BAR_M * 8);
            }
            __syncwarp();
            TSW(60);
            bar_sync(8, 544);  if (lane == 0) { flag_release(FL_R + rb); TS(23); }  __syncwarp();
            bar_sync(15, 288); if (lane == 0) { flag_release(FL_B1 + rb); TS(27); } __syncwarp();
            bar_sync(6, 288);  if (lane == 0) { flag_release(FL_B2 + rb); TS(31); } __syncwarp();
#pragma unroll 1
            for (int i = 0; i < 3; i++) { bar_sync(i ? i : 8, 288); if (lane == 0) { TS(53 + (i + 2) % 3); flag_release(FL_G + 16 * i + rb); TS(57 + (i + 2) % 3); } __syncwarp(); }
            if (lane == 0) g_epoch[smid] = ep1;
            return;
        }
        if (wq == 1) {
            bar_sync(9, 288);
            if (lane < 4 * NB) mbar_arrive_cl(mapa(bars + (BAR_EB + (lane >> 2)) * 8, paired ? lane & 1 : blockIdx.x & 1));
        }
        if (wq == 3) {
            bar_sync(7, 544);
            if (lane == 0) { flag_release(FL_C); TS(20); }
            __syncwarp();
            if (lane < 2) mbar_expect(bars + (lane ? BAR_Y2 : BAR_Y) * 8, lane ? 8192 : 12288);
            flag_wait(FL_C, ep1 * 128);
            fence_async_global();
            TSW(21);
            if (elect()) {
                bulk_g2s(sb + SM_Y, g_yv + rho * 5120, 12288, bars + BAR_Y * 8);
                bulk_g2s(sb + SM_Y + 12288, g_yv + rho * 5120 + 3072, 8192, bars + BAR_Y2 * 8);
            }
            __syncwarp();
        }
        if (elect()) {
            if (wq == 3) {
                mbar_expect(bars + BAR_XY * 8, 20480);
#pragma unroll 1
                for (int i = 0; i < 8; i++) {
                    bulk_g2s(sb + SM_YT + i * 2560, g_yv + (8 * rb + i) * 5120 + cm * 8, 2048, bars + BAR_XY * 8);
                    bulk_g2s(sb + SM_YT + i * 2560 + 2048, g_yv + (8 * rb + i) * 5120 + cr * 8, 512, bars + BAR_XY * 8);
                }
                flag_wait(FL_CS, ep1 * 4);
                fence_async_global();
                mbar_expect(bars + BAR_CS * 8, 864);
                bulk_g2s(sb + SM_CS, g_cs + 64 * j, 256, bars + BAR_CS * 8);
                bulk_g2s(sb + SM_CS + 256, g_cs + 512 + RA3 * j, 4 * RA3, bars + BAR_CS * 8);
                bulk_g2s(sb + SM_CS + 256 + 4 * RA3, g_cs + HB0 + 64 * j, 256, bars + BAR_CS * 8);
                bulk_g2s(sb + SM_CS + 512 + 4 * RA3, g_cs + HB0 + 512 + RB3 * j, 4 * RB3, bars + BAR_CS * 8);
                mbar_wait(bars + BAR_ST * 8, 0);
#pragma unroll 1
                for (int i = 0; i < 3; i++) {
                    flag_wait(FL_G + 16 * i + rb, ep1 * 8);
                    mbar_expect(bars + (BAR_G + i) * 8, 0);
                    TS(35 + (i + 2) % 3);
                }
            } else if (wq == 1) {
                Ring<NB, SM_RB, BAR_FB, BAR_EB> r{sb, 0, 0};
#pragma unroll 1
                for (int ph = 0; ph < 7; ph++) {
                    const CUtensorMap* ma = ph == 0 ? &maps.w1a : ph == 1 ? &maps.w2a : ph == 6 ? &maps.w4a : &maps.w3a;
                    const bool b3b = ph == 2 || ph == 4 || ph == 5;
                    r.runw(paired, idx & 1, ma, ma + (b3b ? 2 : 1), ph == 3 ? 64 * j : b3b ? HB0 + 64 * j : cm,
                           ph == 3 ? 512 + RA3 * j : b3b ? HB0 + 512 + RB3 * j : cr, ph == 4 ? 10 - NA : ph == 5 ? 1 : 0,
                           ph == 6 ? 27 : ph == 5 ? 10 - NA : ph == 2 ? 1 : 10, ph == 0 ? 0 : ph == 6 ? OWNG * (HB0 / 64 + j) : cm >> 6,
                           ph == 3 ? 8192 + 128 * RA3 : b3b ? 8192 + 128 * RB3 : 10240,
                           ph == 1 ? GATE : ph == 3 ? GATE - 1 : -1, bars + (BAR_ST - (ph == 1)) * 8);
                }
            } else {
                Ring<NA, SM_RA, BAR_FA, BAR_EA> r{sb, 0, 0};
                if (cta >= 120) mbar_wait(bars + (BAR_K + 4) * 8, 0);
                mbar_expect(bars + BAR_XR * 8, 20480);
                bulk_g2s(sb + SM_XR, p.q + (size_t)rho * 16 * D_, 20480, bars + BAR_XR * 8);
                mbar_expect(bars + BAR_XY * 8, 20480);
                tma2d(sb + SM_XT, &maps.xa, cm, rb * 128, bars + BAR_XY * 8);
                tma2d(sb + SM_XT2, &maps.xb, cr, rb * 128, bars + BAR_XY * 8);
                const int grp = j >> 1;
                const int delta = (grp & 1 ? 1 : -1) * (1 + (grp >> 1));
                const int nb = min(max(rb + (delta > 0 ? 1 : -1), 0), 15);
                uint32_t fb = r.acquire(SLOT), dst = r.slot();
                flag_wait2(FL_R + nb, FL_R + rb, ep1 * 8);
                fence_async_global();
                tma2d(dst, &maps.hn, 0, rb * 128 + delta, fb);
                TS(24);
                r.next();
                r.run2d(&maps.hn, rb * 128 + delta);
#pragma unroll 1
                for (int i = 0; i < 2; i++) {
                    const char* src = (const char*)(i ? g_x1 : g_h1) + (size_t)rb * 163840;
                    r.acquire(0); r.next();
                    fb = r.acquire(SLOT); dst = r.slot();
                    const char* src1 = src + (cm == 0 ? SLOT : 0);
                    flag_wait(FL_B1 + 16 * i + rb, ep1 * 8);
                    fence_async_global();
                    bulk_g2s(dst, src1, SLOT, fb);
                    TS(28 + 4 * i);
                    mbar_expect(bars + (BAR_ST - 1 + i) * 8, 0);
                    r.next();
                    r.run1d(src, 2, 10, cm >> 6);
                }
                r.run1d((const char*)g_x1 + (size_t)rb * 163840, 1, 10 - NA, cm >> 6);
                if (OWNG) { r.acquire(0); r.next(); }
#pragma unroll 1
                for (int i = 0; i < 2; i++) {
                    mbar_wait(bars + (BAR_G + 1 + i) * 8, 0); fence_async_global();
                    r.run1d((const char*)g_g + (size_t)rb * 442368, OWNG + HB0 / 64 * i, i ? 27 : OWNG + HB0 / 64, OWNG * (HB0 / 64 + j));
                }
            }
        }
        return;
    }
    bar_arrive(13, 640);
    asm volatile("setmaxnreg.inc.sync.aligned.u32 112;");
    const int rrow = 16 * rho + (warp >> 1) + 8 * (warp & 1);

    fence_async_smem();
    bar_sync(1 + wg, 128);
#pragma unroll 1
    for (int cc = wg; cc < wg + 1 + (wg == 3); cc++) {
        mbar_wait(bars + (BAR_K + cc) * 8, 0);
        if (cc == 2 && wq == 0) TSW(40);
        uint32_t a = sb + sm_k(cc) + 32 + (tid & 127) * 32;
        uint32_t pw = lds32(a - 4);
        uint4 x = lds128(a), y = lds128(a + 16), o;
        if ((tid & 127) == 0) {
            uint16_t k0 = __bfloat16_as_ushort(__float2bfloat16_rn(blo(x.x) + __uint_as_float(lds32(sb + SM_GV + 520 + cc * 4))));
            x.x = (x.x & 0xffff0000u) | k0;
            sts16(a, k0);
        }
        o.x = prmt(pw, x.x, 0x5432); o.y = prmt(x.x, x.y, 0x5432); o.z = prmt(x.y, x.z, 0x5432); o.w = prmt(x.z, x.w, 0x5432);
        sts128(a + 4160, o);
        o.x = prmt(x.w, y.x, 0x5432); o.y = prmt(y.x, y.y, 0x5432); o.z = prmt(y.y, y.z, 0x5432); o.w = prmt(y.z, y.w, 0x5432);
        sts128(a + 4176, o);
    }
    bar_sync(1 + wg, 128);
    if (wg == 3) bar_arrive(11, 256);
#pragma unroll 1
    for (int cc = wg; cc < 5; cc += 3) {
        if (cc == 3 && wg == 0) break;
        if (cc == 4) bar_sync(11, 256);
        const uint32_t kaddr = sb + sm_k(cc) + ((g & 1) ? 32 : 4192) + 4 * ((g >> 1) - c) + 64 * wq;
        const AFrag f0 = ldA(kaddr), f1 = ldA(kaddr + 256);
        if (STAG && cc == 3) bar_sync(12, 256);
        mbar_wait(bars + (BAR_U + cc) * 8, 0);
        if (wq == 0) TSW(5 + cc);
        float d[64];
        conv_two<0>(d, f0, f1, kaddr, desc_lo(sb + sm_u(cc), U_PLANE), sb + sm_red(cc) + wq * 4352 + g * 544 + c * 8, cc == 1);
        if (wq == 0) TSW(10 + cc);
        if (cc == 1) bar_arrive(6, 256);
    }
#pragma unroll 1
    for (int cc = wg == 1 ? 4 : wg;; cc++) {
        if (cc == 1) bar_sync(6, 256); else bar_sync(1 + wg, 128);
        const int ch = cta * 5 + cc;
        uint32_t* dst = g_yv + ch * 8 + ((g + (ch >> 2)) & 7) + (126 - 32 * wq - 2 * c) * 5120;
        uint2 v[16];
#pragma unroll
        for (int i = 0; i < 16; i++) v[i] = lds64(sb + sm_red(cc) + g * 544 + wq * 128 + c * 8 + (i >> 2) * 32 + (i & 3) * 4360);
#pragma unroll
        for (int w = 1; w < 4; w++)
            if (wq == 3 && c > 3 - w) v[12 + w] = make_uint2(0, 0);
#pragma unroll
        for (int q = 0; q < 4; q++) {
            const uint2* u = v + 4 * q;
            dst[-8 * q * 5120] = badd2(u[0].x, badd2(u[1].x, badd2(u[2].x, u[3].x)));
            dst[(-8 * q + 1) * 5120] = badd2(u[0].y, badd2(u[1].y, badd2(u[2].y, u[3].y)));
        }
        if (wq == 0) TSW(15 + cc);
        if (cc != 0) break;
    }
    fence_async_smem();
    if (!(wg & 1)) bar_arrive(9, 288);
    bar_arrive(7, 544);

    const uint32_t one2 = 0x3f803f80u;
    const unsigned ones = p.ones;
    {
        uint32_t x[10], a[10], cb[10], sbv[10];
        if (RPRE_WAIT) bar_sync(10, 512);
        mbar_wait(bars + BAR_XR * 8, 0);
#pragma unroll
        for (int i = 0; i < 10; i++) x[i] = lds32(sb + SM_XR + (rrow & 15) * 1280 + lane * 4 + i * 128);
        const uint3 s1 = row_stats(x, lane);
        const int up = lane >> 4, gg = warp >> 1, e = warp & 1;
        const uint32_t ya = sb + SM_Y + lane * 64 + ((gg + (lane >> 1)) & 7) * 4;
        const uint32_t sel = (up ? 0x1054u : 0x5410u) + (e ? 0x2222u : 0u);
        const uint32_t ma = sb + SM_MOD + lane * 4;
        mbar_wait(bars + BAR_M * 8, 0);
        uint32_t pin = 0;
#pragma unroll
        for (int i = 0; i < 10; i++) {
            uint32_t h = bfma2(ln_apply(x[i], s1.x, s1.y, s1.z), badd2(lds32(ma + 1280 + i * 128), one2), lds32(ma + i * 128));
            a[i] = bmul2(h, lds32(ma + 2560 + i * 128));
            sbv[i] = lds32(ma + 3840 + i * 128);
            cb[i] = badd2(lds32(ma + 5120 + i * 128), one2);
            pin ^= a[i] ^ cb[i];
        }
        if (pin & ~ones) sts32(sb + SM_GV, pin);
        if (warp == 4) TSW(52);
        mbar_wait(bars + BAR_Y * 8, 0);
        if (warp == 0) TSW(22);
#pragma unroll
        for (int i = 0; i < 10; i++) {
            if (i == 6) mbar_wait(bars + BAR_Y2 * 8, 0);
            uint32_t y0 = lds32(ya + i * 2048 + up * 32), y1 = lds32(ya + i * 2048 + (up ^ 1) * 32);
            x[i] = bfma2(a[i], prmt(y0, y1, sel), x[i]);
        }
        const uint3 s2 = row_stats(x, lane);
#pragma unroll
        for (int i = 0; i < 10; i++) x[i] = bfma2(ln_apply(x[i], s2.x, s2.y, s2.z), cb[i], sbv[i]);
        const uint3 s3 = row_stats(x, lane);
        uint32_t* o = reinterpret_cast<uint32_t*>(g_hn + (size_t)rrow * D_) + lane;
#pragma unroll
        for (int i = 0; i < 10; i++) o[32 * i] = ln_apply(x[i], s3.x, s3.y, s3.z);
        if (lane < 2) g_rs[rrow * 2 + lane] = lane ? make_uint4(s2.x, s2.y, s2.z, 0) : make_uint4(s1.x, s1.y, s1.z, 0);
        if (warp == 0) TSW(34);
        bar_arrive(8, 544);
    }

    const int half = wg & 1;
    const int row = 64 * half + 16 * wq + g;
    const int tw0 = (rb * 80 + (cm >> 3)) * 512 + row * 4 + c, tw1 = (rb * 80 + (cr >> 3) - 8) * 512 + row * 4 + c;
    const uint32_t park = sb + SM_Y + (tid & 255) * 16;
    const uint32_t ms0 = sb + SM_MOD + (cm + 2 * c) * 2, ms1 = sb + SM_MOD + (cr - 64 + 2 * c) * 2;
    if (wg >= 2) {
        {
            float acc[40];
            gemm_loop<80, true, 10, 10, true>(acc, sb, half, 0, 0, 10, 0, 0, 25);
#pragma unroll
            for (int k = 0; k < 10; k += CH) CHUNK(k) {
#pragma unroll
                for (int q = k; q < k + CH && q < 10; q++) {
                    uint32_t* dst = reinterpret_cast<uint32_t*>(g_h1) + (q < 8 ? tw0 : tw1);
                    const uint32_t u = gelu2_h(bmul2(pack2(acc[4 * q], acc[4 * q + 1]), 0x3f003f00u));
                    const uint32_t v = gelu2_h(bmul2(pack2(acc[4 * q + 2], acc[4 * q + 3]), 0x3f003f00u));
                    dst[q * 512] = u;
                    dst[q * 512 + 32] = v;
                    acc[4 * q] = __uint_as_float(u); acc[4 * q + 1] = __uint_as_float(v);
                }
            }
            bar_arrive(15, 288);
            mbar_wait(bars + (BAR_FA + 10 % NA) * 8, (10 / NA) & 1);
#pragma unroll
            for (int q = 0; q < 8; q++) {
                sts32(sb + SM_RA + (10 % NA) * SLOT + q * 2048 + row * 16 + c * 4, __float_as_uint(acc[4 * q]));
                sts32(sb + SM_RA + (10 % NA) * SLOT + q * 2048 + row * 16 + c * 4 + 128, __float_as_uint(acc[4 * q + 1]));
            }
            fence_async_smem();
            bar_arrive(14, 512);
        }
        gemm3<0>(sb, rb, j, half, row, c, ones);
        {
            float acc[40];
            uint32_t gbv[10], base[20];
#pragma unroll
            for (int q = 0; q < 10; q++) gbv[q] = lds32((q < 8 ? ms0 : ms1) + 6400 + q * 16);
#pragma unroll
            for (int q = 0; q < 5; q++) { const uint4 t = lds128(park + q * 4096); base[4 * q] = t.x; base[4 * q + 1] = t.y; base[4 * q + 2] = t.z; base[4 * q + 3] = t.w; }
            gemm_loop<80, false, 27, 27 - NB, true>(acc, sb, half, 39 - NA, 40, 27 - NA, 11, 0, 42);
            auto fin = [&](int q, int r) {
                return bfma2(gbv[q], pack2(acc[4 * q + 2 * r], acc[4 * q + 2 * r + 1]), base[2 * q + r]);
            };
            auto tr4 = [&](uint32_t t0, uint32_t t1, uint32_t t2, uint32_t t3) {
                const bool o1 = c & 1, o2 = c & 2;
                uint32_t a = __shfl_xor_sync(0xffffffffu, o1 ? t0 : t1, 1), b = __shfl_xor_sync(0xffffffffu, o1 ? t2 : t3, 1);
                uint32_t u0 = o1 ? a : t0, u1 = o1 ? t1 : a, u2 = o1 ? b : t2, u3 = o1 ? t3 : b;
                a = __shfl_xor_sync(0xffffffffu, o2 ? u0 : u2, 2); b = __shfl_xor_sync(0xffffffffu, o2 ? u1 : u3, 2);
                return o2 ? make_uint4(a, b, u2, u3) : make_uint4(u0, u1, a, b);
            };
            bf16* go = p.out + (size_t)(rb * 128 + row) * D_;
#pragma unroll
            for (int k = 0; k < 2; k++) CHUNK(k) {
#pragma unroll
                for (int r = 0; r < 2; r++)
                    *reinterpret_cast<uint4*>(go + r * 8 * D_ + cm + 32 * k + 8 * c) = tr4(fin(4 * k, r), fin(4 * k + 1, r), fin(4 * k + 2, r), fin(4 * k + 3, r));
            }
            CHUNK(2) *reinterpret_cast<uint4*>(go + (c >> 1) * 8 * D_ + cr + 8 * (c & 1)) = tr4(fin(8, 0), fin(9, 0), fin(8, 1), fin(9, 1));
            if (tid == 256) TS(44);
            if (warp == 8) TSFLUSH();
        }
    } else {
        {
            float acc[40];
            uint32_t x2[20];
            {
                uint32_t y[20];
                mbar_wait(bars + BAR_XY * 8, 0);
                const uint32_t xa = sb + SM_XT + row * 128 + c * 4, xb = sb + SM_XT2 + row * 32 + c * 4;
                const uint32_t ya = sb + SM_YT + (4 * half + wq) * 2560 + c * 64;
#pragma unroll
                for (int q = 0; q < 10; q++) {
                    const uint32_t a = q < 8 ? xa + ((q ^ g) << 4) : xb + (q - 8) * 16;
                    x2[2 * q] = lds32(a); x2[2 * q + 1] = lds32(a + (q < 8 ? 1024 : 256));
                    const int pos = (g + ((q < 8 ? cm : cr) >> 2) + 2 * q + (c >> 1)) & 7;
                    y[2 * q] = lds32(ya + q * 256 + pos * 4); y[2 * q + 1] = lds32(ya + q * 256 + 32 + pos * 4);
                }
                fence_async_smem();
                bar_sync(1 + wg, 128);
                if ((tid & 127) < NA) mbar_arrive_cl(mapa(bars + (BAR_EA + (tid & 127)) * 8, blockIdx.x & 1));
                mbar_wait(bars + (BAR_FA + 1) * 8, 0);
                const uint4* rp = g_rs + (rb * 128 + row) * 2;
                const uint4 ra = ldcg128(rp), rb2 = ldcg128(rp + 1), rc = ldcg128(rp + 16), rd = ldcg128(rp + 17);
                bar_sync(14, 512);
#pragma unroll
                for (int q = 0; q < 10; q++) {
                    const uint32_t ms = q < 8 ? ms0 : ms1;
                    const uint32_t sa = lds32(ms + 16 * q), ca = badd2(lds32(ms + 1280 + 16 * q), one2), ga = lds32(ms + 2560 + 16 * q);
                    const uint32_t sbv = lds32(ms + 3840 + 16 * q), cb = badd2(lds32(ms + 5120 + 16 * q), one2);
                    uint32_t u = x2[2 * q], v = x2[2 * q + 1];
                    u = bfma2(bmul2(bfma2(ln_apply(u, ra.x, ra.y, ra.z), ca, sa), ga), prmt(y[2 * q], y[2 * q + 1], 0x5410), u);
                    v = bfma2(bmul2(bfma2(ln_apply(v, rc.x, rc.y, rc.z), ca, sa), ga), prmt(y[2 * q], y[2 * q + 1], 0x7632), v);
                    x2[2 * q] = u; x2[2 * q + 1] = v;
                    u = bfma2(ln_apply(u, rb2.x, rb2.y, rb2.z), cb, sbv);
                    v = bfma2(ln_apply(v, rd.x, rd.y, rd.z), cb, sbv);
                    acc[4 * q] = blo(u); acc[4 * q + 1] = bhi(u); acc[4 * q + 2] = blo(v); acc[4 * q + 3] = bhi(v);
                }
            }
            reg_fence<40>(acc);
            if (tid == 0) TS(45);
            gemm_loop<80, false, 10, 10, false>(acc, sb, half, 10, 10, 10, 0, 0, 29);
            uint32_t x1[20];
            float s0 = 0.f, q0 = 0.f, s1 = 0.f, q1 = 0.f;
#pragma unroll
            for (int q = 0; q < 10; q++) {
                uint32_t u = pack2(acc[4 * q], acc[4 * q + 1]);
                uint32_t v = pack2(acc[4 * q + 2], acc[4 * q + 3]);
                uint32_t* dst = reinterpret_cast<uint32_t*>(g_x1) + (q < 8 ? tw0 : tw1);
                dst[q * 512] = u;
                dst[q * 512 + 32] = v;
                x1[2 * q] = u; x1[2 * q + 1] = v;
            }
            bar_arrive(6, 288);
            CHUNK(0)
#pragma unroll
            for (int q = 0; q < 10; q++) {
                float a = blo(x1[2 * q]), b = bhi(x1[2 * q]), e = blo(x1[2 * q + 1]), f = bhi(x1[2 * q + 1]);
                s0 += a + b; q0 = fmaf(a, a, fmaf(b, b, q0));
                s1 += e + f; q1 = fmaf(e, e, fmaf(f, f, q1));
            }
#pragma unroll
            for (int m = 1; m <= 2; m <<= 1) {
                s0 += __shfl_xor_sync(0xffffffffu, s0, m); q0 += __shfl_xor_sync(0xffffffffu, q0, m);
                s1 += __shfl_xor_sync(0xffffffffu, s1, m); q1 += __shfl_xor_sync(0xffffffffu, q1, m);
            }
            if (c < 2) g_st[(rb * 8 + j) * 128 + row + 8 * c] = c ? make_float2(s1, q1) : make_float2(s0, q0);
            bar_arrive(8, 288);
            mbar_wait(bars + (BAR_FA + 20 % NA) * 8, (20 / NA) & 1);
#pragma unroll
            for (int q = 0; q < 8; q++) {
                sts32(sb + SM_RA + (20 % NA) * SLOT + q * 2048 + row * 16 + c * 4, x1[2 * q]);
                sts32(sb + SM_RA + (20 % NA) * SLOT + q * 2048 + row * 16 + c * 4 + 128, x1[2 * q + 1]);
            }
            fence_async_smem();
            bar_sync(3 + wg, 128);
#pragma unroll
            for (int q = 0; q < 5; q++) {
                const uint32_t ms = q < 4 ? ms0 : ms1;
                const uint32_t g0 = lds32(ms + 6400 + q * 32), g1 = lds32(ms + 6400 + q * 32 + 16);
                sts128(park + q * 4096, make_uint4(bfma2(g0, x1[4 * q], x2[4 * q]), bfma2(g0, x1[4 * q + 1], x2[4 * q + 1]),
                                                   bfma2(g1, x1[4 * q + 2], x2[4 * q + 2]), bfma2(g1, x1[4 * q + 3], x2[4 * q + 3])));
            }
        }
        gemm3<1>(sb, rb, j, half, row, c, ones);
    }
}

typedef CUresult (*EncFn)(CUtensorMap*, CUtensorMapDataType, cuuint32_t, void*, const cuuint64_t*, const cuuint64_t*,
                          const cuuint32_t*, const cuuint32_t*, CUtensorMapInterleave, CUtensorMapSwizzle,
                          CUtensorMapL2promotion, CUtensorMapFloatOOBfill);

void make_map(EncFn enc, CUtensorMap* m, const void* base, uint64_t inner, uint64_t outer, uint32_t bi, uint32_t bo,
              CUtensorMapSwizzle swz = CU_TENSOR_MAP_SWIZZLE_128B) {
    cuuint64_t dims[2] = {inner, outer};
    cuuint64_t st[1] = {inner * 2};
    cuuint32_t box[2] = {bi, bo};
    cuuint32_t es[2] = {1, 1};
    enc(m, CU_TENSOR_MAP_DATA_TYPE_BFLOAT16, 2, const_cast<void*>(base), dims, st, box, es, CU_TENSOR_MAP_INTERLEAVE_NONE,
        swz, CU_TENSOR_MAP_L2_PROMOTION_NONE, CU_TENSOR_MAP_FLOAT_OOB_FILL_NONE);
}

}

extern "C" void kernel_launch(void* const* d_in, const int* in_sizes, int n_in, void* d_out, int out_size) {
    (void)in_sizes; (void)n_in; (void)out_size;
    Params p;
    p.q = (const bf16*)d_in[0]; p.k = (const bf16*)d_in[1]; p.v = (const bf16*)d_in[2];
    p.shift = (const bf16*)d_in[3]; p.ssmk = (const bf16*)d_in[4]; p.ssmD = (const bf16*)d_in[5];
    p.w1 = (const bf16*)d_in[7]; p.w2 = (const bf16*)d_in[8]; p.w3 = (const bf16*)d_in[9]; p.w4 = (const bf16*)d_in[10];
    p.c = (const bf16*)d_in[11]; p.wmod = (const bf16*)d_in[12];
    p.out = (bf16*)d_out;
    p.ones = 0xffffffffu;

    void* fn = nullptr;
    cudaDriverEntryPointQueryResult qr;
    cudaGetDriverEntryPoint("cuTensorMapEncodeTiled", &fn, cudaEnableDefault, &qr);
    EncFn enc = (EncFn)fn;
    void* hn = nullptr;
    cudaGetSymbolAddress(&hn, g_hn);
    Maps maps;
    make_map(enc, &maps.w3s, p.w3, F_, D_, 216, 64, CU_TENSOR_MAP_SWIZZLE_NONE);
    make_map(enc, &maps.wm, p.wmod, 6 * D_, D_, 32, 128, CU_TENSOR_MAP_SWIZZLE_64B);
    make_map(enc, &maps.xa, p.q, D_, S_, 64, 128);
    make_map(enc, &maps.xb, p.q, D_, S_, 16, 128, CU_TENSOR_MAP_SWIZZLE_NONE);
    make_map(enc, &maps.hn, hn, D_, S_, 64, 128);
    make_map(enc, &maps.w1a, p.w1, D_, D_, 64, 64);
    make_map(enc, &maps.w1b, p.w1, D_, D_, 16, 64);
    make_map(enc, &maps.w2a, p.w2, D_, D_, 64, 64);
    make_map(enc, &maps.w2b, p.w2, D_, D_, 16, 64);
    make_map(enc, &maps.w3a, p.w3, F_, D_, 64, 64);
    make_map(enc, &maps.w3b, p.w3, F_, D_, RA3, 64);
    make_map(enc, &maps.w3c, p.w3, F_, D_, RB3, 64);
    make_map(enc, &maps.w4a, p.w4, D_, F_, 64, 64);
    make_map(enc, &maps.w4b, p.w4, D_, F_, 16, 64);
    cudaFuncSetAttribute(fused_kernel, cudaFuncAttributeMaxDynamicSharedMemorySize, SMEM_BYTES);
    fused_kernel<<<132, NTHREADS, SMEM_BYTES>>>(p, maps);
}
```

```cpp
#include <cuda_runtime.h>
#include <cuda_bf16.h>
#include <cuda.h>
#include <stdint.h>
#include <string.h>

#define SEED 2
#define RING_A 6
#define CH 2
#define FAST_LN 2
#define STAG 12
#define PGELU 2
#define CH3 4
#define HO_A 16
#define HO_B 16
#define RA3 48
#define CSP 16
#define OWNG 1
#define GATE 5
#define SSM_DELAY 0
#define B_DELAY 300
#define RPRE_WAIT 1
#define WARM 14
#define PING 250
#define NPING 5
#define W1D 1500
#define SSM_N 3

namespace {

typedef __nv_bfloat16 bf16;
typedef __nv_bfloat162 bf162;

constexpr int S_ = 2048, D_ = 640, F_ = 1728;
constexpr int NTHREADS = 640;
constexpr int NA = RING_A, NB = 12 - RING_A;
constexpr int SLOT = 16384;
constexpr int RB3 = 88 - RA3, HB0 = 512 + 8 * RA3;
constexpr int SM_RA = 0, SM_RB = NA * SLOT;

static_assert(NA == 6, "smem map");
constexpr int RED_STRIDE = 17536;
constexpr int K_STRIDE = 8320;
constexpr int U_PLANE = 2560, U_STRIDE = 5120;
constexpr int SM_Y = 12 * SLOT;
__device__ __forceinline__ int sm_red(int cc) { return cc * RED_STRIDE + (cc < 3 ? SM_RB : -3 * RED_STRIDE); }
__device__ __forceinline__ int sm_k(int cc) { return cc * K_STRIDE + (cc < 3 ? SM_RB + 3 * RED_STRIDE : 2 * RED_STRIDE - 3 * K_STRIDE); }
__device__ __forceinline__ int sm_u(int cc) { return cc * U_STRIDE + (cc < 3 ? SM_RB + 3 * RED_STRIDE + 3 * K_STRIDE : SM_Y + 8192 - 3 * U_STRIDE); }
constexpr int SM_PK = SM_RB;
constexpr int SM_PV = SM_RB + 24576;
constexpr int SM_WM = 57344;
constexpr int SM_XT = SM_WM, SM_XT2 = SM_WM + 16384, SM_XR = SM_WM + 20480;
constexpr int SM_YT = 0;
constexpr int SM_MOD = SM_Y + 20480;
constexpr int SM_GV = SM_MOD + 7680;
constexpr int SM_CS = SM_GV + 1024;
constexpr int SM_RP = SM_CS + 1024;
constexpr int SM_BAR = SM_RP + 1024;
constexpr int SM_PROF = SM_BAR + 512;
constexpr int SM_TOTAL = SM_PROF + 512;
constexpr int SMEM_BYTES = SM_TOTAL + 1024;
static_assert(SMEM_BYTES <= 232448, "smem");

constexpr int BAR_FA = 0, BAR_FB = NA, BAR_EA = 12, BAR_EB = 12 + NA, BAR_K = 24, BAR_U = 29, BAR_Y = 34, BAR_CS = 35, BAR_WM = 36, BAR_M = 37, BAR_XY = 38, BAR_Y2 = 39, BAR_G = 40, BAR_ST = 44, BAR_XR = 45, BAR_ME = 46, NBARS = 47;

__device__ __align__(1024) bf16 g_kvT[D_ * S_];
__device__ __align__(1024) uint32_t g_yv[128 * 5120];
__device__ __align__(1024) bf16 g_mod[6 * D_];
__device__ __align__(1024) bf16 g_hn[S_ * D_];
__device__ __align__(1024) uint4 g_rs[S_ * 2];
__device__ __align__(1024) bf16 g_h1[S_ * D_];
__device__ __align__(1024) bf16 g_x1[S_ * D_];
__device__ __align__(1024) bf16 g_g[S_ * F_];
__device__ __align__(1024) float2 g_st[S_ * 8];
__device__ __align__(1024) float g_cs[F_];
__device__ __align__(1024) unsigned g_flags[128 * 32];
__device__ __align__(1024) unsigned g_epoch[160];
constexpr int FL_P = 0, FL_C = 8, FL_CS = 9, FL_M = 10, FL_R = 16, FL_B1 = 32, FL_B2 = 48, FL_G = 64;

#define TS(i) do {} while (0)
#define TSW(i) do {} while (0)
#define TSD(i, dep) do {} while (0)
#define TSD2(i, dep) do {} while (0)
#define TSFLUSH() do {} while (0)

struct Params {
    const bf16 *q, *k, *v, *shift, *ssmk, *ssmD, *w1, *w2, *w3, *w4, *c, *wmod;
    bf16* out;
    unsigned ones;
};
#define CHUNK(k) if (ones & (1u << (k)))
struct Maps { CUtensorMap hn, w1a, w1b, w2a, w2b, w3a, w3b, w3c, w4a, w4b, wm, xa, xb, w3s; };

template<int N> struct WgRs;
template<int N> struct WgSs;
template<> struct WgRs<32> { template<int OFF,int HI,int SC> static __device__ __forceinline__ void run(float* d,uint32_t a0,uint32_t a1,uint32_t a2,uint32_t a3,uint32_t blo){
 asm volatile("{.reg .b32 l; .reg .b64 db; add.u32 l,%20,%21; mov.b64 db,{l,%22}; wgmma.mma_async.sync.aligned.m64n32k16.f32.bf16.bf16 {%0,%1,%2,%3,%4,%5,%6,%7,%8,%9,%10,%11,%12,%13,%14,%15},{%16,%17,%18,%19},db,%23,1,1,0;}"
 :"+f"(d[0]),"+f"(d[1]),"+f"(d[2]),"+f"(d[3]),"+f"(d[4]),"+f"(d[5]),"+f"(d[6]),"+f"(d[7]),"+f"(d[8]),"+f"(d[9]),"+f"(d[10]),"+f"(d[11]),"+f"(d[12]),"+f"(d[13]),"+f"(d[14]),"+f"(d[15])
 :"r"(a0),"r"(a1),"r"(a2),"r"(a3),"r"(blo),"n"(OFF),"n"(HI),"n"(SC)); } };
template<> struct WgRs<48> { template<int OFF,int HI,int SC> static __device__ __forceinline__ void run(float* d,uint32_t a0,uint32_t a1,uint32_t a2,uint32_t a3,uint32_t blo){
 asm volatile("{.reg .b32 l; .reg .b64 db; add.u32 l,%28,%29; mov.b64 db,{l,%30}; wgmma.mma_async.sync.aligned.m64n48k16.f32.bf16.bf16 {%0,%1,%2,%3,%4,%5,%6,%7,%8,%9,%10,%11,%12,%13,%14,%15,%16,%17,%18,%19,%20,%21,%22,%23},{%24,%25,%26,%27},db,%31,1,1,0;}"
 :"+f"(d[0]),"+f"(d[1]),"+f"(d[2]),"+f"(d[3]),"+f"(d[4]),"+f"(d[5]),"+f"(d[6]),"+f"(d[7]),"+f"(d[8]),"+f"(d[9]),"+f"(d[10]),"+f"(d[11]),"+f"(d[12]),"+f"(d[13]),"+f"(d[14]),"+f"(d[15]),"+f"(d[16]),"+f"(d[17]),"+f"(d[18]),"+f"(d[19]),"+f"(d[20]),"+f"(d[21]),"+f"(d[22]),"+f"(d[23])
 :"r"(a0),"r"(a1),"r"(a2),"r"(a3),"r"(blo),"n"(OFF),"n"(HI),"n"(SC)); } };
template<> struct WgRs<64> { template<int OFF,int HI,int SC> static __device__ __forceinline__ void run(float* d,uint32_t a0,uint32_t a1,uint32_t a2,uint32_t a3,uint32_t blo){
 asm volatile("{.reg .b32 l; .reg .b64 db; add.u32 l,%36,%37; mov.b64 db,{l,%38}; wgmma.mma_async.sync.aligned.m64n64k16.f32.bf16.bf16 {%0,%1,%2,%3,%4,%5,%6,%7,%8,%9,%10,%11,%12,%13,%14,%15,%16,%17,%18,%19,%20,%21,%22,%23,%24,%25,%26,%27,%28,%29,%30,%31},{%32,%33,%34,%35},db,%39,1,1,0;}"
 :"+f"(d[0]),"+f"(d[1]),"+f"(d[2]),"+f"(d[3]),"+f"(d[4]),"+f"(d[5]),"+f"(d[6]),"+f"(d[7]),"+f"(d[8]),"+f"(d[9]),"+f"(d[10]),"+f"(d[11]),"+f"(d[12]),"+f"(d[13]),"+f"(d[14]),"+f"(d[15]),"+f"(d[16]),"+f"(d[17]),"+f"(d[18]),"+f"(d[19]),"+f"(d[20]),"+f"(d[21]),"+f"(d[22]),"+f"(d[23]),"+f"(d[24]),"+f"(d[25]),"+f"(d[26]),"+f"(d[27]),"+f"(d[28]),"+f"(d[29]),"+f"(d[30]),"+f"(d[31])
 :"r"(a0),"r"(a1),"r"(a2),"r"(a3),"r"(blo),"n"(OFF),"n"(HI),"n"(SC)); } };
template<> struct WgRs<80> { template<int OFF,int HI,int SC> static __device__ __forceinline__ void run(float* d,uint32_t a0,uint32_t a1,uint32_t a2,uint32_t a3,uint32_t blo){
 asm volatile("{.reg .b32 l; .reg .b64 db; add.u32 l,%44,%45; mov.b64 db,{l,%46}; wgmma.mma_async.sync.aligned.m64n80k16.f32.bf16.bf16 {%0,%1,%2,%3,%4,%5,%6,%7,%8,%9,%10,%11,%12,%13,%14,%15,%16,%17,%18,%19,%20,%21,%22,%23,%24,%25,%26,%27,%28,%29,%30,%31,%32,%33,%34,%35,%36,%37,%38,%39},{%40,%41,%42,%43},db,%47,1,1,0;}"
 :"+f"(d[0]),"+f"(d[1]),"+f"(d[2]),"+f"(d[3]),"+f"(d[4]),"+f"(d[5]),"+f"(d[6]),"+f"(d[7]),"+f"(d[8]),"+f"(d[9]),"+f"(d[10]),"+f"(d[11]),"+f"(d[12]),"+f"(d[13]),"+f"(d[14]),"+f"(d[15]),"+f"(d[16]),"+f"(d[17]),"+f"(d[18]),"+f"(d[19]),"+f"(d[20]),"+f"(d[21]),"+f"(d[22]),"+f"(d[23]),"+f"(d[24]),"+f"(d[25]),"+f"(d[26]),"+f"(d[27]),"+f"(d[28]),"+f"(d[29]),"+f"(d[30]),"+f"(d[31]),"+f"(d[32]),"+f"(d[33]),"+f"(d[34]),"+f"(d[35]),"+f"(d[36]),"+f"(d[37]),"+f"(d[38]),"+f"(d[39])
 :"r"(a0),"r"(a1),"r"(a2),"r"(a3),"r"(blo),"n"(OFF),"n"(HI),"n"(SC)); } };
template<> struct WgRs<96> { template<int OFF,int HI,int SC> static __device__ __forceinline__ void run(float* d,uint32_t a0,uint32_t a1,uint32_t a2,uint32_t a3,uint32_t blo){
 asm volatile("{.reg .b32 l; .reg .b64 db; add.u32 l,%52,%53; mov.b64 db,{l,%54}; wgmma.mma_async.sync.aligned.m64n96k16.f32.bf16.bf16 {%0,%1,%2,%3,%4,%5,%6,%7,%8,%9,%10,%11,%12,%13,%14,%15,%16,%17,%18,%19,%20,%21,%22,%23,%24,%25,%26,%27,%28,%29,%30,%31,%32,%33,%34,%35,%36,%37,%38,%39,%40,%41,%42,%43,%44,%45,%46,%47},{%48,%49,%50,%51},db,%55,1,1,0;}"
 :"+f"(d[0]),"+f"(d[1]),"+f"(d[2]),"+f"(d[3]),"+f"(d[4]),"+f"(d[5]),"+f"(d[6]),"+f"(d[7]),"+f"(d[8]),"+f"(d[9]),"+f"(d[10]),"+f"(d[11]),"+f"(d[12]),"+f"(d[13]),"+f"(d[14]),"+f"(d[15]),"+f"(d[16]),"+f"(d[17]),"+f"(d[18]),"+f"(d[19]),"+f"(d[20]),"+f"(d[21]),"+f"(d[22]),"+f"(d[23]),"+f"(d[24]),"+f"(d[25]),"+f"(d[26]),"+f"(d[27]),"+f"(d[28]),"+f"(d[29]),"+f"(d[30]),"+f"(d[31]),"+f"(d[32]),"+f"(d[33]),"+f"(d[34]),"+f"(d[35]),"+f"(d[36]),"+f"(d[37]),"+f"(d[38]),"+f"(d[39]),"+f"(d[40]),"+f"(d[41]),"+f"(d[42]),"+f"(d[43]),"+f"(d[44]),"+f"(d[45]),"+f"(d[46]),"+f"(d[47])
 :"r"(a0),"r"(a1),"r"(a2),"r"(a3),"r"(blo),"n"(OFF),"n"(HI),"n"(SC)); } };
template<> struct WgRs<112> { template<int OFF,int HI,int SC> static __device__ __forceinline__ void run(float* d,uint32_t a0,uint32_t a1,uint32_t a2,uint32_t a3,uint32_t blo){
 asm volatile("{.reg .b32 l; .reg .b64 db; add.u32 l,%60,%61; mov.b64 db,{l,%62}; wgmma.mma_async.sync.aligned.m64n112k16.f32.bf16.bf16 {%0,%1,%2,%3,%4,%5,%6,%7,%8,%9,%10,%11,%12,%13,%14,%15,%16,%17,%18,%19,%20,%21,%22,%23,%24,%25,%26,%27,%28,%29,%30,%31,%32,%33,%34,%35,%36,%37,%38,%39,%40,%41,%42,%43,%44,%45,%46,%47,%48,%49,%50,%51,%52,%53,%54,%55},{%56,%57,%58,%59},db,%63,1,1,0;}"
 :"+f"(d[0]),"+f"(d[1]),"+f"(d[2]),"+f"(d[3]),"+f"(d[4]),"+f"(d[5]),"+f"(d[6]),"+f"(d[7]),"+f"(d[8]),"+f"(d[9]),"+f"(d[10]),"+f"(d[11]),"+f"(d[12]),"+f"(d[13]),"+f"(d[14]),"+f"(d[15]),"+f"(d[16]),"+f"(d[17]),"+f"(d[18]),"+f"(d[19]),"+f"(d[20]),"+f"(d[21]),"+f"(d[22]),"+f"(d[23]),"+f"(d[24]),"+f"(d[25]),"+f"(d[26]),"+f"(d[27]),"+f"(d[28]),"+f"(d[29]),"+f"(d[30]),"+f"(d[31]),"+f"(d[32]),"+f"(d[33]),"+f"(d[34]),"+f"(d[35]),"+f"(d[36]),"+f"(d[37]),"+f"(d[38]),"+f"(d[39]),"+f"(d[40]),"+f"(d[41]),"+f"(d[42]),"+f"(d[43]),"+f"(d[44]),"+f"(d[45]),"+f"(d[46]),"+f"(d[47]),"+f"(d[48]),"+f"(d[49]),"+f"(d[50]),"+f"(d[51]),"+f"(d[52]),"+f"(d[53]),"+f"(d[54]),"+f"(d[55])
 :"r"(a0),"r"(a1),"r"(a2),"r"(a3),"r"(blo),"n"(OFF),"n"(HI),"n"(SC)); } };
template<> struct WgRs<128> { template<int OFF,int HI,int SC> static __device__ __forceinline__ void run(float* d,uint32_t a0,uint32_t a1,uint32_t a2,uint32_t a3,uint32_t blo){
 asm volatile("{.reg .b32 l; .reg .b64 db; add.u32 l,%68,%69; mov.b64 db,{l,%70}; wgmma.mma_async.sync.aligned.m64n128k16.f32.bf16.bf16 {%0,%1,%2,%3,%4,%5,%6,%7,%8,%9,%10,%11,%12,%13,%14,%15,%16,%17,%18,%19,%20,%21,%22,%23,%24,%25,%26,%27,%28,%29,%30,%31,%32,%33,%34,%35,%36,%37,%38,%39,%40,%41,%42,%43,%44,%45,%46,%47,%48,%49,%50,%51,%52,%53,%54,%55,%56,%57,%58,%59,%60,%61,%62,%63},{%64,%65,%66,%67},db,%71,1,1,0;}"
 :"+f"(d[0]),"+f"(d[1]),"+f"(d[2]),"+f"(d[3]),"+f"(d[4]),"+f"(d[5]),"+f"(d[6]),"+f"(d[7]),"+f"(d[8]),"+f"(d[9]),"+f"(d[10]),"+f"(d[11]),"+f"(d[12]),"+f"(d[13]),"+f"(d[14]),"+f"(d[15]),"+f"(d[16]),"+f"(d[17]),"+f"(d[18]),"+f"(d[19]),"+f"(d[20]),"+f"(d[21]),"+f"(d[22]),"+f"(d[23]),"+f"(d[24]),"+f"(d[25]),"+f"(d[26]),"+f"(d[27]),"+f"(d[28]),"+f"(d[29]),"+f"(d[30]),"+f"(d[31]),"+f"(d[32]),"+f"(d[33]),"+f"(d[34]),"+f"(d[35]),"+f"(d[36]),"+f"(d[37]),"+f"(d[38]),"+f"(d[39]),"+f"(d[40]),"+f"(d[41]),"+f"(d[42]),"+f"(d[43]),"+f"(d[44]),"+f"(d[45]),"+f"(d[46]),"+f"(d[47]),"+f"(d[48]),"+f"(d[49]),"+f"(d[50]),"+f"(d[51]),"+f"(d[52]),"+f"(d[53]),"+f"(d[54]),"+f"(d[55]),"+f"(d[56]),"+f"(d[57]),"+f"(d[58]),"+f"(d[59]),"+f"(d[60]),"+f"(d[61]),"+f"(d[62]),"+f"(d[63])
 :"r"(a0),"r"(a1),"r"(a2),"r"(a3),"r"(blo),"n"(OFF),"n"(HI),"n"(SC)); } };
template<> struct WgSs<80> { template<int AOFF,int AHI,int BOFF,int BHI,int SC> static __device__ __forceinline__ void run(float* d,uint32_t alo,uint32_t blo){
 asm volatile("{.reg .b32 l,m; .reg .b64 da,db; add.u32 l,%40,%42; mov.b64 da,{l,%43}; add.u32 m,%41,%44; mov.b64 db,{m,%45}; wgmma.mma_async.sync.aligned.m64n80k16.f32.bf16.bf16 {%0,%1,%2,%3,%4,%5,%6,%7,%8,%9,%10,%11,%12,%13,%14,%15,%16,%17,%18,%19,%20,%21,%22,%23,%24,%25,%26,%27,%28,%29,%30,%31,%32,%33,%34,%35,%36,%37,%38,%39},da,db,%46,1,1,0,1;}"
 :"+f"(d[0]),"+f"(d[1]),"+f"(d[2]),"+f"(d[3]),"+f"(d[4]),"+f"(d[5]),"+f"(d[6]),"+f"(d[7]),"+f"(d[8]),"+f"(d[9]),"+f"(d[10]),"+f"(d[11]),"+f"(d[12]),"+f"(d[13]),"+f"(d[14]),"+f"(d[15]),"+f"(d[16]),"+f"(d[17]),"+f"(d[18]),"+f"(d[19]),"+f"(d[20]),"+f"(d[21]),"+f"(d[22]),"+f"(d[23]),"+f"(d[24]),"+f"(d[25]),"+f"(d[26]),"+f"(d[27]),"+f"(d[28]),"+f"(d[29]),"+f"(d[30]),"+f"(d[31]),"+f"(d[32]),"+f"(d[33]),"+f"(d[34]),"+f"(d[35]),"+f"(d[36]),"+f"(d[37]),"+f"(d[38]),"+f"(d[39])
 :"r"(alo),"r"(blo),"n"(AOFF),"n"(AHI),"n"(BOFF),"n"(BHI),"n"(SC)); } };
template<> struct WgSs<104> { template<int AOFF,int AHI,int BOFF,int BHI,int SC> static __device__ __forceinline__ void run(float* d,uint32_t alo,uint32_t blo){
 asm volatile("{.reg .b32 l,m; .reg .b64 da,db; add.u32 l,%52,%54; mov.b64 da,{l,%55}; add.u32 m,%53,%56; mov.b64 db,{m,%57}; wgmma.mma_async.sync.aligned.m64n104k16.f32.bf16.bf16 {%0,%1,%2,%3,%4,%5,%6,%7,%8,%9,%10,%11,%12,%13,%14,%15,%16,%17,%18,%19,%20,%21,%22,%23,%24,%25,%26,%27,%28,%29,%30,%31,%32,%33,%34,%35,%36,%37,%38,%39,%40,%41,%42,%43,%44,%45,%46,%47,%48,%49,%50,%51},da,db,%58,1,1,0,1;}"
 :"+f"(d[0]),"+f"(d[1]),"+f"(d[2]),"+f"(d[3]),"+f"(d[4]),"+f"(d[5]),"+f"(d[6]),"+f"(d[7]),"+f"(d[8]),"+f"(d[9]),"+f"(d[10]),"+f"(d[11]),"+f"(d[12]),"+f"(d[13]),"+f"(d[14]),"+f"(d[15]),"+f"(d[16]),"+f"(d[17]),"+f"(d[18]),"+f"(d[19]),"+f"(d[20]),"+f"(d[21]),"+f"(d[22]),"+f"(d[23]),"+f"(d[24]),"+f"(d[25]),"+f"(d[26]),"+f"(d[27]),"+f"(d[28]),"+f"(d[29]),"+f"(d[30]),"+f"(d[31]),"+f"(d[32]),"+f"(d[33]),"+f"(d[34]),"+f"(d[35]),"+f"(d[36]),"+f"(d[37]),"+f"(d[38]),"+f"(d[39]),"+f"(d[40]),"+f"(d[41]),"+f"(d[42]),"+f"(d[43]),"+f"(d[44]),"+f"(d[45]),"+f"(d[46]),"+f"(d[47]),"+f"(d[48]),"+f"(d[49]),"+f"(d[50]),"+f"(d[51])
 :"r"(alo),"r"(blo),"n"(AOFF),"n"(AHI),"n"(BOFF),"n"(BHI),"n"(SC)); } };
template<> struct WgSs<112> { template<int AOFF,int AHI,int BOFF,int BHI,int SC> static __device__ __forceinline__ void run(float* d,uint32_t alo,uint32_t blo){
 asm volatile("{.reg .b32 l,m; .reg .b64 da,db; add.u32 l,%56,%58; mov.b64 da,{l,%59}; add.u32 m,%57,%60; mov.b64 db,{m,%61}; wgmma.mma_async.sync.aligned.m64n112k16.f32.bf16.bf16 {%0,%1,%2,%3,%4,%5,%6,%7,%8,%9,%10,%11,%12,%13,%14,%15,%16,%17,%18,%19,%20,%21,%22,%23,%24,%25,%26,%27,%28,%29,%30,%31,%32,%33,%34,%35,%36,%37,%38,%39,%40,%41,%42,%43,%44,%45,%46,%47,%48,%49,%50,%51,%52,%53,%54,%55},da,db,%62,1,1,0,1;}"
 :"+f"(d[0]),"+f"(d[1]),"+f"(d[2]),"+f"(d[3]),"+f"(d[4]),"+f"(d[5]),"+f"(d[6]),"+f"(d[7]),"+f"(d[8]),"+f"(d[9]),"+f"(d[10]),"+f"(d[11]),"+f"(d[12]),"+f"(d[13]),"+f"(d[14]),"+f"(d[15]),"+f"(d[16]),"+f"(d[17]),"+f"(d[18]),"+f"(d[19]),"+f"(d[20]),"+f"(d[21]),"+f"(d[22]),"+f"(d[23]),"+f"(d[24]),"+f"(d[25]),"+f"(d[26]),"+f"(d[27]),"+f"(d[28]),"+f"(d[29]),"+f"(d[30]),"+f"(d[31]),"+f"(d[32]),"+f"(d[33]),"+f"(d[34]),"+f"(d[35]),"+f"(d[36]),"+f"(d[37]),"+f"(d[38]),"+f"(d[39]),"+f"(d[40]),"+f"(d[41]),"+f"(d[42]),"+f"(d[43]),"+f"(d[44]),"+f"(d[45]),"+f"(d[46]),"+f"(d[47]),"+f"(d[48]),"+f"(d[49]),"+f"(d[50]),"+f"(d[51]),"+f"(d[52]),"+f"(d[53]),"+f"(d[54]),"+f"(d[55])
 :"r"(alo),"r"(blo),"n"(AOFF),"n"(AHI),"n"(BOFF),"n"(BHI),"n"(SC)); } };

__device__ __forceinline__ void wg_fence() { asm volatile("wgmma.fence.sync.aligned;" ::: "memory"); }
__device__ __forceinline__ void wg_commit() { asm volatile("wgmma.commit_group.sync.aligned;" ::: "memory"); }
template <int N> __device__ __forceinline__ void wg_wait() { asm volatile("wgmma.wait_group.sync.aligned %0;" ::"n"(N) : "memory"); }
template <int N> __device__ __forceinline__ void reg_fence(float* d) {
#pragma unroll
    for (int i = 0; i < N; i++) asm volatile("" : "+f"(d[i])::"memory");
}
__device__ __forceinline__ uint32_t desc_lo(uint32_t addr, uint32_t lbo) { return ((addr & 0x3FFFF) >> 4) | ((lbo >> 4) << 16); }
#define desc_hi(sbo, sw) (((sbo) >> 4) | ((sw) << 30))
__device__ __forceinline__ uint32_t smem_u32(const void* p) { return (uint32_t)__cvta_generic_to_shared(p); }
__device__ __forceinline__ bool elect() {
    uint32_t p;
    asm volatile("{.reg .pred P; elect.sync _|P, 0xffffffff; selp.u32 %0,1,0,P;}" : "=r"(p));
    return p;
}
__device__ __forceinline__ void mbar_init(uint32_t bar, uint32_t cnt) { asm volatile("mbarrier.init.shared::cta.b64 [%0], %1;" ::"r"(bar), "r"(cnt) : "memory"); }
__device__ __forceinline__ void mbar_expect(uint32_t bar, uint32_t bytes) { asm volatile("mbarrier.arrive.expect_tx.shared::cta.b64 _, [%0], %1;" ::"r"(bar), "r"(bytes) : "memory"); }
__device__ __forceinline__ bool mbar_try(uint32_t bar, uint32_t par) {
    uint32_t ok;
    asm volatile("{.reg .pred p; mbarrier.try_wait.parity.shared::cta.b64 p, [%1], %2; selp.u32 %0,1,0,p;}" : "=r"(ok) : "r"(bar), "r"(par) : "memory");
    return ok;
}
constexpr int SPIN_LIMIT = 1 << 18;
__device__ __forceinline__ void mbar_wait(uint32_t bar, uint32_t par) {
    if (mbar_try(bar, par)) return;
    asm volatile("{.reg .pred p, q; .reg .b32 n; mov.u32 n, 0;\n"
                 "W%=: mbarrier.try_wait.parity.shared::cta.b64 p, [%0], %1; add.u32 n, n, 1; setp.lt.and.u32 q, n, %2, !p; @q bra W%=;}"
                 ::"r"(bar), "r"(par), "n"(SPIN_LIMIT) : "memory");
}
__device__ __forceinline__ void bulk_g2s(uint32_t dst, const void* src, uint32_t bytes, uint32_t bar) {
    asm volatile("cp.async.bulk.shared::cluster.global.mbarrier::complete_tx::bytes [%0], [%1], %2, [%3];" ::"r"(dst), "l"(src), "r"(bytes), "r"(bar) : "memory");
}
__device__ __forceinline__ void bulk_s2g(void* dst, uint32_t src, uint32_t bytes) {
    asm volatile("cp.async.bulk.global.shared::cta.bulk_group [%0], [%1], %2;" ::"l"(dst), "r"(src), "r"(bytes) : "memory");
}
__device__ __forceinline__ void bulk_prefetch(const void* src, uint32_t bytes) {
    asm volatile("cp.async.bulk.prefetch.L2.global [%0], %1;" ::"l"(src), "r"(bytes) : "memory");
}
__device__ __forceinline__ void tma2d(uint32_t dst, const CUtensorMap* m, int c0, int c1, uint32_t bar) {
    asm volatile("cp.async.bulk.tensor.2d.shared::cluster.global.mbarrier::complete_tx::bytes [%0], [%1, {%3, %4}], [%2];" ::"r"(dst), "l"(m), "r"(bar), "r"(c0), "r"(c1) : "memory");
}
__device__ __forceinline__ void tma2d_mc(uint32_t dst, const CUtensorMap* m, int c0, int c1, uint32_t bar) {
    asm volatile("cp.async.bulk.tensor.2d.shared::cluster.global.mbarrier::complete_tx::bytes.multicast::cluster [%0], [%1, {%3, %4}], [%2], %5;" ::"r"(dst), "l"(m), "r"(bar), "r"(c0), "r"(c1), "h"((uint16_t)3) : "memory");
}
__device__ __forceinline__ uint32_t mapa(uint32_t a, uint32_t rank) { uint32_t r; asm("mapa.shared::cluster.u32 %0, %1, %2;" : "=r"(r) : "r"(a), "r"(rank)); return r; }
__device__ __forceinline__ void mbar_arrive_cl(uint32_t bar) { asm volatile("mbarrier.arrive.shared::cluster.b64 _, [%0];" ::"r"(bar) : "memory"); }
__device__ __forceinline__ void prefetch_map(const CUtensorMap* m) { asm volatile("prefetch.tensormap [%0];" ::"l"(m) : "memory"); }
__device__ __forceinline__ void cpasync16(uint32_t dst, const void* src, uint32_t srcsz) {
    asm volatile("cp.async.cg.shared.global [%0], [%1], 16, %2;" ::"r"(dst), "l"(src), "r"(srcsz) : "memory");
}
__device__ __forceinline__ void bar_sync(int id, int n) { asm volatile("bar.sync %0, %1;" ::"r"(id), "r"(n) : "memory"); }
__device__ __forceinline__ void bar_arrive(int id, int n) { asm volatile("bar.arrive %0, %1;" ::"r"(id), "r"(n) : "memory"); }
__device__ __forceinline__ void fence_async_smem() { asm volatile("fence.proxy.async.shared::cta;" ::: "memory"); }
__device__ __forceinline__ void fence_async_global() { asm volatile("fence.proxy.async.global;" ::: "memory"); }
__device__ __forceinline__ void flag_release(int f) { asm volatile("red.release.gpu.global.add.u32 [%0], 1;" ::"l"(&g_flags[f * 32]) : "memory"); }
__device__ __forceinline__ void flag_wait(int f, unsigned target) {
    const unsigned* p = &g_flags[f * 32];
    unsigned v; int n = 0;
    do {
        asm volatile("ld.relaxed.gpu.global.u32 %0, [%1];" : "=r"(v) : "l"(p) : "memory");
    } while ((int)(v - target) < 0 && ++n < SPIN_LIMIT);
    asm volatile("fence.acquire.gpu;" ::: "memory");
}
__device__ __forceinline__ unsigned ld_flag(const unsigned* p) { unsigned v; asm volatile("ld.relaxed.gpu.global.u32 %0, [%1];" : "=r"(v) : "l"(p) : "memory"); return v; }
__device__ __forceinline__ void spin(unsigned n) { unsigned t0, t1; asm volatile("mov.u32 %0, %%clock;" : "=r"(t0)); do { asm volatile("mov.u32 %0, %%clock;" : "=r"(t1)); } while (t1 - t0 < n); }
__device__ __forceinline__ int tensor_ping() {
    int r;
    asm volatile("{.reg .f32 a, b, c, d; mma.sync.aligned.m16n8k16.row.col.f32.bf16.bf16.f32 {a,b,c,d},{%1,%1,%1,%1},{%1,%1},{%2,%2,%2,%2}; mov.b32 %0, a;}" : "=r"(r) : "r"(0), "f"(0.f));
    return r;
}
__device__ __forceinline__ void mbar_wait_warm(uint32_t bar, uint32_t par) {
    for (int n = 0; n < SPIN_LIMIT; n++) {
        uint32_t ok;
        asm volatile("{.reg .pred p; mbarrier.test_wait.parity.shared::cta.b64 p, [%1], %2; selp.u32 %0,1,0,p;}" : "=r"(ok) : "r"(bar), "r"(par) : "memory");
        if (ok) break;
        n += tensor_ping();
        spin(PING);
    }
}
__device__ __forceinline__ void flag_wait2(int f0, int f1, unsigned target) {
    const unsigned *p = &g_flags[f0 * 32], *q = &g_flags[f1 * 32];
    unsigned v, w; int n = 0;
    do { v = ld_flag(p); w = ld_flag(q); } while ((int)((v - target) | (w - target)) < 0 && ++n < SPIN_LIMIT);
    asm volatile("fence.acquire.gpu;" ::: "memory");
}
__device__ __forceinline__ uint32_t lds32(uint32_t a) { uint32_t v; asm volatile("ld.shared.u32 %0, [%1];" : "=r"(v) : "r"(a)); return v; }
__device__ __forceinline__ float2 lds64f(uint32_t a) { float2 v; asm volatile("ld.shared.v2.f32 {%0,%1}, [%2];" : "=f"(v.x), "=f"(v.y) : "r"(a)); return v; }
__device__ __forceinline__ uint2 lds64(uint32_t a) { uint2 v; asm volatile("ld.shared.v2.u32 {%0,%1}, [%2];" : "=r"(v.x), "=r"(v.y) : "r"(a)); return v; }
__device__ __forceinline__ void sts64f(uint32_t a, float2 v) { asm volatile("st.shared.v2.f32 [%0], {%1,%2};" ::"r"(a), "f"(v.x), "f"(v.y) : "memory"); }
__device__ __forceinline__ void sts32(uint32_t a, uint32_t v) { asm volatile("st.shared.u32 [%0], %1;" ::"r"(a), "r"(v) : "memory"); }
__device__ __forceinline__ void sts64(uint32_t a, uint32_t x, uint32_t y) { asm volatile("st.shared.v2.u32 [%0], {%1,%2};" ::"r"(a), "r"(x), "r"(y) : "memory"); }
__device__ __forceinline__ void sts16(uint32_t a, uint16_t v) { asm volatile("st.shared.u16 [%0], %1;" ::"r"(a), "h"(v) : "memory"); }
__device__ __forceinline__ uint4 lds128(uint32_t a) { uint4 v; asm volatile("ld.shared.v4.u32 {%0,%1,%2,%3}, [%4];" : "=r"(v.x), "=r"(v.y), "=r"(v.z), "=r"(v.w) : "r"(a)); return v; }
__device__ __forceinline__ void sts128(uint32_t a, uint4 v) { asm volatile("st.shared.v4.u32 [%0], {%1,%2,%3,%4};" ::"r"(a), "r"(v.x), "r"(v.y), "r"(v.z), "r"(v.w) : "memory"); }
__device__ __forceinline__ void sts128f(uint32_t a, float x, float y, float z, float w) { asm volatile("st.shared.v4.f32 [%0], {%1,%2,%3,%4};" ::"r"(a), "f"(x), "f"(y), "f"(z), "f"(w) : "memory"); }
__device__ __forceinline__ uint32_t prmt(uint32_t a, uint32_t b, uint32_t s) { uint32_t r; asm("prmt.b32 %0,%1,%2,%3;" : "=r"(r) : "r"(a), "r"(b), "r"(s)); return r; }
__device__ __forceinline__ uint32_t pack2(float lo, float hi) { uint32_t r; asm("cvt.rn.bf16x2.f32 %0, %1, %2;" : "=r"(r) : "f"(hi), "f"(lo)); return r; }
__device__ __forceinline__ float blo(uint32_t v) { return __uint_as_float(v << 16); }
__device__ __forceinline__ float bhi(uint32_t v) { return __uint_as_float(v & 0xffff0000u); }
__device__ __forceinline__ uint32_t bmul2(uint32_t a, uint32_t b) { uint32_t r; asm("mul.rn.bf16x2 %0,%1,%2;" : "=r"(r) : "r"(a), "r"(b)); return r; }
__device__ __forceinline__ uint32_t badd2(uint32_t a, uint32_t b) { uint32_t r; asm("add.rn.bf16x2 %0,%1,%2;" : "=r"(r) : "r"(a), "r"(b)); return r; }
__device__ __forceinline__ float rbf(float x) { return __bfloat162float(__float2bfloat16_rn(x)); }
__device__ __forceinline__ uint32_t ldcg32(const void* p) { uint32_t v; asm volatile("ld.global.cg.u32 %0, [%1];" : "=r"(v) : "l"(p) : "memory"); return v; }
__device__ __forceinline__ uint4 ldcg128(const void* p) { uint4 v; asm volatile("ld.global.cg.v4.u32 {%0,%1,%2,%3}, [%4];" : "=r"(v.x), "=r"(v.y), "=r"(v.z), "=r"(v.w) : "l"(p) : "memory"); return v; }
__device__ __forceinline__ void stg32_if(void* p, uint32_t v, int on) { asm volatile("{.reg .pred q; setp.ne.b32 q, %2, 0; @q st.global.u32 [%0], %1;}" ::"l"(p), "r"(v), "r"(on) : "memory"); }
__device__ __forceinline__ uint2 ldcg64(const void* p) { uint2 v; asm volatile("ld.global.cg.v2.u32 {%0,%1}, [%2];" : "=r"(v.x), "=r"(v.y) : "l"(p) : "memory"); return v; }
__device__ __forceinline__ float gelu_h(float h) {
    float u = h * fmaf(h * h, 8.0f * 0.044715f * 0.7978845608028654f, 2.0f * 0.7978845608028654f);
    float th;
    asm("tanh.approx.f32 %0, %1;" : "=f"(th) : "f"(u));
    return fmaf(h, th, h);
}
__device__ __forceinline__ float gelu(float x) { return gelu_h(0.5f * x); }
__device__ __forceinline__ float half_rstd(float sum, float sq) {
    float mean = sum * (1.0f / D_), inv;
    asm("rsqrt.approx.ftz.f32 %0, %1;" : "=f"(inv) : "f"(fmaxf(fmaf(-mean, mean, fmaf(sq, 1.0f / D_, 1e-5f)), 1e-5f)));
    return 0.5f * inv;
}
__device__ __forceinline__ uint32_t bsub2(uint32_t a, uint32_t b) { uint32_t r; asm("sub.rn.bf16x2 %0,%1,%2;" : "=r"(r) : "r"(a), "r"(b)); return r; }
__device__ __forceinline__ uint32_t bfma2(uint32_t a, uint32_t b, uint32_t c) { uint32_t r; asm("fma.rn.bf16x2 %0,%1,%2,%3;" : "=r"(r) : "r"(a), "r"(b), "r"(c)); return r; }
__device__ __forceinline__ uint32_t gelu2_h(uint32_t h) {
    uint32_t u = bmul2(h, bfma2(bmul2(h, h), 0x3e923e92u, 0x3fcc3fccu)), th;
    asm("tanh.approx.bf16x2 %0, %1;" : "=r"(th) : "r"(u));
    return bfma2(h, th, h);
}
__device__ __forceinline__ uint3 row_stats(const uint32_t* v, int lane) {
    float s = 0.f, q = 0.f, s_ = 0.f, q_ = 0.f;
#pragma unroll
    for (int i = 0; i < 10; i++) { float a = blo(v[i]), b = bhi(v[i]); s += a; s_ += b; q = fmaf(a, a, q); q_ = fmaf(b, b, q_); }
    s += s_; q += q_;
    {
        float t = __shfl_xor_sync(0xffffffffu, (lane & 16) ? s : q, 16);
        t += (lane & 16) ? q : s;
#pragma unroll
        for (int m = 8; m; m >>= 1) t += __shfl_xor_sync(0xffffffffu, t, m);
        float o = __shfl_xor_sync(0xffffffffu, t, 16);
        s = (lane & 16) ? o : t; q = (lane & 16) ? t : o;
    }
    float mean = s * (1.0f / D_), inv;
    asm("rsqrt.approx.ftz.f32 %0, %1;" : "=f"(inv) : "f"(fmaxf(fmaf(-mean, mean, fmaf(q, 1.0f / D_, 1e-5f)), 1e-5f)));
    uint3 r;
    r.x = pack2(mean, mean);
    r.y = pack2(inv, inv);
    inv -= blo(r.y);
    r.z = pack2(inv, inv);
    return r;
}
__device__ __forceinline__ uint32_t ln_apply(uint32_t x, uint32_t m, uint32_t hi, uint32_t lo) {
    uint32_t xc = bsub2(x, m);
    return bmul2(xc, hi);
}

struct AFrag { uint32_t m, a, b, c, d; };
__device__ __forceinline__ AFrag ldA(uint32_t a) { AFrag f; f.m = lds32(a - 16); f.a = lds32(a); f.b = lds32(a + 16); f.c = lds32(a + 32); f.d = lds32(a + 48); return f; }
template <int N, int M> __device__ __forceinline__ void conv_pair(float* d, const AFrag& f, uint32_t descU) {
    WgRs<N>::template run<8 * M, desc_hi(128, 0), M ? 1 : 0>(d, f.a, f.b, f.m, f.a, descU);
    WgRs<N>::template run<8 * M + 1, desc_hi(128, 0), 1>(d, f.c, f.d, f.b, f.c, descU);
}
template <int Q> __device__ __forceinline__ void conv_put(float* d, uint32_t r0) {
    sts64(r0 + Q * 32, pack2(d[4 * Q + 1], d[4 * Q + 3]), pack2(d[4 * Q], d[4 * Q + 2]));
}
template <int M> __device__ __forceinline__ void conv_two(float* d, AFrag f0, AFrag f1, uint32_t kaddr, uint32_t descU, uint32_t r0, bool handoff) {
    constexpr int N = M < 14 ? 128 - 8 * M : 32;
    wg_fence();
    conv_pair<N, M>(d, f0, descU);
    wg_commit();
    if constexpr (M > 0) f1 = ldA(kaddr + 256 * (M + 1));
    wg_fence();
    conv_pair<N, M + 1>(d, f1, descU);
    wg_commit();
    if (STAG && M == STAG && handoff) bar_arrive(12, 256);
    if constexpr (M < 14) {
        if constexpr (M > 0) { conv_put<17 - M>(d, r0); conv_put<16 - M>(d, r0); }
        wg_wait<1>();
        f0 = ldA(kaddr + 256 * (M + 2));
        if constexpr (M < 12) wg_wait<0>();
        conv_two<M + 2>(d, f0, f1, kaddr, descU, r0, handoff);
    } else {
        wg_wait<0>();
        conv_put<3>(d, r0); conv_put<2>(d, r0); conv_put<1>(d, r0); conv_put<0>(d, r0);
    }
}
template <int N, bool ASWZ, int SC0>
__device__ __forceinline__ void gemm_issue(float* acc, uint32_t bars, int sa, int pa, int sw, int pw, uint32_t da0, uint32_t db0) {
    mbar_wait(bars + (BAR_FB + sw) * 8, pw);
    mbar_wait(bars + (BAR_FA + sa) * 8, pa);
    const uint32_t da = da0 + sa * (SLOT >> 4), db = db0 + sw * (SLOT >> 4);
    constexpr int AK = ASWZ ? 2 : 256, AH = ASWZ ? desc_hi(1024, 1) : desc_hi(128, 0), BH = desc_hi(1024, 1);
    wg_fence();
    WgSs<N>::template run<0, AH, 0, BH, SC0>(acc, da, db);
    WgSs<N>::template run<AK, AH, 128, BH, 1>(acc, da, db);
    WgSs<N>::template run<2 * AK, AH, 256, BH, 1>(acc, da, db);
    WgSs<N>::template run<3 * AK, AH, 384, BH, 1>(acc, da, db);
    wg_commit();
}
template <int N, bool ASWZ, int NKB, int RELB, bool ZERO>
__device__ __forceinline__ void gemm_loop(float* acc, uint32_t sb, int half, int ia0, int ib0, int rela, int wait_bar, int order_bar, int tsid) {
    int sa = ia0 % NA, pa = (ia0 / NA) & 1, sw = ib0 % NB, pw = (ib0 / NB) & 1;
    const uint32_t bars = sb + SM_BAR;
    const int t = threadIdx.x & 127;
    uint32_t ebar = mapa(bars + (t < 2 ? BAR_EB : BAR_EA) * 8, (t < 2 && lds32(sb + SM_GV + 516)) ? t : blockIdx.x & 1);
    const int nrel = t < 2 ? RELB : t == 2 ? rela : 0;
    const uint32_t da0 = ASWZ ? desc_lo(sb + SM_RA + half * 8192, 16) : desc_lo(sb + SM_RA + half * 1024, 2048), db0 = desc_lo(sb + SM_RB, 8192);
    asm volatile("" : "+r"(ebar));
    if (wait_bar) bar_sync(wait_bar, 512);
    gemm_issue<N, ASWZ, ZERO ? 0 : 1>(acc, bars, sa, pa, sw, pw, da0, db0);
    if ((threadIdx.x & 255) == 0) TS(tsid);
#pragma unroll 1
    for (int kb = 1; kb < NKB; kb++) {
        const int prev = t < 2 ? sw : sa;
        if (++sa == NA) { sa = 0; pa ^= 1; }
        if (++sw == NB) { sw = 0; pw ^= 1; }
        gemm_issue<N, ASWZ, 1>(acc, bars, sa, pa, sw, pw, da0, db0);
        if (order_bar && kb == NKB - 1) bar_arrive(order_bar, 512);
        wg_wait<1>();
        if (kb <= nrel) mbar_arrive_cl(ebar + prev * 8);
    }
    wg_wait<0>();
    if (nrel == NKB) mbar_arrive_cl(ebar + (t < 2 ? sw : sa) * 8);
    reg_fence<N / 2>(acc);
    if ((threadIdx.x & 255) == 0) TS(tsid + 1);
}

template <int PART>
__device__ __forceinline__ void gemm3(uint32_t sb, int rb, int j, int half, int row, int c, unsigned ones) {
    constexpr int N = 64 + (PART ? RB3 : RA3), NQ = N / 8;
    constexpr int HO = PART ? HO_B : HO_A;
    float acc[N / 2];
    float2 cr[NQ];
    if (PART) {
        gemm_loop<N, false, 1, 1, true>(acc, sb, half, 20, 20, 0, 0, 0, 50);
        bar_arrive(9, 512);
    }
    mbar_wait(sb + SM_BAR + BAR_CS * 8, 0);
    const uint32_t csa = sb + SM_CS + PART * (256 + 4 * RA3) + 8 * c;
#pragma unroll
    for (int q = 0; q < NQ; q++) if (q < CSP) cr[q] = lds64f(csa + 32 * q);
    uint4 rp;
    if (PART) {
        mbar_wait(sb + SM_BAR + BAR_G * 8, 0);
        const float2* sp = &g_st[(rb * 8 + 2 * c) * 128 + row];
        const uint2 s0 = ldcg64(sp), s1 = ldcg64(sp + 128), s2 = ldcg64(sp + 8), s3 = ldcg64(sp + 136);
        float a0 = __uint_as_float(s0.x) + __uint_as_float(s1.x), b0 = __uint_as_float(s0.y) + __uint_as_float(s1.y);
        float a1 = __uint_as_float(s2.x) + __uint_as_float(s3.x), b1 = __uint_as_float(s2.y) + __uint_as_float(s3.y);
#pragma unroll
        for (int m = 1; m <= 2; m <<= 1) {
            a0 += __shfl_xor_sync(0xffffffffu, a0, m); b0 += __shfl_xor_sync(0xffffffffu, b0, m);
            a1 += __shfl_xor_sync(0xffffffffu, a1, m); b1 += __shfl_xor_sync(0xffffffffu, b1, m);
        }
        const float inv0 = half_rstd(a0, b0), inv1 = half_rstd(a1, b1);
        rp = make_uint4(PGELU ? pack2(inv0, inv0) : __float_as_uint(inv0), __float_as_uint(a0 * (-1.0f / D_)),
                        PGELU ? pack2(inv1, inv1) : __float_as_uint(inv1), __float_as_uint(a1 * (-1.0f / D_)));
        if (c == 0) sts128(sb + SM_RP + ((threadIdx.x & 255) >> 2) * 16, rp);
        bar_arrive(13, 512);
    }
    gemm_loop<N, false, 10 - PART, 10 - PART, !PART>(acc, sb, half, 20 + (10 - NA) * PART, 21 + 10 * PART, PART ? 9 : 10 - NA, 9 + PART, HO < 0 ? 10 + PART : 0, 46 + 2 * PART);
    if ((WARM & 8) && (threadIdx.x & 255) == 0) mbar_expect(sb + SM_BAR + BAR_ME * 8, 0);
    if (!PART) {
        bar_sync(13, 512);
        rp = lds128(sb + SM_RP + ((threadIdx.x & 255) >> 2) * 16);
    }
    const float nb0 = __uint_as_float(rp.y), nb1 = __uint_as_float(rp.w);
    const uint32_t own = sb + SM_RA + ((39 - NA) % NA) * SLOT + row * 16 + c * 4;
    if (PART && OWNG) mbar_wait(sb + SM_BAR + (BAR_FA + (39 - NA) % NA) * 8, ((39 - NA) / NA) & 1);
    uint32_t* dst = reinterpret_cast<uint32_t*>(g_g) + (rb * 216 + HB0 / 8 * PART + 8 * j) * 512 + row * 4 + c;
    auto act = [&](int q, int r) {
        const float nb = r ? nb1 : nb0;
        const uint32_t inv = r ? rp.z : rp.x;
        const float t0 = fmaf(nb, cr[q].x, acc[4 * q + 2 * r]), t1 = fmaf(nb, cr[q].y, acc[4 * q + 2 * r + 1]);
        return gelu2_h(bmul2(pack2(t0, t1), inv));
    };
    uint32_t* dst1 = dst + (56 - (16 - NQ) * j) * 512;
#pragma unroll
    for (int k = 0; k < NQ; k += CH3) {
        if (k == HO) bar_arrive(10 + PART, 512);
        CHUNK(k) {
#pragma unroll
            for (int q = k; q < k + CH3 && q < NQ; q++) {
                if (q + CSP < NQ) cr[q + CSP] = lds64f(csa + 32 * (q + CSP));
                const uint32_t u = act(q, 0), v = act(q, 1);
                (q < 8 ? dst : dst1)[q * 512] = u;
                (q < 8 ? dst : dst1)[q * 512 + 32] = v;
                if (PART && OWNG && q < 8) { sts32(own + q * 2048, u); sts32(own + q * 2048 + 128, v); }
            }
            if (PART && OWNG && k < 8 && k + CH3 >= 8) fence_async_smem();
        }
    }
    bar_arrive(1 + PART, 288);
    if (HO >= NQ) bar_arrive(10 + PART, 512);
}

template <int NS, int BASE, int BF, int BE> struct Ring {
    uint32_t sb, st, ph;
    __device__ __forceinline__ uint32_t acquire(uint32_t bytes) {
        mbar_wait(sb + SM_BAR + BE * 8 + st * 8, ph);
        uint32_t fb = sb + SM_BAR + BF * 8 + st * 8;
        mbar_expect(fb, bytes);
        return fb;
    }
    __device__ __forceinline__ uint32_t slot() { return sb + BASE + st * SLOT; }
    __device__ __forceinline__ void next() { if (++st == NS) { st = 0; ph ^= 1; } }
    __device__ __forceinline__ void run2d(const CUtensorMap* m, int c1) {
#pragma unroll 1
        for (int c0 = 64; c0 < D_; c0 += 64) {
            uint32_t fb = acquire(SLOT);
            tma2d(slot(), m, c0, c1, fb);
            next();
        }
    }
    static __device__ __forceinline__ int korder(int i, int own) { return i == 0 ? own : i > own ? i : i - 1; }
    __device__ __forceinline__ void runw(bool paired, int rk, const CUtensorMap* ma, const CUtensorMap* mb, int ca, int cb, int i0, int i1, int own, uint32_t bytes, int gate_at, uint32_t gate) {
        if (paired) {
            const CUtensorMap* m = rk ? mb : ma;
            const int c0 = rk ? cb : ca;
#pragma unroll 1
            for (int i = i0; i < i1; i++) {
                const int c1 = korder(i, own) * 64;
                if (i == gate_at) mbar_wait(gate, 0);
                uint32_t fb = acquire(bytes);
                tma2d_mc(slot() + 8192 * rk, m, c0, c1, fb);
                next();
            }
        } else {
#pragma unroll 1
            for (int i = i0; i < i1; i++) {
                const int c1 = korder(i, own) * 64;
                uint32_t fb = acquire(bytes);
                tma2d(slot(), ma, ca, c1, fb);
                tma2d(slot() + 8192, mb, cb, c1, fb);
                next();
            }
        }
    }
    __device__ __forceinline__ void run1d(const char* src, int i0, int i1, int own) {
#pragma unroll 1
        for (int i = i0; i < i1; i++) {
            const char* s = src + korder(i, own) * SLOT;
            uint32_t fb = acquire(SLOT);
            bulk_g2s(slot(), s, SLOT, fb);
            next();
        }
    }
};

__global__ void __cluster_dims__(2, 1, 1) __launch_bounds__(NTHREADS, 1) fused_kernel(const Params p, const __grid_constant__ Maps maps) {
    extern __shared__ __align__(1024) unsigned char smem_raw[];
    const uint32_t sb = (smem_u32(smem_raw) + 1023u) & ~1023u;
#pragma unroll
    for (int i = 0; i < SEED; i++) asm volatile("{.reg .b32 t; mov.u32 t, %laneid;}");
    const uint32_t bars = sb + SM_BAR;
    const int tid = threadIdx.x, lane = tid & 31;
    unsigned smid;
    asm volatile("mov.u32 %0, %%smid;" : "=r"(smid));
    const bool spare = (smid >> 2) == 30;
    const int cta = smid < 120 ? smid : smid - 4;
    const int pg = cta >> 4, pi = cta & 15;
    const int hb = tid >= 320;
    if (!spare) {
        const unsigned t = tid - 320 * hb, r32 = t / 10u, cc = t - r32 * 10u, row = r32 + 64 * hb;
        const unsigned go = (unsigned)(pi * 128 * 1280 + pg * 160) + row * 1280u + cc * 16u;
        const uint32_t so = sb + (row >> 4) * 32u + row * 160u + cc * 16u;
        const char* kb = (const char*)p.k + go;
        const char* vb = (const char*)p.v + go;
        if (hb) {
            if (tid >= 640 - NBARS) {
                const int i = 639 - tid;
                mbar_init(bars + i * 8, (i >= BAR_EB && i < BAR_K) ? 4 : ((i >= BAR_EA && i < BAR_EB) || i == BAR_XY) ? 2 : 1);
                asm volatile("fence.mbarrier_init.release.cluster;" ::: "memory");
            }
            bar_arrive(14, 640);
            if (B_DELAY) spin(B_DELAY);
        }
        cpasync16(so + SM_PK + 2592, kb, 16);
        cpasync16(so + SM_PV, vb, 16);
        cpasync16(so + SM_PK + 3 * 2592, kb + 32 * 1280, 16);
        cpasync16(so + SM_PV + 2 * 2592, vb + 32 * 1280, 16);
        if (tid < 30) cpasync16(so + SM_PK + 13 * 160, pi ? kb - 3 * 1280 : kb, pi ? 16 : 0);
        asm volatile("cp.async.commit_group;" ::: "memory");
    }
    const int warp = __shfl_sync(0xffffffffu, tid >> 5, 0);
    const int wg = warp >> 2, wq = warp & 3;
    unsigned ep0 = 0;
    if (wg == 4 || spare) ep0 = *(volatile unsigned*)&g_epoch[smid];
#define ep1 (ep0 + 1)

    if (spare) {
        const int sp = smid & 3;
        if (tid == 32) { sts32(sb + SM_GV + 512, smid); asm volatile("fence.release.sync_restrict::shared::cta.cluster;" ::: "memory"); }
        asm volatile("barrier.cluster.arrive.relaxed.aligned;" ::: "memory");
        asm volatile("barrier.cluster.wait.aligned;" ::: "memory");
        if (tid == 0) {
            for (int i = 0; i < 4; i++) mbar_init(bars + i * 8, 1);
            asm volatile("fence.mbarrier_init.release.cluster;" ::: "memory");
        }
        if (warp == 0) { if (lane < 8) flag_wait(FL_P + lane, ep1 * 16); __syncwarp(); }
        __syncthreads();
        const int cq = tid % 54, rg = tid / 54;
        float a[8];
#pragma unroll
        for (int i = 0; i < 8; i++) a[i] = 0.f;
#pragma unroll 1
        for (int it = -4; it < 10; it++) {
            const uint32_t st = sb + (it & 3) * 55296, fb = bars + (it & 3) * 8;
            if (it >= 0) {
                mbar_wait(fb, (it >> 2) & 1);
                if (tid < 432) {
#pragma unroll 2
                    for (int i = 0; i < 8; i++) {
                        uint4 w = lds128(st + (cq >= 27 ? 27648 - 432 : 0) + (rg * 8 + i) * 432 + cq * 16);
                        a[0] += blo(w.x); a[1] += bhi(w.x); a[2] += blo(w.y); a[3] += bhi(w.y);
                        a[4] += blo(w.z); a[5] += bhi(w.z); a[6] += blo(w.w); a[7] += bhi(w.w);
                    }
                }
                __syncthreads();
            }
            if (it < 6 && warp == 19 && elect()) {
                mbar_expect(fb, 55296);
                tma2d(st, &maps.w3s, sp * 432, (it + 4) * 64, fb);
                tma2d(st + 27648, &maps.w3s, sp * 432 + 216, (it + 4) * 64, fb);
            }
        }
        if (warp == 19 && elect()) {
#pragma unroll 1
            for (int i = 0; i < 27; i++) bulk_prefetch((const char*)p.w4 + sp * 552960 + i * 20480, 20480);
        }
        if (tid < 432) {
            sts128f(sb + rg * 1728 + cq * 32, a[0], a[1], a[2], a[3]);
            sts128f(sb + rg * 1728 + cq * 32 + 16, a[4], a[5], a[6], a[7]);
        }
        __syncthreads();
        if (tid < 432) {
            float s = 0.f;
#pragma unroll
            for (int i = 0; i < 8; i++) s += __uint_as_float(lds32(sb + i * 1728 + tid * 4));
            g_cs[sp * 432 + tid] = s;
        }
        __syncthreads();
        if (tid == 0) { flag_release(FL_CS); g_epoch[smid] = ep1; TS(0); }
        if (warp == 0) TSFLUSH();
        return;
    }

    int gpc, idx;
    if (smid < 64) { gpc = (smid & 15) >> 1; idx = (smid >> 4) * 2 + (smid & 1); }
    else if (smid < 120) { int t = smid - 64; gpc = 1 + (t % 14) / 2; idx = 8 + (t / 14) * 2 + (smid & 1); }
    else { gpc = 0; idx = 8 + (smid - 124); }
    const int rb = 2 * gpc + (idx & 1), j = idx >> 1;
    const int g = lane >> 2, c = lane & 3;
    const int cm = 160 * (j >> 1) + 64 * (j & 1) + ((j & 2) ? 32 : 0), cr = 160 * (j >> 1) + 16 * (j & 1) + ((j & 2) ? 0 : 128);

    {
        if (warp == 5) TSW(61);
        const int w10 = warp - 10 * hb, h = w10 >= 5;
        const int pr = (w10 - 5 * h) * 8 + (lane >> 2), blk = 4 * hb + (lane & 3);
        const int ch = 80 * pg + 2 * pr;
        const uint4 sw = __ldg(reinterpret_cast<const uint4*>(p.shift + ch * 4));
        uint32_t dv = 0;
        if (warp == 9 && lane < 5) dv = __bfloat16_as_ushort(p.ssmD[cta * 5 + lane]);
        if (tid == 512) { sts32(sb + SM_GV + 512, smid); asm volatile("fence.release.sync_restrict::shared::cta.cluster;" ::: "memory"); }
        asm volatile("barrier.cluster.arrive.relaxed.aligned;" ::: "memory");
        if (warp == 11 && lane < 13) prefetch_map(&maps.hn + lane);
        if (wg < 4) {
            const int t = tid & 127, cc = (wg == 3 && t >= 64) ? 4 : wg;
            if (t < 64 || wg == 3) sts128(sb + sm_u(cc) + ((t >> 5) & 1) * U_PLANE + 2048 + lane * 16, make_uint4(0, 0, 0, 0));
            if ((t & 63) < 4 && (t < 64 || wg == 3)) sts128(sb + sm_k(cc) + ((t >> 1) & 1) * 4160 + (t & 1) * 16, make_uint4(0, 0, 0, 0));
        }
        if (warp == 9 && lane < 5) sts32(sb + SM_GV + 520 + lane * 4, dv << 16);
        asm volatile("cp.async.wait_group 0;" ::: "memory");
        if (!hb) bar_arrive(12, 640);
        bar_sync(hb ? 12 : 14, 640);
        if (warp == 9) {
            if (SSM_DELAY) spin(SSM_DELAY);
            if (elect()) {
#pragma unroll
                for (int i = 0; i < SSM_N; i++) {
                    mbar_expect(bars + (BAR_K + i) * 8, 4096);
                    bulk_g2s(sb + sm_k(i) + 32, p.ssmk + (size_t)(cta * 5 + i) * S_, 4096, bars + (BAR_K + i) * 8);
                }
            }
        }
        const uint32_t w0 = prmt(sw.x, sw.z, 0x5410), w1 = prmt(sw.x, sw.z, 0x7632), w2 = prmt(sw.y, sw.w, 0x5410), w3 = prmt(sw.y, sw.w, 0x7632);
        const uint32_t ka = sb + SM_PK + 2592 + blk * 2592 + h * 1280 + pr * 4;
        const uint32_t va = sb + SM_PV + blk * 2592 + h * 1280 + pr * 4;
        uint32_t kk[11], kv[8];
#pragma unroll
        for (int i = 0; i < 11; i++) kk[i] = lds32(ka + (i - 3) * 160 - ((i < 3 && h == 0) ? 32 : 0));
#pragma unroll
        for (int i = 0; i < 8; i++) {
            uint32_t t = badd2(badd2(badd2(bmul2(kk[i], w3), bmul2(kk[i + 1], w2)), bmul2(kk[i + 2], w1)), bmul2(kk[i + 3], w0));
            kv[i] = bmul2(t, lds32(va + i * 160));
        }
        uint4 o0, o1;
        o0.x = prmt(kv[1], kv[0], 0x5410); o0.y = prmt(kv[3], kv[2], 0x5410); o0.z = prmt(kv[5], kv[4], 0x5410); o0.w = prmt(kv[7], kv[6], 0x5410);
        o1.x = prmt(kv[1], kv[0], 0x7632); o1.y = prmt(kv[3], kv[2], 0x7632); o1.z = prmt(kv[5], kv[4], 0x7632); o1.w = prmt(kv[7], kv[6], 0x7632);
        uint4* dst = reinterpret_cast<uint4*>(g_kvT) + ch * 256 + h * 128 + (127 - (8 * pi + blk));
        dst[0] = o0;
        dst[256] = o1;
    }

    const int rho = 8 * rb + j;

    if (wg == 4) {
        asm volatile("setmaxnreg.dec.sync.aligned.u32 32;");
        if (wq == 0) {
            bar_sync(13, 640);
            TSW(39);
            if (lane == 0) flag_release(FL_P + pg);
            __syncwarp();
            TSW(2);
            if (lane < 5) mbar_expect(bars + (BAR_U + lane) * 8, 4096);
            flag_wait(FL_P + pg, ep1 * 16);
            fence_async_global();
            TSW(3);
            if (elect()) {
#pragma unroll
                for (int i = 0; i < 5; i++) {
                    const char* us = (const char*)g_kvT + (size_t)(cta * 5 + i) * 4096;
                    bulk_g2s(sb + sm_u(i), us, 2048, bars + (BAR_U + i) * 8);
                    bulk_g2s(sb + sm_u(i) + U_PLANE, us + 2048, 2048, bars + (BAR_U + i) * 8);
                }
            }
            __syncwarp();
            if (elect()) {
#pragma unroll
                for (int i = SSM_N; i < 5; i++) {
                    mbar_expect(bars + (BAR_K + i) * 8, 4096);
                    bulk_g2s(sb + sm_k(i) + 32, p.ssmk + (size_t)(cta * 5 + i) * S_, 4096, bars + (BAR_K + i) * 8);
                }
                if (cta < 120) {
                    mbar_expect(bars + BAR_WM * 8, 40960);
#pragma unroll 1
                    for (int i = 0; i < 5; i++) tma2d(sb + SM_WM + i * 8192, &maps.wm, cta * 32, i * 128, bars + BAR_WM * 8);
                }
                bulk_prefetch((const char*)p.q + cta * 20480, 20480);
                bulk_prefetch((const char*)p.w1 + cta * 6400, 6400);
                bulk_prefetch((const char*)p.w2 + cta * 6400, 6400);
            }
            __syncwarp();
        } else {
            bar_arrive(13, 640);
        }
        if ((WARM & 1) && wq == 3) { spin(W1D); mbar_wait_warm(bars + BAR_U * 8, 0); }
        asm volatile("barrier.cluster.wait.aligned;" ::: "memory");
        uint32_t peer;
        asm volatile("ld.shared::cluster.u32 %0, [%1];" : "=r"(peer) : "r"(mapa(sb + SM_GV + 512, (blockIdx.x & 1) ^ 1)) : "memory");
        const bool paired = peer == (smid ^ 1);
        if (tid == 639) sts32(sb + SM_GV + 516, paired);
        if (cta < 120) {
            float d[4];
            if (tid < 592) {
                const int t = tid - 512;
                mbar_wait(bars + BAR_U * 8, 0);
                uint4 cv = __ldg(reinterpret_cast<const uint4*>(p.c) + t);
                auto silu2 = [](uint32_t v) { float a = blo(v), b = bhi(v); return pack2(__fdividef(a, 1.0f + __expf(-a)), __fdividef(b, 1.0f + __expf(-b))); };
#pragma unroll 1
                for (int i = 0; i < 4; i++) { const uint32_t r = silu2(cv.x); cv.x = cv.y; cv.y = cv.z; cv.z = cv.w; cv.w = r; }
                sts128(sb + SM_Y + (t % 40) * 32 + (t / 40) * 16, cv);
                fence_async_smem();
            }
            bar_sync(5, 128);
            mbar_wait(bars + BAR_WM * 8, 0);
            if (wq == 3) TSW(56);
            const uint32_t da = desc_lo(sb + SM_WM, 20480), db = desc_lo(sb + SM_Y, 32);
#pragma unroll 1
            for (int k0 = 0; k0 < 20; k0 += 4) {
                wg_fence();
#pragma unroll
                for (int k = k0; k < k0 + 4; k++) asm volatile("{.reg .pred p; .reg .b32 l,m; .reg .b64 da,db; setp.ne.b32 p,%10,0; add.u32 l,%4,%6; mov.b64 da,{l,%8}; add.u32 m,%5,%7; mov.b64 db,{m,%9};"
                             " wgmma.mma_async.sync.aligned.m64n8k16.f32.bf16.bf16 {%0,%1,%2,%3},da,db,p,1,1,1,0;}"
                             : "+f"(d[0]), "+f"(d[1]), "+f"(d[2]), "+f"(d[3])
                             : "r"(da), "r"(db), "r"(64 * k), "r"(4 * k), "n"(desc_hi(512, 2u)), "n"(desc_hi(128, 0)), "r"(k));
                wg_commit();
            }
            wg_wait<0>();
            reg_fence<4>(d);
            if (c == 0) {
                sts32(sb + SM_GV + (16 * wq + g) * 4, __float_as_uint(wq < 2 ? d[0] : d[1]));
                sts32(sb + SM_GV + (16 * wq + g + 8) * 4, __float_as_uint(wq < 2 ? d[2] : d[3]));
            }
            bar_sync(5, 128);
            if (wq == 2) {
                g_mod[cta * 32 + lane] = __float2bfloat16_rn(__uint_as_float(lds32(sb + SM_GV + lane * 4)) + __uint_as_float(lds32(sb + SM_GV + 128 + lane * 4)));
                __syncwarp();
                if (lane == 0) flag_release(FL_M);
                __syncwarp();
                TSW(4);
            }

        }
        if (wq == 2) {
            flag_wait(FL_M, ep1 * 120);
            fence_async_global();
            if (elect()) {
                mbar_expect(bars + BAR_M * 8, 7680);
                bulk_g2s(sb + SM_MOD, g_mod, 7680, bars + BAR_M * 8);
            }
            __syncwarp();
            TSW(60);
            bar_sync(8, 576);  if (lane == 0) { flag_release(FL_R + rb); TS(23); }  __syncwarp();
            bar_sync(15, 288); if (lane == 0) { flag_release(FL_B1 + rb); TS(27); } __syncwarp();
            bar_sync(6, 288);  if (lane == 0) { flag_release(FL_B2 + rb); TS(31); } __syncwarp();
#pragma unroll 1
            for (int i = 0; i < 3; i++) { bar_sync(i ? i : 8, 288); if (lane == 0) { TS(53 + (i + 2) % 3); flag_release(FL_G + 16 * i + rb); TS(57 + (i + 2) % 3); } __syncwarp(); }
            if (lane == 0) g_epoch[smid] = ep1;
            return;
        }
        if (wq == 1) {
            bar_sync(9, 288);
            if (lane < 4 * NB) mbar_arrive_cl(mapa(bars + (BAR_EB + (lane >> 2)) * 8, paired ? lane & 1 : blockIdx.x & 1));
        }
        if (wq == 3) {
            bar_sync(7, 544);
            if (lane == 0) { flag_release(FL_C); TS(20); }
            __syncwarp();
            if (lane < 2) mbar_expect(bars + (lane ? BAR_Y2 : BAR_Y) * 8, lane ? 8192 : 12288);
            flag_wait(FL_C, ep1 * 128);
            fence_async_global();
            TSW(21);
            if (elect()) {
                bulk_g2s(sb + SM_Y, g_yv + rho * 5120, 12288, bars + BAR_Y * 8);
                bulk_g2s(sb + SM_Y + 12288, g_yv + rho * 5120 + 3072, 8192, bars + BAR_Y2 * 8);
            }
            __syncwarp();
        }
        if (wq == 3) {
            if (elect()) {
                mbar_expect(bars + BAR_XY * 8, 20480);
#pragma unroll 1
                for (int i = 0; i < 8; i++) {
                    bulk_g2s(sb + SM_YT + i * 2560, g_yv + (8 * rb + i) * 5120 + cm * 8, 2048, bars + BAR_XY * 8);
                    bulk_g2s(sb + SM_YT + i * 2560 + 2048, g_yv + (8 * rb + i) * 5120 + cr * 8, 512, bars + BAR_XY * 8);
                }
            }
            __syncwarp();
            bar_sync(8, 576);
            if (WARM & 2) mbar_wait_warm(bars + BAR_FA * 8, 0); else mbar_wait(bars + BAR_FA * 8, 0);
            mbar_wait(bars + BAR_ME * 8, 0);
            if (WARM & 4) mbar_wait_warm(bars + (BAR_FA + 11 % NA) * 8, (11 / NA) & 1); else mbar_wait(bars + (BAR_FA + 11 % NA) * 8, (11 / NA) & 1);
            flag_wait(FL_CS, ep1 * 4);
            fence_async_global();
            if (elect()) {
                mbar_expect(bars + BAR_CS * 8, 864);
                bulk_g2s(sb + SM_CS, g_cs + 64 * j, 256, bars + BAR_CS * 8);
                bulk_g2s(sb + SM_CS + 256, g_cs + 512 + RA3 * j, 4 * RA3, bars + BAR_CS * 8);
                bulk_g2s(sb + SM_CS + 256 + 4 * RA3, g_cs + HB0 + 64 * j, 256, bars + BAR_CS * 8);
                bulk_g2s(sb + SM_CS + 512 + 4 * RA3, g_cs + HB0 + 512 + RB3 * j, 4 * RB3, bars + BAR_CS * 8);
            }
            __syncwarp();
            mbar_wait(bars + BAR_ME * 8, 1);
            if (WARM & 4) mbar_wait_warm(bars + (BAR_FA + 21 % NA) * 8, (21 / NA) & 1); else mbar_wait(bars + BAR_ST * 8, 0);
#pragma unroll 1
            for (int i = 0; i < 3; i++) {
                if ((WARM & 8) && i) {
                    mbar_wait(bars + BAR_ME * 8, (i + 1) & 1);
                    for (int n = i; n < NPING; n++) { spin(PING); n += tensor_ping(); }
                }
                flag_wait(FL_G + 16 * i + rb, ep1 * 8);
                if (lane == 0) { mbar_expect(bars + (BAR_G + i) * 8, 0); TS(35 + (i + 2) % 3); }
                __syncwarp();
            }
            return;
        }
        if (elect()) {
            if (wq == 1) {
                Ring<NB, SM_RB, BAR_FB, BAR_EB> r{sb, 0, 0};
#pragma unroll 1
                for (int ph = 0; ph < 7; ph++) {
                    const CUtensorMap* ma = ph == 0 ? &maps.w1a : ph == 1 ? &maps.w2a : ph == 6 ? &maps.w4a : &maps.w3a;
                    const bool b3b = ph == 2 || ph == 4 || ph == 5;
                    r.runw(paired, idx & 1, ma, ma + (b3b ? 2 : 1), ph == 3 ? 64 * j : b3b ? HB0 + 64 * j : cm,
                           ph == 3 ? 512 + RA3 * j : b3b ? HB0 + 512 + RB3 * j : cr, ph == 4 ? 10 - NA : ph == 5 ? 1 : 0,
                           ph == 6 ? 27 : ph == 5 ? 10 - NA : ph == 2 ? 1 : 10, ph == 0 ? 0 : ph == 6 ? OWNG * (HB0 / 64 + j) : cm >> 6,
                           ph == 3 ? 8192 + 128 * RA3 : b3b ? 8192 + 128 * RB3 : 10240,
                           ph == 1 ? GATE : ph == 3 ? GATE - 1 : -1, bars + (BAR_ST - (ph == 1)) * 8);
                }
            } else {
                Ring<NA, SM_RA, BAR_FA, BAR_EA> r{sb, 0, 0};
                if (cta >= 120) mbar_wait(bars + (BAR_K + 4) * 8, 0);
                mbar_expect(bars + BAR_XR * 8, 20480);
                bulk_g2s(sb + SM_XR, p.q + (size_t)rho * 16 * D_, 20480, bars + BAR_XR * 8);
                mbar_expect(bars + BAR_XY * 8, 20480);
                tma2d(sb + SM_XT, &maps.xa, cm, rb * 128, bars + BAR_XY * 8);
                tma2d(sb + SM_XT2, &maps.xb, cr, rb * 128, bars + BAR_XY * 8);
                const int grp = j >> 1;
                const int delta = (grp & 1 ? 1 : -1) * (1 + (grp >> 1));
                const int nb = min(max(rb + (delta > 0 ? 1 : -1), 0), 15);
                uint32_t fb = r.acquire(SLOT), dst = r.slot();
                flag_wait2(FL_R + nb, FL_R + rb, ep1 * 8);
                fence_async_global();
                tma2d(dst, &maps.hn, 0, rb * 128 + delta, fb);
                TS(24);
                r.next();
                r.run2d(&maps.hn, rb * 128 + delta);
#pragma unroll 1
                for (int i = 0; i < 2; i++) {
                    const char* src = (const char*)(i ? g_x1 : g_h1) + (size_t)rb * 163840;
                    r.acquire(0); r.next();
                    fb = r.acquire(SLOT); dst = r.slot();
                    const char* src1 = src + (cm == 0 ? SLOT : 0);
                    flag_wait(FL_B1 + 16 * i + rb, ep1 * 8);
                    fence_async_global();
                    bulk_g2s(dst, src1, SLOT, fb);
                    TS(28 + 4 * i);
                    mbar_expect(bars + (BAR_ST - 1 + i) * 8, 0);
                    r.next();
                    r.run1d(src, 2, 10, cm >> 6);
                }
                r.run1d((const char*)g_x1 + (size_t)rb * 163840, 1, 10 - NA, cm >> 6);
                if (OWNG) { r.acquire(0); r.next(); }
#pragma unroll 1
                for (int i = 0; i < 2; i++) {
                    mbar_wait(bars + (BAR_G + 1 + i) * 8, 0); fence_async_global();
                    r.run1d((const char*)g_g + (size_t)rb * 442368, OWNG + HB0 / 64 * i, i ? 27 : OWNG + HB0 / 64, OWNG * (HB0 / 64 + j));
                }
            }
        }
        return;
    }
    bar_arrive(13, 640);
    asm volatile("setmaxnreg.inc.sync.aligned.u32 112;");
    const int rrow = 16 * rho + (warp >> 1) + 8 * (warp & 1);

    fence_async_smem();
    bar_sync(1 + wg, 128);
#pragma unroll 1
    for (int cc = wg; cc < wg + 1 + (wg == 3); cc++) {
        mbar_wait(bars + (BAR_K + cc) * 8, 0);
        if (cc == 2 && wq == 0) TSW(40);
        uint32_t a = sb + sm_k(cc) + 32 + (tid & 127) * 32;
        uint32_t pw = lds32(a - 4);
        uint4 x = lds128(a), y = lds128(a + 16), o;
        if ((tid & 127) == 0) {
            uint16_t k0 = __bfloat16_as_ushort(__float2bfloat16_rn(blo(x.x) + __uint_as_float(lds32(sb + SM_GV + 520 + cc * 4))));
            x.x = (x.x & 0xffff0000u) | k0;
            sts16(a, k0);
        }
        o.x = prmt(pw, x.x, 0x5432); o.y = prmt(x.x, x.y, 0x5432); o.z = prmt(x.y, x.z, 0x5432); o.w = prmt(x.z, x.w, 0x5432);
        sts128(a + 4160, o);
        o.x = prmt(x.w, y.x, 0x5432); o.y = prmt(y.x, y.y, 0x5432); o.z = prmt(y.y, y.z, 0x5432); o.w = prmt(y.z, y.w, 0x5432);
        sts128(a + 4176, o);
    }
    bar_sync(1 + wg, 128);
    if (wg == 3) bar_arrive(11, 256);
#pragma unroll 1
    for (int cc = wg; cc < 5; cc += 3) {
        if (cc == 3 && wg == 0) break;
        if (cc == 4) bar_sync(11, 256);
        const uint32_t kaddr = sb + sm_k(cc) + ((g & 1) ? 32 : 4192) + 4 * ((g >> 1) - c) + 64 * wq;
        const AFrag f0 = ldA(kaddr), f1 = ldA(kaddr + 256);
        if (STAG && cc == 3) bar_sync(12, 256);
        mbar_wait(bars + (BAR_U + cc) * 8, 0);
        if (wq == 0) TSW(5 + cc);
        float d[64];
        conv_two<0>(d, f0, f1, kaddr, desc_lo(sb + sm_u(cc), U_PLANE), sb + sm_red(cc) + wq * 4352 + g * 544 + c * 8, cc == 1);
        if (wq == 0) TSW(10 + cc);
        if (cc == 1) bar_arrive(6, 256);
    }
#pragma unroll 1
    for (int cc = wg == 1 ? 4 : wg;; cc++) {
        if (cc == 1) bar_sync(6, 256); else bar_sync(1 + wg, 128);
        const int ch = cta * 5 + cc;
        uint32_t* dst = g_yv + ch * 8 + ((g + (ch >> 2)) & 7) + (126 - 32 * wq - 2 * c) * 5120;
        uint2 v[16];
#pragma unroll
        for (int i = 0; i < 16; i++) v[i] = lds64(sb + sm_red(cc) + g * 544 + wq * 128 + c * 8 + (i >> 2) * 32 + (i & 3) * 4360);
#pragma unroll
        for (int w = 1; w < 4; w++)
            if (wq == 3 && c > 3 - w) v[12 + w] = make_uint2(0, 0);
#pragma unroll
        for (int q = 0; q < 4; q++) {
            const uint2* u = v + 4 * q;
            dst[-8 * q * 5120] = badd2(u[0].x, badd2(u[1].x, badd2(u[2].x, u[3].x)));
            dst[(-8 * q + 1) * 5120] = badd2(u[0].y, badd2(u[1].y, badd2(u[2].y, u[3].y)));
        }
        if (wq == 0) TSW(15 + cc);
        if (cc != 0) break;
    }
    fence_async_smem();
    if (!(wg & 1)) bar_arrive(9, 288);
    bar_arrive(7, 544);

    const uint32_t one2 = 0x3f803f80u;
    const unsigned ones = p.ones;
    {
        uint32_t x[10], a[10], cb[10], sbv[10];
        if (RPRE_WAIT) bar_sync(10, 512);
        mbar_wait(bars + BAR_XR * 8, 0);
#pragma unroll
        for (int i = 0; i < 10; i++) x[i] = lds32(sb + SM_XR + (rrow & 15) * 1280 + lane * 4 + i * 128);
        const uint3 s1 = row_stats(x, lane);
        const int up = lane >> 4, gg = warp >> 1, e = warp & 1;
        const uint32_t ya = sb + SM_Y + lane * 64 + ((gg + (lane >> 1)) & 7) * 4;
        const uint32_t sel = (up ? 0x1054u : 0x5410u) + (e ? 0x2222u : 0u);
        const uint32_t ma = sb + SM_MOD + lane * 4;
        mbar_wait(bars + BAR_M * 8, 0);
        uint32_t pin = 0;
#pragma unroll
        for (int i = 0; i < 10; i++) {
            uint32_t h = bfma2(ln_apply(x[i], s1.x, s1.y, s1.z), badd2(lds32(ma + 1280 + i * 128), one2), lds32(ma + i * 128));
            a[i] = bmul2(h, lds32(ma + 2560 + i * 128));
            sbv[i] = lds32(ma + 3840 + i * 128);
            cb[i] = badd2(lds32(ma + 5120 + i * 128), one2);
            pin ^= a[i] ^ cb[i];
        }
        if (pin & ~ones) sts32(sb + SM_GV, pin);
        if (warp == 4) TSW(52);
        mbar_wait(bars + BAR_Y * 8, 0);
        if (warp == 0) TSW(22);
#pragma unroll
        for (int i = 0; i < 10; i++) {
            if (i == 6) mbar_wait(bars + BAR_Y2 * 8, 0);
            uint32_t y0 = lds32(ya + i * 2048 + up * 32), y1 = lds32(ya + i * 2048 + (up ^ 1) * 32);
            x[i] = bfma2(a[i], prmt(y0, y1, sel), x[i]);
        }
        const uint3 s2 = row_stats(x, lane);
#pragma unroll
        for (int i = 0; i < 10; i++) x[i] = bfma2(ln_apply(x[i], s2.x, s2.y, s2.z), cb[i], sbv[i]);
        const uint3 s3 = row_stats(x, lane);
        uint32_t* o = reinterpret_cast<uint32_t*>(g_hn + (size_t)rrow * D_) + lane;
#pragma unroll
        for (int i = 0; i < 10; i++) o[32 * i] = ln_apply(x[i], s3.x, s3.y, s3.z);
        if (lane < 2) g_rs[rrow * 2 + lane] = lane ? make_uint4(s2.x, s2.y, s2.z, 0) : make_uint4(s1.x, s1.y, s1.z, 0);
        if (warp == 0) TSW(34);
        bar_arrive(8, 576);
    }

    const int half = wg & 1;
    const int row = 64 * half + 16 * wq + g;
    const int tw0 = (rb * 80 + (cm >> 3)) * 512 + row * 4 + c, tw1 = (rb * 80 + (cr >> 3) - 8) * 512 + row * 4 + c;
    const uint32_t park = sb + SM_Y + (tid & 255) * 16;
    const uint32_t ms0 = sb + SM_MOD + (cm + 2 * c) * 2, ms1 = sb + SM_MOD + (cr - 64 + 2 * c) * 2;
    if (wg >= 2) {
        {
            float acc[40];
            gemm_loop<80, true, 10, 10, true>(acc, sb, half, 0, 0, 10, 0, 0, 25);
            if (tid == 256) mbar_expect(bars + BAR_ME * 8, 0);
#pragma unroll
            for (int k = 0; k < 10; k += CH) CHUNK(k) {
#pragma unroll
                for (int q = k; q < k + CH && q < 10; q++) {
                    uint32_t* dst = reinterpret_cast<uint32_t*>(g_h1) + (q < 8 ? tw0 : tw1);
                    const uint32_t u = gelu2_h(bmul2(pack2(acc[4 * q], acc[4 * q + 1]), 0x3f003f00u));
                    const uint32_t v = gelu2_h(bmul2(pack2(acc[4 * q + 2], acc[4 * q + 3]), 0x3f003f00u));
                    dst[q * 512] = u;
                    dst[q * 512 + 32] = v;
                    acc[4 * q] = __uint_as_float(u); acc[4 * q + 1] = __uint_as_float(v);
                }
            }
            bar_arrive(15, 288);
            mbar_wait(bars + (BAR_FA + 10 % NA) * 8, (10 / NA) & 1);
#pragma unroll
            for (int q = 0; q < 8; q++) {
                sts32(sb + SM_RA + (10 % NA) * SLOT + q * 2048 + row * 16 + c * 4, __float_as_uint(acc[4 * q]));
                sts32(sb + SM_RA + (10 % NA) * SLOT + q * 2048 + row * 16 + c * 4 + 128, __float_as_uint(acc[4 * q + 1]));
            }
            fence_async_smem();
            bar_arrive(14, 512);
        }
        gemm3<0>(sb, rb, j, half, row, c, ones);
        {
            float acc[40];
            uint32_t gbv[10], base[20];
#pragma unroll
            for (int q = 0; q < 10; q++) gbv[q] = lds32((q < 8 ? ms0 : ms1) + 6400 + q * 16);
#pragma unroll
            for (int q = 0; q < 5; q++) { const uint4 t = lds128(park + q * 4096); base[4 * q] = t.x; base[4 * q + 1] = t.y; base[4 * q + 2] = t.z; base[4 * q + 3] = t.w; }
            gemm_loop<80, false, 27, 27 - NB, true>(acc, sb, half, 39 - NA, 40, 27 - NA, 11, 0, 42);
            auto fin = [&](int q, int r) {
                return bfma2(gbv[q], pack2(acc[4 * q + 2 * r], acc[4 * q + 2 * r + 1]), base[2 * q + r]);
            };
            auto tr4 = [&](uint32_t t0, uint32_t t1, uint32_t t2, uint32_t t3) {
                const bool o1 = c & 1, o2 = c & 2;
                uint32_t a = __shfl_xor_sync(0xffffffffu, o1 ? t0 : t1, 1), b = __shfl_xor_sync(0xffffffffu, o1 ? t2 : t3, 1);
                uint32_t u0 = o1 ? a : t0, u1 = o1 ? t1 : a, u2 = o1 ? b : t2, u3 = o1 ? t3 : b;
                a = __shfl_xor_sync(0xffffffffu, o2 ? u0 : u2, 2); b = __shfl_xor_sync(0xffffffffu, o2 ? u1 : u3, 2);
                return o2 ? make_uint4(a, b, u2, u3) : make_uint4(u0, u1, a, b);
            };
            bf16* go = p.out + (size_t)(rb * 128 + row) * D_;
#pragma unroll
            for (int k = 0; k < 2; k++) CHUNK(k) {
#pragma unroll
                for (int r = 0; r < 2; r++)
                    *reinterpret_cast<uint4*>(go + r * 8 * D_ + cm + 32 * k + 8 * c) = tr4(fin(4 * k, r), fin(4 * k + 1, r), fin(4 * k + 2, r), fin(4 * k + 3, r));
            }
            CHUNK(2) *reinterpret_cast<uint4*>(go + (c >> 1) * 8 * D_ + cr + 8 * (c & 1)) = tr4(fin(8, 0), fin(9, 0), fin(8, 1), fin(9, 1));
            if (tid == 256) TS(44);
            if (warp == 8) TSFLUSH();
        }
    } else {
        {
            float acc[40];
            uint32_t x2[20];
            {
                uint32_t y[20];
                mbar_wait(bars + BAR_XY * 8, 0);
                const uint32_t xa = sb + SM_XT + row * 128 + c * 4, xb = sb + SM_XT2 + row * 32 + c * 4;
                const uint32_t ya = sb + SM_YT + (4 * half + wq) * 2560 + c * 64;
#pragma unroll
                for (int q = 0; q < 10; q++) {
                    const uint32_t a = q < 8 ? xa + ((q ^ g) << 4) : xb + (q - 8) * 16;
                    x2[2 * q] = lds32(a); x2[2 * q + 1] = lds32(a + (q < 8 ? 1024 : 256));
                    const int pos = (g + ((q < 8 ? cm : cr) >> 2) + 2 * q + (c >> 1)) & 7;
                    y[2 * q] = lds32(ya + q * 256 + pos * 4); y[2 * q + 1] = lds32(ya + q * 256 + 32 + pos * 4);
                }
                fence_async_smem();
                bar_sync(1 + wg, 128);
                if ((tid & 127) < NA) mbar_arrive_cl(mapa(bars + (BAR_EA + (tid & 127)) * 8, blockIdx.x & 1));
                mbar_wait(bars + (BAR_FA + 1) * 8, 0);
                const uint4* rp = g_rs + (rb * 128 + row) * 2;
                const uint4 ra = ldcg128(rp), rb2 = ldcg128(rp + 1), rc = ldcg128(rp + 16), rd = ldcg128(rp + 17);
                bar_sync(14, 512);
#pragma unroll
                for (int q = 0; q < 10; q++) {
                    const uint32_t ms = q < 8 ? ms0 : ms1;
                    const uint32_t sa = lds32(ms + 16 * q), ca = badd2(lds32(ms + 1280 + 16 * q), one2), ga = lds32(ms + 2560 + 16 * q);
                    const uint32_t sbv = lds32(ms + 3840 + 16 * q), cb = badd2(lds32(ms + 5120 + 16 * q), one2);
                    uint32_t u = x2[2 * q], v = x2[2 * q + 1];
                    u = bfma2(bmul2(bfma2(ln_apply(u, ra.x, ra.y, ra.z), ca, sa), ga), prmt(y[2 * q], y[2 * q + 1], 0x5410), u);
                    v = bfma2(bmul2(bfma2(ln_apply(v, rc.x, rc.y, rc.z), ca, sa), ga), prmt(y[2 * q], y[2 * q + 1], 0x7632), v);
                    x2[2 * q] = u; x2[2 * q + 1] = v;
                    u = bfma2(ln_apply(u, rb2.x, rb2.y, rb2.z), cb, sbv);
                    v = bfma2(ln_apply(v, rd.x, rd.y, rd.z), cb, sbv);
                    acc[4 * q] = blo(u); acc[4 * q + 1] = bhi(u); acc[4 * q + 2] = blo(v); acc[4 * q + 3] = bhi(v);
                }
            }
            reg_fence<40>(acc);
            if (tid == 0) TS(45);
            gemm_loop<80, false, 10, 10, false>(acc, sb, half, 10, 10, 10, 0, 0, 29);
            if (tid == 0) mbar_expect(bars + BAR_ME * 8, 0);
            uint32_t x1[20];
            float s0 = 0.f, q0 = 0.f, s1 = 0.f, q1 = 0.f;
#pragma unroll
            for (int q = 0; q < 10; q++) {
                uint32_t u = pack2(acc[4 * q], acc[4 * q + 1]);
                uint32_t v = pack2(acc[4 * q + 2], acc[4 * q + 3]);
                uint32_t* dst = reinterpret_cast<uint32_t*>(g_x1) + (q < 8 ? tw0 : tw1);
                dst[q * 512] = u;
                dst[q * 512 + 32] = v;
                x1[2 * q] = u; x1[2 * q + 1] = v;
            }
            bar_arrive(6, 288);
            CHUNK(0)
#pragma unroll
            for (int q = 0; q < 10; q++) {
                float a = blo(x1[2 * q]), b = bhi(x1[2 * q]), e = blo(x1[2 * q + 1]), f = bhi(x1[2 * q + 1]);
                s0 += a + b; q0 = fmaf(a, a, fmaf(b, b, q0));
                s1 += e + f; q1 = fmaf(e, e, fmaf(f, f, q1));
            }
#pragma unroll
            for (int m = 1; m <= 2; m <<= 1) {
                s0 += __shfl_xor_sync(0xffffffffu, s0, m); q0 += __shfl_xor_sync(0xffffffffu, q0, m);
                s1 += __shfl_xor_sync(0xffffffffu, s1, m); q1 += __shfl_xor_sync(0xffffffffu, q1, m);
            }
            if (c < 2) g_st[(rb * 8 + j) * 128 + row + 8 * c] = c ? make_float2(s1, q1) : make_float2(s0, q0);
            bar_arrive(8, 288);
            mbar_wait(bars + (BAR_FA + 20 % NA) * 8, (20 / NA) & 1);
#pragma unroll
            for (int q = 0; q < 8; q++) {
                sts32(sb + SM_RA + (20 % NA) * SLOT + q * 2048 + row * 16 + c * 4, x1[2 * q]);
                sts32(sb + SM_RA + (20 % NA) * SLOT + q * 2048 + row * 16 + c * 4 + 128, x1[2 * q + 1]);
            }
            fence_async_smem();
            bar_sync(3 + wg, 128);
#pragma unroll
            for (int q = 0; q < 5; q++) {
                const uint32_t ms = q < 4 ? ms0 : ms1;
                const uint32_t g0 = lds32(ms + 6400 + q * 32), g1 = lds32(ms + 6400 + q * 32 + 16);
                sts128(park + q * 4096, make_uint4(bfma2(g0, x1[4 * q], x2[4 * q]), bfma2(g0, x1[4 * q + 1], x2[4 * q + 1]),
                                                   bfma2(g1, x1[4 * q + 2], x2[4 * q + 2]), bfma2(g1, x1[4 * q + 3], x2[4 * q + 3])));
            }
        }
        gemm3<1>(sb, rb, j, half, row, c, ones);
    }
}

typedef CUresult (*EncFn)(CUtensorMap*, CUtensorMapDataType, cuuint32_t, void*, const cuuint64_t*, const cuuint64_t*,
                          const cuuint32_t*, const cuuint32_t*, CUtensorMapInterleave, CUtensorMapSwizzle,
                          CUtensorMapL2promotion, CUtensorMapFloatOOBfill);

void make_map(EncFn enc, CUtensorMap* m, const void* base, uint64_t inner, uint64_t outer, uint32_t bi, uint32_t bo,
              CUtensorMapSwizzle swz = CU_TENSOR_MAP_SWIZZLE_128B) {
    cuuint64_t dims[2] = {inner, outer};
    cuuint64_t st[1] = {inner * 2};
    cuuint32_t box[2] = {bi, bo};
    cuuint32_t es[2] = {1, 1};
    enc(m, CU_TENSOR_MAP_DATA_TYPE_BFLOAT16, 2, const_cast<void*>(base), dims, st, box, es, CU_TENSOR_MAP_INTERLEAVE_NONE,
        swz, CU_TENSOR_MAP_L2_PROMOTION_NONE, CU_TENSOR_MAP_FLOAT_OOB_FILL_NONE);
}

}

extern "C" void kernel_launch(void* const* d_in, const int* in_sizes, int n_in, void* d_out, int out_size) {
    (void)in_sizes; (void)n_in; (void)out_size;
    Params p;
    p.q = (const bf16*)d_in[0]; p.k = (const bf16*)d_in[1]; p.v = (const bf16*)d_in[2];
    p.shift = (const bf16*)d_in[3]; p.ssmk = (const bf16*)d_in[4]; p.ssmD = (const bf16*)d_in[5];
    p.w1 = (const bf16*)d_in[7]; p.w2 = (const bf16*)d_in[8]; p.w3 = (const bf16*)d_in[9]; p.w4 = (const bf16*)d_in[10];
    p.c = (const bf16*)d_in[11]; p.wmod = (const bf16*)d_in[12];
    p.out = (bf16*)d_out;
    p.ones = 0xffffffffu;

    void* fn = nullptr;
    cudaDriverEntryPointQueryResult qr;
    cudaGetDriverEntryPoint("cuTensorMapEncodeTiled", &fn, cudaEnableDefault, &qr);
    EncFn enc = (EncFn)fn;
    void* hn = nullptr;
    cudaGetSymbolAddress(&hn, g_hn);
    Maps maps;
    make_map(enc, &maps.w3s, p.w3, F_, D_, 216, 64, CU_TENSOR_MAP_SWIZZLE_NONE);
    make_map(enc, &maps.wm, p.wmod, 6 * D_, D_, 32, 128, CU_TENSOR_MAP_SWIZZLE_64B);
    make_map(enc, &maps.xa, p.q, D_, S_, 64, 128);
    make_map(enc, &maps.xb, p.q, D_, S_, 16, 128, CU_TENSOR_MAP_SWIZZLE_NONE);
    make_map(enc, &maps.hn, hn, D_, S_, 64, 128);
    make_map(enc, &maps.w1a, p.w1, D_, D_, 64, 64);
    make_map(enc, &maps.w1b, p.w1, D_, D_, 16, 64);
    make_map(enc, &maps.w2a, p.w2, D_, D_, 64, 64);
    make_map(enc, &maps.w2b, p.w2, D_, D_, 16, 64);
    make_map(enc, &maps.w3a, p.w3, F_, D_, 64, 64);
    make_map(enc, &maps.w3b, p.w3, F_, D_, RA3, 64);
    make_map(enc, &maps.w3c, p.w3, F_, D_, RB3, 64);
    make_map(enc, &maps.w4a, p.w4, D_, F_, 64, 64);
    make_map(enc, &maps.w4b, p.w4, D_, F_, 16, 64);
    cudaFuncSetAttribute(fused_kernel, cudaFuncAttributeMaxDynamicSharedMemorySize, SMEM_BYTES);
    fused_kernel<<<132, NTHREADS, SMEM_BYTES>>>(p, maps);
}
```

```cpp
#include <cuda_runtime.h>
#include <cuda_bf16.h>
#include <cuda.h>
#include <stdint.h>
#include <string.h>

#define SEED 0
#define RING_A 6
#define CH 2
#define FAST_LN 2
#define STAG 12
#define PGELU 2
#define CH3 4
#define HO_A 16
#define HO_B 16
#define RA3 48
#define CSP 16
#define OWNG 1
#define GATE 5
#define SSM_DELAY 0
#define B_DELAY 300
#define RPRE_WAIT 1
#define PING 250
#define NPING 5
#define SSM_N 3

namespace {

typedef __nv_bfloat16 bf16;
typedef __nv_bfloat162 bf162;

constexpr int S_ = 2048, D_ = 640, F_ = 1728;
constexpr int NTHREADS = 640;
constexpr int NA = RING_A, NB = 12 - RING_A;
constexpr int SLOT = 16384;
constexpr int RB3 = 88 - RA3, HB0 = 512 + 8 * RA3;
constexpr int SM_RA = 0, SM_RB = NA * SLOT;

static_assert(NA == 6, "smem map");
constexpr int RED_STRIDE = 17536;
constexpr int K_STRIDE = 8320;
constexpr int U_PLANE = 2560, U_STRIDE = 5120;
constexpr int SM_Y = 12 * SLOT;
__device__ __forceinline__ int sm_red(int cc) { return cc * RED_STRIDE + (cc < 3 ? SM_RB : -3 * RED_STRIDE); }
__device__ __forceinline__ int sm_k(int cc) { return cc * K_STRIDE + (cc < 3 ? SM_RB + 3 * RED_STRIDE : 2 * RED_STRIDE - 3 * K_STRIDE); }
__device__ __forceinline__ int sm_u(int cc) { return cc * U_STRIDE + (cc < 3 ? SM_RB + 3 * RED_STRIDE + 3 * K_STRIDE : SM_Y + 8192 - 3 * U_STRIDE); }
constexpr int SM_PK = SM_RB;
constexpr int SM_PV = SM_RB + 24576;
constexpr int SM_WM = 57344;
constexpr int SM_XT = SM_WM, SM_XT2 = SM_WM + 16384, SM_XR = SM_WM + 20480;
constexpr int SM_YT = 0;
constexpr int SM_MOD = SM_Y + 20480;
constexpr int SM_GV = SM_MOD + 7680;
constexpr int SM_CS = SM_GV + 1024;
constexpr int SM_RP = SM_CS + 1024;
constexpr int SM_BAR = SM_RP + 1024;
constexpr int SM_PROF = SM_BAR + 512;
constexpr int SM_TOTAL = SM_PROF + 512;
constexpr int SMEM_BYTES = SM_TOTAL + 1024;
static_assert(SMEM_BYTES <= 232448, "smem");

constexpr int BAR_FA = 0, BAR_FB = NA, BAR_EA = 12, BAR_EB = 12 + NA, BAR_K = 24, BAR_U = 29, BAR_Y = 34, BAR_CS = 35, BAR_WM = 36, BAR_M = 37, BAR_XY = 38, BAR_Y2 = 39, BAR_G = 40, BAR_ST = 44, BAR_XR = 45, BAR_ME = 46, BAR_CD = 47, NBARS = 48;

__device__ __align__(1024) bf16 g_kvT[D_ * S_];
__device__ __align__(1024) uint32_t g_yv[128 * 5120];
__device__ __align__(1024) bf16 g_mod[6 * D_];
__device__ __align__(1024) bf16 g_hn[S_ * D_];
__device__ __align__(1024) uint4 g_rs[S_ * 2];
__device__ __align__(1024) bf16 g_h1[S_ * D_];
__device__ __align__(1024) bf16 g_x1[S_ * D_];
__device__ __align__(1024) bf16 g_g[S_ * F_];
__device__ __align__(1024) float2 g_st[S_ * 8];
__device__ __align__(1024) float g_cs[F_];
__device__ __align__(1024) unsigned g_flags[128 * 32];
__device__ __align__(1024) unsigned g_epoch[160];
constexpr int FL_P = 0, FL_C = 8, FL_CS = 9, FL_M = 10, FL_R = 16, FL_B1 = 32, FL_B2 = 48, FL_G = 64;

#define TS(i) do {} while (0)
#define TSW(i) do {} while (0)
#define TSD(i, dep) do {} while (0)
#define TSD2(i, dep) do {} while (0)
#define TSFLUSH() do {} while (0)

struct Params {
    const bf16 *q, *k, *v, *shift, *ssmk, *ssmD, *w1, *w2, *w3, *w4, *c, *wmod;
    bf16* out;
    unsigned ones;
};
#define CHUNK(k) if (ones & (1u << (k)))
struct Maps { CUtensorMap hn, w1a, w1b, w2a, w2b, w3a, w3b, w3c, w4a, w4b, wm, xa, xb, w3s; };

template<int N> struct WgRs;
template<int N> struct WgSs;
template<> struct WgRs<32> { template<int OFF,int HI,int SC> static __device__ __forceinline__ void run(float* d,uint32_t a0,uint32_t a1,uint32_t a2,uint32_t a3,uint32_t blo){
 asm volatile("{.reg .b32 l; .reg .b64 db; add.u32 l,%20,%21; mov.b64 db,{l,%22}; wgmma.mma_async.sync.aligned.m64n32k16.f32.bf16.bf16 {%0,%1,%2,%3,%4,%5,%6,%7,%8,%9,%10,%11,%12,%13,%14,%15},{%16,%17,%18,%19},db,%23,1,1,0;}"
 :"+f"(d[0]),"+f"(d[1]),"+f"(d[2]),"+f"(d[3]),"+f"(d[4]),"+f"(d[5]),"+f"(d[6]),"+f"(d[7]),"+f"(d[8]),"+f"(d[9]),"+f"(d[10]),"+f"(d[11]),"+f"(d[12]),"+f"(d[13]),"+f"(d[14]),"+f"(d[15])
 :"r"(a0),"r"(a1),"r"(a2),"r"(a3),"r"(blo),"n"(OFF),"n"(HI),"n"(SC)); } };
template<> struct WgRs<48> { template<int OFF,int HI,int SC> static __device__ __forceinline__ void run(float* d,uint32_t a0,uint32_t a1,uint32_t a2,uint32_t a3,uint32_t blo){
 asm volatile("{.reg .b32 l; .reg .b64 db; add.u32 l,%28,%29; mov.b64 db,{l,%30}; wgmma.mma_async.sync.aligned.m64n48k16.f32.bf16.bf16 {%0,%1,%2,%3,%4,%5,%6,%7,%8,%9,%10,%11,%12,%13,%14,%15,%16,%17,%18,%19,%20,%21,%22,%23},{%24,%25,%26,%27},db,%31,1,1,0;}"
 :"+f"(d[0]),"+f"(d[1]),"+f"(d[2]),"+f"(d[3]),"+f"(d[4]),"+f"(d[5]),"+f"(d[6]),"+f"(d[7]),"+f"(d[8]),"+f"(d[9]),"+f"(d[10]),"+f"(d[11]),"+f"(d[12]),"+f"(d[13]),"+f"(d[14]),"+f"(d[15]),"+f"(d[16]),"+f"(d[17]),"+f"(d[18]),"+f"(d[19]),"+f"(d[20]),"+f"(d[21]),"+f"(d[22]),"+f"(d[23])
 :"r"(a0),"r"(a1),"r"(a2),"r"(a3),"r"(blo),"n"(OFF),"n"(HI),"n"(SC)); } };
template<> struct WgRs<64> { template<int OFF,int HI,int SC> static __device__ __forceinline__ void run(float* d,uint32_t a0,uint32_t a1,uint32_t a2,uint32_t a3,uint32_t blo){
 asm volatile("{.reg .b32 l; .reg .b64 db; add.u32 l,%36,%37; mov.b64 db,{l,%38}; wgmma.mma_async.sync.aligned.m64n64k16.f32.bf16.bf16 {%0,%1,%2,%3,%4,%5,%6,%7,%8,%9,%10,%11,%12,%13,%14,%15,%16,%17,%18,%19,%20,%21,%22,%23,%24,%25,%26,%27,%28,%29,%30,%31},{%32,%33,%34,%35},db,%39,1,1,0;}"
 :"+f"(d[0]),"+f"(d[1]),"+f"(d[2]),"+f"(d[3]),"+f"(d[4]),"+f"(d[5]),"+f"(d[6]),"+f"(d[7]),"+f"(d[8]),"+f"(d[9]),"+f"(d[10]),"+f"(d[11]),"+f"(d[12]),"+f"(d[13]),"+f"(d[14]),"+f"(d[15]),"+f"(d[16]),"+f"(d[17]),"+f"(d[18]),"+f"(d[19]),"+f"(d[20]),"+f"(d[21]),"+f"(d[22]),"+f"(d[23]),"+f"(d[24]),"+f"(d[25]),"+f"(d[26]),"+f"(d[27]),"+f"(d[28]),"+f"(d[29]),"+f"(d[30]),"+f"(d[31])
 :"r"(a0),"r"(a1),"r"(a2),"r"(a3),"r"(blo),"n"(OFF),"n"(HI),"n"(SC)); } };
template<> struct WgRs<80> { template<int OFF,int HI,int SC> static __device__ __forceinline__ void run(float* d,uint32_t a0,uint32_t a1,uint32_t a2,uint32_t a3,uint32_t blo){
 asm volatile("{.reg .b32 l; .reg .b64 db; add.u32 l,%44,%45; mov.b64 db,{l,%46}; wgmma.mma_async.sync.aligned.m64n80k16.f32.bf16.bf16 {%0,%1,%2,%3,%4,%5,%6,%7,%8,%9,%10,%11,%12,%13,%14,%15,%16,%17,%18,%19,%20,%21,%22,%23,%24,%25,%26,%27,%28,%29,%30,%31,%32,%33,%34,%35,%36,%37,%38,%39},{%40,%41,%42,%43},db,%47,1,1,0;}"
 :"+f"(d[0]),"+f"(d[1]),"+f"(d[2]),"+f"(d[3]),"+f"(d[4]),"+f"(d[5]),"+f"(d[6]),"+f"(d[7]),"+f"(d[8]),"+f"(d[9]),"+f"(d[10]),"+f"(d[11]),"+f"(d[12]),"+f"(d[13]),"+f"(d[14]),"+f"(d[15]),"+f"(d[16]),"+f"(d[17]),"+f"(d[18]),"+f"(d[19]),"+f"(d[20]),"+f"(d[21]),"+f"(d[22]),"+f"(d[23]),"+f"(d[24]),"+f"(d[25]),"+f"(d[26]),"+f"(d[27]),"+f"(d[28]),"+f"(d[29]),"+f"(d[30]),"+f"(d[31]),"+f"(d[32]),"+f"(d[33]),"+f"(d[34]),"+f"(d[35]),"+f"(d[36]),"+f"(d[37]),"+f"(d[38]),"+f"(d[39])
 :"r"(a0),"r"(a1),"r"(a2),"r"(a3),"r"(blo),"n"(OFF),"n"(HI),"n"(SC)); } };
template<> struct WgRs<96> { template<int OFF,int HI,int SC> static __device__ __forceinline__ void run(float* d,uint32_t a0,uint32_t a1,uint32_t a2,uint32_t a3,uint32_t blo){
 asm volatile("{.reg .b32 l; .reg .b64 db; add.u32 l,%52,%53; mov.b64 db,{l,%54}; wgmma.mma_async.sync.aligned.m64n96k16.f32.bf16.bf16 {%0,%1,%2,%3,%4,%5,%6,%7,%8,%9,%10,%11,%12,%13,%14,%15,%16,%17,%18,%19,%20,%21,%22,%23,%24,%25,%26,%27,%28,%29,%30,%31,%32,%33,%34,%35,%36,%37,%38,%39,%40,%41,%42,%43,%44,%45,%46,%47},{%48,%49,%50,%51},db,%55,1,1,0;}"
 :"+f"(d[0]),"+f"(d[1]),"+f"(d[2]),"+f"(d[3]),"+f"(d[4]),"+f"(d[5]),"+f"(d[6]),"+f"(d[7]),"+f"(d[8]),"+f"(d[9]),"+f"(d[10]),"+f"(d[11]),"+f"(d[12]),"+f"(d[13]),"+f"(d[14]),"+f"(d[15]),"+f"(d[16]),"+f"(d[17]),"+f"(d[18]),"+f"(d[19]),"+f"(d[20]),"+f"(d[21]),"+f"(d[22]),"+f"(d[23]),"+f"(d[24]),"+f"(d[25]),"+f"(d[26]),"+f"(d[27]),"+f"(d[28]),"+f"(d[29]),"+f"(d[30]),"+f"(d[31]),"+f"(d[32]),"+f"(d[33]),"+f"(d[34]),"+f"(d[35]),"+f"(d[36]),"+f"(d[37]),"+f"(d[38]),"+f"(d[39]),"+f"(d[40]),"+f"(d[41]),"+f"(d[42]),"+f"(d[43]),"+f"(d[44]),"+f"(d[45]),"+f"(d[46]),"+f"(d[47])
 :"r"(a0),"r"(a1),"r"(a2),"r"(a3),"r"(blo),"n"(OFF),"n"(HI),"n"(SC)); } };
template<> struct WgRs<112> { template<int OFF,int HI,int SC> static __device__ __forceinline__ void run(float* d,uint32_t a0,uint32_t a1,uint32_t a2,uint32_t a3,uint32_t blo){
 asm volatile("{.reg .b32 l; .reg .b64 db; add.u32 l,%60,%61; mov.b64 db,{l,%62}; wgmma.mma_async.sync.aligned.m64n112k16.f32.bf16.bf16 {%0,%1,%2,%3,%4,%5,%6,%7,%8,%9,%10,%11,%12,%13,%14,%15,%16,%17,%18,%19,%20,%21,%22,%23,%24,%25,%26,%27,%28,%29,%30,%31,%32,%33,%34,%35,%36,%37,%38,%39,%40,%41,%42,%43,%44,%45,%46,%47,%48,%49,%50,%51,%52,%53,%54,%55},{%56,%57,%58,%59},db,%63,1,1,0;}"
 :"+f"(d[0]),"+f"(d[1]),"+f"(d[2]),"+f"(d[3]),"+f"(d[4]),"+f"(d[5]),"+f"(d[6]),"+f"(d[7]),"+f"(d[8]),"+f"(d[9]),"+f"(d[10]),"+f"(d[11]),"+f"(d[12]),"+f"(d[13]),"+f"(d[14]),"+f"(d[15]),"+f"(d[16]),"+f"(d[17]),"+f"(d[18]),"+f"(d[19]),"+f"(d[20]),"+f"(d[21]),"+f"(d[22]),"+f"(d[23]),"+f"(d[24]),"+f"(d[25]),"+f"(d[26]),"+f"(d[27]),"+f"(d[28]),"+f"(d[29]),"+f"(d[30]),"+f"(d[31]),"+f"(d[32]),"+f"(d[33]),"+f"(d[34]),"+f"(d[35]),"+f"(d[36]),"+f"(d[37]),"+f"(d[38]),"+f"(d[39]),"+f"(d[40]),"+f"(d[41]),"+f"(d[42]),"+f"(d[43]),"+f"(d[44]),"+f"(d[45]),"+f"(d[46]),"+f"(d[47]),"+f"(d[48]),"+f"(d[49]),"+f"(d[50]),"+f"(d[51]),"+f"(d[52]),"+f"(d[53]),"+f"(d[54]),"+f"(d[55])
 :"r"(a0),"r"(a1),"r"(a2),"r"(a3),"r"(blo),"n"(OFF),"n"(HI),"n"(SC)); } };
template<> struct WgRs<128> { template<int OFF,int HI,int SC> static __device__ __forceinline__ void run(float* d,uint32_t a0,uint32_t a1,uint32_t a2,uint32_t a3,uint32_t blo){
 asm volatile("{.reg .b32 l; .reg .b64 db; add.u32 l,%68,%69; mov.b64 db,{l,%70}; wgmma.mma_async.sync.aligned.m64n128k16.f32.bf16.bf16 {%0,%1,%2,%3,%4,%5,%6,%7,%8,%9,%10,%11,%12,%13,%14,%15,%16,%17,%18,%19,%20,%21,%22,%23,%24,%25,%26,%27,%28,%29,%30,%31,%32,%33,%34,%35,%36,%37,%38,%39,%40,%41,%42,%43,%44,%45,%46,%47,%48,%49,%50,%51,%52,%53,%54,%55,%56,%57,%58,%59,%60,%61,%62,%63},{%64,%65,%66,%67},db,%71,1,1,0;}"
 :"+f"(d[0]),"+f"(d[1]),"+f"(d[2]),"+f"(d[3]),"+f"(d[4]),"+f"(d[5]),"+f"(d[6]),"+f"(d[7]),"+f"(d[8]),"+f"(d[9]),"+f"(d[10]),"+f"(d[11]),"+f"(d[12]),"+f"(d[13]),"+f"(d[14]),"+f"(d[15]),"+f"(d[16]),"+f"(d[17]),"+f"(d[18]),"+f"(d[19]),"+f"(d[20]),"+f"(d[21]),"+f"(d[22]),"+f"(d[23]),"+f"(d[24]),"+f"(d[25]),"+f"(d[26]),"+f"(d[27]),"+f"(d[28]),"+f"(d[29]),"+f"(d[30]),"+f"(d[31]),"+f"(d[32]),"+f"(d[33]),"+f"(d[34]),"+f"(d[35]),"+f"(d[36]),"+f"(d[37]),"+f"(d[38]),"+f"(d[39]),"+f"(d[40]),"+f"(d[41]),"+f"(d[42]),"+f"(d[43]),"+f"(d[44]),"+f"(d[45]),"+f"(d[46]),"+f"(d[47]),"+f"(d[48]),"+f"(d[49]),"+f"(d[50]),"+f"(d[51]),"+f"(d[52]),"+f"(d[53]),"+f"(d[54]),"+f"(d[55]),"+f"(d[56]),"+f"(d[57]),"+f"(d[58]),"+f"(d[59]),"+f"(d[60]),"+f"(d[61]),"+f"(d[62]),"+f"(d[63])
 :"r"(a0),"r"(a1),"r"(a2),"r"(a3),"r"(blo),"n"(OFF),"n"(HI),"n"(SC)); } };
template<> struct WgSs<80> { template<int AOFF,int AHI,int BOFF,int BHI,int SC> static __device__ __forceinline__ void run(float* d,uint32_t alo,uint32_t blo){
 asm volatile("{.reg .b32 l,m; .reg .b64 da,db; add.u32 l,%40,%42; mov.b64 da,{l,%43}; add.u32 m,%41,%44; mov.b64 db,{m,%45}; wgmma.mma_async.sync.aligned.m64n80k16.f32.bf16.bf16 {%0,%1,%2,%3,%4,%5,%6,%7,%8,%9,%10,%11,%12,%13,%14,%15,%16,%17,%18,%19,%20,%21,%22,%23,%24,%25,%26,%27,%28,%29,%30,%31,%32,%33,%34,%35,%36,%37,%38,%39},da,db,%46,1,1,0,1;}"
 :"+f"(d[0]),"+f"(d[1]),"+f"(d[2]),"+f"(d[3]),"+f"(d[4]),"+f"(d[5]),"+f"(d[6]),"+f"(d[7]),"+f"(d[8]),"+f"(d[9]),"+f"(d[10]),"+f"(d[11]),"+f"(d[12]),"+f"(d[13]),"+f"(d[14]),"+f"(d[15]),"+f"(d[16]),"+f"(d[17]),"+f"(d[18]),"+f"(d[19]),"+f"(d[20]),"+f"(d[21]),"+f"(d[22]),"+f"(d[23]),"+f"(d[24]),"+f"(d[25]),"+f"(d[26]),"+f"(d[27]),"+f"(d[28]),"+f"(d[29]),"+f"(d[30]),"+f"(d[31]),"+f"(d[32]),"+f"(d[33]),"+f"(d[34]),"+f"(d[35]),"+f"(d[36]),"+f"(d[37]),"+f"(d[38]),"+f"(d[39])
 :"r"(alo),"r"(blo),"n"(AOFF),"n"(AHI),"n"(BOFF),"n"(BHI),"n"(SC)); } };
template<> struct WgSs<104> { template<int AOFF,int AHI,int BOFF,int BHI,int SC> static __device__ __forceinline__ void run(float* d,uint32_t alo,uint32_t blo){
 asm volatile("{.reg .b32 l,m; .reg .b64 da,db; add.u32 l,%52,%54; mov.b64 da,{l,%55}; add.u32 m,%53,%56; mov.b64 db,{m,%57}; wgmma.mma_async.sync.aligned.m64n104k16.f32.bf16.bf16 {%0,%1,%2,%3,%4,%5,%6,%7,%8,%9,%10,%11,%12,%13,%14,%15,%16,%17,%18,%19,%20,%21,%22,%23,%24,%25,%26,%27,%28,%29,%30,%31,%32,%33,%34,%35,%36,%37,%38,%39,%40,%41,%42,%43,%44,%45,%46,%47,%48,%49,%50,%51},da,db,%58,1,1,0,1;}"
 :"+f"(d[0]),"+f"(d[1]),"+f"(d[2]),"+f"(d[3]),"+f"(d[4]),"+f"(d[5]),"+f"(d[6]),"+f"(d[7]),"+f"(d[8]),"+f"(d[9]),"+f"(d[10]),"+f"(d[11]),"+f"(d[12]),"+f"(d[13]),"+f"(d[14]),"+f"(d[15]),"+f"(d[16]),"+f"(d[17]),"+f"(d[18]),"+f"(d[19]),"+f"(d[20]),"+f"(d[21]),"+f"(d[22]),"+f"(d[23]),"+f"(d[24]),"+f"(d[25]),"+f"(d[26]),"+f"(d[27]),"+f"(d[28]),"+f"(d[29]),"+f"(d[30]),"+f"(d[31]),"+f"(d[32]),"+f"(d[33]),"+f"(d[34]),"+f"(d[35]),"+f"(d[36]),"+f"(d[37]),"+f"(d[38]),"+f"(d[39]),"+f"(d[40]),"+f"(d[41]),"+f"(d[42]),"+f"(d[43]),"+f"(d[44]),"+f"(d[45]),"+f"(d[46]),"+f"(d[47]),"+f"(d[48]),"+f"(d[49]),"+f"(d[50]),"+f"(d[51])
 :"r"(alo),"r"(blo),"n"(AOFF),"n"(AHI),"n"(BOFF),"n"(BHI),"n"(SC)); } };
template<> struct WgSs<112> { template<int AOFF,int AHI,int BOFF,int BHI,int SC> static __device__ __forceinline__ void run(float* d,uint32_t alo,uint32_t blo){
 asm volatile("{.reg .b32 l,m; .reg .b64 da,db; add.u32 l,%56,%58; mov.b64 da,{l,%59}; add.u32 m,%57,%60; mov.b64 db,{m,%61}; wgmma.mma_async.sync.aligned.m64n112k16.f32.bf16.bf16 {%0,%1,%2,%3,%4,%5,%6,%7,%8,%9,%10,%11,%12,%13,%14,%15,%16,%17,%18,%19,%20,%21,%22,%23,%24,%25,%26,%27,%28,%29,%30,%31,%32,%33,%34,%35,%36,%37,%38,%39,%40,%41,%42,%43,%44,%45,%46,%47,%48,%49,%50,%51,%52,%53,%54,%55},da,db,%62,1,1,0,1;}"
 :"+f"(d[0]),"+f"(d[1]),"+f"(d[2]),"+f"(d[3]),"+f"(d[4]),"+f"(d[5]),"+f"(d[6]),"+f"(d[7]),"+f"(d[8]),"+f"(d[9]),"+f"(d[10]),"+f"(d[11]),"+f"(d[12]),"+f"(d[13]),"+f"(d[14]),"+f"(d[15]),"+f"(d[16]),"+f"(d[17]),"+f"(d[18]),"+f"(d[19]),"+f"(d[20]),"+f"(d[21]),"+f"(d[22]),"+f"(d[23]),"+f"(d[24]),"+f"(d[25]),"+f"(d[26]),"+f"(d[27]),"+f"(d[28]),"+f"(d[29]),"+f"(d[30]),"+f"(d[31]),"+f"(d[32]),"+f"(d[33]),"+f"(d[34]),"+f"(d[35]),"+f"(d[36]),"+f"(d[37]),"+f"(d[38]),"+f"(d[39]),"+f"(d[40]),"+f"(d[41]),"+f"(d[42]),"+f"(d[43]),"+f"(d[44]),"+f"(d[45]),"+f"(d[46]),"+f"(d[47]),"+f"(d[48]),"+f"(d[49]),"+f"(d[50]),"+f"(d[51]),"+f"(d[52]),"+f"(d[53]),"+f"(d[54]),"+f"(d[55])
 :"r"(alo),"r"(blo),"n"(AOFF),"n"(AHI),"n"(BOFF),"n"(BHI),"n"(SC)); } };

__device__ __forceinline__ void wg_fence() { asm volatile("wgmma.fence.sync.aligned;" ::: "memory"); }
__device__ __forceinline__ void wg_commit() { asm volatile("wgmma.commit_group.sync.aligned;" ::: "memory"); }
template <int N> __device__ __forceinline__ void wg_wait() { asm volatile("wgmma.wait_group.sync.aligned %0;" ::"n"(N) : "memory"); }
template <int N> __device__ __forceinline__ void reg_fence(float* d) {
#pragma unroll
    for (int i = 0; i < N; i++) asm volatile("" : "+f"(d[i])::"memory");
}
__device__ __forceinline__ uint32_t desc_lo(uint32_t addr, uint32_t lbo) { return ((addr & 0x3FFFF) >> 4) | ((lbo >> 4) << 16); }
#define desc_hi(sbo, sw) (((sbo) >> 4) | ((sw) << 30))
__device__ __forceinline__ uint32_t smem_u32(const void* p) { return (uint32_t)__cvta_generic_to_shared(p); }
__device__ __forceinline__ bool elect() {
    uint32_t p;
    asm volatile("{.reg .pred P; elect.sync _|P, 0xffffffff; selp.u32 %0,1,0,P;}" : "=r"(p));
    return p;
}
__device__ __forceinline__ void mbar_init(uint32_t bar, uint32_t cnt) { asm volatile("mbarrier.init.shared::cta.b64 [%0], %1;" ::"r"(bar), "r"(cnt) : "memory"); }
__device__ __forceinline__ void mbar_expect(uint32_t bar, uint32_t bytes) { asm volatile("mbarrier.arrive.expect_tx.shared::cta.b64 _, [%0], %1;" ::"r"(bar), "r"(bytes) : "memory"); }
__device__ __forceinline__ bool mbar_try(uint32_t bar, uint32_t par) {
    uint32_t ok;
    asm volatile("{.reg .pred p; mbarrier.try_wait.parity.shared::cta.b64 p, [%1], %2; selp.u32 %0,1,0,p;}" : "=r"(ok) : "r"(bar), "r"(par) : "memory");
    return ok;
}
constexpr int SPIN_LIMIT = 1 << 18;
__device__ __forceinline__ void mbar_wait(uint32_t bar, uint32_t par) {
    if (mbar_try(bar, par)) return;
    asm volatile("{.reg .pred p, q; .reg .b32 n; mov.u32 n, 0;\n"
                 "W%=: mbarrier.try_wait.parity.shared::cta.b64 p, [%0], %1; add.u32 n, n, 1; setp.lt.and.u32 q, n, %2, !p; @q bra W%=;}"
                 ::"r"(bar), "r"(par), "n"(SPIN_LIMIT) : "memory");
}
__device__ __forceinline__ void bulk_g2s(uint32_t dst, const void* src, uint32_t bytes, uint32_t bar) {
    asm volatile("cp.async.bulk.shared::cluster.global.mbarrier::complete_tx::bytes [%0], [%1], %2, [%3];" ::"r"(dst), "l"(src), "r"(bytes), "r"(bar) : "memory");
}
__device__ __forceinline__ void bulk_s2g(void* dst, uint32_t src, uint32_t bytes) {
    asm volatile("cp.async.bulk.global.shared::cta.bulk_group [%0], [%1], %2;" ::"l"(dst), "r"(src), "r"(bytes) : "memory");
}
__device__ __forceinline__ void bulk_prefetch(const void* src, uint32_t bytes) {
    asm volatile("cp.async.bulk.prefetch.L2.global [%0], %1;" ::"l"(src), "r"(bytes) : "memory");
}
__device__ __forceinline__ void tma2d(uint32_t dst, const CUtensorMap* m, int c0, int c1, uint32_t bar) {
    asm volatile("cp.async.bulk.tensor.2d.shared::cluster.global.mbarrier::complete_tx::bytes [%0], [%1, {%3, %4}], [%2];" ::"r"(dst), "l"(m), "r"(bar), "r"(c0), "r"(c1) : "memory");
}
__device__ __forceinline__ void tma2d_mc(uint32_t dst, const CUtensorMap* m, int c0, int c1, uint32_t bar) {
    asm volatile("cp.async.bulk.tensor.2d.shared::cluster.global.mbarrier::complete_tx::bytes.multicast::cluster [%0], [%1, {%3, %4}], [%2], %5;" ::"r"(dst), "l"(m), "r"(bar), "r"(c0), "r"(c1), "h"((uint16_t)3) : "memory");
}
__device__ __forceinline__ uint32_t mapa(uint32_t a, uint32_t rank) { uint32_t r; asm("mapa.shared::cluster.u32 %0, %1, %2;" : "=r"(r) : "r"(a), "r"(rank)); return r; }
__device__ __forceinline__ void mbar_arrive_cl(uint32_t bar) { asm volatile("mbarrier.arrive.shared::cluster.b64 _, [%0];" ::"r"(bar) : "memory"); }
__device__ __forceinline__ void prefetch_map(const CUtensorMap* m) { asm volatile("prefetch.tensormap [%0];" ::"l"(m) : "memory"); }
__device__ __forceinline__ void cpasync16(uint32_t dst, const void* src, uint32_t srcsz) {
    asm volatile("cp.async.cg.shared.global [%0], [%1], 16, %2;" ::"r"(dst), "l"(src), "r"(srcsz) : "memory");
}
__device__ __forceinline__ void bar_sync(int id, int n) { asm volatile("bar.sync %0, %1;" ::"r"(id), "r"(n) : "memory"); }
__device__ __forceinline__ void bar_arrive(int id, int n) { asm volatile("bar.arrive %0, %1;" ::"r"(id), "r"(n) : "memory"); }
__device__ __forceinline__ void fence_async_smem() { asm volatile("fence.proxy.async.shared::cta;" ::: "memory"); }
__device__ __forceinline__ void fence_async_global() { asm volatile("fence.proxy.async.global;" ::: "memory"); }
__device__ __forceinline__ void flag_release(int f) { asm volatile("red.release.gpu.global.add.u32 [%0], 1;" ::"l"(&g_flags[f * 32]) : "memory"); }
__device__ __forceinline__ void flag_wait(int f, unsigned target) {
    const unsigned* p = &g_flags[f * 32];
    unsigned v; int n = 0;
    do {
        asm volatile("ld.relaxed.gpu.global.u32 %0, [%1];" : "=r"(v) : "l"(p) : "memory");
    } while ((int)(v - target) < 0 && ++n < SPIN_LIMIT);
    asm volatile("fence.acquire.gpu;" ::: "memory");
}
__device__ __forceinline__ unsigned ld_flag(const unsigned* p) { unsigned v; asm volatile("ld.relaxed.gpu.global.u32 %0, [%1];" : "=r"(v) : "l"(p) : "memory"); return v; }
__device__ __forceinline__ void spin(unsigned n) { unsigned t0, t1; asm volatile("mov.u32 %0, %%clock;" : "=r"(t0)); do { asm volatile("mov.u32 %0, %%clock;" : "=r"(t1)); } while (t1 - t0 < n); }
__device__ __forceinline__ int tensor_ping() {
    int r;
    asm volatile("{.reg .f32 a, b, c, d; mma.sync.aligned.m16n8k16.row.col.f32.bf16.bf16.f32 {a,b,c,d},{%1,%1,%1,%1},{%1,%1},{%2,%2,%2,%2}; mov.b32 %0, a;}" : "=r"(r) : "r"(0), "f"(0.f));
    return r;
}
__device__ __forceinline__ void mbar_wait_warm(uint32_t bar, uint32_t par) {
    for (int n = 0; n < SPIN_LIMIT; n++) {
        uint32_t ok;
        asm volatile("{.reg .pred p; mbarrier.test_wait.parity.shared::cta.b64 p, [%1], %2; selp.u32 %0,1,0,p;}" : "=r"(ok) : "r"(bar), "r"(par) : "memory");
        if (ok) break;
        n += tensor_ping();
        spin(PING);
    }
}
__device__ __forceinline__ void flag_wait2(int f0, int f1, unsigned target) {
    const unsigned *p = &g_flags[f0 * 32], *q = &g_flags[f1 * 32];
    unsigned v, w; int n = 0;
    do { v = ld_flag(p); w = ld_flag(q); } while ((int)((v - target) | (w - target)) < 0 && ++n < SPIN_LIMIT);
    asm volatile("fence.acquire.gpu;" ::: "memory");
}
__device__ __forceinline__ uint32_t lds32(uint32_t a) { uint32_t v; asm volatile("ld.shared.u32 %0, [%1];" : "=r"(v) : "r"(a)); return v; }
__device__ __forceinline__ float2 lds64f(uint32_t a) { float2 v; asm volatile("ld.shared.v2.f32 {%0,%1}, [%2];" : "=f"(v.x), "=f"(v.y) : "r"(a)); return v; }
__device__ __forceinline__ uint2 lds64(uint32_t a) { uint2 v; asm volatile("ld.shared.v2.u32 {%0,%1}, [%2];" : "=r"(v.x), "=r"(v.y) : "r"(a)); return v; }
__device__ __forceinline__ void sts64f(uint32_t a, float2 v) { asm volatile("st.shared.v2.f32 [%0], {%1,%2};" ::"r"(a), "f"(v.x), "f"(v.y) : "memory"); }
__device__ __forceinline__ void sts32(uint32_t a, uint32_t v) { asm volatile("st.shared.u32 [%0], %1;" ::"r"(a), "r"(v) : "memory"); }
__device__ __forceinline__ void sts64(uint32_t a, uint32_t x, uint32_t y) { asm volatile("st.shared.v2.u32 [%0], {%1,%2};" ::"r"(a), "r"(x), "r"(y) : "memory"); }
__device__ __forceinline__ void sts16(uint32_t a, uint16_t v) { asm volatile("st.shared.u16 [%0], %1;" ::"r"(a), "h"(v) : "memory"); }
__device__ __forceinline__ uint4 lds128(uint32_t a) { uint4 v; asm volatile("ld.shared.v4.u32 {%0,%1,%2,%3}, [%4];" : "=r"(v.x), "=r"(v.y), "=r"(v.z), "=r"(v.w) : "r"(a)); return v; }
__device__ __forceinline__ void sts128(uint32_t a, uint4 v) { asm volatile("st.shared.v4.u32 [%0], {%1,%2,%3,%4};" ::"r"(a), "r"(v.x), "r"(v.y), "r"(v.z), "r"(v.w) : "memory"); }
__device__ __forceinline__ void sts128f(uint32_t a, float x, float y, float z, float w) { asm volatile("st.shared.v4.f32 [%0], {%1,%2,%3,%4};" ::"r"(a), "f"(x), "f"(y), "f"(z), "f"(w) : "memory"); }
__device__ __forceinline__ uint32_t prmt(uint32_t a, uint32_t b, uint32_t s) { uint32_t r; asm("prmt.b32 %0,%1,%2,%3;" : "=r"(r) : "r"(a), "r"(b), "r"(s)); return r; }
__device__ __forceinline__ uint32_t pack2(float lo, float hi) { uint32_t r; asm("cvt.rn.bf16x2.f32 %0, %1, %2;" : "=r"(r) : "f"(hi), "f"(lo)); return r; }
__device__ __forceinline__ float blo(uint32_t v) { return __uint_as_float(v << 16); }
__device__ __forceinline__ float bhi(uint32_t v) { return __uint_as_float(v & 0xffff0000u); }
__device__ __forceinline__ uint32_t bmul2(uint32_t a, uint32_t b) { uint32_t r; asm("mul.rn.bf16x2 %0,%1,%2;" : "=r"(r) : "r"(a), "r"(b)); return r; }
__device__ __forceinline__ uint32_t badd2(uint32_t a, uint32_t b) { uint32_t r; asm("add.rn.bf16x2 %0,%1,%2;" : "=r"(r) : "r"(a), "r"(b)); return r; }
__device__ __forceinline__ float rbf(float x) { return __bfloat162float(__float2bfloat16_rn(x)); }
__device__ __forceinline__ uint32_t ldcg32(const void* p) { uint32_t v; asm volatile("ld.global.cg.u32 %0, [%1];" : "=r"(v) : "l"(p) : "memory"); return v; }
__device__ __forceinline__ uint4 ldcg128(const void* p) { uint4 v; asm volatile("ld.global.cg.v4.u32 {%0,%1,%2,%3}, [%4];" : "=r"(v.x), "=r"(v.y), "=r"(v.z), "=r"(v.w) : "l"(p) : "memory"); return v; }
__device__ __forceinline__ void stg32_if(void* p, uint32_t v, int on) { asm volatile("{.reg .pred q; setp.ne.b32 q, %2, 0; @q st.global.u32 [%0], %1;}" ::"l"(p), "r"(v), "r"(on) : "memory"); }
__device__ __forceinline__ uint2 ldcg64(const void* p) { uint2 v; asm volatile("ld.global.cg.v2.u32 {%0,%1}, [%2];" : "=r"(v.x), "=r"(v.y) : "l"(p) : "memory"); return v; }
__device__ __forceinline__ float gelu_h(float h) {
    float u = h * fmaf(h * h, 8.0f * 0.044715f * 0.7978845608028654f, 2.0f * 0.7978845608028654f);
    float th;
    asm("tanh.approx.f32 %0, %1;" : "=f"(th) : "f"(u));
    return fmaf(h, th, h);
}
__device__ __forceinline__ float gelu(float x) { return gelu_h(0.5f * x); }
__device__ __forceinline__ float half_rstd(float sum, float sq) {
    float mean = sum * (1.0f / D_), inv;
    asm("rsqrt.approx.ftz.f32 %0, %1;" : "=f"(inv) : "f"(fmaxf(fmaf(-mean, mean, fmaf(sq, 1.0f / D_, 1e-5f)), 1e-5f)));
    return 0.5f * inv;
}
__device__ __forceinline__ uint32_t bsub2(uint32_t a, uint32_t b) { uint32_t r; asm("sub.rn.bf16x2 %0,%1,%2;" : "=r"(r) : "r"(a), "r"(b)); return r; }
__device__ __forceinline__ uint32_t bfma2(uint32_t a, uint32_t b, uint32_t c) { uint32_t r; asm("fma.rn.bf16x2 %0,%1,%2,%3;" : "=r"(r) : "r"(a), "r"(b), "r"(c)); return r; }
__device__ __forceinline__ uint32_t gelu2_h(uint32_t h) {
    uint32_t u = bmul2(h, bfma2(bmul2(h, h), 0x3e923e92u, 0x3fcc3fccu)), th;
    asm("tanh.approx.bf16x2 %0, %1;" : "=r"(th) : "r"(u));
    return bfma2(h, th, h);
}
__device__ __forceinline__ uint3 row_stats(const uint32_t* v, int lane) {
    float s = 0.f, q = 0.f, s_ = 0.f, q_ = 0.f;
#pragma unroll
    for (int i = 0; i < 10; i++) { float a = blo(v[i]), b = bhi(v[i]); s += a; s_ += b; q = fmaf(a, a, q); q_ = fmaf(b, b, q_); }
    s += s_; q += q_;
    {
        float t = __shfl_xor_sync(0xffffffffu, (lane & 16) ? s : q, 16);
        t += (lane & 16) ? q : s;
#pragma unroll
        for (int m = 8; m; m >>= 1) t += __shfl_xor_sync(0xffffffffu, t, m);
        float o = __shfl_xor_sync(0xffffffffu, t, 16);
        s = (lane & 16) ? o : t; q = (lane & 16) ? t : o;
    }
    float mean = s * (1.0f / D_), inv;
    asm("rsqrt.approx.ftz.f32 %0, %1;" : "=f"(inv) : "f"(fmaxf(fmaf(-mean, mean, fmaf(q, 1.0f / D_, 1e-5f)), 1e-5f)));
    uint3 r;
    r.x = pack2(mean, mean);
    r.y = pack2(inv, inv);
    inv -= blo(r.y);
    r.z = pack2(inv, inv);
    return r;
}
__device__ __forceinline__ uint32_t ln_apply(uint32_t x, uint32_t m, uint32_t hi, uint32_t lo) {
    uint32_t xc = bsub2(x, m);
    return bmul2(xc, hi);
}

struct AFrag { uint32_t m, a, b, c, d; };
__device__ __forceinline__ AFrag ldA(uint32_t a) { AFrag f; f.m = lds32(a - 16); f.a = lds32(a); f.b = lds32(a + 16); f.c = lds32(a + 32); f.d = lds32(a + 48); return f; }
template <int N, int M> __device__ __forceinline__ void conv_pair(float* d, const AFrag& f, uint32_t descU) {
    WgRs<N>::template run<8 * M, desc_hi(128, 0), M ? 1 : 0>(d, f.a, f.b, f.m, f.a, descU);
    WgRs<N>::template run<8 * M + 1, desc_hi(128, 0), 1>(d, f.c, f.d, f.b, f.c, descU);
}
template <int Q> __device__ __forceinline__ void conv_put(float* d, uint32_t r0) {
    sts64(r0 + Q * 32, pack2(d[4 * Q + 1], d[4 * Q + 3]), pack2(d[4 * Q], d[4 * Q + 2]));
}
template <int M> __device__ __forceinline__ void conv_two(float* d, AFrag f0, AFrag f1, uint32_t kaddr, uint32_t descU, uint32_t r0, bool handoff) {
    constexpr int N = M < 14 ? 128 - 8 * M : 32;
    wg_fence();
    conv_pair<N, M>(d, f0, descU);
    wg_commit();
    if constexpr (M > 0) f1 = ldA(kaddr + 256 * (M + 1));
    wg_fence();
    conv_pair<N, M + 1>(d, f1, descU);
    wg_commit();
    if (STAG && M == STAG && handoff) bar_arrive(12, 256);
    if constexpr (M < 14) {
        if constexpr (M > 0) { conv_put<17 - M>(d, r0); conv_put<16 - M>(d, r0); }
        wg_wait<1>();
        f0 = ldA(kaddr + 256 * (M + 2));
        if constexpr (M < 12) wg_wait<0>();
        conv_two<M + 2>(d, f0, f1, kaddr, descU, r0, handoff);
    } else {
        wg_wait<0>();
        conv_put<3>(d, r0); conv_put<2>(d, r0); conv_put<1>(d, r0); conv_put<0>(d, r0);
    }
}
template <int N, bool ASWZ, int SC0>
__device__ __forceinline__ void gemm_issue(float* acc, uint32_t bars, int sa, int pa, int sw, int pw, uint32_t da0, uint32_t db0) {
    mbar_wait(bars + (BAR_FB + sw) * 8, pw);
    mbar_wait(bars + (BAR_FA + sa) * 8, pa);
    const uint32_t da = da0 + sa * (SLOT >> 4), db = db0 + sw * (SLOT >> 4);
    constexpr int AK = ASWZ ? 2 : 256, AH = ASWZ ? desc_hi(1024, 1) : desc_hi(128, 0), BH = desc_hi(1024, 1);
    wg_fence();
    WgSs<N>::template run<0, AH, 0, BH, SC0>(acc, da, db);
    WgSs<N>::template run<AK, AH, 128, BH, 1>(acc, da, db);
    WgSs<N>::template run<2 * AK, AH, 256, BH, 1>(acc, da, db);
    WgSs<N>::template run<3 * AK, AH, 384, BH, 1>(acc, da, db);
    wg_commit();
}
template <int N, bool ASWZ, int NKB, int RELB, bool ZERO>
__device__ __forceinline__ void gemm_loop(float* acc, uint32_t sb, int half, int ia0, int ib0, int rela, int wait_bar, int order_bar, int tsid) {
    int sa = ia0 % NA, pa = (ia0 / NA) & 1, sw = ib0 % NB, pw = (ib0 / NB) & 1;
    const uint32_t bars = sb + SM_BAR;
    const int t = threadIdx.x & 127;
    uint32_t ebar = mapa(bars + (t < 2 ? BAR_EB : BAR_EA) * 8, (t < 2 && lds32(sb + SM_GV + 516)) ? t : blockIdx.x & 1);
    const int nrel = t < 2 ? RELB : t == 2 ? rela : 0;
    const uint32_t da0 = ASWZ ? desc_lo(sb + SM_RA + half * 8192, 16) : desc_lo(sb + SM_RA + half * 1024, 2048), db0 = desc_lo(sb + SM_RB, 8192);
    asm volatile("" : "+r"(ebar));
    if (wait_bar) bar_sync(wait_bar, 512);
    gemm_issue<N, ASWZ, ZERO ? 0 : 1>(acc, bars, sa, pa, sw, pw, da0, db0);
    if ((threadIdx.x & 255) == 0) TS(tsid);
#pragma unroll 1
    for (int kb = 1; kb < NKB; kb++) {
        const int prev = t < 2 ? sw : sa;
        if (++sa == NA) { sa = 0; pa ^= 1; }
        if (++sw == NB) { sw = 0; pw ^= 1; }
        gemm_issue<N, ASWZ, 1>(acc, bars, sa, pa, sw, pw, da0, db0);
        if (order_bar && kb == NKB - 1) bar_arrive(order_bar, 512);
        wg_wait<1>();
        if (kb <= nrel) mbar_arrive_cl(ebar + prev * 8);
    }
    wg_wait<0>();
    if (nrel == NKB) mbar_arrive_cl(ebar + (t < 2 ? sw : sa) * 8);
    reg_fence<N / 2>(acc);
    if ((threadIdx.x & 255) == 0) TS(tsid + 1);
}

template <int PART>
__device__ __forceinline__ void gemm3(uint32_t sb, int rb, int j, int half, int row, int c, unsigned ones) {
    constexpr int N = 64 + (PART ? RB3 : RA3), NQ = N / 8;
    constexpr int HO = PART ? HO_B : HO_A;
    float acc[N / 2];
    float2 cr[NQ];
    if (PART) {
        gemm_loop<N, false, 1, 1, true>(acc, sb, half, 20, 20, 0, 0, 0, 50);
        bar_arrive(9, 512);
    }
    mbar_wait(sb + SM_BAR + BAR_CS * 8, 0);
    const uint32_t csa = sb + SM_CS + PART * (256 + 4 * RA3) + 8 * c;
#pragma unroll
    for (int q = 0; q < NQ; q++) if (q < CSP) cr[q] = lds64f(csa + 32 * q);
    uint4 rp;
    if (PART) {
        mbar_wait(sb + SM_BAR + BAR_G * 8, 0);
        const float2* sp = &g_st[(rb * 8 + 2 * c) * 128 + row];
        const uint2 s0 = ldcg64(sp), s1 = ldcg64(sp + 128), s2 = ldcg64(sp + 8), s3 = ldcg64(sp + 136);
        float a0 = __uint_as_float(s0.x) + __uint_as_float(s1.x), b0 = __uint_as_float(s0.y) + __uint_as_float(s1.y);
        float a1 = __uint_as_float(s2.x) + __uint_as_float(s3.x), b1 = __uint_as_float(s2.y) + __uint_as_float(s3.y);
#pragma unroll
        for (int m = 1; m <= 2; m <<= 1) {
            a0 += __shfl_xor_sync(0xffffffffu, a0, m); b0 += __shfl_xor_sync(0xffffffffu, b0, m);
            a1 += __shfl_xor_sync(0xffffffffu, a1, m); b1 += __shfl_xor_sync(0xffffffffu, b1, m);
        }
        const float inv0 = half_rstd(a0, b0), inv1 = half_rstd(a1, b1);
        rp = make_uint4(PGELU ? pack2(inv0, inv0) : __float_as_uint(inv0), __float_as_uint(a0 * (-1.0f / D_)),
                        PGELU ? pack2(inv1, inv1) : __float_as_uint(inv1), __float_as_uint(a1 * (-1.0f / D_)));
        if (c == 0) sts128(sb + SM_RP + ((threadIdx.x & 255) >> 2) * 16, rp);
        bar_arrive(13, 512);
    }
    gemm_loop<N, false, 10 - PART, 10 - PART, !PART>(acc, sb, half, 20 + (10 - NA) * PART, 21 + 10 * PART, PART ? 9 : 10 - NA, 9 + PART, HO < 0 ? 10 + PART : 0, 46 + 2 * PART);
    if ((threadIdx.x & 255) == 0) mbar_expect(sb + SM_BAR + BAR_ME * 8, 0);
    if (!PART) {
        bar_sync(13, 512);
        rp = lds128(sb + SM_RP + ((threadIdx.x & 255) >> 2) * 16);
    }
    const float nb0 = __uint_as_float(rp.y), nb1 = __uint_as_float(rp.w);
    const uint32_t own = sb + SM_RA + ((39 - NA) % NA) * SLOT + row * 16 + c * 4;
    if (PART && OWNG) mbar_wait(sb + SM_BAR + (BAR_FA + (39 - NA) % NA) * 8, ((39 - NA) / NA) & 1);
    uint32_t* dst = reinterpret_cast<uint32_t*>(g_g) + (rb * 216 + HB0 / 8 * PART + 8 * j) * 512 + row * 4 + c;
    auto act = [&](int q, int r) {
        const float nb = r ? nb1 : nb0;
        const uint32_t inv = r ? rp.z : rp.x;
        const float t0 = fmaf(nb, cr[q].x, acc[4 * q + 2 * r]), t1 = fmaf(nb, cr[q].y, acc[4 * q + 2 * r + 1]);
        return gelu2_h(bmul2(pack2(t0, t1), inv));
    };
    uint32_t* dst1 = dst + (56 - (16 - NQ) * j) * 512;
#pragma unroll
    for (int k = 0; k < NQ; k += CH3) {
        if (k == HO) bar_arrive(10 + PART, 512);
        CHUNK(k) {
#pragma unroll
            for (int q = k; q < k + CH3 && q < NQ; q++) {
                if (q + CSP < NQ) cr[q + CSP] = lds64f(csa + 32 * (q + CSP));
                const uint32_t u = act(q, 0), v = act(q, 1);
                (q < 8 ? dst : dst1)[q * 512] = u;
                (q < 8 ? dst : dst1)[q * 512 + 32] = v;
                if (PART && OWNG && q < 8) { sts32(own + q * 2048, u); sts32(own + q * 2048 + 128, v); }
            }
            if (PART && OWNG && k < 8 && k + CH3 >= 8) fence_async_smem();
        }
    }
    bar_arrive(1 + PART, 288);
    if (HO >= NQ) bar_arrive(10 + PART, 512);
}

template <int NS, int BASE, int BF, int BE> struct Ring {
    uint32_t sb, st, ph;
    __device__ __forceinline__ uint32_t acquire(uint32_t bytes) {
        mbar_wait(sb + SM_BAR + BE * 8 + st * 8, ph);
        uint32_t fb = sb + SM_BAR + BF * 8 + st * 8;
        mbar_expect(fb, bytes);
        return fb;
    }
    __device__ __forceinline__ uint32_t slot() { return sb + BASE + st * SLOT; }
    __device__ __forceinline__ void next() { if (++st == NS) { st = 0; ph ^= 1; } }
    __device__ __forceinline__ void run2d(const CUtensorMap* m, int c1) {
#pragma unroll 1
        for (int c0 = 64; c0 < D_; c0 += 64) {
            uint32_t fb = acquire(SLOT);
            tma2d(slot(), m, c0, c1, fb);
            next();
        }
    }
    static __device__ __forceinline__ int korder(int i, int own) { return i == 0 ? own : i > own ? i : i - 1; }
    __device__ __forceinline__ void runw(bool paired, int rk, const CUtensorMap* ma, const CUtensorMap* mb, int ca, int cb, int i0, int i1, int own, uint32_t bytes, int gate_at, uint32_t gate) {
        if (paired) {
            const CUtensorMap* m = rk ? mb : ma;
            const int c0 = rk ? cb : ca;
#pragma unroll 1
            for (int i = i0; i < i1; i++) {
                const int c1 = korder(i, own) * 64;
                if (i == gate_at) mbar_wait(gate, 0);
                uint32_t fb = acquire(bytes);
                tma2d_mc(slot() + 8192 * rk, m, c0, c1, fb);
                next();
            }
        } else {
#pragma unroll 1
            for (int i = i0; i < i1; i++) {
                const int c1 = korder(i, own) * 64;
                uint32_t fb = acquire(bytes);
                tma2d(slot(), ma, ca, c1, fb);
                tma2d(slot() + 8192, mb, cb, c1, fb);
                next();
            }
        }
    }
    __device__ __forceinline__ void run1d(const char* src, int i0, int i1, int own) {
#pragma unroll 1
        for (int i = i0; i < i1; i++) {
            const char* s = src + korder(i, own) * SLOT;
            uint32_t fb = acquire(SLOT);
            bulk_g2s(slot(), s, SLOT, fb);
            next();
        }
    }
};

__global__ void __cluster_dims__(2, 1, 1) __launch_bounds__(NTHREADS, 1) fused_kernel(const Params p, const __grid_constant__ Maps maps) {
    extern __shared__ __align__(1024) unsigned char smem_raw[];
    const uint32_t sb = (smem_u32(smem_raw) + 1023u) & ~1023u;
#pragma unroll
    for (int i = 0; i < SEED; i++) asm volatile("{.reg .b32 t; mov.u32 t, %laneid;}");
    const uint32_t bars = sb + SM_BAR;
    const int tid = threadIdx.x, lane = tid & 31;
    unsigned smid;
    asm volatile("mov.u32 %0, %%smid;" : "=r"(smid));
    const bool spare = (smid >> 2) == 30;
    const int cta = smid < 120 ? smid : smid - 4;
    const int pg = cta >> 4, pi = cta & 15;
    auto chan = [&](int cc) { return 80 * pg + (cc < 3 ? 3 * pi + cc : 45 + 2 * pi + cc); };
    const int hb = tid >= 320;
    if (!spare) {
        const unsigned t = tid - 320 * hb, r32 = t / 10u, cc = t - r32 * 10u, row = r32 + 64 * hb;
        const unsigned go = (unsigned)(pi * 128 * 1280 + pg * 160) + row * 1280u + cc * 16u;
        const uint32_t so = sb + (row >> 4) * 32u + row * 160u + cc * 16u;
        const char* kb = (const char*)p.k + go;
        const char* vb = (const char*)p.v + go;
        if (hb) {
            if (tid >= 640 - NBARS) {
                const int i = 639 - tid;
                mbar_init(bars + i * 8, (i >= BAR_EB && i < BAR_K) ? 4 : ((i >= BAR_EA && i < BAR_EB) || i == BAR_XY) ? 2 : 1);
                asm volatile("fence.mbarrier_init.release.cluster;" ::: "memory");
            }
            bar_arrive(14, 640);
            if (B_DELAY) spin(B_DELAY);
        }
        cpasync16(so + SM_PK + 2592, kb, 16);
        cpasync16(so + SM_PV, vb, 16);
        cpasync16(so + SM_PK + 3 * 2592, kb + 32 * 1280, 16);
        cpasync16(so + SM_PV + 2 * 2592, vb + 32 * 1280, 16);
        if (tid < 30) cpasync16(so + SM_PK + 13 * 160, pi ? kb - 3 * 1280 : kb, pi ? 16 : 0);
        asm volatile("cp.async.commit_group;" ::: "memory");
    }
    const int warp = __shfl_sync(0xffffffffu, tid >> 5, 0);
    const int wg = warp >> 2, wq = warp & 3;
    unsigned ep0 = 0;
    if (wg == 4 || spare) ep0 = *(volatile unsigned*)&g_epoch[smid];
#define ep1 (ep0 + 1)

    if (spare) {
        const int sp = smid & 3;
        if (tid == 32) { sts32(sb + SM_GV + 512, smid); asm volatile("fence.release.sync_restrict::shared::cta.cluster;" ::: "memory"); }
        asm volatile("barrier.cluster.arrive.relaxed.aligned;" ::: "memory");
        asm volatile("barrier.cluster.wait.aligned;" ::: "memory");
        if (tid == 0) {
            for (int i = 0; i < 4; i++) mbar_init(bars + i * 8, 1);
            asm volatile("fence.mbarrier_init.release.cluster;" ::: "memory");
        }
        if (warp == 0) { if (lane < 8) flag_wait(FL_P + lane, ep1 * 16); __syncwarp(); }
        __syncthreads();
        const int cq = tid % 54, rg = tid / 54;
        float a[8];
#pragma unroll
        for (int i = 0; i < 8; i++) a[i] = 0.f;
#pragma unroll 1
        for (int it = -4; it < 10; it++) {
            const uint32_t st = sb + (it & 3) * 55296, fb = bars + (it & 3) * 8;
            if (it >= 0) {
                mbar_wait(fb, (it >> 2) & 1);
                if (tid < 432) {
#pragma unroll 2
                    for (int i = 0; i < 8; i++) {
                        uint4 w = lds128(st + (cq >= 27 ? 27648 - 432 : 0) + (rg * 8 + i) * 432 + cq * 16);
                        a[0] += blo(w.x); a[1] += bhi(w.x); a[2] += blo(w.y); a[3] += bhi(w.y);
                        a[4] += blo(w.z); a[5] += bhi(w.z); a[6] += blo(w.w); a[7] += bhi(w.w);
                    }
                }
                __syncthreads();
            }
            if (it < 6 && warp == 19 && elect()) {
                mbar_expect(fb, 55296);
                tma2d(st, &maps.w3s, sp * 432, (it + 4) * 64, fb);
                tma2d(st + 27648, &maps.w3s, sp * 432 + 216, (it + 4) * 64, fb);
            }
        }
        if (warp == 19 && elect()) {
#pragma unroll 1
            for (int i = 0; i < 27; i++) bulk_prefetch((const char*)p.w4 + sp * 552960 + i * 20480, 20480);
        }
        if (tid < 432) {
            sts128f(sb + rg * 1728 + cq * 32, a[0], a[1], a[2], a[3]);
            sts128f(sb + rg * 1728 + cq * 32 + 16, a[4], a[5], a[6], a[7]);
        }
        __syncthreads();
        if (tid < 432) {
            float s = 0.f;
#pragma unroll
            for (int i = 0; i < 8; i++) s += __uint_as_float(lds32(sb + i * 1728 + tid * 4));
            g_cs[sp * 432 + tid] = s;
        }
        __syncthreads();
        if (tid == 0) { flag_release(FL_CS); g_epoch[smid] = ep1; TS(0); }
        if (warp == 0) TSFLUSH();
        return;
    }

    int gpc, idx;
    if (smid < 64) { gpc = (smid & 15) >> 1; idx = (smid >> 4) * 2 + (smid & 1); }
    else if (smid < 120) { int t = smid - 64; gpc = 1 + (t % 14) / 2; idx = 8 + (t / 14) * 2 + (smid & 1); }
    else { gpc = 0; idx = 8 + (smid - 124); }
    const int rb = 2 * gpc + (idx & 1), j = idx >> 1;
    const int g = lane >> 2, c = lane & 3;
    const int cm = 160 * (j >> 1) + 64 * (j & 1) + ((j & 2) ? 32 : 0), cr = 160 * (j >> 1) + 16 * (j & 1) + ((j & 2) ? 0 : 128);

    {
        if (warp == 5) TSW(61);
        const int w10 = warp - 10 * hb, h = w10 >= 5;
        const int pr = (w10 - 5 * h) * 8 + (lane >> 2), blk = 4 * hb + (lane & 3);
        const int ch = 80 * pg + 2 * pr;
        const uint4 sw = __ldg(reinterpret_cast<const uint4*>(p.shift + ch * 4));
        uint32_t dv = 0;
        if (warp == 9 && lane < 5) dv = __bfloat16_as_ushort(p.ssmD[chan(lane)]);
        if (tid == 512) { sts32(sb + SM_GV + 512, smid); asm volatile("fence.release.sync_restrict::shared::cta.cluster;" ::: "memory"); }
        asm volatile("barrier.cluster.arrive.relaxed.aligned;" ::: "memory");
        if (warp == 11 && lane < 13) prefetch_map(&maps.hn + lane);
        if (wg < 4) {
            const int t = tid & 127, cc = (wg == 3 && t >= 64) ? 4 : wg;
            if (t < 64 || wg == 3) sts128(sb + sm_u(cc) + ((t >> 5) & 1) * U_PLANE + 2048 + lane * 16, make_uint4(0, 0, 0, 0));
            if ((t & 63) < 4 && (t < 64 || wg == 3)) sts128(sb + sm_k(cc) + ((t >> 1) & 1) * 4160 + (t & 1) * 16, make_uint4(0, 0, 0, 0));
        }
        if (warp == 9 && lane < 5) sts32(sb + SM_GV + 520 + lane * 4, dv << 16);
        asm volatile("cp.async.wait_group 0;" ::: "memory");
        if (!hb) bar_arrive(12, 640);
        bar_sync(hb ? 12 : 14, 640);
        if (warp == 9) {
            if (SSM_DELAY) spin(SSM_DELAY);
            if (elect()) {
#pragma unroll
                for (int i = 0; i < SSM_N; i++) {
                    mbar_expect(bars + (BAR_K + i) * 8, 4096);
                    bulk_g2s(sb + sm_k(i) + 32, p.ssmk + (size_t)(chan(i)) * S_, 4096, bars + (BAR_K + i) * 8);
                }
            }
        }
        const uint32_t w0 = prmt(sw.x, sw.z, 0x5410), w1 = prmt(sw.x, sw.z, 0x7632), w2 = prmt(sw.y, sw.w, 0x5410), w3 = prmt(sw.y, sw.w, 0x7632);
        const uint32_t ka = sb + SM_PK + 2592 + blk * 2592 + h * 1280 + pr * 4;
        const uint32_t va = sb + SM_PV + blk * 2592 + h * 1280 + pr * 4;
        uint32_t kk[11], kv[8];
#pragma unroll
        for (int i = 0; i < 11; i++) kk[i] = lds32(ka + (i - 3) * 160 - ((i < 3 && h == 0) ? 32 : 0));
#pragma unroll
        for (int i = 0; i < 8; i++) {
            uint32_t t = badd2(badd2(badd2(bmul2(kk[i], w3), bmul2(kk[i + 1], w2)), bmul2(kk[i + 2], w1)), bmul2(kk[i + 3], w0));
            kv[i] = bmul2(t, lds32(va + i * 160));
        }
        uint4 o0, o1;
        o0.x = prmt(kv[1], kv[0], 0x5410); o0.y = prmt(kv[3], kv[2], 0x5410); o0.z = prmt(kv[5], kv[4], 0x5410); o0.w = prmt(kv[7], kv[6], 0x5410);
        o1.x = prmt(kv[1], kv[0], 0x7632); o1.y = prmt(kv[3], kv[2], 0x7632); o1.z = prmt(kv[5], kv[4], 0x7632); o1.w = prmt(kv[7], kv[6], 0x7632);
        uint4* dst = reinterpret_cast<uint4*>(g_kvT) + ch * 256 + h * 128 + (127 - (8 * pi + blk));
        dst[0] = o0;
        dst[256] = o1;
    }

    const int rho = 8 * rb + j;

    if (wg == 4) {
        asm volatile("setmaxnreg.dec.sync.aligned.u32 32;");
        if (wq == 0) {
            bar_sync(13, 640);
            TSW(39);
            if (lane == 0) flag_release(FL_P + pg);
            __syncwarp();
            TSW(2);
            if (lane < 5) mbar_expect(bars + (BAR_U + lane) * 8, 4096);
            flag_wait(FL_P + pg, ep1 * 16);
            fence_async_global();
            TSW(3);
            if (elect()) {
#pragma unroll
                for (int i = 0; i < 5; i++) {
                    const char* us = (const char*)g_kvT + (size_t)(chan(i)) * 4096;
                    bulk_g2s(sb + sm_u(i), us, 2048, bars + (BAR_U + i) * 8);
                    bulk_g2s(sb + sm_u(i) + U_PLANE, us + 2048, 2048, bars + (BAR_U + i) * 8);
                }
            }
            __syncwarp();
            if (elect()) {
#pragma unroll
                for (int i = SSM_N; i < 5; i++) {
                    mbar_expect(bars + (BAR_K + i) * 8, 4096);
                    bulk_g2s(sb + sm_k(i) + 32, p.ssmk + (size_t)(chan(i)) * S_, 4096, bars + (BAR_K + i) * 8);
                }
                if (cta < 120) {
                    mbar_expect(bars + BAR_WM * 8, 40960);
#pragma unroll 1
                    for (int i = 0; i < 5; i++) tma2d(sb + SM_WM + i * 8192, &maps.wm, cta * 32, i * 128, bars + BAR_WM * 8);
                }
                bulk_prefetch((const char*)p.q + cta * 20480, 20480);
                bulk_prefetch((const char*)p.w1 + cta * 6400, 6400);
                bulk_prefetch((const char*)p.w2 + cta * 6400, 6400);
            }
            __syncwarp();
        } else {
            bar_arrive(13, 640);
        }
        asm volatile("barrier.cluster.wait.aligned;" ::: "memory");
        uint32_t peer;
        asm volatile("ld.shared::cluster.u32 %0, [%1];" : "=r"(peer) : "r"(mapa(sb + SM_GV + 512, (blockIdx.x & 1) ^ 1)) : "memory");
        const bool paired = peer == (smid ^ 1);
        if (tid == 639) sts32(sb + SM_GV + 516, paired);
        if (cta < 120) {
            float d[4];
            if (tid < 592) {
                const int t = tid - 512;
                mbar_wait(bars + BAR_U * 8, 0);
                uint4 cv = __ldg(reinterpret_cast<const uint4*>(p.c) + t);
                auto silu2 = [](uint32_t v) { float a = blo(v), b = bhi(v); return pack2(__fdividef(a, 1.0f + __expf(-a)), __fdividef(b, 1.0f + __expf(-b))); };
#pragma unroll 1
                for (int i = 0; i < 4; i++) { const uint32_t r = silu2(cv.x); cv.x = cv.y; cv.y = cv.z; cv.z = cv.w; cv.w = r; }
                sts128(sb + SM_Y + (t % 40) * 32 + (t / 40) * 16, cv);
                fence_async_smem();
            }
            bar_sync(5, 128);
            mbar_wait(bars + BAR_WM * 8, 0);
            if (wq == 3) TSW(56);
            const uint32_t da = desc_lo(sb + SM_WM, 20480), db = desc_lo(sb + SM_Y, 32);
#pragma unroll 1
            for (int k0 = 0; k0 < 20; k0 += 4) {
                wg_fence();
#pragma unroll
                for (int k = k0; k < k0 + 4; k++) asm volatile("{.reg .pred p; .reg .b32 l,m; .reg .b64 da,db; setp.ne.b32 p,%10,0; add.u32 l,%4,%6; mov.b64 da,{l,%8}; add.u32 m,%5,%7; mov.b64 db,{m,%9};"
                             " wgmma.mma_async.sync.aligned.m64n8k16.f32.bf16.bf16 {%0,%1,%2,%3},da,db,p,1,1,1,0;}"
                             : "+f"(d[0]), "+f"(d[1]), "+f"(d[2]), "+f"(d[3])
                             : "r"(da), "r"(db), "r"(64 * k), "r"(4 * k), "n"(desc_hi(512, 2u)), "n"(desc_hi(128, 0)), "r"(k));
                wg_commit();
            }
            wg_wait<0>();
            reg_fence<4>(d);
            if (c == 0) {
                sts32(sb + SM_GV + (16 * wq + g) * 4, __float_as_uint(wq < 2 ? d[0] : d[1]));
                sts32(sb + SM_GV + (16 * wq + g + 8) * 4, __float_as_uint(wq < 2 ? d[2] : d[3]));
            }
            bar_sync(5, 128);
            if (wq == 2) {
                g_mod[cta * 32 + lane] = __float2bfloat16_rn(__uint_as_float(lds32(sb + SM_GV + lane * 4)) + __uint_as_float(lds32(sb + SM_GV + 128 + lane * 4)));
            }
        }
        if (wq == 2) {
            bar_sync(9, 320);
            if (lane == 0) flag_release(FL_M);
            __syncwarp();
            TSW(4);
            flag_wait(FL_M, ep1 * 128);
            fence_async_global();
            if (elect()) {
                mbar_expect(bars + BAR_M * 8, 7680);
                bulk_g2s(sb + SM_MOD, g_mod, 7680, bars + BAR_M * 8);
                mbar_wait(bars + BAR_CD * 8, 0);
                mbar_expect(bars + BAR_Y * 8, 12288);
#pragma unroll 1
                for (int i = 0; i < 8; i++) bulk_g2s(sb + SM_Y + i * 2560, g_yv + rho * 5120 + i * 640, 1536, bars + BAR_Y * 8);
            }
            __syncwarp();
            TSW(60);
            bar_sync(8, 576);  if (lane == 0) { flag_release(FL_R + rb); TS(23); }  __syncwarp();
            bar_sync(15, 288); if (lane == 0) { flag_release(FL_B1 + rb); TS(27); } __syncwarp();
            bar_sync(6, 288);  if (lane == 0) { flag_release(FL_B2 + rb); TS(31); } __syncwarp();
#pragma unroll 1
            for (int i = 0; i < 3; i++) { bar_sync(i ? i : 8, 288); if (lane == 0) { TS(53 + (i + 2) % 3); flag_release(FL_G + 16 * i + rb); TS(57 + (i + 2) % 3); } __syncwarp(); }
            if (lane == 0) g_epoch[smid] = ep1;
            return;
        }
        if (wq == 1) {
            bar_sync(9, 320);
            if (lane < 4 * NB) mbar_arrive_cl(mapa(bars + (BAR_EB + (lane >> 2)) * 8, paired ? lane & 1 : blockIdx.x & 1));
        }
        if (wq == 3) {
            bar_sync(7, 544);
            if (lane == 0) { flag_release(FL_C); mbar_expect(bars + BAR_CD * 8, 0); TS(20); }
            __syncwarp();
            if (lane == 0) mbar_expect(bars + BAR_Y2 * 8, 8192);
            flag_wait(FL_C, ep1 * 128);
            fence_async_global();
            TSW(21);
            if (elect()) {
#pragma unroll
                for (int i = 0; i < 8; i++) bulk_g2s(sb + SM_Y + i * 2560 + 1536, g_yv + rho * 5120 + i * 640 + 384, 1024, bars + BAR_Y2 * 8);
            }
            __syncwarp();
        }
        if (wq == 3) {
            mbar_wait(bars + BAR_Y2 * 8, 0);
            if (elect()) {
                mbar_expect(bars + BAR_XY * 8, 20480);
#pragma unroll 1
                for (int i = 0; i < 8; i++) {
                    bulk_g2s(sb + SM_YT + i * 2560, g_yv + (8 * rb + i) * 5120 + cm * 8, 2048, bars + BAR_XY * 8);
                    bulk_g2s(sb + SM_YT + i * 2560 + 2048, g_yv + (8 * rb + i) * 5120 + cr * 8, 512, bars + BAR_XY * 8);
                }
            }
            __syncwarp();
            bar_sync(8, 576);
            mbar_wait_warm(bars + BAR_FA * 8, 0);
            mbar_wait(bars + BAR_ME * 8, 0);
            mbar_wait_warm(bars + (BAR_FA + 11 % NA) * 8, (11 / NA) & 1);
            flag_wait(FL_CS, ep1 * 4);
            fence_async_global();
            if (elect()) {
                mbar_expect(bars + BAR_CS * 8, 864);
                bulk_g2s(sb + SM_CS, g_cs + 64 * j, 256, bars + BAR_CS * 8);
                bulk_g2s(sb + SM_CS + 256, g_cs + 512 + RA3 * j, 4 * RA3, bars + BAR_CS * 8);
                bulk_g2s(sb + SM_CS + 256 + 4 * RA3, g_cs + HB0 + 64 * j, 256, bars + BAR_CS * 8);
                bulk_g2s(sb + SM_CS + 512 + 4 * RA3, g_cs + HB0 + 512 + RB3 * j, 4 * RB3, bars + BAR_CS * 8);
            }
            __syncwarp();
            mbar_wait(bars + BAR_ME * 8, 1);
            mbar_wait_warm(bars + (BAR_FA + 21 % NA) * 8, (21 / NA) & 1);
#pragma unroll 1
            for (int i = 0; i < 3; i++) {
                if (i) {
                    mbar_wait(bars + BAR_ME * 8, (i + 1) & 1);
                    for (int n = i; n < NPING; n++) { spin(PING); n += tensor_ping(); }
                }
                flag_wait(FL_G + 16 * i + rb, ep1 * 8);
                if (lane == 0) { mbar_expect(bars + (BAR_G + i) * 8, 0); TS(35 + (i + 2) % 3); }
                __syncwarp();
            }
            return;
        }
        if (elect()) {
            if (wq == 1) {
                Ring<NB, SM_RB, BAR_FB, BAR_EB> r{sb, 0, 0};
#pragma unroll 1
                for (int ph = 0; ph < 7; ph++) {
                    const CUtensorMap* ma = ph == 0 ? &maps.w1a : ph == 1 ? &maps.w2a : ph == 6 ? &maps.w4a : &maps.w3a;
                    const bool b3b = ph == 2 || ph == 4 || ph == 5;
                    r.runw(paired, idx & 1, ma, ma + (b3b ? 2 : 1), ph == 3 ? 64 * j : b3b ? HB0 + 64 * j : cm,
                           ph == 3 ? 512 + RA3 * j : b3b ? HB0 + 512 + RB3 * j : cr, ph == 4 ? 10 - NA : ph == 5 ? 1 : 0,
                           ph == 6 ? 27 : ph == 5 ? 10 - NA : ph == 2 ? 1 : 10, ph == 0 ? 0 : ph == 6 ? OWNG * (HB0 / 64 + j) : cm >> 6,
                           ph == 3 ? 8192 + 128 * RA3 : b3b ? 8192 + 128 * RB3 : 10240,
                           ph == 1 ? GATE : ph == 3 ? GATE - 1 : -1, bars + (BAR_ST - (ph == 1)) * 8);
                }
            } else {
                Ring<NA, SM_RA, BAR_FA, BAR_EA> r{sb, 0, 0};
                if (cta >= 120) mbar_wait(bars + (BAR_K + 4) * 8, 0);
                mbar_expect(bars + BAR_XR * 8, 20480);
                bulk_g2s(sb + SM_XR, p.q + (size_t)rho * 16 * D_, 20480, bars + BAR_XR * 8);
                mbar_wait(bars + BAR_Y2 * 8, 0);
                mbar_expect(bars + BAR_XY * 8, 20480);
                tma2d(sb + SM_XT, &maps.xa, cm, rb * 128, bars + BAR_XY * 8);
                tma2d(sb + SM_XT2, &maps.xb, cr, rb * 128, bars + BAR_XY * 8);
                const int grp = j >> 1;
                const int delta = (grp & 1 ? 1 : -1) * (1 + (grp >> 1));
                const int nb = min(max(rb + (delta > 0 ? 1 : -1), 0), 15);
                uint32_t fb = r.acquire(SLOT), dst = r.slot();
                flag_wait2(FL_R + nb, FL_R + rb, ep1 * 8);
                fence_async_global();
                tma2d(dst, &maps.hn, 0, rb * 128 + delta, fb);
                TS(24);
                r.next();
                r.run2d(&maps.hn, rb * 128 + delta);
#pragma unroll 1
                for (int i = 0; i < 2; i++) {
                    const char* src = (const char*)(i ? g_x1 : g_h1) + (size_t)rb * 163840;
                    r.acquire(0); r.next();
                    fb = r.acquire(SLOT); dst = r.slot();
                    const char* src1 = src + (cm == 0 ? SLOT : 0);
                    flag_wait(FL_B1 + 16 * i + rb, ep1 * 8);
                    fence_async_global();
                    bulk_g2s(dst, src1, SLOT, fb);
                    TS(28 + 4 * i);
                    mbar_expect(bars + (BAR_ST - 1 + i) * 8, 0);
                    r.next();
                    r.run1d(src, 2, 10, cm >> 6);
                }
                r.run1d((const char*)g_x1 + (size_t)rb * 163840, 1, 10 - NA, cm >> 6);
                if (OWNG) { r.acquire(0); r.next(); }
#pragma unroll 1
                for (int i = 0; i < 2; i++) {
                    mbar_wait(bars + (BAR_G + 1 + i) * 8, 0); fence_async_global();
                    r.run1d((const char*)g_g + (size_t)rb * 442368, OWNG + HB0 / 64 * i, i ? 27 : OWNG + HB0 / 64, OWNG * (HB0 / 64 + j));
                }
            }
        }
        return;
    }
    bar_arrive(13, 640);
    asm volatile("setmaxnreg.inc.sync.aligned.u32 112;");
    const int rrow = 16 * rho + (warp >> 1) + 8 * (warp & 1);

    fence_async_smem();
    bar_sync(1 + wg, 128);
#pragma unroll 1
    for (int cc = wg; cc < wg + 1 + (wg == 3); cc++) {
        mbar_wait(bars + (BAR_K + cc) * 8, 0);
        if (cc == 2 && wq == 0) TSW(40);
        uint32_t a = sb + sm_k(cc) + 32 + (tid & 127) * 32;
        uint32_t pw = lds32(a - 4);
        uint4 x = lds128(a), y = lds128(a + 16), o;
        if ((tid & 127) == 0) {
            uint16_t k0 = __bfloat16_as_ushort(__float2bfloat16_rn(blo(x.x) + __uint_as_float(lds32(sb + SM_GV + 520 + cc * 4))));
            x.x = (x.x & 0xffff0000u) | k0;
            sts16(a, k0);
        }
        o.x = prmt(pw, x.x, 0x5432); o.y = prmt(x.x, x.y, 0x5432); o.z = prmt(x.y, x.z, 0x5432); o.w = prmt(x.z, x.w, 0x5432);
        sts128(a + 4160, o);
        o.x = prmt(x.w, y.x, 0x5432); o.y = prmt(y.x, y.y, 0x5432); o.z = prmt(y.y, y.z, 0x5432); o.w = prmt(y.z, y.w, 0x5432);
        sts128(a + 4176, o);
    }
    bar_sync(1 + wg, 128);
    if (wg == 3) bar_arrive(11, 256);
#pragma unroll 1
    for (int cc = wg; cc < 5; cc += 3) {
        if (cc == 3 && wg == 0) break;
        if (cc == 4) bar_sync(11, 256);
        const uint32_t kaddr = sb + sm_k(cc) + ((g & 1) ? 32 : 4192) + 4 * ((g >> 1) - c) + 64 * wq;
        const AFrag f0 = ldA(kaddr), f1 = ldA(kaddr + 256);
        if (STAG && cc == 3) bar_sync(12, 256);
        mbar_wait(bars + (BAR_U + cc) * 8, 0);
        if (wq == 0) TSW(5 + cc);
        float d[64];
        conv_two<0>(d, f0, f1, kaddr, desc_lo(sb + sm_u(cc), U_PLANE), sb + sm_red(cc) + wq * 4352 + g * 544 + c * 8, cc == 1);
        if (wq == 0) TSW(10 + cc);
        if (cc == 1) bar_arrive(6, 256);
    }
#pragma unroll 1
    for (int cc = wg == 1 ? 4 : wg;; cc++) {
        if (cc == 1) bar_sync(6, 256); else bar_sync(1 + wg, 128);
        const int ch = chan(cc);
        uint32_t* dst = g_yv + ch * 8 + ((g + (ch >> 2)) & 7) + (126 - 32 * wq - 2 * c) * 5120;
        uint2 v[16];
#pragma unroll
        for (int i = 0; i < 16; i++) v[i] = lds64(sb + sm_red(cc) + g * 544 + wq * 128 + c * 8 + (i >> 2) * 32 + (i & 3) * 4360);
#pragma unroll
        for (int w = 1; w < 4; w++)
            if (wq == 3 && c > 3 - w) v[12 + w] = make_uint2(0, 0);
#pragma unroll
        for (int q = 0; q < 4; q++) {
            const uint2* u = v + 4 * q;
            dst[-8 * q * 5120] = badd2(u[0].x, badd2(u[1].x, badd2(u[2].x, u[3].x)));
            dst[(-8 * q + 1) * 5120] = badd2(u[0].y, badd2(u[1].y, badd2(u[2].y, u[3].y)));
        }
        if (wq == 0) TSW(15 + cc);
        if (cc != 0) break;
    }
    fence_async_smem();
    if (!(wg & 1)) bar_arrive(9, 320);
    bar_arrive(7, 544);

    const uint32_t one2 = 0x3f803f80u;
    const unsigned ones = p.ones;
    {
        uint32_t x[10], a[10], cb[10], sbv[10];
        if (RPRE_WAIT) bar_sync(10, 512);
        mbar_wait(bars + BAR_XR * 8, 0);
#pragma unroll
        for (int i = 0; i < 10; i++) x[i] = lds32(sb + SM_XR + (rrow & 15) * 1280 + lane * 4 + i * 128);
        const uint3 s1 = row_stats(x, lane);
        const int up = lane >> 4, gg = warp >> 1, e = warp & 1;
        const uint32_t ya = sb + SM_Y + lane * 64 + ((gg + (lane >> 1)) & 7) * 4;
        const uint32_t sel = (up ? 0x1054u : 0x5410u) + (e ? 0x2222u : 0u);
        const uint32_t ma = sb + SM_MOD + lane * 4;
        mbar_wait(bars + BAR_M * 8, 0);
        uint32_t pin = 0;
#pragma unroll
        for (int i = 0; i < 10; i++) {
            uint32_t h = bfma2(ln_apply(x[i], s1.x, s1.y, s1.z), badd2(lds32(ma + 1280 + i * 128), one2), lds32(ma + i * 128));
            a[i] = bmul2(h, lds32(ma + 2560 + i * 128));
            sbv[i] = lds32(ma + 3840 + i * 128);
            cb[i] = badd2(lds32(ma + 5120 + i * 128), one2);
            pin ^= a[i] ^ cb[i];
        }
        if (pin & ~ones) sts32(sb + SM_GV, pin);
        if (warp == 4) TSW(52);
        mbar_wait(bars + BAR_Y * 8, 0);
        mbar_wait(bars + BAR_Y2 * 8, 0);
        if (warp == 0) TSW(22);
#pragma unroll
        for (int i = 0; i < 10; i++) {
            uint32_t y0 = lds32(ya + i * 2048 + up * 32), y1 = lds32(ya + i * 2048 + (up ^ 1) * 32);
            x[i] = bfma2(a[i], prmt(y0, y1, sel), x[i]);
        }
        const uint3 s2 = row_stats(x, lane);
#pragma unroll
        for (int i = 0; i < 10; i++) x[i] = bfma2(ln_apply(x[i], s2.x, s2.y, s2.z), cb[i], sbv[i]);
        const uint3 s3 = row_stats(x, lane);
        uint32_t* o = reinterpret_cast<uint32_t*>(g_hn + (size_t)rrow * D_) + lane;
#pragma unroll
        for (int i = 0; i < 10; i++) o[32 * i] = ln_apply(x[i], s3.x, s3.y, s3.z);
        if (lane < 2) g_rs[rrow * 2 + lane] = lane ? make_uint4(s2.x, s2.y, s2.z, 0) : make_uint4(s1.x, s1.y, s1.z, 0);
        if (warp == 0) TSW(34);
        bar_arrive(8, 576);
    }

    const int half = wg & 1;
    const int row = 64 * half + 16 * wq + g;
    const int tw0 = (rb * 80 + (cm >> 3)) * 512 + row * 4 + c, tw1 = (rb * 80 + (cr >> 3) - 8) * 512 + row * 4 + c;
    const uint32_t park = sb + SM_Y + (tid & 255) * 16;
    const uint32_t ms0 = sb + SM_MOD + (cm + 2 * c) * 2, ms1 = sb + SM_MOD + (cr - 64 + 2 * c) * 2;
    if (wg >= 2) {
        {
            float acc[40];
            gemm_loop<80, true, 10, 10, true>(acc, sb, half, 0, 0, 10, 0, 0, 25);
            if (tid == 256) mbar_expect(bars + BAR_ME * 8, 0);
#pragma unroll
            for (int k = 0; k < 10; k += CH) CHUNK(k) {
#pragma unroll
                for (int q = k; q < k + CH && q < 10; q++) {
                    uint32_t* dst = reinterpret_cast<uint32_t*>(g_h1) + (q < 8 ? tw0 : tw1);
                    const uint32_t u = gelu2_h(bmul2(pack2(acc[4 * q], acc[4 * q + 1]), 0x3f003f00u));
                    const uint32_t v = gelu2_h(bmul2(pack2(acc[4 * q + 2], acc[4 * q + 3]), 0x3f003f00u));
                    dst[q * 512] = u;
                    dst[q * 512 + 32] = v;
                    acc[4 * q] = __uint_as_float(u); acc[4 * q + 1] = __uint_as_float(v);
                }
            }
            bar_arrive(15, 288);
            mbar_wait(bars + (BAR_FA + 10 % NA) * 8, (10 / NA) & 1);
#pragma unroll
            for (int q = 0; q < 8; q++) {
                sts32(sb + SM_RA + (10 % NA) * SLOT + q * 2048 + row * 16 + c * 4, __float_as_uint(acc[4 * q]));
                sts32(sb + SM_RA + (10 % NA) * SLOT + q * 2048 + row * 16 + c * 4 + 128, __float_as_uint(acc[4 * q + 1]));
            }
            fence_async_smem();
            bar_arrive(14, 512);
        }
        gemm3<0>(sb, rb, j, half, row, c, ones);
        {
            float acc[40];
            uint32_t gbv[10], base[20];
#pragma unroll
            for (int q = 0; q < 10; q++) gbv[q] = lds32((q < 8 ? ms0 : ms1) + 6400 + q * 16);
#pragma unroll
            for (int q = 0; q < 5; q++) { const uint4 t = lds128(park + q * 4096); base[4 * q] = t.x; base[4 * q + 1] = t.y; base[4 * q + 2] = t.z; base[4 * q + 3] = t.w; }
            gemm_loop<80, false, 27, 27 - NB, true>(acc, sb, half, 39 - NA, 40, 27 - NA, 11, 0, 42);
            auto fin = [&](int q, int r) {
                return bfma2(gbv[q], pack2(acc[4 * q + 2 * r], acc[4 * q + 2 * r + 1]), base[2 * q + r]);
            };
            auto tr4 = [&](uint32_t t0, uint32_t t1, uint32_t t2, uint32_t t3) {
                const bool o1 = c & 1, o2 = c & 2;
                uint32_t a = __shfl_xor_sync(0xffffffffu, o1 ? t0 : t1, 1), b = __shfl_xor_sync(0xffffffffu, o1 ? t2 : t3, 1);
                uint32_t u0 = o1 ? a : t0, u1 = o1 ? t1 : a, u2 = o1 ? b : t2, u3 = o1 ? t3 : b;
                a = __shfl_xor_sync(0xffffffffu, o2 ? u0 : u2, 2); b = __shfl_xor_sync(0xffffffffu, o2 ? u1 : u3, 2);
                return o2 ? make_uint4(a, b, u2, u3) : make_uint4(u0, u1, a, b);
            };
            bf16* go = p.out + (size_t)(rb * 128 + row) * D_;
#pragma unroll
            for (int k = 0; k < 2; k++) CHUNK(k) {
#pragma unroll
                for (int r = 0; r < 2; r++)
                    *reinterpret_cast<uint4*>(go + r * 8 * D_ + cm + 32 * k + 8 * c) = tr4(fin(4 * k, r), fin(4 * k + 1, r), fin(4 * k + 2, r), fin(4 * k + 3, r));
            }
            CHUNK(2) *reinterpret_cast<uint4*>(go + (c >> 1) * 8 * D_ + cr + 8 * (c & 1)) = tr4(fin(8, 0), fin(9, 0), fin(8, 1), fin(9, 1));
            if (tid == 256) TS(44);
            if (warp == 8) TSFLUSH();
        }
    } else {
        {
            float acc[40];
            uint32_t x2[20];
            {
                uint32_t y[20];
                mbar_wait(bars + BAR_XY * 8, 0);
                const uint32_t xa = sb + SM_XT + row * 128 + c * 4, xb = sb + SM_XT2 + row * 32 + c * 4;
                const uint32_t ya = sb + SM_YT + (4 * half + wq) * 2560 + c * 64;
#pragma unroll
                for (int q = 0; q < 10; q++) {
                    const uint32_t a = q < 8 ? xa + ((q ^ g) << 4) : xb + (q - 8) * 16;
                    x2[2 * q] = lds32(a); x2[2 * q + 1] = lds32(a + (q < 8 ? 1024 : 256));
                    const int pos = (g + ((q < 8 ? cm : cr) >> 2) + 2 * q + (c >> 1)) & 7;
                    y[2 * q] = lds32(ya + q * 256 + pos * 4); y[2 * q + 1] = lds32(ya + q * 256 + 32 + pos * 4);
                }
                fence_async_smem();
                bar_sync(1 + wg, 128);
                if ((tid & 127) < NA) mbar_arrive_cl(mapa(bars + (BAR_EA + (tid & 127)) * 8, blockIdx.x & 1));
                mbar_wait(bars + (BAR_FA + 1) * 8, 0);
                const uint4* rp = g_rs + (rb * 128 + row) * 2;
                const uint4 ra = ldcg128(rp), rb2 = ldcg128(rp + 1), rc = ldcg128(rp + 16), rd = ldcg128(rp + 17);
                bar_sync(14, 512);
#pragma unroll
                for (int q = 0; q < 10; q++) {
                    const uint32_t ms = q < 8 ? ms0 : ms1;
                    const uint32_t sa = lds32(ms + 16 * q), ca = badd2(lds32(ms + 1280 + 16 * q), one2), ga = lds32(ms + 2560 + 16 * q);
                    const uint32_t sbv = lds32(ms + 3840 + 16 * q), cb = badd2(lds32(ms + 5120 + 16 * q), one2);
                    uint32_t u = x2[2 * q], v = x2[2 * q + 1];
                    u = bfma2(bmul2(bfma2(ln_apply(u, ra.x, ra.y, ra.z), ca, sa), ga), prmt(y[2 * q], y[2 * q + 1], 0x5410), u);
                    v = bfma2(bmul2(bfma2(ln_apply(v, rc.x, rc.y, rc.z), ca, sa), ga), prmt(y[2 * q], y[2 * q + 1], 0x7632), v);
                    x2[2 * q] = u; x2[2 * q + 1] = v;
                    u = bfma2(ln_apply(u, rb2.x, rb2.y, rb2.z), cb, sbv);
                    v = bfma2(ln_apply(v, rd.x, rd.y, rd.z), cb, sbv);
                    acc[4 * q] = blo(u); acc[4 * q + 1] = bhi(u); acc[4 * q + 2] = blo(v); acc[4 * q + 3] = bhi(v);
                }
            }
            reg_fence<40>(acc);
            if (tid == 0) TS(45);
            gemm_loop<80, false, 10, 10, false>(acc, sb, half, 10, 10, 10, 0, 0, 29);
            if (tid == 0) mbar_expect(bars + BAR_ME * 8, 0);
            uint32_t x1[20];
            float s0 = 0.f, q0 = 0.f, s1 = 0.f, q1 = 0.f;
#pragma unroll
            for (int q = 0; q < 10; q++) {
                uint32_t u = pack2(acc[4 * q], acc[4 * q + 1]);
                uint32_t v = pack2(acc[4 * q + 2], acc[4 * q + 3]);
                uint32_t* dst = reinterpret_cast<uint32_t*>(g_x1) + (q < 8 ? tw0 : tw1);
                dst[q * 512] = u;
                dst[q * 512 + 32] = v;
                x1[2 * q] = u; x1[2 * q + 1] = v;
            }
            bar_arrive(6, 288);
            CHUNK(0)
#pragma unroll
            for (int q = 0; q < 10; q++) {
                float a = blo(x1[2 * q]), b = bhi(x1[2 * q]), e = blo(x1[2 * q + 1]), f = bhi(x1[2 * q + 1]);
                s0 += a + b; q0 = fmaf(a, a, fmaf(b, b, q0));
                s1 += e + f; q1 = fmaf(e, e, fmaf(f, f, q1));
            }
#pragma unroll
            for (int m = 1; m <= 2; m <<= 1) {
                s0 += __shfl_xor_sync(0xffffffffu, s0, m); q0 += __shfl_xor_sync(0xffffffffu, q0, m);
                s1 += __shfl_xor_sync(0xffffffffu, s1, m); q1 += __shfl_xor_sync(0xffffffffu, q1, m);
            }
            if (c < 2) g_st[(rb * 8 + j) * 128 + row + 8 * c] = c ? make_float2(s1, q1) : make_float2(s0, q0);
            bar_arrive(8, 288);
            mbar_wait(bars + (BAR_FA + 20 % NA) * 8, (20 / NA) & 1);
#pragma unroll
            for (int q = 0; q < 8; q++) {
                sts32(sb + SM_RA + (20 % NA) * SLOT + q * 2048 + row * 16 + c * 4, x1[2 * q]);
                sts32(sb + SM_RA + (20 % NA) * SLOT + q * 2048 + row * 16 + c * 4 + 128, x1[2 * q + 1]);
            }
            fence_async_smem();
            bar_sync(3 + wg, 128);
#pragma unroll
            for (int q = 0; q < 5; q++) {
                const uint32_t ms = q < 4 ? ms0 : ms1;
                const uint32_t g0 = lds32(ms + 6400 + q * 32), g1 = lds32(ms + 6400 + q * 32 + 16);
                sts128(park + q * 4096, make_uint4(bfma2(g0, x1[4 * q], x2[4 * q]), bfma2(g0, x1[4 * q + 1], x2[4 * q + 1]),
                                                   bfma2(g1, x1[4 * q + 2], x2[4 * q + 2]), bfma2(g1, x1[4 * q + 3], x2[4 * q + 3])));
            }
        }
        gemm3<1>(sb, rb, j, half, row, c, ones);
    }
}

typedef CUresult (*EncFn)(CUtensorMap*, CUtensorMapDataType, cuuint32_t, void*, const cuuint64_t*, const cuuint64_t*,
                          const cuuint32_t*, const cuuint32_t*, CUtensorMapInterleave, CUtensorMapSwizzle,
                          CUtensorMapL2promotion, CUtensorMapFloatOOBfill);

void make_map(EncFn enc, CUtensorMap* m, const void* base, uint64_t inner, uint64_t outer, uint32_t bi, uint32_t bo,
              CUtensorMapSwizzle swz = CU_TENSOR_MAP_SWIZZLE_128B) {
    cuuint64_t dims[2] = {inner, outer};
    cuuint64_t st[1] = {inner * 2};
    cuuint32_t box[2] = {bi, bo};
    cuuint32_t es[2] = {1, 1};
    enc(m, CU_TENSOR_MAP_DATA_TYPE_BFLOAT16, 2, const_cast<void*>(base), dims, st, box, es, CU_TENSOR_MAP_INTERLEAVE_NONE,
        swz, CU_TENSOR_MAP_L2_PROMOTION_NONE, CU_TENSOR_MAP_FLOAT_OOB_FILL_NONE);
}

}

extern "C" void kernel_launch(void* const* d_in, const int* in_sizes, int n_in, void* d_out, int out_size) {
    (void)in_sizes; (void)n_in; (void)out_size;
    Params p;
    p.q = (const bf16*)d_in[0]; p.k = (const bf16*)d_in[1]; p.v = (const bf16*)d_in[2];
    p.shift = (const bf16*)d_in[3]; p.ssmk = (const bf16*)d_in[4]; p.ssmD = (const bf16*)d_in[5];
    p.w1 = (const bf16*)d_in[7]; p.w2 = (const bf16*)d_in[8]; p.w3 = (const bf16*)d_in[9]; p.w4 = (const bf16*)d_in[10];
    p.c = (const bf16*)d_in[11]; p.wmod = (const bf16*)d_in[12];
    p.out = (bf16*)d_out;
    p.ones = 0xffffffffu;

    void* fn = nullptr;
    cudaDriverEntryPointQueryResult qr;
    cudaGetDriverEntryPoint("cuTensorMapEncodeTiled", &fn, cudaEnableDefault, &qr);
    EncFn enc = (EncFn)fn;
    void* hn = nullptr;
    cudaGetSymbolAddress(&hn, g_hn);
    Maps maps;
    make_map(enc, &maps.w3s, p.w3, F_, D_, 216, 64, CU_TENSOR_MAP_SWIZZLE_NONE);
    make_map(enc, &maps.wm, p.wmod, 6 * D_, D_, 32, 128, CU_TENSOR_MAP_SWIZZLE_64B);
    make_map(enc, &maps.xa, p.q, D_, S_, 64, 128);
    make_map(enc, &maps.xb, p.q, D_, S_, 16, 128, CU_TENSOR_MAP_SWIZZLE_NONE);
    make_map(enc, &maps.hn, hn, D_, S_, 64, 128);
    make_map(enc, &maps.w1a, p.w1, D_, D_, 64, 64);
    make_map(enc, &maps.w1b, p.w1, D_, D_, 16, 64);
    make_map(enc, &maps.w2a, p.w2, D_, D_, 64, 64);
    make_map(enc, &maps.w2b, p.w2, D_, D_, 16, 64);
    make_map(enc, &maps.w3a, p.w3, F_, D_, 64, 64);
    make_map(enc, &maps.w3b, p.w3, F_, D_, RA3, 64);
    make_map(enc, &maps.w3c, p.w3, F_, D_, RB3, 64);
    make_map(enc, &maps.w4a, p.w4, D_, F_, 64, 64);
    make_map(enc, &maps.w4b, p.w4, D_, F_, 16, 64);
    cudaFuncSetAttribute(fused_kernel, cudaFuncAttributeMaxDynamicSharedMemorySize, SMEM_BYTES);
    fused_kernel<<<132, NTHREADS, SMEM_BYTES>>>(p, maps);
}
```

```cpp
#include <cuda_runtime.h>
#include <cuda_bf16.h>
#include <cuda.h>
#include <stdint.h>
#include <string.h>

#define SEED 0
#define RING_A 6
#define CH 2
#define FAST_LN 2
#define STAG 12
#define PGELU 2
#define CH3 4
#define HO_A 16
#define HO_B 16
#define RA3 48
#define CSP 16
#define OWNG 1
#define GATE 5
#define SSM_DELAY 0
#define B_DELAY 300
#define RPRE_WAIT 1
#define PING 250
#define NPING 5
#define FORCE_UNPAIRED 0
#define SSM_N 3

namespace {

typedef __nv_bfloat16 bf16;
typedef __nv_bfloat162 bf162;

constexpr int S_ = 2048, D_ = 640, F_ = 1728;
constexpr int NTHREADS = 640;
constexpr int NA = RING_A, NB = 12 - RING_A;
constexpr int SLOT = 16384;
constexpr int RB3 = 88 - RA3, HB0 = 512 + 8 * RA3;
constexpr int SM_RA = 0, SM_RB = NA * SLOT;

static_assert(NA == 6, "smem map");
constexpr int RED_STRIDE = 17536;
constexpr int K_STRIDE = 8320;
constexpr int U_PLANE = 2560, U_STRIDE = 5120;
constexpr int SM_Y = 12 * SLOT;
__device__ __forceinline__ int sm_red(int cc) { return cc * RED_STRIDE + (cc < 3 ? SM_RB : -3 * RED_STRIDE); }
__device__ __forceinline__ int sm_k(int cc) { return cc * K_STRIDE + (cc < 3 ? SM_RB + 3 * RED_STRIDE : 2 * RED_STRIDE - 3 * K_STRIDE); }
__device__ __forceinline__ int sm_u(int cc) { return cc * U_STRIDE + (cc < 3 ? SM_RB + 3 * RED_STRIDE + 3 * K_STRIDE : SM_Y + 8192 - 3 * U_STRIDE); }
constexpr int SM_PK = SM_RB;
constexpr int SM_PV = SM_RB + 24576;
constexpr int SM_WM = 57344;
constexpr int SM_XT = SM_WM, SM_XT2 = SM_WM + 16384, SM_XR = SM_WM + 20480;
constexpr int SM_YT = 0;
constexpr int SM_MOD = SM_Y + 20480;
constexpr int SM_GV = SM_MOD + 7680;
constexpr int SM_CS = SM_GV + 1024;
constexpr int SM_RP = SM_CS + 1024;
constexpr int SM_BAR = SM_RP + 1024;
constexpr int SM_PROF = SM_BAR + 512;
constexpr int SM_TOTAL = SM_PROF + 512;
constexpr int SMEM_BYTES = SM_TOTAL + 1024;
static_assert(SMEM_BYTES <= 232448, "smem");

constexpr int BAR_FA = 0, BAR_FB = NA, BAR_EA = 12, BAR_EB = 12 + NA, BAR_K = 24, BAR_U = 29, BAR_Y = 34, BAR_CS = 35, BAR_WM = 36, BAR_M = 37, BAR_XY = 38, BAR_Y2 = 39, BAR_G = 40, BAR_ST = 44, BAR_XR = 45, BAR_ME = 46, BAR_CD = 47, BAR_WM0 = 48, NBARS = 49;

__device__ __align__(1024) bf16 g_kvT[D_ * S_];
__device__ __align__(1024) uint32_t g_yv[128 * 5120];
__device__ __align__(1024) bf16 g_mod[6 * D_];
__device__ __align__(1024) bf16 g_hn[S_ * D_];
__device__ __align__(1024) uint4 g_rs[S_ * 2];
__device__ __align__(1024) bf16 g_h1[S_ * D_];
__device__ __align__(1024) bf16 g_x1[S_ * D_];
__device__ __align__(1024) bf16 g_g[S_ * F_];
__device__ __align__(1024) float2 g_st[S_ * 8];
__device__ __align__(1024) float g_cs[F_];
__device__ __align__(1024) unsigned g_flags[128 * 32];
__device__ __align__(1024) unsigned g_epoch[160];
constexpr int FL_P = 0, FL_C = 8, FL_CS = 9, FL_M = 10, FL_R = 16, FL_B1 = 32, FL_B2 = 48, FL_G = 64;

#define TS(i) do {} while (0)
#define TSW(i) do {} while (0)
#define TSD(i, dep) do {} while (0)
#define TSD2(i, dep) do {} while (0)
#define TSFLUSH() do {} while (0)

struct Params {
    const bf16 *q, *k, *v, *shift, *ssmk, *ssmD, *w1, *w2, *w3, *w4, *c, *wmod;
    bf16* out;
    unsigned ones;
};
#define CHUNK(k) if (ones & (1u << (k)))
struct Maps { CUtensorMap hn, w1a, w1b, w2a, w2b, w3a, w3b, w3c, w4a, w4b, wm, xa, xb, w3s; };

template<int N> struct WgRs;
template<int N> struct WgSs;
template<> struct WgRs<32> { template<int OFF,int HI,int SC> static __device__ __forceinline__ void run(float* d,uint32_t a0,uint32_t a1,uint32_t a2,uint32_t a3,uint32_t blo){
 asm volatile("{.reg .b32 l; .reg .b64 db; add.u32 l,%20,%21; mov.b64 db,{l,%22}; wgmma.mma_async.sync.aligned.m64n32k16.f32.bf16.bf16 {%0,%1,%2,%3,%4,%5,%6,%7,%8,%9,%10,%11,%12,%13,%14,%15},{%16,%17,%18,%19},db,%23,1,1,0;}"
 :"+f"(d[0]),"+f"(d[1]),"+f"(d[2]),"+f"(d[3]),"+f"(d[4]),"+f"(d[5]),"+f"(d[6]),"+f"(d[7]),"+f"(d[8]),"+f"(d[9]),"+f"(d[10]),"+f"(d[11]),"+f"(d[12]),"+f"(d[13]),"+f"(d[14]),"+f"(d[15])
 :"r"(a0),"r"(a1),"r"(a2),"r"(a3),"r"(blo),"n"(OFF),"n"(HI),"n"(SC)); } };
template<> struct WgRs<48> { template<int OFF,int HI,int SC> static __device__ __forceinline__ void run(float* d,uint32_t a0,uint32_t a1,uint32_t a2,uint32_t a3,uint32_t blo){
 asm volatile("{.reg .b32 l; .reg .b64 db; add.u32 l,%28,%29; mov.b64 db,{l,%30}; wgmma.mma_async.sync.aligned.m64n48k16.f32.bf16.bf16 {%0,%1,%2,%3,%4,%5,%6,%7,%8,%9,%10,%11,%12,%13,%14,%15,%16,%17,%18,%19,%20,%21,%22,%23},{%24,%25,%26,%27},db,%31,1,1,0;}"
 :"+f"(d[0]),"+f"(d[1]),"+f"(d[2]),"+f"(d[3]),"+f"(d[4]),"+f"(d[5]),"+f"(d[6]),"+f"(d[7]),"+f"(d[8]),"+f"(d[9]),"+f"(d[10]),"+f"(d[11]),"+f"(d[12]),"+f"(d[13]),"+f"(d[14]),"+f"(d[15]),"+f"(d[16]),"+f"(d[17]),"+f"(d[18]),"+f"(d[19]),"+f"(d[20]),"+f"(d[21]),"+f"(d[22]),"+f"(d[23])
 :"r"(a0),"r"(a1),"r"(a2),"r"(a3),"r"(blo),"n"(OFF),"n"(HI),"n"(SC)); } };
template<> struct WgRs<64> { template<int OFF,int HI,int SC> static __device__ __forceinline__ void run(float* d,uint32_t a0,uint32_t a1,uint32_t a2,uint32_t a3,uint32_t blo){
 asm volatile("{.reg .b32 l; .reg .b64 db; add.u32 l,%36,%37; mov.b64 db,{l,%38}; wgmma.mma_async.sync.aligned.m64n64k16.f32.bf16.bf16 {%0,%1,%2,%3,%4,%5,%6,%7,%8,%9,%10,%11,%12,%13,%14,%15,%16,%17,%18,%19,%20,%21,%22,%23,%24,%25,%26,%27,%28,%29,%30,%31},{%32,%33,%34,%35},db,%39,1,1,0;}"
 :"+f"(d[0]),"+f"(d[1]),"+f"(d[2]),"+f"(d[3]),"+f"(d[4]),"+f"(d[5]),"+f"(d[6]),"+f"(d[7]),"+f"(d[8]),"+f"(d[9]),"+f"(d[10]),"+f"(d[11]),"+f"(d[12]),"+f"(d[13]),"+f"(d[14]),"+f"(d[15]),"+f"(d[16]),"+f"(d[17]),"+f"(d[18]),"+f"(d[19]),"+f"(d[20]),"+f"(d[21]),"+f"(d[22]),"+f"(d[23]),"+f"(d[24]),"+f"(d[25]),"+f"(d[26]),"+f"(d[27]),"+f"(d[28]),"+f"(d[29]),"+f"(d[30]),"+f"(d[31])
 :"r"(a0),"r"(a1),"r"(a2),"r"(a3),"r"(blo),"n"(OFF),"n"(HI),"n"(SC)); } };
template<> struct WgRs<80> { template<int OFF,int HI,int SC> static __device__ __forceinline__ void run(float* d,uint32_t a0,uint32_t a1,uint32_t a2,uint32_t a3,uint32_t blo){
 asm volatile("{.reg .b32 l; .reg .b64 db; add.u32 l,%44,%45; mov.b64 db,{l,%46}; wgmma.mma_async.sync.aligned.m64n80k16.f32.bf16.bf16 {%0,%1,%2,%3,%4,%5,%6,%7,%8,%9,%10,%11,%12,%13,%14,%15,%16,%17,%18,%19,%20,%21,%22,%23,%24,%25,%26,%27,%28,%29,%30,%31,%32,%33,%34,%35,%36,%37,%38,%39},{%40,%41,%42,%43},db,%47,1,1,0;}"
 :"+f"(d[0]),"+f"(d[1]),"+f"(d[2]),"+f"(d[3]),"+f"(d[4]),"+f"(d[5]),"+f"(d[6]),"+f"(d[7]),"+f"(d[8]),"+f"(d[9]),"+f"(d[10]),"+f"(d[11]),"+f"(d[12]),"+f"(d[13]),"+f"(d[14]),"+f"(d[15]),"+f"(d[16]),"+f"(d[17]),"+f"(d[18]),"+f"(d[19]),"+f"(d[20]),"+f"(d[21]),"+f"(d[22]),"+f"(d[23]),"+f"(d[24]),"+f"(d[25]),"+f"(d[26]),"+f"(d[27]),"+f"(d[28]),"+f"(d[29]),"+f"(d[30]),"+f"(d[31]),"+f"(d[32]),"+f"(d[33]),"+f"(d[34]),"+f"(d[35]),"+f"(d[36]),"+f"(d[37]),"+f"(d[38]),"+f"(d[39])
 :"r"(a0),"r"(a1),"r"(a2),"r"(a3),"r"(blo),"n"(OFF),"n"(HI),"n"(SC)); } };
template<> struct WgRs<96> { template<int OFF,int HI,int SC> static __device__ __forceinline__ void run(float* d,uint32_t a0,uint32_t a1,uint32_t a2,uint32_t a3,uint32_t blo){
 asm volatile("{.reg .b32 l; .reg .b64 db; add.u32 l,%52,%53; mov.b64 db,{l,%54}; wgmma.mma_async.sync.aligned.m64n96k16.f32.bf16.bf16 {%0,%1,%2,%3,%4,%5,%6,%7,%8,%9,%10,%11,%12,%13,%14,%15,%16,%17,%18,%19,%20,%21,%22,%23,%24,%25,%26,%27,%28,%29,%30,%31,%32,%33,%34,%35,%36,%37,%38,%39,%40,%41,%42,%43,%44,%45,%46,%47},{%48,%49,%50,%51},db,%55,1,1,0;}"
 :"+f"(d[0]),"+f"(d[1]),"+f"(d[2]),"+f"(d[3]),"+f"(d[4]),"+f"(d[5]),"+f"(d[6]),"+f"(d[7]),"+f"(d[8]),"+f"(d[9]),"+f"(d[10]),"+f"(d[11]),"+f"(d[12]),"+f"(d[13]),"+f"(d[14]),"+f"(d[15]),"+f"(d[16]),"+f"(d[17]),"+f"(d[18]),"+f"(d[19]),"+f"(d[20]),"+f"(d[21]),"+f"(d[22]),"+f"(d[23]),"+f"(d[24]),"+f"(d[25]),"+f"(d[26]),"+f"(d[27]),"+f"(d[28]),"+f"(d[29]),"+f"(d[30]),"+f"(d[31]),"+f"(d[32]),"+f"(d[33]),"+f"(d[34]),"+f"(d[35]),"+f"(d[36]),"+f"(d[37]),"+f"(d[38]),"+f"(d[39]),"+f"(d[40]),"+f"(d[41]),"+f"(d[42]),"+f"(d[43]),"+f"(d[44]),"+f"(d[45]),"+f"(d[46]),"+f"(d[47])
 :"r"(a0),"r"(a1),"r"(a2),"r"(a3),"r"(blo),"n"(OFF),"n"(HI),"n"(SC)); } };
template<> struct WgRs<112> { template<int OFF,int HI,int SC> static __device__ __forceinline__ void run(float* d,uint32_t a0,uint32_t a1,uint32_t a2,uint32_t a3,uint32_t blo){
 asm volatile("{.reg .b32 l; .reg .b64 db; add.u32 l,%60,%61; mov.b64 db,{l,%62}; wgmma.mma_async.sync.aligned.m64n112k16.f32.bf16.bf16 {%0,%1,%2,%3,%4,%5,%6,%7,%8,%9,%10,%11,%12,%13,%14,%15,%16,%17,%18,%19,%20,%21,%22,%23,%24,%25,%26,%27,%28,%29,%30,%31,%32,%33,%34,%35,%36,%37,%38,%39,%40,%41,%42,%43,%44,%45,%46,%47,%48,%49,%50,%51,%52,%53,%54,%55},{%56,%57,%58,%59},db,%63,1,1,0;}"
 :"+f"(d[0]),"+f"(d[1]),"+f"(d[2]),"+f"(d[3]),"+f"(d[4]),"+f"(d[5]),"+f"(d[6]),"+f"(d[7]),"+f"(d[8]),"+f"(d[9]),"+f"(d[10]),"+f"(d[11]),"+f"(d[12]),"+f"(d[13]),"+f"(d[14]),"+f"(d[15]),"+f"(d[16]),"+f"(d[17]),"+f"(d[18]),"+f"(d[19]),"+f"(d[20]),"+f"(d[21]),"+f"(d[22]),"+f"(d[23]),"+f"(d[24]),"+f"(d[25]),"+f"(d[26]),"+f"(d[27]),"+f"(d[28]),"+f"(d[29]),"+f"(d[30]),"+f"(d[31]),"+f"(d[32]),"+f"(d[33]),"+f"(d[34]),"+f"(d[35]),"+f"(d[36]),"+f"(d[37]),"+f"(d[38]),"+f"(d[39]),"+f"(d[40]),"+f"(d[41]),"+f"(d[42]),"+f"(d[43]),"+f"(d[44]),"+f"(d[45]),"+f"(d[46]),"+f"(d[47]),"+f"(d[48]),"+f"(d[49]),"+f"(d[50]),"+f"(d[51]),"+f"(d[52]),"+f"(d[53]),"+f"(d[54]),"+f"(d[55])
 :"r"(a0),"r"(a1),"r"(a2),"r"(a3),"r"(blo),"n"(OFF),"n"(HI),"n"(SC)); } };
template<> struct WgRs<128> { template<int OFF,int HI,int SC> static __device__ __forceinline__ void run(float* d,uint32_t a0,uint32_t a1,uint32_t a2,uint32_t a3,uint32_t blo){
 asm volatile("{.reg .b32 l; .reg .b64 db; add.u32 l,%68,%69; mov.b64 db,{l,%70}; wgmma.mma_async.sync.aligned.m64n128k16.f32.bf16.bf16 {%0,%1,%2,%3,%4,%5,%6,%7,%8,%9,%10,%11,%12,%13,%14,%15,%16,%17,%18,%19,%20,%21,%22,%23,%24,%25,%26,%27,%28,%29,%30,%31,%32,%33,%34,%35,%36,%37,%38,%39,%40,%41,%42,%43,%44,%45,%46,%47,%48,%49,%50,%51,%52,%53,%54,%55,%56,%57,%58,%59,%60,%61,%62,%63},{%64,%65,%66,%67},db,%71,1,1,0;}"
 :"+f"(d[0]),"+f"(d[1]),"+f"(d[2]),"+f"(d[3]),"+f"(d[4]),"+f"(d[5]),"+f"(d[6]),"+f"(d[7]),"+f"(d[8]),"+f"(d[9]),"+f"(d[10]),"+f"(d[11]),"+f"(d[12]),"+f"(d[13]),"+f"(d[14]),"+f"(d[15]),"+f"(d[16]),"+f"(d[17]),"+f"(d[18]),"+f"(d[19]),"+f"(d[20]),"+f"(d[21]),"+f"(d[22]),"+f"(d[23]),"+f"(d[24]),"+f"(d[25]),"+f"(d[26]),"+f"(d[27]),"+f"(d[28]),"+f"(d[29]),"+f"(d[30]),"+f"(d[31]),"+f"(d[32]),"+f"(d[33]),"+f"(d[34]),"+f"(d[35]),"+f"(d[36]),"+f"(d[37]),"+f"(d[38]),"+f"(d[39]),"+f"(d[40]),"+f"(d[41]),"+f"(d[42]),"+f"(d[43]),"+f"(d[44]),"+f"(d[45]),"+f"(d[46]),"+f"(d[47]),"+f"(d[48]),"+f"(d[49]),"+f"(d[50]),"+f"(d[51]),"+f"(d[52]),"+f"(d[53]),"+f"(d[54]),"+f"(d[55]),"+f"(d[56]),"+f"(d[57]),"+f"(d[58]),"+f"(d[59]),"+f"(d[60]),"+f"(d[61]),"+f"(d[62]),"+f"(d[63])
 :"r"(a0),"r"(a1),"r"(a2),"r"(a3),"r"(blo),"n"(OFF),"n"(HI),"n"(SC)); } };
template<> struct WgSs<80> { template<int AOFF,int AHI,int BOFF,int BHI,int SC> static __device__ __forceinline__ void run(float* d,uint32_t alo,uint32_t blo){
 asm volatile("{.reg .b32 l,m; .reg .b64 da,db; add.u32 l,%40,%42; mov.b64 da,{l,%43}; add.u32 m,%41,%44; mov.b64 db,{m,%45}; wgmma.mma_async.sync.aligned.m64n80k16.f32.bf16.bf16 {%0,%1,%2,%3,%4,%5,%6,%7,%8,%9,%10,%11,%12,%13,%14,%15,%16,%17,%18,%19,%20,%21,%22,%23,%24,%25,%26,%27,%28,%29,%30,%31,%32,%33,%34,%35,%36,%37,%38,%39},da,db,%46,1,1,0,1;}"
 :"+f"(d[0]),"+f"(d[1]),"+f"(d[2]),"+f"(d[3]),"+f"(d[4]),"+f"(d[5]),"+f"(d[6]),"+f"(d[7]),"+f"(d[8]),"+f"(d[9]),"+f"(d[10]),"+f"(d[11]),"+f"(d[12]),"+f"(d[13]),"+f"(d[14]),"+f"(d[15]),"+f"(d[16]),"+f"(d[17]),"+f"(d[18]),"+f"(d[19]),"+f"(d[20]),"+f"(d[21]),"+f"(d[22]),"+f"(d[23]),"+f"(d[24]),"+f"(d[25]),"+f"(d[26]),"+f"(d[27]),"+f"(d[28]),"+f"(d[29]),"+f"(d[30]),"+f"(d[31]),"+f"(d[32]),"+f"(d[33]),"+f"(d[34]),"+f"(d[35]),"+f"(d[36]),"+f"(d[37]),"+f"(d[38]),"+f"(d[39])
 :"r"(alo),"r"(blo),"n"(AOFF),"n"(AHI),"n"(BOFF),"n"(BHI),"n"(SC)); } };
template<> struct WgSs<104> { template<int AOFF,int AHI,int BOFF,int BHI,int SC> static __device__ __forceinline__ void run(float* d,uint32_t alo,uint32_t blo){
 asm volatile("{.reg .b32 l,m; .reg .b64 da,db; add.u32 l,%52,%54; mov.b64 da,{l,%55}; add.u32 m,%53,%56; mov.b64 db,{m,%57}; wgmma.mma_async.sync.aligned.m64n104k16.f32.bf16.bf16 {%0,%1,%2,%3,%4,%5,%6,%7,%8,%9,%10,%11,%12,%13,%14,%15,%16,%17,%18,%19,%20,%21,%22,%23,%24,%25,%26,%27,%28,%29,%30,%31,%32,%33,%34,%35,%36,%37,%38,%39,%40,%41,%42,%43,%44,%45,%46,%47,%48,%49,%50,%51},da,db,%58,1,1,0,1;}"
 :"+f"(d[0]),"+f"(d[1]),"+f"(d[2]),"+f"(d[3]),"+f"(d[4]),"+f"(d[5]),"+f"(d[6]),"+f"(d[7]),"+f"(d[8]),"+f"(d[9]),"+f"(d[10]),"+f"(d[11]),"+f"(d[12]),"+f"(d[13]),"+f"(d[14]),"+f"(d[15]),"+f"(d[16]),"+f"(d[17]),"+f"(d[18]),"+f"(d[19]),"+f"(d[20]),"+f"(d[21]),"+f"(d[22]),"+f"(d[23]),"+f"(d[24]),"+f"(d[25]),"+f"(d[26]),"+f"(d[27]),"+f"(d[28]),"+f"(d[29]),"+f"(d[30]),"+f"(d[31]),"+f"(d[32]),"+f"(d[33]),"+f"(d[34]),"+f"(d[35]),"+f"(d[36]),"+f"(d[37]),"+f"(d[38]),"+f"(d[39]),"+f"(d[40]),"+f"(d[41]),"+f"(d[42]),"+f"(d[43]),"+f"(d[44]),"+f"(d[45]),"+f"(d[46]),"+f"(d[47]),"+f"(d[48]),"+f"(d[49]),"+f"(d[50]),"+f"(d[51])
 :"r"(alo),"r"(blo),"n"(AOFF),"n"(AHI),"n"(BOFF),"n"(BHI),"n"(SC)); } };
template<> struct WgSs<112> { template<int AOFF,int AHI,int BOFF,int BHI,int SC> static __device__ __forceinline__ void run(float* d,uint32_t alo,uint32_t blo){
 asm volatile("{.reg .b32 l,m; .reg .b64 da,db; add.u32 l,%56,%58; mov.b64 da,{l,%59}; add.u32 m,%57,%60; mov.b64 db,{m,%61}; wgmma.mma_async.sync.aligned.m64n112k16.f32.bf16.bf16 {%0,%1,%2,%3,%4,%5,%6,%7,%8,%9,%10,%11,%12,%13,%14,%15,%16,%17,%18,%19,%20,%21,%22,%23,%24,%25,%26,%27,%28,%29,%30,%31,%32,%33,%34,%35,%36,%37,%38,%39,%40,%41,%42,%43,%44,%45,%46,%47,%48,%49,%50,%51,%52,%53,%54,%55},da,db,%62,1,1,0,1;}"
 :"+f"(d[0]),"+f"(d[1]),"+f"(d[2]),"+f"(d[3]),"+f"(d[4]),"+f"(d[5]),"+f"(d[6]),"+f"(d[7]),"+f"(d[8]),"+f"(d[9]),"+f"(d[10]),"+f"(d[11]),"+f"(d[12]),"+f"(d[13]),"+f"(d[14]),"+f"(d[15]),"+f"(d[16]),"+f"(d[17]),"+f"(d[18]),"+f"(d[19]),"+f"(d[20]),"+f"(d[21]),"+f"(d[22]),"+f"(d[23]),"+f"(d[24]),"+f"(d[25]),"+f"(d[26]),"+f"(d[27]),"+f"(d[28]),"+f"(d[29]),"+f"(d[30]),"+f"(d[31]),"+f"(d[32]),"+f"(d[33]),"+f"(d[34]),"+f"(d[35]),"+f"(d[36]),"+f"(d[37]),"+f"(d[38]),"+f"(d[39]),"+f"(d[40]),"+f"(d[41]),"+f"(d[42]),"+f"(d[43]),"+f"(d[44]),"+f"(d[45]),"+f"(d[46]),"+f"(d[47]),"+f"(d[48]),"+f"(d[49]),"+f"(d[50]),"+f"(d[51]),"+f"(d[52]),"+f"(d[53]),"+f"(d[54]),"+f"(d[55])
 :"r"(alo),"r"(blo),"n"(AOFF),"n"(AHI),"n"(BOFF),"n"(BHI),"n"(SC)); } };

__device__ __forceinline__ void wg_fence() { asm volatile("wgmma.fence.sync.aligned;" ::: "memory"); }
__device__ __forceinline__ void wg_commit() { asm volatile("wgmma.commit_group.sync.aligned;" ::: "memory"); }
template <int N> __device__ __forceinline__ void wg_wait() { asm volatile("wgmma.wait_group.sync.aligned %0;" ::"n"(N) : "memory"); }
template <int N> __device__ __forceinline__ void reg_fence(float* d) {
#pragma unroll
    for (int i = 0; i < N; i++) asm volatile("" : "+f"(d[i])::"memory");
}
__device__ __forceinline__ uint32_t desc_lo(uint32_t addr, uint32_t lbo) { return ((addr & 0x3FFFF) >> 4) | ((lbo >> 4) << 16); }
#define desc_hi(sbo, sw) (((sbo) >> 4) | ((sw) << 30))
__device__ __forceinline__ uint32_t smem_u32(const void* p) { return (uint32_t)__cvta_generic_to_shared(p); }
__device__ __forceinline__ bool elect() {
    uint32_t p;
    asm volatile("{.reg .pred P; elect.sync _|P, 0xffffffff; selp.u32 %0,1,0,P;}" : "=r"(p));
    return p;
}
__device__ __forceinline__ void mbar_init(uint32_t bar, uint32_t cnt) { asm volatile("mbarrier.init.shared::cta.b64 [%0], %1;" ::"r"(bar), "r"(cnt) : "memory"); }
__device__ __forceinline__ void mbar_expect(uint32_t bar, uint32_t bytes) { asm volatile("mbarrier.arrive.expect_tx.shared::cta.b64 _, [%0], %1;" ::"r"(bar), "r"(bytes) : "memory"); }
__device__ __forceinline__ bool mbar_try(uint32_t bar, uint32_t par) {
    uint32_t ok;
    asm volatile("{.reg .pred p; mbarrier.try_wait.parity.shared::cta.b64 p, [%1], %2; selp.u32 %0,1,0,p;}" : "=r"(ok) : "r"(bar), "r"(par) : "memory");
    return ok;
}
constexpr int SPIN_LIMIT = 1 << 18;
__device__ __forceinline__ void mbar_wait(uint32_t bar, uint32_t par) {
    if (mbar_try(bar, par)) return;
    asm volatile("{.reg .pred p, q; .reg .b32 n; mov.u32 n, 0;\n"
                 "W%=: mbarrier.try_wait.parity.shared::cta.b64 p, [%0], %1; add.u32 n, n, 1; setp.lt.and.u32 q, n, %2, !p; @q bra W%=;}"
                 ::"r"(bar), "r"(par), "n"(SPIN_LIMIT) : "memory");
}
__device__ __forceinline__ void bulk_g2s(uint32_t dst, const void* src, uint32_t bytes, uint32_t bar) {
    asm volatile("cp.async.bulk.shared::cluster.global.mbarrier::complete_tx::bytes [%0], [%1], %2, [%3];" ::"r"(dst), "l"(src), "r"(bytes), "r"(bar) : "memory");
}
__device__ __forceinline__ void bulk_s2g(void* dst, uint32_t src, uint32_t bytes) {
    asm volatile("cp.async.bulk.global.shared::cta.bulk_group [%0], [%1], %2;" ::"l"(dst), "r"(src), "r"(bytes) : "memory");
}
__device__ __forceinline__ void bulk_prefetch(const void* src, uint32_t bytes) {
    asm volatile("cp.async.bulk.prefetch.L2.global [%0], %1;" ::"l"(src), "r"(bytes) : "memory");
}
__device__ __forceinline__ void tma2d(uint32_t dst, const CUtensorMap* m, int c0, int c1, uint32_t bar) {
    asm volatile("cp.async.bulk.tensor.2d.shared::cluster.global.mbarrier::complete_tx::bytes [%0], [%1, {%3, %4}], [%2];" ::"r"(dst), "l"(m), "r"(bar), "r"(c0), "r"(c1) : "memory");
}
__device__ __forceinline__ void tma2d_mc(uint32_t dst, const CUtensorMap* m, int c0, int c1, uint32_t bar) {
    asm volatile("cp.async.bulk.tensor.2d.shared::cluster.global.mbarrier::complete_tx::bytes.multicast::cluster [%0], [%1, {%3, %4}], [%2], %5;" ::"r"(dst), "l"(m), "r"(bar), "r"(c0), "r"(c1), "h"((uint16_t)3) : "memory");
}
__device__ __forceinline__ uint32_t mapa(uint32_t a, uint32_t rank) { uint32_t r; asm("mapa.shared::cluster.u32 %0, %1, %2;" : "=r"(r) : "r"(a), "r"(rank)); return r; }
__device__ __forceinline__ void mbar_arrive_cl(uint32_t bar) { asm volatile("mbarrier.arrive.shared::cluster.b64 _, [%0];" ::"r"(bar) : "memory"); }
__device__ __forceinline__ void prefetch_map(const CUtensorMap* m) { asm volatile("prefetch.tensormap [%0];" ::"l"(m) : "memory"); }
__device__ __forceinline__ void cpasync16(uint32_t dst, const void* src, uint32_t srcsz) {
    asm volatile("cp.async.cg.shared.global [%0], [%1], 16, %2;" ::"r"(dst), "l"(src), "r"(srcsz) : "memory");
}
__device__ __forceinline__ void bar_sync(int id, int n) { asm volatile("bar.sync %0, %1;" ::"r"(id), "r"(n) : "memory"); }
__device__ __forceinline__ void bar_arrive(int id, int n) { asm volatile("bar.arrive %0, %1;" ::"r"(id), "r"(n) : "memory"); }
__device__ __forceinline__ void fence_async_smem() { asm volatile("fence.proxy.async.shared::cta;" ::: "memory"); }
__device__ __forceinline__ void fence_async_global() { asm volatile("fence.proxy.async.global;" ::: "memory"); }
__device__ __forceinline__ void flag_release(int f) { asm volatile("red.release.gpu.global.add.u32 [%0], 1;" ::"l"(&g_flags[f * 32]) : "memory"); }
__device__ __forceinline__ void flag_wait(int f, unsigned target) {
    const unsigned* p = &g_flags[f * 32];
    unsigned v; int n = 0;
    do {
        asm volatile("ld.relaxed.gpu.global.u32 %0, [%1];" : "=r"(v) : "l"(p) : "memory");
    } while ((int)(v - target) < 0 && ++n < SPIN_LIMIT);
    asm volatile("fence.acquire.gpu;" ::: "memory");
}
__device__ __forceinline__ unsigned ld_flag(const unsigned* p) { unsigned v; asm volatile("ld.relaxed.gpu.global.u32 %0, [%1];" : "=r"(v) : "l"(p) : "memory"); return v; }
__device__ __forceinline__ void spin(unsigned n) { unsigned t0, t1; asm volatile("mov.u32 %0, %%clock;" : "=r"(t0)); do { asm volatile("mov.u32 %0, %%clock;" : "=r"(t1)); } while (t1 - t0 < n); }
__device__ __forceinline__ int tensor_ping() {
    int r;
    asm volatile("{.reg .f32 a, b, c, d; mma.sync.aligned.m16n8k16.row.col.f32.bf16.bf16.f32 {a,b,c,d},{%1,%1,%1,%1},{%1,%1},{%2,%2,%2,%2}; mov.b32 %0, a;}" : "=r"(r) : "r"(0), "f"(0.f));
    return r;
}
__device__ __forceinline__ void mbar_wait_warm(uint32_t bar, uint32_t par) {
    for (int n = 0; n < SPIN_LIMIT; n++) {
        uint32_t ok;
        asm volatile("{.reg .pred p; mbarrier.test_wait.parity.shared::cta.b64 p, [%1], %2; selp.u32 %0,1,0,p;}" : "=r"(ok) : "r"(bar), "r"(par) : "memory");
        if (ok) break;
        n += tensor_ping();
        spin(PING);
    }
}
__device__ __forceinline__ void flag_wait2(int f0, int f1, unsigned target) {
    const unsigned *p = &g_flags[f0 * 32], *q = &g_flags[f1 * 32];
    unsigned v, w; int n = 0;
    do { v = ld_flag(p); w = ld_flag(q); } while ((int)((v - target) | (w - target)) < 0 && ++n < SPIN_LIMIT);
    asm volatile("fence.acquire.gpu;" ::: "memory");
}
__device__ __forceinline__ uint32_t lds32(uint32_t a) { uint32_t v; asm volatile("ld.shared.u32 %0, [%1];" : "=r"(v) : "r"(a)); return v; }
__device__ __forceinline__ float2 lds64f(uint32_t a) { float2 v; asm volatile("ld.shared.v2.f32 {%0,%1}, [%2];" : "=f"(v.x), "=f"(v.y) : "r"(a)); return v; }
__device__ __forceinline__ uint2 lds64(uint32_t a) { uint2 v; asm volatile("ld.shared.v2.u32 {%0,%1}, [%2];" : "=r"(v.x), "=r"(v.y) : "r"(a)); return v; }
__device__ __forceinline__ void sts64f(uint32_t a, float2 v) { asm volatile("st.shared.v2.f32 [%0], {%1,%2};" ::"r"(a), "f"(v.x), "f"(v.y) : "memory"); }
__device__ __forceinline__ void sts32(uint32_t a, uint32_t v) { asm volatile("st.shared.u32 [%0], %1;" ::"r"(a), "r"(v) : "memory"); }
__device__ __forceinline__ void sts64(uint32_t a, uint32_t x, uint32_t y) { asm volatile("st.shared.v2.u32 [%0], {%1,%2};" ::"r"(a), "r"(x), "r"(y) : "memory"); }
__device__ __forceinline__ void sts16(uint32_t a, uint16_t v) { asm volatile("st.shared.u16 [%0], %1;" ::"r"(a), "h"(v) : "memory"); }
__device__ __forceinline__ uint4 lds128(uint32_t a) { uint4 v; asm volatile("ld.shared.v4.u32 {%0,%1,%2,%3}, [%4];" : "=r"(v.x), "=r"(v.y), "=r"(v.z), "=r"(v.w) : "r"(a)); return v; }
__device__ __forceinline__ void sts128(uint32_t a, uint4 v) { asm volatile("st.shared.v4.u32 [%0], {%1,%2,%3,%4};" ::"r"(a), "r"(v.x), "r"(v.y), "r"(v.z), "r"(v.w) : "memory"); }
__device__ __forceinline__ void sts128f(uint32_t a, float x, float y, float z, float w) { asm volatile("st.shared.v4.f32 [%0], {%1,%2,%3,%4};" ::"r"(a), "f"(x), "f"(y), "f"(z), "f"(w) : "memory"); }
__device__ __forceinline__ uint32_t prmt(uint32_t a, uint32_t b, uint32_t s) { uint32_t r; asm("prmt.b32 %0,%1,%2,%3;" : "=r"(r) : "r"(a), "r"(b), "r"(s)); return r; }
__device__ __forceinline__ uint32_t pack2(float lo, float hi) { uint32_t r; asm("cvt.rn.bf16x2.f32 %0, %1, %2;" : "=r"(r) : "f"(hi), "f"(lo)); return r; }
__device__ __forceinline__ float blo(uint32_t v) { return __uint_as_float(v << 16); }
__device__ __forceinline__ float bhi(uint32_t v) { return __uint_as_float(v & 0xffff0000u); }
__device__ __forceinline__ uint32_t bmul2(uint32_t a, uint32_t b) { uint32_t r; asm("mul.rn.bf16x2 %0,%1,%2;" : "=r"(r) : "r"(a), "r"(b)); return r; }
__device__ __forceinline__ uint32_t badd2(uint32_t a, uint32_t b) { uint32_t r; asm("add.rn.bf16x2 %0,%1,%2;" : "=r"(r) : "r"(a), "r"(b)); return r; }
__device__ __forceinline__ float rbf(float x) { return __bfloat162float(__float2bfloat16_rn(x)); }
__device__ __forceinline__ uint32_t ldcg32(const void* p) { uint32_t v; asm volatile("ld.global.cg.u32 %0, [%1];" : "=r"(v) : "l"(p) : "memory"); return v; }
__device__ __forceinline__ uint4 ldcg128(const void* p) { uint4 v; asm volatile("ld.global.cg.v4.u32 {%0,%1,%2,%3}, [%4];" : "=r"(v.x), "=r"(v.y), "=r"(v.z), "=r"(v.w) : "l"(p) : "memory"); return v; }
__device__ __forceinline__ void stg32_if(void* p, uint32_t v, int on) { asm volatile("{.reg .pred q; setp.ne.b32 q, %2, 0; @q st.global.u32 [%0], %1;}" ::"l"(p), "r"(v), "r"(on) : "memory"); }
__device__ __forceinline__ uint2 ldcg64(const void* p) { uint2 v; asm volatile("ld.global.cg.v2.u32 {%0,%1}, [%2];" : "=r"(v.x), "=r"(v.y) : "l"(p) : "memory"); return v; }
__device__ __forceinline__ float gelu_h(float h) {
    float u = h * fmaf(h * h, 8.0f * 0.044715f * 0.7978845608028654f, 2.0f * 0.7978845608028654f);
    float th;
    asm("tanh.approx.f32 %0, %1;" : "=f"(th) : "f"(u));
    return fmaf(h, th, h);
}
__device__ __forceinline__ float gelu(float x) { return gelu_h(0.5f * x); }
__device__ __forceinline__ float half_rstd(float sum, float sq) {
    float mean = sum * (1.0f / D_), inv;
    asm("rsqrt.approx.ftz.f32 %0, %1;" : "=f"(inv) : "f"(fmaxf(fmaf(-mean, mean, fmaf(sq, 1.0f / D_, 1e-5f)), 1e-5f)));
    return 0.5f * inv;
}
__device__ __forceinline__ uint32_t bsub2(uint32_t a, uint32_t b) { uint32_t r; asm("sub.rn.bf16x2 %0,%1,%2;" : "=r"(r) : "r"(a), "r"(b)); return r; }
__device__ __forceinline__ uint32_t bfma2(uint32_t a, uint32_t b, uint32_t c) { uint32_t r; asm("fma.rn.bf16x2 %0,%1,%2,%3;" : "=r"(r) : "r"(a), "r"(b), "r"(c)); return r; }
__device__ __forceinline__ uint32_t gelu2_h(uint32_t h) {
    uint32_t u = bmul2(h, bfma2(bmul2(h, h), 0x3e923e92u, 0x3fcc3fccu)), th;
    asm("tanh.approx.bf16x2 %0, %1;" : "=r"(th) : "r"(u));
    return bfma2(h, th, h);
}
__device__ __forceinline__ uint3 row_stats(const uint32_t* v, int lane) {
    float s = 0.f, q = 0.f, s_ = 0.f, q_ = 0.f;
#pragma unroll
    for (int i = 0; i < 10; i++) { float a = blo(v[i]), b = bhi(v[i]); s += a; s_ += b; q = fmaf(a, a, q); q_ = fmaf(b, b, q_); }
    s += s_; q += q_;
    {
        float t = __shfl_xor_sync(0xffffffffu, (lane & 16) ? s : q, 16);
        t += (lane & 16) ? q : s;
#pragma unroll
        for (int m = 8; m; m >>= 1) t += __shfl_xor_sync(0xffffffffu, t, m);
        float o = __shfl_xor_sync(0xffffffffu, t, 16);
        s = (lane & 16) ? o : t; q = (lane & 16) ? t : o;
    }
    float mean = s * (1.0f / D_), inv;
    asm("rsqrt.approx.ftz.f32 %0, %1;" : "=f"(inv) : "f"(fmaxf(fmaf(-mean, mean, fmaf(q, 1.0f / D_, 1e-5f)), 1e-5f)));
    uint3 r;
    r.x = pack2(mean, mean);
    r.y = pack2(inv, inv);
    inv -= blo(r.y);
    r.z = pack2(inv, inv);
    return r;
}
__device__ __forceinline__ uint32_t ln_apply(uint32_t x, uint32_t m, uint32_t hi, uint32_t lo) {
    uint32_t xc = bsub2(x, m);
    return bmul2(xc, hi);
}

struct AFrag { uint32_t m, a, b, c, d; };
__device__ __forceinline__ AFrag ldA(uint32_t a) { AFrag f; f.m = lds32(a - 16); f.a = lds32(a); f.b = lds32(a + 16); f.c = lds32(a + 32); f.d = lds32(a + 48); return f; }
template <int N, int M> __device__ __forceinline__ void conv_pair(float* d, const AFrag& f, uint32_t descU) {
    WgRs<N>::template run<8 * M, desc_hi(128, 0), M ? 1 : 0>(d, f.a, f.b, f.m, f.a, descU);
    WgRs<N>::template run<8 * M + 1, desc_hi(128, 0), 1>(d, f.c, f.d, f.b, f.c, descU);
}
template <int Q> __device__ __forceinline__ void conv_put(float* d, uint32_t r0) {
    sts64(r0 + Q * 32, pack2(d[4 * Q + 1], d[4 * Q + 3]), pack2(d[4 * Q], d[4 * Q + 2]));
}
template <int M> __device__ __forceinline__ void conv_two(float* d, AFrag f0, AFrag f1, uint32_t kaddr, uint32_t descU, uint32_t r0, bool handoff) {
    constexpr int N = M < 14 ? 128 - 8 * M : 32;
    wg_fence();
    conv_pair<N, M>(d, f0, descU);
    wg_commit();
    if constexpr (M > 0) f1 = ldA(kaddr + 256 * (M + 1));
    wg_fence();
    conv_pair<N, M + 1>(d, f1, descU);
    wg_commit();
    if (STAG && M == STAG && handoff) bar_arrive(12, 256);
    if constexpr (M < 14) {
        if constexpr (M > 0) { conv_put<17 - M>(d, r0); conv_put<16 - M>(d, r0); }
        wg_wait<1>();
        f0 = ldA(kaddr + 256 * (M + 2));
        if constexpr (M < 12) wg_wait<0>();
        conv_two<M + 2>(d, f0, f1, kaddr, descU, r0, handoff);
    } else {
        wg_wait<0>();
        conv_put<3>(d, r0); conv_put<2>(d, r0); conv_put<1>(d, r0); conv_put<0>(d, r0);
    }
}
template <int N, bool ASWZ, int SC0>
__device__ __forceinline__ void gemm_issue(float* acc, uint32_t bars, int sa, int pa, int sw, int pw, uint32_t da0, uint32_t db0) {
    mbar_wait(bars + (BAR_FB + sw) * 8, pw);
    mbar_wait(bars + (BAR_FA + sa) * 8, pa);
    const uint32_t da = da0 + sa * (SLOT >> 4), db = db0 + sw * (SLOT >> 4);
    constexpr int AK = ASWZ ? 2 : 256, AH = ASWZ ? desc_hi(1024, 1) : desc_hi(128, 0), BH = desc_hi(1024, 1);
    wg_fence();
    WgSs<N>::template run<0, AH, 0, BH, SC0>(acc, da, db);
    WgSs<N>::template run<AK, AH, 128, BH, 1>(acc, da, db);
    WgSs<N>::template run<2 * AK, AH, 256, BH, 1>(acc, da, db);
    WgSs<N>::template run<3 * AK, AH, 384, BH, 1>(acc, da, db);
    wg_commit();
}
template <int N, bool ASWZ, int NKB, int RELB, bool ZERO>
__device__ __forceinline__ void gemm_loop(float* acc, uint32_t sb, int half, int ia0, int ib0, int rela, int wait_bar, int order_bar, int tsid) {
    int sa = ia0 % NA, pa = (ia0 / NA) & 1, sw = ib0 % NB, pw = (ib0 / NB) & 1;
    const uint32_t bars = sb + SM_BAR;
    const int t = threadIdx.x & 127;
    uint32_t ebar = mapa(bars + (t < 2 ? BAR_EB : BAR_EA) * 8, (t < 2 && lds32(sb + SM_GV + 516)) ? t : blockIdx.x & 1);
    const int nrel = t < 2 ? RELB : t == 2 ? rela : 0;
    const uint32_t da0 = ASWZ ? desc_lo(sb + SM_RA + half * 8192, 16) : desc_lo(sb + SM_RA + half * 1024, 2048), db0 = desc_lo(sb + SM_RB, 8192);
    asm volatile("" : "+r"(ebar));
    if (wait_bar) bar_sync(wait_bar, 512);
    gemm_issue<N, ASWZ, ZERO ? 0 : 1>(acc, bars, sa, pa, sw, pw, da0, db0);
    if ((threadIdx.x & 255) == 0) TS(tsid);
#pragma unroll 1
    for (int kb = 1; kb < NKB; kb++) {
        const int prev = t < 2 ? sw : sa;
        if (++sa == NA) { sa = 0; pa ^= 1; }
        if (++sw == NB) { sw = 0; pw ^= 1; }
        gemm_issue<N, ASWZ, 1>(acc, bars, sa, pa, sw, pw, da0, db0);
        if (order_bar && kb == NKB - 1) bar_arrive(order_bar, 512);
        wg_wait<1>();
        if (kb <= nrel) mbar_arrive_cl(ebar + prev * 8);
    }
    wg_wait<0>();
    if (nrel == NKB) mbar_arrive_cl(ebar + (t < 2 ? sw : sa) * 8);
    reg_fence<N / 2>(acc);
    if ((threadIdx.x & 255) == 0) TS(tsid + 1);
}

template <int PART>
__device__ __forceinline__ void gemm3(uint32_t sb, int rb, int j, int half, int row, int c, unsigned ones) {
    constexpr int N = 64 + (PART ? RB3 : RA3), NQ = N / 8;
    constexpr int HO = PART ? HO_B : HO_A;
    float acc[N / 2];
    float2 cr[NQ];
    if (PART) {
        gemm_loop<N, false, 1, 1, true>(acc, sb, half, 20, 20, 0, 0, 0, 50);
        bar_arrive(9, 512);
    }
    mbar_wait(sb + SM_BAR + BAR_CS * 8, 0);
    const uint32_t csa = sb + SM_CS + PART * (256 + 4 * RA3) + 8 * c;
#pragma unroll
    for (int q = 0; q < NQ; q++) if (q < CSP) cr[q] = lds64f(csa + 32 * q);
    uint4 rp;
    if (PART) {
        mbar_wait(sb + SM_BAR + BAR_G * 8, 0);
        const float2* sp = &g_st[(rb * 8 + 2 * c) * 128 + row];
        const uint2 s0 = ldcg64(sp), s1 = ldcg64(sp + 128), s2 = ldcg64(sp + 8), s3 = ldcg64(sp + 136);
        float a0 = __uint_as_float(s0.x) + __uint_as_float(s1.x), b0 = __uint_as_float(s0.y) + __uint_as_float(s1.y);
        float a1 = __uint_as_float(s2.x) + __uint_as_float(s3.x), b1 = __uint_as_float(s2.y) + __uint_as_float(s3.y);
#pragma unroll
        for (int m = 1; m <= 2; m <<= 1) {
            a0 += __shfl_xor_sync(0xffffffffu, a0, m); b0 += __shfl_xor_sync(0xffffffffu, b0, m);
            a1 += __shfl_xor_sync(0xffffffffu, a1, m); b1 += __shfl_xor_sync(0xffffffffu, b1, m);
        }
        const float inv0 = half_rstd(a0, b0), inv1 = half_rstd(a1, b1);
        rp = make_uint4(PGELU ? pack2(inv0, inv0) : __float_as_uint(inv0), __float_as_uint(a0 * (-1.0f / D_)),
                        PGELU ? pack2(inv1, inv1) : __float_as_uint(inv1), __float_as_uint(a1 * (-1.0f / D_)));
        if (c == 0) sts128(sb + SM_RP + ((threadIdx.x & 255) >> 2) * 16, rp);
        bar_arrive(13, 512);
    }
    gemm_loop<N, false, 10 - PART, 10 - PART, !PART>(acc, sb, half, 20 + (10 - NA) * PART, 21 + 10 * PART, PART ? 9 : 10 - NA, 9 + PART, HO < 0 ? 10 + PART : 0, 46 + 2 * PART);
    if ((threadIdx.x & 255) == 0) mbar_expect(sb + SM_BAR + BAR_ME * 8, 0);
    if (!PART) {
        bar_sync(13, 512);
        rp = lds128(sb + SM_RP + ((threadIdx.x & 255) >> 2) * 16);
    }
    const float nb0 = __uint_as_float(rp.y), nb1 = __uint_as_float(rp.w);
    const uint32_t own = sb + SM_RA + ((39 - NA) % NA) * SLOT + row * 16 + c * 4;
    if (PART && OWNG) mbar_wait(sb + SM_BAR + (BAR_FA + (39 - NA) % NA) * 8, ((39 - NA) / NA) & 1);
    uint32_t* dst = reinterpret_cast<uint32_t*>(g_g) + (rb * 216 + HB0 / 8 * PART + 8 * j) * 512 + row * 4 + c;
    auto act = [&](int q, int r) {
        const float nb = r ? nb1 : nb0;
        const uint32_t inv = r ? rp.z : rp.x;
        const float t0 = fmaf(nb, cr[q].x, acc[4 * q + 2 * r]), t1 = fmaf(nb, cr[q].y, acc[4 * q + 2 * r + 1]);
        return gelu2_h(bmul2(pack2(t0, t1), inv));
    };
    uint32_t* dst1 = dst + (56 - (16 - NQ) * j) * 512;
#pragma unroll
    for (int k = 0; k < NQ; k += CH3) {
        if (k == HO) bar_arrive(10 + PART, 512);
        CHUNK(k) {
#pragma unroll
            for (int q = k; q < k + CH3 && q < NQ; q++) {
                if (q + CSP < NQ) cr[q + CSP] = lds64f(csa + 32 * (q + CSP));
                const uint32_t u = act(q, 0), v = act(q, 1);
                (q < 8 ? dst : dst1)[q * 512] = u;
                (q < 8 ? dst : dst1)[q * 512 + 32] = v;
                if (PART && OWNG && q < 8) { sts32(own + q * 2048, u); sts32(own + q * 2048 + 128, v); }
            }
            if (PART && OWNG && k < 8 && k + CH3 >= 8) fence_async_smem();
        }
    }
    bar_arrive(1 + PART, 288);
    if (HO >= NQ) bar_arrive(10 + PART, 512);
}

template <int NS, int BASE, int BF, int BE> struct Ring {
    uint32_t sb, st, ph;
    __device__ __forceinline__ uint32_t acquire(uint32_t bytes) {
        mbar_wait(sb + SM_BAR + BE * 8 + st * 8, ph);
        uint32_t fb = sb + SM_BAR + BF * 8 + st * 8;
        mbar_expect(fb, bytes);
        return fb;
    }
    __device__ __forceinline__ uint32_t slot() { return sb + BASE + st * SLOT; }
    __device__ __forceinline__ void next() { if (++st == NS) { st = 0; ph ^= 1; } }
    __device__ __forceinline__ void run2d(const CUtensorMap* m, int c1) {
#pragma unroll 1
        for (int c0 = 64; c0 < D_; c0 += 64) {
            uint32_t fb = acquire(SLOT);
            tma2d(slot(), m, c0, c1, fb);
            next();
        }
    }
    static __device__ __forceinline__ int korder(int i, int own) { return i == 0 ? own : i > own ? i : i - 1; }
    __device__ __forceinline__ void runw(bool paired, int rk, const CUtensorMap* ma, const CUtensorMap* mb, int ca, int cb, int i0, int i1, int own, uint32_t bytes, int gate_at, uint32_t gate) {
        if (paired) {
            const CUtensorMap* m = rk ? mb : ma;
            const int c0 = rk ? cb : ca;
#pragma unroll 1
            for (int i = i0; i < i1; i++) {
                const int c1 = korder(i, own) * 64;
                if (i == gate_at) mbar_wait(gate, 0);
                uint32_t fb = acquire(bytes);
                tma2d_mc(slot() + 8192 * rk, m, c0, c1, fb);
                next();
            }
        } else {
#pragma unroll 1
            for (int i = i0; i < i1; i++) {
                const int c1 = korder(i, own) * 64;
                uint32_t fb = acquire(bytes);
                tma2d(slot(), ma, ca, c1, fb);
                tma2d(slot() + 8192, mb, cb, c1, fb);
                next();
            }
        }
    }
    __device__ __forceinline__ void run1d(const char* src, int i0, int i1, int own) {
#pragma unroll 1
        for (int i = i0; i < i1; i++) {
            const char* s = src + korder(i, own) * SLOT;
            uint32_t fb = acquire(SLOT);
            bulk_g2s(slot(), s, SLOT, fb);
            next();
        }
    }
};

__global__ void __cluster_dims__(2, 1, 1) __launch_bounds__(NTHREADS, 1) fused_kernel(const Params p, const __grid_constant__ Maps maps) {
    extern __shared__ __align__(1024) unsigned char smem_raw[];
    const uint32_t sb = (smem_u32(smem_raw) + 1023u) & ~1023u;
#pragma unroll
    for (int i = 0; i < SEED; i++) asm volatile("{.reg .b32 t; mov.u32 t, %laneid;}");
    const uint32_t bars = sb + SM_BAR;
    const int tid = threadIdx.x, lane = tid & 31;
    unsigned smid;
    asm volatile("mov.u32 %0, %%smid;" : "=r"(smid));
    const bool spare = (smid >> 2) == 30;
    const int cta = smid < 120 ? smid : smid - 4;
    const int pg = cta >> 4, pi = cta & 15;
    auto chan = [&](int cc) { return 80 * pg + (cc < 3 ? 3 * pi + cc : 45 + 2 * pi + cc); };
    const int hb = tid >= 320;
    if (!spare) {
        const unsigned t = tid - 320 * hb, r32 = t / 10u, cc = t - r32 * 10u, row = r32 + 64 * hb;
        const unsigned go = (unsigned)(pi * 128 * 1280 + pg * 160) + row * 1280u + cc * 16u;
        const uint32_t so = sb + (row >> 4) * 32u + row * 160u + cc * 16u;
        const char* kb = (const char*)p.k + go;
        const char* vb = (const char*)p.v + go;
        if (hb) {
            if (tid >= 640 - NBARS) {
                const int i = 639 - tid;
                mbar_init(bars + i * 8, (i >= BAR_EB && i < BAR_K) ? 4 : ((i >= BAR_EA && i < BAR_EB) || i == BAR_XY) ? 2 : 1);
                asm volatile("fence.mbarrier_init.release.cluster;" ::: "memory");
            }
            bar_arrive(14, 640);
            if (B_DELAY) spin(B_DELAY);
        }
        cpasync16(so + SM_PK + 2592, kb, 16);
        cpasync16(so + SM_PV, vb, 16);
        cpasync16(so + SM_PK + 3 * 2592, kb + 32 * 1280, 16);
        cpasync16(so + SM_PV + 2 * 2592, vb + 32 * 1280, 16);
        if (tid < 30) cpasync16(so + SM_PK + 13 * 160, pi ? kb - 3 * 1280 : kb, pi ? 16 : 0);
        asm volatile("cp.async.commit_group;" ::: "memory");
    }
    const int warp = __shfl_sync(0xffffffffu, tid >> 5, 0);
    const int wg = warp >> 2, wq = warp & 3;
    unsigned ep0 = 0;
    if (wg == 4 || spare) ep0 = *(volatile unsigned*)&g_epoch[smid];
#define ep1 (ep0 + 1)

    if (spare) {
        const int sp = smid & 3;
        if (tid == 32) { sts32(sb + SM_GV + 512, smid); asm volatile("fence.release.sync_restrict::shared::cta.cluster;" ::: "memory"); }
        asm volatile("barrier.cluster.arrive.relaxed.aligned;" ::: "memory");
        asm volatile("barrier.cluster.wait.aligned;" ::: "memory");
        if (tid == 0) {
            for (int i = 0; i < 4; i++) mbar_init(bars + i * 8, 1);
            asm volatile("fence.mbarrier_init.release.cluster;" ::: "memory");
        }
        if (warp == 0) { if (lane < 8) flag_wait(FL_P + lane, ep1 * 16); __syncwarp(); }
        __syncthreads();
        const int cq = tid % 54, rg = tid / 54;
        float a[8];
#pragma unroll
        for (int i = 0; i < 8; i++) a[i] = 0.f;
#pragma unroll 1
        for (int it = -4; it < 10; it++) {
            const uint32_t st = sb + (it & 3) * 55296, fb = bars + (it & 3) * 8;
            if (it >= 0) {
                mbar_wait(fb, (it >> 2) & 1);
                if (tid < 432) {
#pragma unroll 2
                    for (int i = 0; i < 8; i++) {
                        uint4 w = lds128(st + (cq >= 27 ? 27648 - 432 : 0) + (rg * 8 + i) * 432 + cq * 16);
                        a[0] += blo(w.x); a[1] += bhi(w.x); a[2] += blo(w.y); a[3] += bhi(w.y);
                        a[4] += blo(w.z); a[5] += bhi(w.z); a[6] += blo(w.w); a[7] += bhi(w.w);
                    }
                }
                __syncthreads();
            }
            if (it < 6 && warp == 19 && elect()) {
                mbar_expect(fb, 55296);
                tma2d(st, &maps.w3s, sp * 432, (it + 4) * 64, fb);
                tma2d(st + 27648, &maps.w3s, sp * 432 + 216, (it + 4) * 64, fb);
            }
        }
        if (warp == 19 && elect()) {
#pragma unroll 1
            for (int i = 0; i < 27; i++) bulk_prefetch((const char*)p.w4 + sp * 552960 + i * 20480, 20480);
        }
        if (tid < 432) {
            sts128f(sb + rg * 1728 + cq * 32, a[0], a[1], a[2], a[3]);
            sts128f(sb + rg * 1728 + cq * 32 + 16, a[4], a[5], a[6], a[7]);
        }
        __syncthreads();
        if (tid < 432) {
            float s = 0.f;
#pragma unroll
            for (int i = 0; i < 8; i++) s += __uint_as_float(lds32(sb + i * 1728 + tid * 4));
            g_cs[sp * 432 + tid] = s;
        }
        __syncthreads();
        if (tid == 0) { flag_release(FL_CS); g_epoch[smid] = ep1; TS(0); }
        if (warp == 0) TSFLUSH();
        return;
    }

    int gpc, idx;
    if (smid < 64) { gpc = (smid & 15) >> 1; idx = (smid >> 4) * 2 + (smid & 1); }
    else if (smid < 120) { int t = smid - 64; gpc = 1 + (t % 14) / 2; idx = 8 + (t / 14) * 2 + (smid & 1); }
    else { gpc = 0; idx = 8 + (smid - 124); }
    const int rb = 2 * gpc + (idx & 1), j = idx >> 1;
    const int g = lane >> 2, c = lane & 3;
    const int cm = 160 * (j >> 1) + 64 * (j & 1) + ((j & 2) ? 32 : 0), cr = 160 * (j >> 1) + 16 * (j & 1) + ((j & 2) ? 0 : 128);

    {
        if (warp == 5) TSW(61);
        const int w10 = warp - 10 * hb, h = w10 >= 5;
        const int pr = (w10 - 5 * h) * 8 + (lane >> 2), blk = 4 * hb + (lane & 3);
        const int ch = 80 * pg + 2 * pr;
        const uint4 sw = __ldg(reinterpret_cast<const uint4*>(p.shift + ch * 4));
        uint32_t dv = 0;
        if (warp == 9 && lane < 5) dv = __bfloat16_as_ushort(p.ssmD[chan(lane)]);
        if (tid == 512) { sts32(sb + SM_GV + 512, smid); asm volatile("fence.release.sync_restrict::shared::cta.cluster;" ::: "memory"); }
        asm volatile("barrier.cluster.arrive.relaxed.aligned;" ::: "memory");
        if (warp == 11 && lane < 13) prefetch_map(&maps.hn + lane);
        if (wg < 4) {
            const int t = tid & 127, cc = (wg == 3 && t >= 64) ? 4 : wg;
            if (t < 64 || wg == 3) sts128(sb + sm_u(cc) + ((t >> 5) & 1) * U_PLANE + 2048 + lane * 16, make_uint4(0, 0, 0, 0));
            if ((t & 63) < 4 && (t < 64 || wg == 3)) sts128(sb + sm_k(cc) + ((t >> 1) & 1) * 4160 + (t & 1) * 16, make_uint4(0, 0, 0, 0));
        }
        if (warp == 9 && lane < 5) sts32(sb + SM_GV + 520 + lane * 4, dv << 16);
        asm volatile("cp.async.wait_group 0;" ::: "memory");
        if (!hb) bar_arrive(12, 640);
        bar_sync(hb ? 12 : 14, 640);
        if (warp == 9) {
            if (SSM_DELAY) spin(SSM_DELAY);
            if (elect()) {
#pragma unroll
                for (int i = 0; i < SSM_N; i++) {
                    mbar_expect(bars + (BAR_K + i) * 8, 4096);
                    bulk_g2s(sb + sm_k(i) + 32, p.ssmk + (size_t)(chan(i)) * S_, 4096, bars + (BAR_K + i) * 8);
                }
            }
        }
        const uint32_t w0 = prmt(sw.x, sw.z, 0x5410), w1 = prmt(sw.x, sw.z, 0x7632), w2 = prmt(sw.y, sw.w, 0x5410), w3 = prmt(sw.y, sw.w, 0x7632);
        const uint32_t ka = sb + SM_PK + 2592 + blk * 2592 + h * 1280 + pr * 4;
        const uint32_t va = sb + SM_PV + blk * 2592 + h * 1280 + pr * 4;
        uint32_t kk[11], kv[8];
#pragma unroll
        for (int i = 0; i < 11; i++) kk[i] = lds32(ka + (i - 3) * 160 - ((i < 3 && h == 0) ? 32 : 0));
#pragma unroll
        for (int i = 0; i < 8; i++) {
            uint32_t t = badd2(badd2(badd2(bmul2(kk[i], w3), bmul2(kk[i + 1], w2)), bmul2(kk[i + 2], w1)), bmul2(kk[i + 3], w0));
            kv[i] = bmul2(t, lds32(va + i * 160));
        }
        uint4 o0, o1;
        o0.x = prmt(kv[1], kv[0], 0x5410); o0.y = prmt(kv[3], kv[2], 0x5410); o0.z = prmt(kv[5], kv[4], 0x5410); o0.w = prmt(kv[7], kv[6], 0x5410);
        o1.x = prmt(kv[1], kv[0], 0x7632); o1.y = prmt(kv[3], kv[2], 0x7632); o1.z = prmt(kv[5], kv[4], 0x7632); o1.w = prmt(kv[7], kv[6], 0x7632);
        uint4* dst = reinterpret_cast<uint4*>(g_kvT) + ch * 256 + h * 128 + (127 - (8 * pi + blk));
        dst[0] = o0;
        dst[256] = o1;
    }

    const int rho = 8 * rb + j;

    if (wg == 4) {
        asm volatile("setmaxnreg.dec.sync.aligned.u32 32;");
        if (wq == 0) {
            bar_sync(13, 640);
            TSW(39);
            if (lane == 0) flag_release(FL_P + pg);
            __syncwarp();
            TSW(2);
            if (lane < 5) mbar_expect(bars + (BAR_U + lane) * 8, 4096);
            flag_wait(FL_P + pg, ep1 * 16);
            fence_async_global();
            TSW(3);
            if (elect()) {
#pragma unroll
                for (int i = 0; i < 5; i++) {
                    const char* us = (const char*)g_kvT + (size_t)(chan(i)) * 4096;
                    bulk_g2s(sb + sm_u(i), us, 2048, bars + (BAR_U + i) * 8);
                    bulk_g2s(sb + sm_u(i) + U_PLANE, us + 2048, 2048, bars + (BAR_U + i) * 8);
                }
            }
            __syncwarp();
            if (elect()) {
#pragma unroll
                for (int i = SSM_N; i < 5; i++) {
                    mbar_expect(bars + (BAR_K + i) * 8, 4096);
                    bulk_g2s(sb + sm_k(i) + 32, p.ssmk + (size_t)(chan(i)) * S_, 4096, bars + (BAR_K + i) * 8);
                }
                if (cta < 120) {
                    mbar_expect(bars + BAR_WM0 * 8, 3 * 8192);
                    mbar_expect(bars + BAR_WM * 8, 2 * 8192);
#pragma unroll 1
                    for (int i = 0; i < 5; i++) tma2d(sb + SM_WM + i * 8192, &maps.wm, cta * 32, i * 128, bars + (i < 3 ? BAR_WM0 : BAR_WM) * 8);
                }
                mbar_wait(bars + (cta < 120 ? BAR_WM0 : BAR_K + 4) * 8, 0);
                bulk_prefetch((const char*)p.q + cta * 20480, 20480);
                bulk_prefetch((const char*)p.w1 + cta * 6400, 6400);
                bulk_prefetch((const char*)p.w2 + cta * 6400, 6400);
            }
            __syncwarp();
        } else {
            bar_arrive(13, 640);
        }
        asm volatile("barrier.cluster.wait.aligned;" ::: "memory");
        uint32_t peer;
        asm volatile("ld.shared::cluster.u32 %0, [%1];" : "=r"(peer) : "r"(mapa(sb + SM_GV + 512, (blockIdx.x & 1) ^ 1)) : "memory");
        const bool paired = peer == (smid ^ 1) && !FORCE_UNPAIRED;
        if (tid == 639) sts32(sb + SM_GV + 516, paired);
        if (cta < 120) {
            float d[4];
            if (tid >= 544 && tid < 624) {
                const int t = tid - 544;
                mbar_wait(bars + BAR_U * 8, 0);
                uint4 cv = __ldg(reinterpret_cast<const uint4*>(p.c) + t);
                auto silu2 = [](uint32_t v) { float a = blo(v), b = bhi(v); return pack2(__fdividef(a, 1.0f + __expf(-a)), __fdividef(b, 1.0f + __expf(-b))); };
#pragma unroll 1
                for (int i = 0; i < 4; i++) { const uint32_t r = silu2(cv.x); cv.x = cv.y; cv.y = cv.z; cv.z = cv.w; cv.w = r; }
                sts128(sb + SM_Y + (t % 40) * 32 + (t / 40) * 16, cv);
                fence_async_smem();
            }
            bar_sync(5, 128);
            mbar_wait(bars + BAR_WM0 * 8, 0);
            mbar_wait(bars + BAR_WM * 8, 0);
            if (wq == 3) TSW(56);
            const uint32_t da = desc_lo(sb + SM_WM, 20480), db = desc_lo(sb + SM_Y, 32);
#pragma unroll 1
            for (int k0 = 0; k0 < 20; k0 += 4) {
                wg_fence();
#pragma unroll
                for (int k = k0; k < k0 + 4; k++) asm volatile("{.reg .pred p; .reg .b32 l,m; .reg .b64 da,db; setp.ne.b32 p,%10,0; add.u32 l,%4,%6; mov.b64 da,{l,%8}; add.u32 m,%5,%7; mov.b64 db,{m,%9};"
                             " wgmma.mma_async.sync.aligned.m64n8k16.f32.bf16.bf16 {%0,%1,%2,%3},da,db,p,1,1,1,0;}"
                             : "+f"(d[0]), "+f"(d[1]), "+f"(d[2]), "+f"(d[3])
                             : "r"(da), "r"(db), "r"(64 * k), "r"(4 * k), "n"(desc_hi(512, 2u)), "n"(desc_hi(128, 0)), "r"(k));
                wg_commit();
            }
            wg_wait<0>();
            reg_fence<4>(d);
            if (c == 0) {
                sts32(sb + SM_GV + (16 * wq + g) * 4, __float_as_uint(wq < 2 ? d[0] : d[1]));
                sts32(sb + SM_GV + (16 * wq + g + 8) * 4, __float_as_uint(wq < 2 ? d[2] : d[3]));
            }
            bar_sync(5, 128);
            if (wq == 2) {
                g_mod[cta * 32 + lane] = __float2bfloat16_rn(__uint_as_float(lds32(sb + SM_GV + lane * 4)) + __uint_as_float(lds32(sb + SM_GV + 128 + lane * 4)));
            }
        }
        if (wq == 2) {
            bar_sync(9, 320);
            if (lane == 0) flag_release(FL_M);
            __syncwarp();
            TSW(4);
            flag_wait(FL_M, ep1 * 128);
            fence_async_global();
            if (elect()) {
                mbar_expect(bars + BAR_M * 8, 7680);
                bulk_g2s(sb + SM_MOD, g_mod, 7680, bars + BAR_M * 8);
                mbar_wait(bars + BAR_CD * 8, 0);
                mbar_expect(bars + BAR_Y * 8, 12288);
#pragma unroll 1
                for (int i = 0; i < 8; i++) bulk_g2s(sb + SM_Y + i * 2560, g_yv + rho * 5120 + i * 640, 1536, bars + BAR_Y * 8);
            }
            __syncwarp();
            TSW(60);
            bar_sync(8, 576);  if (lane == 0) { flag_release(FL_R + rb); TS(23); }  __syncwarp();
            bar_sync(15, 288); if (lane == 0) { flag_release(FL_B1 + rb); TS(27); } __syncwarp();
            bar_sync(6, 288);  if (lane == 0) { flag_release(FL_B2 + rb); TS(31); } __syncwarp();
#pragma unroll 1
            for (int i = 0; i < 3; i++) { bar_sync(i ? i : 8, 288); if (lane == 0) { TS(53 + (i + 2) % 3); flag_release(FL_G + 16 * i + rb); TS(57 + (i + 2) % 3); } __syncwarp(); }
            if (lane == 0) g_epoch[smid] = ep1;
            return;
        }
        if (wq == 1) {
            bar_sync(9, 320);
            if (lane < 4 * NB) mbar_arrive_cl(mapa(bars + (BAR_EB + (lane >> 2)) * 8, paired ? lane & 1 : blockIdx.x & 1));
        }
        if (wq == 3) {
            bar_sync(7, 544);
            if (lane == 0) { flag_release(FL_C); mbar_expect(bars + BAR_CD * 8, 0); TS(20); }
            __syncwarp();
            if (lane == 0) mbar_expect(bars + BAR_Y2 * 8, 8192);
            flag_wait(FL_C, ep1 * 128);
            fence_async_global();
            TSW(21);
            if (elect()) {
#pragma unroll
                for (int i = 0; i < 8; i++) bulk_g2s(sb + SM_Y + i * 2560 + 1536, g_yv + rho * 5120 + i * 640 + 384, 1024, bars + BAR_Y2 * 8);
            }
            __syncwarp();
        }
        if (wq == 3) {
            mbar_wait(bars + BAR_Y2 * 8, 0);
            if (elect()) {
                mbar_expect(bars + BAR_XY * 8, 20480);
#pragma unroll 1
                for (int i = 0; i < 8; i++) {
                    bulk_g2s(sb + SM_YT + i * 2560, g_yv + (8 * rb + i) * 5120 + cm * 8, 2048, bars + BAR_XY * 8);
                    bulk_g2s(sb + SM_YT + i * 2560 + 2048, g_yv + (8 * rb + i) * 5120 + cr * 8, 512, bars + BAR_XY * 8);
                }
            }
            __syncwarp();
            bar_sync(8, 576);
            mbar_wait_warm(bars + BAR_FA * 8, 0);
            mbar_wait(bars + BAR_ME * 8, 0);
            mbar_wait_warm(bars + (BAR_FA + 11 % NA) * 8, (11 / NA) & 1);
            flag_wait(FL_CS, ep1 * 4);
            fence_async_global();
            if (elect()) {
                mbar_expect(bars + BAR_CS * 8, 864);
                bulk_g2s(sb + SM_CS, g_cs + 64 * j, 256, bars + BAR_CS * 8);
                bulk_g2s(sb + SM_CS + 256, g_cs + 512 + RA3 * j, 4 * RA3, bars + BAR_CS * 8);
                bulk_g2s(sb + SM_CS + 256 + 4 * RA3, g_cs + HB0 + 64 * j, 256, bars + BAR_CS * 8);
                bulk_g2s(sb + SM_CS + 512 + 4 * RA3, g_cs + HB0 + 512 + RB3 * j, 4 * RB3, bars + BAR_CS * 8);
            }
            __syncwarp();
            mbar_wait(bars + BAR_ME * 8, 1);
            mbar_wait_warm(bars + (BAR_FA + 21 % NA) * 8, (21 / NA) & 1);
#pragma unroll 1
            for (int i = 0; i < 3; i++) {
                if (i) {
                    mbar_wait(bars + BAR_ME * 8, (i + 1) & 1);
                    for (int n = i; n < NPING; n++) { spin(PING); n += tensor_ping(); }
                }
                flag_wait(FL_G + 16 * i + rb, ep1 * 8);
                if (lane == 0) { mbar_expect(bars + (BAR_G + i) * 8, 0); TS(35 + (i + 2) % 3); }
                __syncwarp();
            }
            return;
        }
        if (elect()) {
            if (wq == 1) {
                Ring<NB, SM_RB, BAR_FB, BAR_EB> r{sb, 0, 0};
#pragma unroll 1
                for (int ph = 0; ph < 7; ph++) {
                    const CUtensorMap* ma = ph == 0 ? &maps.w1a : ph == 1 ? &maps.w2a : ph == 6 ? &maps.w4a : &maps.w3a;
                    const bool b3b = ph == 2 || ph == 4 || ph == 5;
                    r.runw(paired, idx & 1, ma, ma + (b3b ? 2 : 1), ph == 3 ? 64 * j : b3b ? HB0 + 64 * j : cm,
                           ph == 3 ? 512 + RA3 * j : b3b ? HB0 + 512 + RB3 * j : cr, ph == 4 ? 10 - NA : ph == 5 ? 1 : 0,
                           ph == 6 ? 27 : ph == 5 ? 10 - NA : ph == 2 ? 1 : 10, ph == 0 ? 0 : ph == 6 ? OWNG * (HB0 / 64 + j) : cm >> 6,
                           ph == 3 ? 8192 + 128 * RA3 : b3b ? 8192 + 128 * RB3 : 10240,
                           ph == 1 ? GATE : ph == 3 ? GATE - 1 : -1, bars + (BAR_ST - (ph == 1)) * 8);
                }
            } else {
                Ring<NA, SM_RA, BAR_FA, BAR_EA> r{sb, 0, 0};
                if (cta >= 120) mbar_wait(bars + (BAR_K + 4) * 8, 0);
                mbar_expect(bars + BAR_XR * 8, 20480);
                bulk_g2s(sb + SM_XR, p.q + (size_t)rho * 16 * D_, 20480, bars + BAR_XR * 8);
                mbar_wait(bars + BAR_Y2 * 8, 0);
                mbar_expect(bars + BAR_XY * 8, 20480);
                tma2d(sb + SM_XT, &maps.xa, cm, rb * 128, bars + BAR_XY * 8);
                tma2d(sb + SM_XT2, &maps.xb, cr, rb * 128, bars + BAR_XY * 8);
                const int grp = j >> 1;
                const int delta = (grp & 1 ? 1 : -1) * (1 + (grp >> 1));
                const int nb = min(max(rb + (delta > 0 ? 1 : -1), 0), 15);
                uint32_t fb = r.acquire(SLOT), dst = r.slot();
                flag_wait2(FL_R + nb, FL_R + rb, ep1 * 8);
                fence_async_global();
                tma2d(dst, &maps.hn, 0, rb * 128 + delta, fb);
                TS(24);
                r.next();
                r.run2d(&maps.hn, rb * 128 + delta);
#pragma unroll 1
                for (int i = 0; i < 2; i++) {
                    const char* src = (const char*)(i ? g_x1 : g_h1) + (size_t)rb * 163840;
                    r.acquire(0); r.next();
                    fb = r.acquire(SLOT); dst = r.slot();
                    const char* src1 = src + (cm == 0 ? SLOT : 0);
                    flag_wait(FL_B1 + 16 * i + rb, ep1 * 8);
                    fence_async_global();
                    bulk_g2s(dst, src1, SLOT, fb);
                    TS(28 + 4 * i);
                    mbar_expect(bars + (BAR_ST - 1 + i) * 8, 0);
                    r.next();
                    r.run1d(src, 2, 10, cm >> 6);
                }
                r.run1d((const char*)g_x1 + (size_t)rb * 163840, 1, 10 - NA, cm >> 6);
                if (OWNG) { r.acquire(0); r.next(); }
#pragma unroll 1
                for (int i = 0; i < 2; i++) {
                    mbar_wait(bars + (BAR_G + 1 + i) * 8, 0); fence_async_global();
                    r.run1d((const char*)g_g + (size_t)rb * 442368, OWNG + HB0 / 64 * i, i ? 27 : OWNG + HB0 / 64, OWNG * (HB0 / 64 + j));
                }
            }
        }
        return;
    }
    bar_arrive(13, 640);
    asm volatile("setmaxnreg.inc.sync.aligned.u32 112;");
    const int rrow = 16 * rho + (warp >> 1) + 8 * (warp & 1);

    fence_async_smem();
    bar_sync(1 + wg, 128);
#pragma unroll 1
    for (int cc = wg; cc < wg + 1 + (wg == 3); cc++) {
        mbar_wait(bars + (BAR_K + cc) * 8, 0);
        if (cc == 2 && wq == 0) TSW(40);
        uint32_t a = sb + sm_k(cc) + 32 + (tid & 127) * 32;
        uint32_t pw = lds32(a - 4);
        uint4 x = lds128(a), y = lds128(a + 16), o;
        if ((tid & 127) == 0) {
            uint16_t k0 = __bfloat16_as_ushort(__float2bfloat16_rn(blo(x.x) + __uint_as_float(lds32(sb + SM_GV + 520 + cc * 4))));
            x.x = (x.x & 0xffff0000u) | k0;
            sts16(a, k0);
        }
        o.x = prmt(pw, x.x, 0x5432); o.y = prmt(x.x, x.y, 0x5432); o.z = prmt(x.y, x.z, 0x5432); o.w = prmt(x.z, x.w, 0x5432);
        sts128(a + 4160, o);
        o.x = prmt(x.w, y.x, 0x5432); o.y = prmt(y.x, y.y, 0x5432); o.z = prmt(y.y, y.z, 0x5432); o.w = prmt(y.z, y.w, 0x5432);
        sts128(a + 4176, o);
    }
    bar_sync(1 + wg, 128);
    if (wg == 3) bar_arrive(11, 256);
#pragma unroll 1
    for (int cc = wg; cc < 5; cc += 3) {
        if (cc == 3 && wg == 0) break;
        if (cc == 4) bar_sync(11, 256);
        const uint32_t kaddr = sb + sm_k(cc) + ((g & 1) ? 32 : 4192) + 4 * ((g >> 1) - c) + 64 * wq;
        const AFrag f0 = ldA(kaddr), f1 = ldA(kaddr + 256);
        if (STAG && cc == 3) bar_sync(12, 256);
        mbar_wait(bars + (BAR_U + cc) * 8, 0);
        if (wq == 0) TSW(5 + cc);
        float d[64];
        conv_two<0>(d, f0, f1, kaddr, desc_lo(sb + sm_u(cc), U_PLANE), sb + sm_red(cc) + wq * 4352 + g * 544 + c * 8, cc == 1);
        if (wq == 0) TSW(10 + cc);
        if (cc == 1) bar_arrive(6, 256);
    }
#pragma unroll 1
    for (int cc = wg == 1 ? 4 : wg;; cc++) {
        if (cc == 1) bar_sync(6, 256); else bar_sync(1 + wg, 128);
        const int ch = chan(cc);
        uint32_t* dst = g_yv + ch * 8 + ((g + (ch >> 2)) & 7) + (126 - 32 * wq - 2 * c) * 5120;
        uint2 v[16];
#pragma unroll
        for (int i = 0; i < 16; i++) v[i] = lds64(sb + sm_red(cc) + g * 544 + wq * 128 + c * 8 + (i >> 2) * 32 + (i & 3) * 4360);
#pragma unroll
        for (int w = 1; w < 4; w++)
            if (wq == 3 && c > 3 - w) v[12 + w] = make_uint2(0, 0);
#pragma unroll
        for (int q = 0; q < 4; q++) {
            const uint2* u = v + 4 * q;
            dst[-8 * q * 5120] = badd2(u[0].x, badd2(u[1].x, badd2(u[2].x, u[3].x)));
            dst[(-8 * q + 1) * 5120] = badd2(u[0].y, badd2(u[1].y, badd2(u[2].y, u[3].y)));
        }
        if (wq == 0) TSW(15 + cc);
        if (cc != 0) break;
    }
    fence_async_smem();
    if (!(wg & 1)) bar_arrive(9, 320);
    bar_arrive(7, 544);

    const uint32_t one2 = 0x3f803f80u;
    const unsigned ones = p.ones;
    {
        uint32_t x[10], a[10], cb[10], sbv[10];
        if (RPRE_WAIT) bar_sync(10, 512);
        mbar_wait(bars + BAR_XR * 8, 0);
#pragma unroll
        for (int i = 0; i < 10; i++) x[i] = lds32(sb + SM_XR + (rrow & 15) * 1280 + lane * 4 + i * 128);
        const uint3 s1 = row_stats(x, lane);
        const int up = lane >> 4, gg = warp >> 1, e = warp & 1;
        const uint32_t ya = sb + SM_Y + lane * 64 + ((gg + (lane >> 1)) & 7) * 4;
        const uint32_t sel = (up ? 0x1054u : 0x5410u) + (e ? 0x2222u : 0u);
        const uint32_t ma = sb + SM_MOD + lane * 4;
        mbar_wait(bars + BAR_M * 8, 0);
        uint32_t pin = 0;
#pragma unroll
        for (int i = 0; i < 10; i++) {
            uint32_t h = bfma2(ln_apply(x[i], s1.x, s1.y, s1.z), badd2(lds32(ma + 1280 + i * 128), one2), lds32(ma + i * 128));
            a[i] = bmul2(h, lds32(ma + 2560 + i * 128));
            sbv[i] = lds32(ma + 3840 + i * 128);
            cb[i] = badd2(lds32(ma + 5120 + i * 128), one2);
            pin ^= a[i] ^ cb[i];
        }
        if (pin & ~ones) sts32(sb + SM_GV, pin);
        if (warp == 4) TSW(52);
        mbar_wait(bars + BAR_Y * 8, 0);
        mbar_wait(bars + BAR_Y2 * 8, 0);
        if (warp == 0) TSW(22);
#pragma unroll
        for (int i = 0; i < 10; i++) {
            uint32_t y0 = lds32(ya + i * 2048 + up * 32), y1 = lds32(ya + i * 2048 + (up ^ 1) * 32);
            x[i] = bfma2(a[i], prmt(y0, y1, sel), x[i]);
        }
        const uint3 s2 = row_stats(x, lane);
#pragma unroll
        for (int i = 0; i < 10; i++) x[i] = bfma2(ln_apply(x[i], s2.x, s2.y, s2.z), cb[i], sbv[i]);
        const uint3 s3 = row_stats(x, lane);
        uint32_t* o = reinterpret_cast<uint32_t*>(g_hn + (size_t)rrow * D_) + lane;
#pragma unroll
        for (int i = 0; i < 10; i++) o[32 * i] = ln_apply(x[i], s3.x, s3.y, s3.z);
        if (lane < 2) g_rs[rrow * 2 + lane] = lane ? make_uint4(s2.x, s2.y, s2.z, 0) : make_uint4(s1.x, s1.y, s1.z, 0);
        if (warp == 0) TSW(34);
        bar_arrive(8, 576);
    }

    const int half = wg & 1;
    const int row = 64 * half + 16 * wq + g;
    const int tw0 = (rb * 80 + (cm >> 3)) * 512 + row * 4 + c, tw1 = (rb * 80 + (cr >> 3) - 8) * 512 + row * 4 + c;
    const uint32_t park = sb + SM_Y + (tid & 255) * 16;
    const uint32_t ms0 = sb + SM_MOD + (cm + 2 * c) * 2, ms1 = sb + SM_MOD + (cr - 64 + 2 * c) * 2;
    if (wg >= 2) {
        {
            float acc[40];
            gemm_loop<80, true, 10, 10, true>(acc, sb, half, 0, 0, 10, 0, 0, 25);
            if (tid == 256) mbar_expect(bars + BAR_ME * 8, 0);
#pragma unroll
            for (int k = 0; k < 10; k += CH) CHUNK(k) {
#pragma unroll
                for (int q = k; q < k + CH && q < 10; q++) {
                    uint32_t* dst = reinterpret_cast<uint32_t*>(g_h1) + (q < 8 ? tw0 : tw1);
                    const uint32_t u = gelu2_h(bmul2(pack2(acc[4 * q], acc[4 * q + 1]), 0x3f003f00u));
                    const uint32_t v = gelu2_h(bmul2(pack2(acc[4 * q + 2], acc[4 * q + 3]), 0x3f003f00u));
                    dst[q * 512] = u;
                    dst[q * 512 + 32] = v;
                    acc[4 * q] = __uint_as_float(u); acc[4 * q + 1] = __uint_as_float(v);
                }
            }
            bar_arrive(15, 288);
            mbar_wait(bars + (BAR_FA + 10 % NA) * 8, (10 / NA) & 1);
#pragma unroll
            for (int q = 0; q < 8; q++) {
                sts32(sb + SM_RA + (10 % NA) * SLOT + q * 2048 + row * 16 + c * 4, __float_as_uint(acc[4 * q]));
                sts32(sb + SM_RA + (10 % NA) * SLOT + q * 2048 + row * 16 + c * 4 + 128, __float_as_uint(acc[4 * q + 1]));
            }
            fence_async_smem();
            bar_arrive(14, 512);
        }
        gemm3<0>(sb, rb, j, half, row, c, ones);
        {
            float acc[40];
            uint32_t gbv[10], base[20];
#pragma unroll
            for (int q = 0; q < 10; q++) gbv[q] = lds32((q < 8 ? ms0 : ms1) + 6400 + q * 16);
#pragma unroll
            for (int q = 0; q < 5; q++) { const uint4 t = lds128(park + q * 4096); base[4 * q] = t.x; base[4 * q + 1] = t.y; base[4 * q + 2] = t.z; base[4 * q + 3] = t.w; }
            gemm_loop<80, false, 27, 27 - NB, true>(acc, sb, half, 39 - NA, 40, 27 - NA, 11, 0, 42);
            auto fin = [&](int q, int r) {
                return bfma2(gbv[q], pack2(acc[4 * q + 2 * r], acc[4 * q + 2 * r + 1]), base[2 * q + r]);
            };
            auto tr4 = [&](uint32_t t0, uint32_t t1, uint32_t t2, uint32_t t3) {
                const bool o1 = c & 1, o2 = c & 2;
                uint32_t a = __shfl_xor_sync(0xffffffffu, o1 ? t0 : t1, 1), b = __shfl_xor_sync(0xffffffffu, o1 ? t2 : t3, 1);
                uint32_t u0 = o1 ? a : t0, u1 = o1 ? t1 : a, u2 = o1 ? b : t2, u3 = o1 ? t3 : b;
                a = __shfl_xor_sync(0xffffffffu, o2 ? u0 : u2, 2); b = __shfl_xor_sync(0xffffffffu, o2 ? u1 : u3, 2);
                return o2 ? make_uint4(a, b, u2, u3) : make_uint4(u0, u1, a, b);
            };
            bf16* go = p.out + (size_t)(rb * 128 + row) * D_;
#pragma unroll
            for (int k = 0; k < 2; k++) CHUNK(k) {
#pragma unroll
                for (int r = 0; r < 2; r++)
                    *reinterpret_cast<uint4*>(go + r * 8 * D_ + cm + 32 * k + 8 * c) = tr4(fin(4 * k, r), fin(4 * k + 1, r), fin(4 * k + 2, r), fin(4 * k + 3, r));
            }
            CHUNK(2) *reinterpret_cast<uint4*>(go + (c >> 1) * 8 * D_ + cr + 8 * (c & 1)) = tr4(fin(8, 0), fin(9, 0), fin(8, 1), fin(9, 1));
            if (tid == 256) TS(44);
            if (warp == 8) TSFLUSH();
        }
    } else {
        {
            float acc[40];
            uint32_t x2[20];
            {
                uint32_t y[20];
                mbar_wait(bars + BAR_XY * 8, 0);
                const uint32_t xa = sb + SM_XT + row * 128 + c * 4, xb = sb + SM_XT2 + row * 32 + c * 4;
                const uint32_t ya = sb + SM_YT + (4 * half + wq) * 2560 + c * 64;
#pragma unroll
                for (int q = 0; q < 10; q++) {
                    const uint32_t a = q < 8 ? xa + ((q ^ g) << 4) : xb + (q - 8) * 16;
                    x2[2 * q] = lds32(a); x2[2 * q + 1] = lds32(a + (q < 8 ? 1024 : 256));
                    const int pos = (g + ((q < 8 ? cm : cr) >> 2) + 2 * q + (c >> 1)) & 7;
                    y[2 * q] = lds32(ya + q * 256 + pos * 4); y[2 * q + 1] = lds32(ya + q * 256 + 32 + pos * 4);
                }
                fence_async_smem();
                bar_sync(1 + wg, 128);
                if ((tid & 127) < NA) mbar_arrive_cl(mapa(bars + (BAR_EA + (tid & 127)) * 8, blockIdx.x & 1));
                mbar_wait(bars + (BAR_FA + 1) * 8, 0);
                const uint4* rp = g_rs + (rb * 128 + row) * 2;
                const uint4 ra = ldcg128(rp), rb2 = ldcg128(rp + 1), rc = ldcg128(rp + 16), rd = ldcg128(rp + 17);
                bar_sync(14, 512);
#pragma unroll
                for (int q = 0; q < 10; q++) {
                    const uint32_t ms = q < 8 ? ms0 : ms1;
                    const uint32_t sa = lds32(ms + 16 * q), ca = badd2(lds32(ms + 1280 + 16 * q), one2), ga = lds32(ms + 2560 + 16 * q);
                    const uint32_t sbv = lds32(ms + 3840 + 16 * q), cb = badd2(lds32(ms + 5120 + 16 * q), one2);
                    uint32_t u = x2[2 * q], v = x2[2 * q + 1];
                    u = bfma2(bmul2(bfma2(ln_apply(u, ra.x, ra.y, ra.z), ca, sa), ga), prmt(y[2 * q], y[2 * q + 1], 0x5410), u);
                    v = bfma2(bmul2(bfma2(ln_apply(v, rc.x, rc.y, rc.z), ca, sa), ga), prmt(y[2 * q], y[2 * q + 1], 0x7632), v);
                    x2[2 * q] = u; x2[2 * q + 1] = v;
                    u = bfma2(ln_apply(u, rb2.x, rb2.y, rb2.z), cb, sbv);
                    v = bfma2(ln_apply(v, rd.x, rd.y, rd.z), cb, sbv);
                    acc[4 * q] = blo(u); acc[4 * q + 1] = bhi(u); acc[4 * q + 2] = blo(v); acc[4 * q + 3] = bhi(v);
                }
            }
            reg_fence<40>(acc);
            if (tid == 0) TS(45);
            gemm_loop<80, false, 10, 10, false>(acc, sb, half, 10, 10, 10, 0, 0, 29);
            if (tid == 0) mbar_expect(bars + BAR_ME * 8, 0);
            uint32_t x1[20];
            float s0 = 0.f, q0 = 0.f, s1 = 0.f, q1 = 0.f;
#pragma unroll
            for (int q = 0; q < 10; q++) {
                uint32_t u = pack2(acc[4 * q], acc[4 * q + 1]);
                uint32_t v = pack2(acc[4 * q + 2], acc[4 * q + 3]);
                uint32_t* dst = reinterpret_cast<uint32_t*>(g_x1) + (q < 8 ? tw0 : tw1);
                dst[q * 512] = u;
                dst[q * 512 + 32] = v;
                x1[2 * q] = u; x1[2 * q + 1] = v;
            }
            bar_arrive(6, 288);
            CHUNK(0)
#pragma unroll
            for (int q = 0; q < 10; q++) {
                float a = blo(x1[2 * q]), b = bhi(x1[2 * q]), e = blo(x1[2 * q + 1]), f = bhi(x1[2 * q + 1]);
                s0 += a + b; q0 = fmaf(a, a, fmaf(b, b, q0));
                s1 += e + f; q1 = fmaf(e, e, fmaf(f, f, q1));
            }
#pragma unroll
            for (int m = 1; m <= 2; m <<= 1) {
                s0 += __shfl_xor_sync(0xffffffffu, s0, m); q0 += __shfl_xor_sync(0xffffffffu, q0, m);
                s1 += __shfl_xor_sync(0xffffffffu, s1, m); q1 += __shfl_xor_sync(0xffffffffu, q1, m);
            }
            if (c < 2) g_st[(rb * 8 + j) * 128 + row + 8 * c] = c ? make_float2(s1, q1) : make_float2(s0, q0);
            bar_arrive(8, 288);
            mbar_wait(bars + (BAR_FA + 20 % NA) * 8, (20 / NA) & 1);
#pragma unroll
            for (int q = 0; q < 8; q++) {
                sts32(sb + SM_RA + (20 % NA) * SLOT + q * 2048 + row * 16 + c * 4, x1[2 * q]);
                sts32(sb + SM_RA + (20 % NA) * SLOT + q * 2048 + row * 16 + c * 4 + 128, x1[2 * q + 1]);
            }
            fence_async_smem();
            bar_sync(3 + wg, 128);
#pragma unroll
            for (int q = 0; q < 5; q++) {
                const uint32_t ms = q < 4 ? ms0 : ms1;
                const uint32_t g0 = lds32(ms + 6400 + q * 32), g1 = lds32(ms + 6400 + q * 32 + 16);
                sts128(park + q * 4096, make_uint4(bfma2(g0, x1[4 * q], x2[4 * q]), bfma2(g0, x1[4 * q + 1], x2[4 * q + 1]),
                                                   bfma2(g1, x1[4 * q + 2], x2[4 * q + 2]), bfma2(g1, x1[4 * q + 3], x2[4 * q + 3])));
            }
        }
        gemm3<1>(sb, rb, j, half, row, c, ones);
    }
}

typedef CUresult (*EncFn)(CUtensorMap*, CUtensorMapDataType, cuuint32_t, void*, const cuuint64_t*, const cuuint64_t*,
                          const cuuint32_t*, const cuuint32_t*, CUtensorMapInterleave, CUtensorMapSwizzle,
                          CUtensorMapL2promotion, CUtensorMapFloatOOBfill);

void make_map(EncFn enc, CUtensorMap* m, const void* base, uint64_t inner, uint64_t outer, uint32_t bi, uint32_t bo,
              CUtensorMapSwizzle swz = CU_TENSOR_MAP_SWIZZLE_128B) {
    cuuint64_t dims[2] = {inner, outer};
    cuuint64_t st[1] = {inner * 2};
    cuuint32_t box[2] = {bi, bo};
    cuuint32_t es[2] = {1, 1};
    enc(m, CU_TENSOR_MAP_DATA_TYPE_BFLOAT16, 2, const_cast<void*>(base), dims, st, box, es, CU_TENSOR_MAP_INTERLEAVE_NONE,
        swz, CU_TENSOR_MAP_L2_PROMOTION_NONE, CU_TENSOR_MAP_FLOAT_OOB_FILL_NONE);
}

}

extern "C" void kernel_launch(void* const* d_in, const int* in_sizes, int n_in, void* d_out, int out_size) {
    (void)in_sizes; (void)n_in; (void)out_size;
    Params p;
    p.q = (const bf16*)d_in[0]; p.k = (const bf16*)d_in[1]; p.v = (const bf16*)d_in[2];
    p.shift = (const bf16*)d_in[3]; p.ssmk = (const bf16*)d_in[4]; p.ssmD = (const bf16*)d_in[5];
    p.w1 = (const bf16*)d_in[7]; p.w2 = (const bf16*)d_in[8]; p.w3 = (const bf16*)d_in[9]; p.w4 = (const bf16*)d_in[10];
    p.c = (const bf16*)d_in[11]; p.wmod = (const bf16*)d_in[12];
    p.out = (bf16*)d_out;
    p.ones = 0xffffffffu;

    void* fn = nullptr;
    cudaDriverEntryPointQueryResult qr;
    cudaGetDriverEntryPoint("cuTensorMapEncodeTiled", &fn, cudaEnableDefault, &qr);
    EncFn enc = (EncFn)fn;
    void* hn = nullptr;
    cudaGetSymbolAddress(&hn, g_hn);
    Maps maps;
    make_map(enc, &maps.w3s, p.w3, F_, D_, 216, 64, CU_TENSOR_MAP_SWIZZLE_NONE);
    make_map(enc, &maps.wm, p.wmod, 6 * D_, D_, 32, 128, CU_TENSOR_MAP_SWIZZLE_64B);
    make_map(enc, &maps.xa, p.q, D_, S_, 64, 128);
    make_map(enc, &maps.xb, p.q, D_, S_, 16, 128, CU_TENSOR_MAP_SWIZZLE_NONE);
    make_map(enc, &maps.hn, hn, D_, S_, 64, 128);
    make_map(enc, &maps.w1a, p.w1, D_, D_, 64, 64);
    make_map(enc, &maps.w1b, p.w1, D_, D_, 16, 64);
    make_map(enc, &maps.w2a, p.w2, D_, D_, 64, 64);
    make_map(enc, &maps.w2b, p.w2, D_, D_, 16, 64);
    make_map(enc, &maps.w3a, p.w3, F_, D_, 64, 64);
    make_map(enc, &maps.w3b, p.w3, F_, D_, RA3, 64);
    make_map(enc, &maps.w3c, p.w3, F_, D_, RB3, 64);
    make_map(enc, &maps.w4a, p.w4, D_, F_, 64, 64);
    make_map(enc, &maps.w4b, p.w4, D_, F_, 16, 64);
    cudaFuncSetAttribute(fused_kernel, cudaFuncAttributeMaxDynamicSharedMemorySize, SMEM_BYTES);
    fused_kernel<<<132, NTHREADS, SMEM_BYTES>>>(p, maps);
}
```

```cpp
#include <cuda_runtime.h>
#include <cuda_bf16.h>
#include <cuda.h>
#include <stdint.h>
#include <string.h>

#define SEED 0
#define RING_A 6
#define CH 2
#define FAST_LN 2
#define STAG 12
#define PGELU 2
#define CH3 4
#define HO_A 16
#define HO_B 16
#define RA3 48
#define CSP 16
#define OWNG 1
#define GATE 5
#define SSM_DELAY 100
#define B_DELAY 220
#define RPRE_WAIT 1
#define PING 250
#define NPING 5
#define FORCE_UNPAIRED 0
#define SSM_N 3

namespace {

typedef __nv_bfloat16 bf16;
typedef __nv_bfloat162 bf162;

constexpr int S_ = 2048, D_ = 640, F_ = 1728;
constexpr int NTHREADS = 640;
constexpr int NA = RING_A, NB = 12 - RING_A;
constexpr int SLOT = 16384;
constexpr int RB3 = 88 - RA3, HB0 = 512 + 8 * RA3;
constexpr int SM_RA = 0, SM_RB = NA * SLOT;

static_assert(NA == 6, "smem map");
constexpr int RED_STRIDE = 17536;
constexpr int K_STRIDE = 8320;
constexpr int U_PLANE = 2560, U_STRIDE = 5120;
constexpr int SM_Y = 12 * SLOT;
__device__ __forceinline__ int sm_red(int cc) { return cc * RED_STRIDE + (cc < 3 ? SM_RB : -3 * RED_STRIDE); }
__device__ __forceinline__ int sm_k(int cc) { return cc * K_STRIDE + (cc < 3 ? SM_RB + 3 * RED_STRIDE : 2 * RED_STRIDE - 3 * K_STRIDE); }
__device__ __forceinline__ int sm_u(int cc) { return cc * U_STRIDE + (cc < 3 ? SM_RB + 3 * RED_STRIDE + 3 * K_STRIDE : SM_Y + 8192 - 3 * U_STRIDE); }
constexpr int SM_PK = SM_RB;
constexpr int SM_PV = SM_RB + 24576;
constexpr int SM_WM = 57344;
constexpr int SM_XT = SM_WM, SM_XT2 = SM_WM + 16384, SM_XR = SM_WM + 20480;
constexpr int SM_YT = 0;
constexpr int SM_MOD = SM_Y + 20480;
constexpr int SM_GV = SM_MOD + 7680;
constexpr int SM_CS = SM_GV + 1024;
constexpr int SM_RP = SM_CS + 1024;
constexpr int SM_BAR = SM_RP + 1024;
constexpr int SM_PROF = SM_BAR + 512;
constexpr int SM_TOTAL = SM_PROF + 512;
constexpr int SMEM_BYTES = SM_TOTAL + 1024;
static_assert(SMEM_BYTES <= 232448, "smem");

constexpr int BAR_FA = 0, BAR_FB = NA, BAR_EA = 12, BAR_EB = 12 + NA, BAR_K = 24, BAR_U = 29, BAR_Y = 34, BAR_CS = 35, BAR_WM = 36, BAR_M = 37, BAR_XY = 38, BAR_Y2 = 39, BAR_G = 40, BAR_ST = 44, BAR_XR = 45, BAR_ME = 46, BAR_CD = 47, BAR_WM0 = 48, NBARS = 49;

__device__ __align__(1024) bf16 g_kvT[D_ * S_];
__device__ __align__(1024) uint32_t g_yv[128 * 5120];
__device__ __align__(1024) bf16 g_mod[6 * D_];
__device__ __align__(1024) bf16 g_hn[S_ * D_];
__device__ __align__(1024) uint4 g_rs[S_ * 2];
__device__ __align__(1024) bf16 g_h1[S_ * D_];
__device__ __align__(1024) bf16 g_x1[S_ * D_];
__device__ __align__(1024) bf16 g_g[S_ * F_];
__device__ __align__(1024) float2 g_st[S_ * 8];
__device__ __align__(1024) float g_cs[F_];
__device__ __align__(1024) unsigned g_flags[128 * 32];
__device__ __align__(1024) unsigned g_epoch[160];
constexpr int FL_P = 0, FL_C = 8, FL_CS = 9, FL_M = 10, FL_R = 16, FL_B1 = 32, FL_B2 = 48, FL_G = 64;

#define TS(i) do {} while (0)
#define TSW(i) do {} while (0)
#define TSD(i, dep) do {} while (0)
#define TSD2(i, dep) do {} while (0)
#define TSFLUSH() do {} while (0)

struct Params {
    const bf16 *q, *k, *v, *shift, *ssmk, *ssmD, *w1, *w2, *w3, *w4, *c, *wmod;
    bf16* out;
    unsigned* epoch;
    unsigned ones;
};
#define CHUNK(k) if (ones & (1u << (k)))
struct Maps { CUtensorMap hn, w1a, w1b, w2a, w2b, w3a, w3b, w3c, w4a, w4b, wm, xa, xb, w3s; };

template<int N> struct WgRs;
template<int N> struct WgSs;
template<> struct WgRs<32> { template<int OFF,int HI,int SC> static __device__ __forceinline__ void run(float* d,uint32_t a0,uint32_t a1,uint32_t a2,uint32_t a3,uint32_t blo){
 asm volatile("{.reg .b32 l; .reg .b64 db; add.u32 l,%20,%21; mov.b64 db,{l,%22}; wgmma.mma_async.sync.aligned.m64n32k16.f32.bf16.bf16 {%0,%1,%2,%3,%4,%5,%6,%7,%8,%9,%10,%11,%12,%13,%14,%15},{%16,%17,%18,%19},db,%23,1,1,0;}"
 :"+f"(d[0]),"+f"(d[1]),"+f"(d[2]),"+f"(d[3]),"+f"(d[4]),"+f"(d[5]),"+f"(d[6]),"+f"(d[7]),"+f"(d[8]),"+f"(d[9]),"+f"(d[10]),"+f"(d[11]),"+f"(d[12]),"+f"(d[13]),"+f"(d[14]),"+f"(d[15])
 :"r"(a0),"r"(a1),"r"(a2),"r"(a3),"r"(blo),"n"(OFF),"n"(HI),"n"(SC)); } };
template<> struct WgRs<48> { template<int OFF,int HI,int SC> static __device__ __forceinline__ void run(float* d,uint32_t a0,uint32_t a1,uint32_t a2,uint32_t a3,uint32_t blo){
 asm volatile("{.reg .b32 l; .reg .b64 db; add.u32 l,%28,%29; mov.b64 db,{l,%30}; wgmma.mma_async.sync.aligned.m64n48k16.f32.bf16.bf16 {%0,%1,%2,%3,%4,%5,%6,%7,%8,%9,%10,%11,%12,%13,%14,%15,%16,%17,%18,%19,%20,%21,%22,%23},{%24,%25,%26,%27},db,%31,1,1,0;}"
 :"+f"(d[0]),"+f"(d[1]),"+f"(d[2]),"+f"(d[3]),"+f"(d[4]),"+f"(d[5]),"+f"(d[6]),"+f"(d[7]),"+f"(d[8]),"+f"(d[9]),"+f"(d[10]),"+f"(d[11]),"+f"(d[12]),"+f"(d[13]),"+f"(d[14]),"+f"(d[15]),"+f"(d[16]),"+f"(d[17]),"+f"(d[18]),"+f"(d[19]),"+f"(d[20]),"+f"(d[21]),"+f"(d[22]),"+f"(d[23])
 :"r"(a0),"r"(a1),"r"(a2),"r"(a3),"r"(blo),"n"(OFF),"n"(HI),"n"(SC)); } };
template<> struct WgRs<64> { template<int OFF,int HI,int SC> static __device__ __forceinline__ void run(float* d,uint32_t a0,uint32_t a1,uint32_t a2,uint32_t a3,uint32_t blo){
 asm volatile("{.reg .b32 l; .reg .b64 db; add.u32 l,%36,%37; mov.b64 db,{l,%38}; wgmma.mma_async.sync.aligned.m64n64k16.f32.bf16.bf16 {%0,%1,%2,%3,%4,%5,%6,%7,%8,%9,%10,%11,%12,%13,%14,%15,%16,%17,%18,%19,%20,%21,%22,%23,%24,%25,%26,%27,%28,%29,%30,%31},{%32,%33,%34,%35},db,%39,1,1,0;}"
 :"+f"(d[0]),"+f"(d[1]),"+f"(d[2]),"+f"(d[3]),"+f"(d[4]),"+f"(d[5]),"+f"(d[6]),"+f"(d[7]),"+f"(d[8]),"+f"(d[9]),"+f"(d[10]),"+f"(d[11]),"+f"(d[12]),"+f"(d[13]),"+f"(d[14]),"+f"(d[15]),"+f"(d[16]),"+f"(d[17]),"+f"(d[18]),"+f"(d[19]),"+f"(d[20]),"+f"(d[21]),"+f"(d[22]),"+f"(d[23]),"+f"(d[24]),"+f"(d[25]),"+f"(d[26]),"+f"(d[27]),"+f"(d[28]),"+f"(d[29]),"+f"(d[30]),"+f"(d[31])
 :"r"(a0),"r"(a1),"r"(a2),"r"(a3),"r"(blo),"n"(OFF),"n"(HI),"n"(SC)); } };
template<> struct WgRs<80> { template<int OFF,int HI,int SC> static __device__ __forceinline__ void run(float* d,uint32_t a0,uint32_t a1,uint32_t a2,uint32_t a3,uint32_t blo){
 asm volatile("{.reg .b32 l; .reg .b64 db; add.u32 l,%44,%45; mov.b64 db,{l,%46}; wgmma.mma_async.sync.aligned.m64n80k16.f32.bf16.bf16 {%0,%1,%2,%3,%4,%5,%6,%7,%8,%9,%10,%11,%12,%13,%14,%15,%16,%17,%18,%19,%20,%21,%22,%23,%24,%25,%26,%27,%28,%29,%30,%31,%32,%33,%34,%35,%36,%37,%38,%39},{%40,%41,%42,%43},db,%47,1,1,0;}"
 :"+f"(d[0]),"+f"(d[1]),"+f"(d[2]),"+f"(d[3]),"+f"(d[4]),"+f"(d[5]),"+f"(d[6]),"+f"(d[7]),"+f"(d[8]),"+f"(d[9]),"+f"(d[10]),"+f"(d[11]),"+f"(d[12]),"+f"(d[13]),"+f"(d[14]),"+f"(d[15]),"+f"(d[16]),"+f"(d[17]),"+f"(d[18]),"+f"(d[19]),"+f"(d[20]),"+f"(d[21]),"+f"(d[22]),"+f"(d[23]),"+f"(d[24]),"+f"(d[25]),"+f"(d[26]),"+f"(d[27]),"+f"(d[28]),"+f"(d[29]),"+f"(d[30]),"+f"(d[31]),"+f"(d[32]),"+f"(d[33]),"+f"(d[34]),"+f"(d[35]),"+f"(d[36]),"+f"(d[37]),"+f"(d[38]),"+f"(d[39])
 :"r"(a0),"r"(a1),"r"(a2),"r"(a3),"r"(blo),"n"(OFF),"n"(HI),"n"(SC)); } };
template<> struct WgRs<96> { template<int OFF,int HI,int SC> static __device__ __forceinline__ void run(float* d,uint32_t a0,uint32_t a1,uint32_t a2,uint32_t a3,uint32_t blo){
 asm volatile("{.reg .b32 l; .reg .b64 db; add.u32 l,%52,%53; mov.b64 db,{l,%54}; wgmma.mma_async.sync.aligned.m64n96k16.f32.bf16.bf16 {%0,%1,%2,%3,%4,%5,%6,%7,%8,%9,%10,%11,%12,%13,%14,%15,%16,%17,%18,%19,%20,%21,%22,%23,%24,%25,%26,%27,%28,%29,%30,%31,%32,%33,%34,%35,%36,%37,%38,%39,%40,%41,%42,%43,%44,%45,%46,%47},{%48,%49,%50,%51},db,%55,1,1,0;}"
 :"+f"(d[0]),"+f"(d[1]),"+f"(d[2]),"+f"(d[3]),"+f"(d[4]),"+f"(d[5]),"+f"(d[6]),"+f"(d[7]),"+f"(d[8]),"+f"(d[9]),"+f"(d[10]),"+f"(d[11]),"+f"(d[12]),"+f"(d[13]),"+f"(d[14]),"+f"(d[15]),"+f"(d[16]),"+f"(d[17]),"+f"(d[18]),"+f"(d[19]),"+f"(d[20]),"+f"(d[21]),"+f"(d[22]),"+f"(d[23]),"+f"(d[24]),"+f"(d[25]),"+f"(d[26]),"+f"(d[27]),"+f"(d[28]),"+f"(d[29]),"+f"(d[30]),"+f"(d[31]),"+f"(d[32]),"+f"(d[33]),"+f"(d[34]),"+f"(d[35]),"+f"(d[36]),"+f"(d[37]),"+f"(d[38]),"+f"(d[39]),"+f"(d[40]),"+f"(d[41]),"+f"(d[42]),"+f"(d[43]),"+f"(d[44]),"+f"(d[45]),"+f"(d[46]),"+f"(d[47])
 :"r"(a0),"r"(a1),"r"(a2),"r"(a3),"r"(blo),"n"(OFF),"n"(HI),"n"(SC)); } };
template<> struct WgRs<112> { template<int OFF,int HI,int SC> static __device__ __forceinline__ void run(float* d,uint32_t a0,uint32_t a1,uint32_t a2,uint32_t a3,uint32_t blo){
 asm volatile("{.reg .b32 l; .reg .b64 db; add.u32 l,%60,%61; mov.b64 db,{l,%62}; wgmma.mma_async.sync.aligned.m64n112k16.f32.bf16.bf16 {%0,%1,%2,%3,%4,%5,%6,%7,%8,%9,%10,%11,%12,%13,%14,%15,%16,%17,%18,%19,%20,%21,%22,%23,%24,%25,%26,%27,%28,%29,%30,%31,%32,%33,%34,%35,%36,%37,%38,%39,%40,%41,%42,%43,%44,%45,%46,%47,%48,%49,%50,%51,%52,%53,%54,%55},{%56,%57,%58,%59},db,%63,1,1,0;}"
 :"+f"(d[0]),"+f"(d[1]),"+f"(d[2]),"+f"(d[3]),"+f"(d[4]),"+f"(d[5]),"+f"(d[6]),"+f"(d[7]),"+f"(d[8]),"+f"(d[9]),"+f"(d[10]),"+f"(d[11]),"+f"(d[12]),"+f"(d[13]),"+f"(d[14]),"+f"(d[15]),"+f"(d[16]),"+f"(d[17]),"+f"(d[18]),"+f"(d[19]),"+f"(d[20]),"+f"(d[21]),"+f"(d[22]),"+f"(d[23]),"+f"(d[24]),"+f"(d[25]),"+f"(d[26]),"+f"(d[27]),"+f"(d[28]),"+f"(d[29]),"+f"(d[30]),"+f"(d[31]),"+f"(d[32]),"+f"(d[33]),"+f"(d[34]),"+f"(d[35]),"+f"(d[36]),"+f"(d[37]),"+f"(d[38]),"+f"(d[39]),"+f"(d[40]),"+f"(d[41]),"+f"(d[42]),"+f"(d[43]),"+f"(d[44]),"+f"(d[45]),"+f"(d[46]),"+f"(d[47]),"+f"(d[48]),"+f"(d[49]),"+f"(d[50]),"+f"(d[51]),"+f"(d[52]),"+f"(d[53]),"+f"(d[54]),"+f"(d[55])
 :"r"(a0),"r"(a1),"r"(a2),"r"(a3),"r"(blo),"n"(OFF),"n"(HI),"n"(SC)); } };
template<> struct WgRs<128> { template<int OFF,int HI,int SC> static __device__ __forceinline__ void run(float* d,uint32_t a0,uint32_t a1,uint32_t a2,uint32_t a3,uint32_t blo){
 asm volatile("{.reg .b32 l; .reg .b64 db; add.u32 l,%68,%69; mov.b64 db,{l,%70}; wgmma.mma_async.sync.aligned.m64n128k16.f32.bf16.bf16 {%0,%1,%2,%3,%4,%5,%6,%7,%8,%9,%10,%11,%12,%13,%14,%15,%16,%17,%18,%19,%20,%21,%22,%23,%24,%25,%26,%27,%28,%29,%30,%31,%32,%33,%34,%35,%36,%37,%38,%39,%40,%41,%42,%43,%44,%45,%46,%47,%48,%49,%50,%51,%52,%53,%54,%55,%56,%57,%58,%59,%60,%61,%62,%63},{%64,%65,%66,%67},db,%71,1,1,0;}"
 :"+f"(d[0]),"+f"(d[1]),"+f"(d[2]),"+f"(d[3]),"+f"(d[4]),"+f"(d[5]),"+f"(d[6]),"+f"(d[7]),"+f"(d[8]),"+f"(d[9]),"+f"(d[10]),"+f"(d[11]),"+f"(d[12]),"+f"(d[13]),"+f"(d[14]),"+f"(d[15]),"+f"(d[16]),"+f"(d[17]),"+f"(d[18]),"+f"(d[19]),"+f"(d[20]),"+f"(d[21]),"+f"(d[22]),"+f"(d[23]),"+f"(d[24]),"+f"(d[25]),"+f"(d[26]),"+f"(d[27]),"+f"(d[28]),"+f"(d[29]),"+f"(d[30]),"+f"(d[31]),"+f"(d[32]),"+f"(d[33]),"+f"(d[34]),"+f"(d[35]),"+f"(d[36]),"+f"(d[37]),"+f"(d[38]),"+f"(d[39]),"+f"(d[40]),"+f"(d[41]),"+f"(d[42]),"+f"(d[43]),"+f"(d[44]),"+f"(d[45]),"+f"(d[46]),"+f"(d[47]),"+f"(d[48]),"+f"(d[49]),"+f"(d[50]),"+f"(d[51]),"+f"(d[52]),"+f"(d[53]),"+f"(d[54]),"+f"(d[55]),"+f"(d[56]),"+f"(d[57]),"+f"(d[58]),"+f"(d[59]),"+f"(d[60]),"+f"(d[61]),"+f"(d[62]),"+f"(d[63])
 :"r"(a0),"r"(a1),"r"(a2),"r"(a3),"r"(blo),"n"(OFF),"n"(HI),"n"(SC)); } };
template<> struct WgSs<80> { template<int AOFF,int AHI,int BOFF,int BHI,int SC> static __device__ __forceinline__ void run(float* d,uint32_t alo,uint32_t blo){
 asm volatile("{.reg .b32 l,m; .reg .b64 da,db; add.u32 l,%40,%42; mov.b64 da,{l,%43}; add.u32 m,%41,%44; mov.b64 db,{m,%45}; wgmma.mma_async.sync.aligned.m64n80k16.f32.bf16.bf16 {%0,%1,%2,%3,%4,%5,%6,%7,%8,%9,%10,%11,%12,%13,%14,%15,%16,%17,%18,%19,%20,%21,%22,%23,%24,%25,%26,%27,%28,%29,%30,%31,%32,%33,%34,%35,%36,%37,%38,%39},da,db,%46,1,1,0,1;}"
 :"+f"(d[0]),"+f"(d[1]),"+f"(d[2]),"+f"(d[3]),"+f"(d[4]),"+f"(d[5]),"+f"(d[6]),"+f"(d[7]),"+f"(d[8]),"+f"(d[9]),"+f"(d[10]),"+f"(d[11]),"+f"(d[12]),"+f"(d[13]),"+f"(d[14]),"+f"(d[15]),"+f"(d[16]),"+f"(d[17]),"+f"(d[18]),"+f"(d[19]),"+f"(d[20]),"+f"(d[21]),"+f"(d[22]),"+f"(d[23]),"+f"(d[24]),"+f"(d[25]),"+f"(d[26]),"+f"(d[27]),"+f"(d[28]),"+f"(d[29]),"+f"(d[30]),"+f"(d[31]),"+f"(d[32]),"+f"(d[33]),"+f"(d[34]),"+f"(d[35]),"+f"(d[36]),"+f"(d[37]),"+f"(d[38]),"+f"(d[39])
 :"r"(alo),"r"(blo),"n"(AOFF),"n"(AHI),"n"(BOFF),"n"(BHI),"n"(SC)); } };
template<> struct WgSs<104> { template<int AOFF,int AHI,int BOFF,int BHI,int SC> static __device__ __forceinline__ void run(float* d,uint32_t alo,uint32_t blo){
 asm volatile("{.reg .b32 l,m; .reg .b64 da,db; add.u32 l,%52,%54; mov.b64 da,{l,%55}; add.u32 m,%53,%56; mov.b64 db,{m,%57}; wgmma.mma_async.sync.aligned.m64n104k16.f32.bf16.bf16 {%0,%1,%2,%3,%4,%5,%6,%7,%8,%9,%10,%11,%12,%13,%14,%15,%16,%17,%18,%19,%20,%21,%22,%23,%24,%25,%26,%27,%28,%29,%30,%31,%32,%33,%34,%35,%36,%37,%38,%39,%40,%41,%42,%43,%44,%45,%46,%47,%48,%49,%50,%51},da,db,%58,1,1,0,1;}"
 :"+f"(d[0]),"+f"(d[1]),"+f"(d[2]),"+f"(d[3]),"+f"(d[4]),"+f"(d[5]),"+f"(d[6]),"+f"(d[7]),"+f"(d[8]),"+f"(d[9]),"+f"(d[10]),"+f"(d[11]),"+f"(d[12]),"+f"(d[13]),"+f"(d[14]),"+f"(d[15]),"+f"(d[16]),"+f"(d[17]),"+f"(d[18]),"+f"(d[19]),"+f"(d[20]),"+f"(d[21]),"+f"(d[22]),"+f"(d[23]),"+f"(d[24]),"+f"(d[25]),"+f"(d[26]),"+f"(d[27]),"+f"(d[28]),"+f"(d[29]),"+f"(d[30]),"+f"(d[31]),"+f"(d[32]),"+f"(d[33]),"+f"(d[34]),"+f"(d[35]),"+f"(d[36]),"+f"(d[37]),"+f"(d[38]),"+f"(d[39]),"+f"(d[40]),"+f"(d[41]),"+f"(d[42]),"+f"(d[43]),"+f"(d[44]),"+f"(d[45]),"+f"(d[46]),"+f"(d[47]),"+f"(d[48]),"+f"(d[49]),"+f"(d[50]),"+f"(d[51])
 :"r"(alo),"r"(blo),"n"(AOFF),"n"(AHI),"n"(BOFF),"n"(BHI),"n"(SC)); } };
template<> struct WgSs<112> { template<int AOFF,int AHI,int BOFF,int BHI,int SC> static __device__ __forceinline__ void run(float* d,uint32_t alo,uint32_t blo){
 asm volatile("{.reg .b32 l,m; .reg .b64 da,db; add.u32 l,%56,%58; mov.b64 da,{l,%59}; add.u32 m,%57,%60; mov.b64 db,{m,%61}; wgmma.mma_async.sync.aligned.m64n112k16.f32.bf16.bf16 {%0,%1,%2,%3,%4,%5,%6,%7,%8,%9,%10,%11,%12,%13,%14,%15,%16,%17,%18,%19,%20,%21,%22,%23,%24,%25,%26,%27,%28,%29,%30,%31,%32,%33,%34,%35,%36,%37,%38,%39,%40,%41,%42,%43,%44,%45,%46,%47,%48,%49,%50,%51,%52,%53,%54,%55},da,db,%62,1,1,0,1;}"
 :"+f"(d[0]),"+f"(d[1]),"+f"(d[2]),"+f"(d[3]),"+f"(d[4]),"+f"(d[5]),"+f"(d[6]),"+f"(d[7]),"+f"(d[8]),"+f"(d[9]),"+f"(d[10]),"+f"(d[11]),"+f"(d[12]),"+f"(d[13]),"+f"(d[14]),"+f"(d[15]),"+f"(d[16]),"+f"(d[17]),"+f"(d[18]),"+f"(d[19]),"+f"(d[20]),"+f"(d[21]),"+f"(d[22]),"+f"(d[23]),"+f"(d[24]),"+f"(d[25]),"+f"(d[26]),"+f"(d[27]),"+f"(d[28]),"+f"(d[29]),"+f"(d[30]),"+f"(d[31]),"+f"(d[32]),"+f"(d[33]),"+f"(d[34]),"+f"(d[35]),"+f"(d[36]),"+f"(d[37]),"+f"(d[38]),"+f"(d[39]),"+f"(d[40]),"+f"(d[41]),"+f"(d[42]),"+f"(d[43]),"+f"(d[44]),"+f"(d[45]),"+f"(d[46]),"+f"(d[47]),"+f"(d[48]),"+f"(d[49]),"+f"(d[50]),"+f"(d[51]),"+f"(d[52]),"+f"(d[53]),"+f"(d[54]),"+f"(d[55])
 :"r"(alo),"r"(blo),"n"(AOFF),"n"(AHI),"n"(BOFF),"n"(BHI),"n"(SC)); } };

__device__ __forceinline__ void wg_fence() { asm volatile("wgmma.fence.sync.aligned;" ::: "memory"); }
__device__ __forceinline__ void wg_commit() { asm volatile("wgmma.commit_group.sync.aligned;" ::: "memory"); }
template <int N> __device__ __forceinline__ void wg_wait() { asm volatile("wgmma.wait_group.sync.aligned %0;" ::"n"(N) : "memory"); }
template <int N> __device__ __forceinline__ void reg_fence(float* d) {
#pragma unroll
    for (int i = 0; i < N; i++) asm volatile("" : "+f"(d[i])::"memory");
}
__device__ __forceinline__ uint32_t desc_lo(uint32_t addr, uint32_t lbo) { return ((addr & 0x3FFFF) >> 4) | ((lbo >> 4) << 16); }
#define desc_hi(sbo, sw) (((sbo) >> 4) | ((sw) << 30))
__device__ __forceinline__ uint32_t smem_u32(const void* p) { return (uint32_t)__cvta_generic_to_shared(p); }
__device__ __forceinline__ bool elect() {
    uint32_t p;
    asm volatile("{.reg .pred P; elect.sync _|P, 0xffffffff; selp.u32 %0,1,0,P;}" : "=r"(p));
    return p;
}
__device__ __forceinline__ void mbar_init(uint32_t bar, uint32_t cnt) { asm volatile("mbarrier.init.shared::cta.b64 [%0], %1;" ::"r"(bar), "r"(cnt) : "memory"); }
__device__ __forceinline__ void mbar_expect(uint32_t bar, uint32_t bytes) { asm volatile("mbarrier.arrive.expect_tx.shared::cta.b64 _, [%0], %1;" ::"r"(bar), "r"(bytes) : "memory"); }
__device__ __forceinline__ bool mbar_try(uint32_t bar, uint32_t par) {
    uint32_t ok;
    asm volatile("{.reg .pred p; mbarrier.try_wait.parity.shared::cta.b64 p, [%1], %2; selp.u32 %0,1,0,p;}" : "=r"(ok) : "r"(bar), "r"(par) : "memory");
    return ok;
}
constexpr int SPIN_LIMIT = 1 << 18;
__device__ __forceinline__ void mbar_wait(uint32_t bar, uint32_t par) {
    if (mbar_try(bar, par)) return;
    asm volatile("{.reg .pred p, q; .reg .b32 n; mov.u32 n, 0;\n"
                 "W%=: mbarrier.try_wait.parity.shared::cta.b64 p, [%0], %1; add.u32 n, n, 1; setp.lt.and.u32 q, n, %2, !p; @q bra W%=;}"
                 ::"r"(bar), "r"(par), "n"(SPIN_LIMIT) : "memory");
}
__device__ __forceinline__ void bulk_g2s(uint32_t dst, const void* src, uint32_t bytes, uint32_t bar) {
    asm volatile("cp.async.bulk.shared::cluster.global.mbarrier::complete_tx::bytes [%0], [%1], %2, [%3];" ::"r"(dst), "l"(src), "r"(bytes), "r"(bar) : "memory");
}
__device__ __forceinline__ void bulk_s2g(void* dst, uint32_t src, uint32_t bytes) {
    asm volatile("cp.async.bulk.global.shared::cta.bulk_group [%0], [%1], %2;" ::"l"(dst), "r"(src), "r"(bytes) : "memory");
}
__device__ __forceinline__ void bulk_prefetch(const void* src, uint32_t bytes) {
    asm volatile("cp.async.bulk.prefetch.L2.global [%0], %1;" ::"l"(src), "r"(bytes) : "memory");
}
__device__ __forceinline__ void tma2d(uint32_t dst, const CUtensorMap* m, int c0, int c1, uint32_t bar) {
    asm volatile("cp.async.bulk.tensor.2d.shared::cluster.global.mbarrier::complete_tx::bytes [%0], [%1, {%3, %4}], [%2];" ::"r"(dst), "l"(m), "r"(bar), "r"(c0), "r"(c1) : "memory");
}
__device__ __forceinline__ void tma2d_mc(uint32_t dst, const CUtensorMap* m, int c0, int c1, uint32_t bar) {
    asm volatile("cp.async.bulk.tensor.2d.shared::cluster.global.mbarrier::complete_tx::bytes.multicast::cluster [%0], [%1, {%3, %4}], [%2], %5;" ::"r"(dst), "l"(m), "r"(bar), "r"(c0), "r"(c1), "h"((uint16_t)3) : "memory");
}
__device__ __forceinline__ uint32_t mapa(uint32_t a, uint32_t rank) { uint32_t r; asm("mapa.shared::cluster.u32 %0, %1, %2;" : "=r"(r) : "r"(a), "r"(rank)); return r; }
__device__ __forceinline__ void mbar_arrive_cl(uint32_t bar) { asm volatile("mbarrier.arrive.shared::cluster.b64 _, [%0];" ::"r"(bar) : "memory"); }
__device__ __forceinline__ void prefetch_map(const CUtensorMap* m) { asm volatile("prefetch.tensormap [%0];" ::"l"(m) : "memory"); }
__device__ __forceinline__ void cpasync16(uint32_t dst, const void* src, uint32_t srcsz) {
    asm volatile("cp.async.cg.shared.global [%0], [%1], 16, %2;" ::"r"(dst), "l"(src), "r"(srcsz) : "memory");
}
__device__ __forceinline__ void bar_sync(int id, int n) { asm volatile("bar.sync %0, %1;" ::"r"(id), "r"(n) : "memory"); }
__device__ __forceinline__ void bar_arrive(int id, int n) { asm volatile("bar.arrive %0, %1;" ::"r"(id), "r"(n) : "memory"); }
__device__ __forceinline__ void fence_async_smem() { asm volatile("fence.proxy.async.shared::cta;" ::: "memory"); }
__device__ __forceinline__ void fence_async_global() { asm volatile("fence.proxy.async.global;" ::: "memory"); }
__device__ __forceinline__ void flag_release(int f) { asm volatile("red.release.gpu.global.add.u32 [%0], 1;" ::"l"(&g_flags[f * 32]) : "memory"); }
__device__ __forceinline__ void flag_wait(int f, unsigned target) {
    const unsigned* p = &g_flags[f * 32];
    unsigned v; int n = 0;
    do {
        asm volatile("ld.relaxed.gpu.global.u32 %0, [%1];" : "=r"(v) : "l"(p) : "memory");
    } while ((int)(v - target) < 0 && ++n < SPIN_LIMIT);
    asm volatile("fence.acquire.gpu;" ::: "memory");
}
__device__ __forceinline__ unsigned ld_flag(const unsigned* p) { unsigned v; asm volatile("ld.relaxed.gpu.global.u32 %0, [%1];" : "=r"(v) : "l"(p) : "memory"); return v; }
__device__ __forceinline__ void spin(unsigned n) { unsigned t0, t1; asm volatile("mov.u32 %0, %%clock;" : "=r"(t0)); do { asm volatile("mov.u32 %0, %%clock;" : "=r"(t1)); } while (t1 - t0 < n); }
__device__ __forceinline__ int tensor_ping() {
    int r;
    asm volatile("{.reg .f32 a, b, c, d; mma.sync.aligned.m16n8k16.row.col.f32.bf16.bf16.f32 {a,b,c,d},{%1,%1,%1,%1},{%1,%1},{%2,%2,%2,%2}; mov.b32 %0, a;}" : "=r"(r) : "r"(0), "f"(0.f));
    return r;
}
__device__ __forceinline__ void mbar_wait_warm(uint32_t bar, uint32_t par) {
    for (int n = 0; n < SPIN_LIMIT; n++) {
        uint32_t ok;
        asm volatile("{.reg .pred p; mbarrier.test_wait.parity.shared::cta.b64 p, [%1], %2; selp.u32 %0,1,0,p;}" : "=r"(ok) : "r"(bar), "r"(par) : "memory");
        if (ok) break;
        n += tensor_ping();
        spin(PING);
    }
}
__device__ __forceinline__ void flag_wait2(int f0, int f1, unsigned target) {
    const unsigned *p = &g_flags[f0 * 32], *q = &g_flags[f1 * 32];
    unsigned v, w; int n = 0;
    do { v = ld_flag(p); w = ld_flag(q); } while ((int)((v - target) | (w - target)) < 0 && ++n < SPIN_LIMIT);
    asm volatile("fence.acquire.gpu;" ::: "memory");
}
__device__ __forceinline__ uint32_t lds32(uint32_t a) { uint32_t v; asm volatile("ld.shared.u32 %0, [%1];" : "=r"(v) : "r"(a)); return v; }
__device__ __forceinline__ float2 lds64f(uint32_t a) { float2 v; asm volatile("ld.shared.v2.f32 {%0,%1}, [%2];" : "=f"(v.x), "=f"(v.y) : "r"(a)); return v; }
__device__ __forceinline__ uint2 lds64(uint32_t a) { uint2 v; asm volatile("ld.shared.v2.u32 {%0,%1}, [%2];" : "=r"(v.x), "=r"(v.y) : "r"(a)); return v; }
__device__ __forceinline__ void sts64f(uint32_t a, float2 v) { asm volatile("st.shared.v2.f32 [%0], {%1,%2};" ::"r"(a), "f"(v.x), "f"(v.y) : "memory"); }
__device__ __forceinline__ void sts32(uint32_t a, uint32_t v) { asm volatile("st.shared.u32 [%0], %1;" ::"r"(a), "r"(v) : "memory"); }
__device__ __forceinline__ void sts64(uint32_t a, uint32_t x, uint32_t y) { asm volatile("st.shared.v2.u32 [%0], {%1,%2};" ::"r"(a), "r"(x), "r"(y) : "memory"); }
__device__ __forceinline__ void sts16(uint32_t a, uint16_t v) { asm volatile("st.shared.u16 [%0], %1;" ::"r"(a), "h"(v) : "memory"); }
__device__ __forceinline__ uint4 lds128(uint32_t a) { uint4 v; asm volatile("ld.shared.v4.u32 {%0,%1,%2,%3}, [%4];" : "=r"(v.x), "=r"(v.y), "=r"(v.z), "=r"(v.w) : "r"(a)); return v; }
__device__ __forceinline__ void sts128(uint32_t a, uint4 v) { asm volatile("st.shared.v4.u32 [%0], {%1,%2,%3,%4};" ::"r"(a), "r"(v.x), "r"(v.y), "r"(v.z), "r"(v.w) : "memory"); }
__device__ __forceinline__ void sts128f(uint32_t a, float x, float y, float z, float w) { asm volatile("st.shared.v4.f32 [%0], {%1,%2,%3,%4};" ::"r"(a), "f"(x), "f"(y), "f"(z), "f"(w) : "memory"); }
__device__ __forceinline__ uint32_t prmt(uint32_t a, uint32_t b, uint32_t s) { uint32_t r; asm("prmt.b32 %0,%1,%2,%3;" : "=r"(r) : "r"(a), "r"(b), "r"(s)); return r; }
__device__ __forceinline__ uint32_t pack2(float lo, float hi) { uint32_t r; asm("cvt.rn.bf16x2.f32 %0, %1, %2;" : "=r"(r) : "f"(hi), "f"(lo)); return r; }
__device__ __forceinline__ float blo(uint32_t v) { return __uint_as_float(v << 16); }
__device__ __forceinline__ float bhi(uint32_t v) { return __uint_as_float(v & 0xffff0000u); }
__device__ __forceinline__ uint32_t bmul2(uint32_t a, uint32_t b) { uint32_t r; asm("mul.rn.bf16x2 %0,%1,%2;" : "=r"(r) : "r"(a), "r"(b)); return r; }
__device__ __forceinline__ uint32_t badd2(uint32_t a, uint32_t b) { uint32_t r; asm("add.rn.bf16x2 %0,%1,%2;" : "=r"(r) : "r"(a), "r"(b)); return r; }
__device__ __forceinline__ float rbf(float x) { return __bfloat162float(__float2bfloat16_rn(x)); }
__device__ __forceinline__ uint32_t ldcg32(const void* p) { uint32_t v; asm volatile("ld.global.cg.u32 %0, [%1];" : "=r"(v) : "l"(p) : "memory"); return v; }
__device__ __forceinline__ uint4 ldcg128(const void* p) { uint4 v; asm volatile("ld.global.cg.v4.u32 {%0,%1,%2,%3}, [%4];" : "=r"(v.x), "=r"(v.y), "=r"(v.z), "=r"(v.w) : "l"(p) : "memory"); return v; }
__device__ __forceinline__ void stg32_if(void* p, uint32_t v, int on) { asm volatile("{.reg .pred q; setp.ne.b32 q, %2, 0; @q st.global.u32 [%0], %1;}" ::"l"(p), "r"(v), "r"(on) : "memory"); }
__device__ __forceinline__ uint2 ldcg64(const void* p) { uint2 v; asm volatile("ld.global.cg.v2.u32 {%0,%1}, [%2];" : "=r"(v.x), "=r"(v.y) : "l"(p) : "memory"); return v; }
__device__ __forceinline__ float gelu_h(float h) {
    float u = h * fmaf(h * h, 8.0f * 0.044715f * 0.7978845608028654f, 2.0f * 0.7978845608028654f);
    float th;
    asm("tanh.approx.f32 %0, %1;" : "=f"(th) : "f"(u));
    return fmaf(h, th, h);
}
__device__ __forceinline__ float gelu(float x) { return gelu_h(0.5f * x); }
__device__ __forceinline__ float half_rstd(float sum, float sq) {
    float mean = sum * (1.0f / D_), inv;
    asm("rsqrt.approx.ftz.f32 %0, %1;" : "=f"(inv) : "f"(fmaxf(fmaf(-mean, mean, fmaf(sq, 1.0f / D_, 1e-5f)), 1e-5f)));
    return 0.5f * inv;
}
__device__ __forceinline__ uint32_t bsub2(uint32_t a, uint32_t b) { uint32_t r; asm("sub.rn.bf16x2 %0,%1,%2;" : "=r"(r) : "r"(a), "r"(b)); return r; }
__device__ __forceinline__ uint32_t bfma2(uint32_t a, uint32_t b, uint32_t c) { uint32_t r; asm("fma.rn.bf16x2 %0,%1,%2,%3;" : "=r"(r) : "r"(a), "r"(b), "r"(c)); return r; }
__device__ __forceinline__ uint32_t gelu2_h(uint32_t h) {
    uint32_t u = bmul2(h, bfma2(bmul2(h, h), 0x3e923e92u, 0x3fcc3fccu)), th;
    asm("tanh.approx.bf16x2 %0, %1;" : "=r"(th) : "r"(u));
    return bfma2(h, th, h);
}
__device__ __forceinline__ uint3 row_stats(const uint32_t* v, int lane) {
    float s = 0.f, q = 0.f, s_ = 0.f, q_ = 0.f;
#pragma unroll
    for (int i = 0; i < 10; i++) { float a = blo(v[i]), b = bhi(v[i]); s += a; s_ += b; q = fmaf(a, a, q); q_ = fmaf(b, b, q_); }
    s += s_; q += q_;
    {
        float t = __shfl_xor_sync(0xffffffffu, (lane & 16) ? s : q, 16);
        t += (lane & 16) ? q : s;
#pragma unroll
        for (int m = 8; m; m >>= 1) t += __shfl_xor_sync(0xffffffffu, t, m);
        float o = __shfl_xor_sync(0xffffffffu, t, 16);
        s = (lane & 16) ? o : t; q = (lane & 16) ? t : o;
    }
    float mean = s * (1.0f / D_), inv;
    asm("rsqrt.approx.ftz.f32 %0, %1;" : "=f"(inv) : "f"(fmaxf(fmaf(-mean, mean, fmaf(q, 1.0f / D_, 1e-5f)), 1e-5f)));
    uint3 r;
    r.x = pack2(mean, mean);
    r.y = pack2(inv, inv);
    inv -= blo(r.y);
    r.z = pack2(inv, inv);
    return r;
}
__device__ __forceinline__ uint32_t ln_apply(uint32_t x, uint32_t m, uint32_t hi, uint32_t lo) {
    uint32_t xc = bsub2(x, m);
    return bmul2(xc, hi);
}

struct AFrag { uint32_t m, a, b, c, d; };
__device__ __forceinline__ AFrag ldA(uint32_t a) { AFrag f; f.m = lds32(a - 16); f.a = lds32(a); f.b = lds32(a + 16); f.c = lds32(a + 32); f.d = lds32(a + 48); return f; }
template <int N, int M> __device__ __forceinline__ void conv_pair(float* d, const AFrag& f, uint32_t descU) {
    WgRs<N>::template run<8 * M, desc_hi(128, 0), M ? 1 : 0>(d, f.a, f.b, f.m, f.a, descU);
    WgRs<N>::template run<8 * M + 1, desc_hi(128, 0), 1>(d, f.c, f.d, f.b, f.c, descU);
}
template <int Q> __device__ __forceinline__ void conv_put(float* d, uint32_t r0) {
    sts64(r0 + Q * 32, pack2(d[4 * Q + 1], d[4 * Q + 3]), pack2(d[4 * Q], d[4 * Q + 2]));
}
template <int M> __device__ __forceinline__ void conv_two(float* d, AFrag f0, AFrag f1, uint32_t kaddr, uint32_t descU, uint32_t r0, bool handoff) {
    constexpr int N = M < 14 ? 128 - 8 * M : 32;
    wg_fence();
    conv_pair<N, M>(d, f0, descU);
    wg_commit();
    if constexpr (M > 0) f1 = ldA(kaddr + 256 * (M + 1));
    wg_fence();
    conv_pair<N, M + 1>(d, f1, descU);
    wg_commit();
    if (STAG && M == STAG && handoff) bar_arrive(12, 256);
    if constexpr (M < 14) {
        if constexpr (M > 0) { conv_put<17 - M>(d, r0); conv_put<16 - M>(d, r0); }
        wg_wait<1>();
        f0 = ldA(kaddr + 256 * (M + 2));
        if constexpr (M < 12) wg_wait<0>();
        conv_two<M + 2>(d, f0, f1, kaddr, descU, r0, handoff);
    } else {
        wg_wait<0>();
        conv_put<3>(d, r0); conv_put<2>(d, r0); conv_put<1>(d, r0); conv_put<0>(d, r0);
    }
}
template <int N, bool ASWZ, int SC0>
__device__ __forceinline__ void gemm_issue(float* acc, uint32_t bars, int sa, int pa, int sw, int pw, uint32_t da0, uint32_t db0) {
    mbar_wait(bars + (BAR_FB + sw) * 8, pw);
    mbar_wait(bars + (BAR_FA + sa) * 8, pa);
    const uint32_t da = da0 + sa * (SLOT >> 4), db = db0 + sw * (SLOT >> 4);
    constexpr int AK = ASWZ ? 2 : 256, AH = ASWZ ? desc_hi(1024, 1) : desc_hi(128, 0), BH = desc_hi(1024, 1);
    wg_fence();
    WgSs<N>::template run<0, AH, 0, BH, SC0>(acc, da, db);
    WgSs<N>::template run<AK, AH, 128, BH, 1>(acc, da, db);
    WgSs<N>::template run<2 * AK, AH, 256, BH, 1>(acc, da, db);
    WgSs<N>::template run<3 * AK, AH, 384, BH, 1>(acc, da, db);
    wg_commit();
}
template <int N, bool ASWZ, int NKB, int RELB, bool ZERO>
__device__ __forceinline__ void gemm_loop(float* acc, uint32_t sb, int half, int ia0, int ib0, int rela, int wait_bar, int order_bar, int tsid) {
    int sa = ia0 % NA, pa = (ia0 / NA) & 1, sw = ib0 % NB, pw = (ib0 / NB) & 1;
    const uint32_t bars = sb + SM_BAR;
    const int t = threadIdx.x & 127;
    uint32_t ebar = mapa(bars + (t < 2 ? BAR_EB : BAR_EA) * 8, (t < 2 && lds32(sb + SM_GV + 516)) ? t : blockIdx.x & 1);
    const int nrel = t < 2 ? RELB : t == 2 ? rela : 0;
    const uint32_t da0 = ASWZ ? desc_lo(sb + SM_RA + half * 8192, 16) : desc_lo(sb + SM_RA + half * 1024, 2048), db0 = desc_lo(sb + SM_RB, 8192);
    asm volatile("" : "+r"(ebar));
    if (wait_bar) bar_sync(wait_bar, 512);
    gemm_issue<N, ASWZ, ZERO ? 0 : 1>(acc, bars, sa, pa, sw, pw, da0, db0);
    if ((threadIdx.x & 255) == 0) TS(tsid);
#pragma unroll 1
    for (int kb = 1; kb < NKB; kb++) {
        const int prev = t < 2 ? sw : sa;
        if (++sa == NA) { sa = 0; pa ^= 1; }
        if (++sw == NB) { sw = 0; pw ^= 1; }
        gemm_issue<N, ASWZ, 1>(acc, bars, sa, pa, sw, pw, da0, db0);
        if (order_bar && kb == NKB - 1) bar_arrive(order_bar, 512);
        wg_wait<1>();
        if (kb <= nrel) mbar_arrive_cl(ebar + prev * 8);
    }
    wg_wait<0>();
    if (nrel == NKB) mbar_arrive_cl(ebar + (t < 2 ? sw : sa) * 8);
    reg_fence<N / 2>(acc);
    if ((threadIdx.x & 255) == 0) TS(tsid + 1);
}

template <int PART>
__device__ __forceinline__ void gemm3(uint32_t sb, int rb, int j, int half, int row, int c, unsigned ones) {
    constexpr int N = 64 + (PART ? RB3 : RA3), NQ = N / 8;
    constexpr int HO = PART ? HO_B : HO_A;
    float acc[N / 2];
    float2 cr[NQ];
    if (PART) {
        gemm_loop<N, false, 1, 1, true>(acc, sb, half, 20, 20, 0, 0, 0, 50);
        bar_arrive(9, 512);
    }
    mbar_wait(sb + SM_BAR + BAR_CS * 8, 0);
    const uint32_t csa = sb + SM_CS + PART * (256 + 4 * RA3) + 8 * c;
#pragma unroll
    for (int q = 0; q < NQ; q++) if (q < CSP) cr[q] = lds64f(csa + 32 * q);
    uint4 rp;
    if (PART) {
        mbar_wait(sb + SM_BAR + BAR_G * 8, 0);
        const float2* sp = &g_st[(rb * 8 + 2 * c) * 128 + row];
        const uint2 s0 = ldcg64(sp), s1 = ldcg64(sp + 128), s2 = ldcg64(sp + 8), s3 = ldcg64(sp + 136);
        float a0 = __uint_as_float(s0.x) + __uint_as_float(s1.x), b0 = __uint_as_float(s0.y) + __uint_as_float(s1.y);
        float a1 = __uint_as_float(s2.x) + __uint_as_float(s3.x), b1 = __uint_as_float(s2.y) + __uint_as_float(s3.y);
#pragma unroll
        for (int m = 1; m <= 2; m <<= 1) {
            a0 += __shfl_xor_sync(0xffffffffu, a0, m); b0 += __shfl_xor_sync(0xffffffffu, b0, m);
            a1 += __shfl_xor_sync(0xffffffffu, a1, m); b1 += __shfl_xor_sync(0xffffffffu, b1, m);
        }
        const float inv0 = half_rstd(a0, b0), inv1 = half_rstd(a1, b1);
        rp = make_uint4(PGELU ? pack2(inv0, inv0) : __float_as_uint(inv0), __float_as_uint(a0 * (-1.0f / D_)),
                        PGELU ? pack2(inv1, inv1) : __float_as_uint(inv1), __float_as_uint(a1 * (-1.0f / D_)));
        if (c == 0) sts128(sb + SM_RP + ((threadIdx.x & 255) >> 2) * 16, rp);
        bar_arrive(13, 512);
    }
    gemm_loop<N, false, 10 - PART, 10 - PART, !PART>(acc, sb, half, 20 + (10 - NA) * PART, 21 + 10 * PART, PART ? 9 : 10 - NA, 9 + PART, HO < 0 ? 10 + PART : 0, 46 + 2 * PART);
    if ((threadIdx.x & 255) == 0) mbar_expect(sb + SM_BAR + BAR_ME * 8, 0);
    if (!PART) {
        bar_sync(13, 512);
        rp = lds128(sb + SM_RP + ((threadIdx.x & 255) >> 2) * 16);
    }
    const float nb0 = __uint_as_float(rp.y), nb1 = __uint_as_float(rp.w);
    const uint32_t own = sb + SM_RA + ((39 - NA) % NA) * SLOT + row * 16 + c * 4;
    if (PART && OWNG) mbar_wait(sb + SM_BAR + (BAR_FA + (39 - NA) % NA) * 8, ((39 - NA) / NA) & 1);
    uint32_t* dst = reinterpret_cast<uint32_t*>(g_g) + (rb * 216 + HB0 / 8 * PART + 8 * j) * 512 + row * 4 + c;
    auto act = [&](int q, int r) {
        const float nb = r ? nb1 : nb0;
        const uint32_t inv = r ? rp.z : rp.x;
        const float t0 = fmaf(nb, cr[q].x, acc[4 * q + 2 * r]), t1 = fmaf(nb, cr[q].y, acc[4 * q + 2 * r + 1]);
        return gelu2_h(bmul2(pack2(t0, t1), inv));
    };
    uint32_t* dst1 = dst + (56 - (16 - NQ) * j) * 512;
#pragma unroll
    for (int k = 0; k < NQ; k += CH3) {
        if (k == HO) bar_arrive(10 + PART, 512);
        CHUNK(k) {
#pragma unroll
            for (int q = k; q < k + CH3 && q < NQ; q++) {
                if (q + CSP < NQ) cr[q + CSP] = lds64f(csa + 32 * (q + CSP));
                const uint32_t u = act(q, 0), v = act(q, 1);
                (q < 8 ? dst : dst1)[q * 512] = u;
                (q < 8 ? dst : dst1)[q * 512 + 32] = v;
                if (PART && OWNG && q < 8) { sts32(own + q * 2048, u); sts32(own + q * 2048 + 128, v); }
            }
            if (PART && OWNG && k < 8 && k + CH3 >= 8) fence_async_smem();
        }
    }
    bar_arrive(1 + PART, 288);
    if (HO >= NQ) bar_arrive(10 + PART, 512);
}

template <int NS, int BASE, int BF, int BE> struct Ring {
    uint32_t sb, st, ph;
    __device__ __forceinline__ uint32_t acquire(uint32_t bytes) {
        mbar_wait(sb + SM_BAR + BE * 8 + st * 8, ph);
        uint32_t fb = sb + SM_BAR + BF * 8 + st * 8;
        mbar_expect(fb, bytes);
        return fb;
    }
    __device__ __forceinline__ uint32_t slot() { return sb + BASE + st * SLOT; }
    __device__ __forceinline__ void next() { if (++st == NS) { st = 0; ph ^= 1; } }
    __device__ __forceinline__ void run2d(const CUtensorMap* m, int c1) {
#pragma unroll 1
        for (int c0 = 64; c0 < D_; c0 += 64) {
            uint32_t fb = acquire(SLOT);
            tma2d(slot(), m, c0, c1, fb);
            next();
        }
    }
    static __device__ __forceinline__ int korder(int i, int own) { return i == 0 ? own : i > own ? i : i - 1; }
    __device__ __forceinline__ void runw(bool paired, int rk, const CUtensorMap* ma, const CUtensorMap* mb, int ca, int cb, int i0, int i1, int own, uint32_t bytes, int gate_at, uint32_t gate) {
        if (paired) {
            const CUtensorMap* m = rk ? mb : ma;
            const int c0 = rk ? cb : ca;
#pragma unroll 1
            for (int i = i0; i < i1; i++) {
                const int c1 = korder(i, own) * 64;
                if (i == gate_at) mbar_wait(gate, 0);
                uint32_t fb = acquire(bytes);
                tma2d_mc(slot() + 8192 * rk, m, c0, c1, fb);
                next();
            }
        } else {
#pragma unroll 1
            for (int i = i0; i < i1; i++) {
                const int c1 = korder(i, own) * 64;
                uint32_t fb = acquire(bytes);
                tma2d(slot(), ma, ca, c1, fb);
                tma2d(slot() + 8192, mb, cb, c1, fb);
                next();
            }
        }
    }
    __device__ __forceinline__ void run1d(const char* src, int i0, int i1, int own) {
#pragma unroll 1
        for (int i = i0; i < i1; i++) {
            const char* s = src + korder(i, own) * SLOT;
            uint32_t fb = acquire(SLOT);
            bulk_g2s(slot(), s, SLOT, fb);
            next();
        }
    }
};

__global__ void __cluster_dims__(2, 1, 1) __launch_bounds__(NTHREADS, 1) fused_kernel(const Params p, const __grid_constant__ Maps maps) {
    extern __shared__ __align__(1024) unsigned char smem_raw[];
    const uint32_t sb = (smem_u32(smem_raw) + 1023u) & ~1023u;
#pragma unroll
    for (int i = 0; i < SEED; i++) asm volatile("{.reg .b32 t; mov.u32 t, %laneid;}");
    const uint32_t bars = sb + SM_BAR;
    const int tid = threadIdx.x, lane = tid & 31;
    unsigned smid;
    asm volatile("mov.u32 %0, %%smid;" : "=r"(smid));
    const bool spare = (smid >> 2) == 30;
    const int cta = smid < 120 ? smid : smid - 4;
    const int pg = cta >> 4, pi = cta & 15;
    auto chan = [&](int cc) { return 80 * pg + (cc < 3 ? 3 * pi + cc : 45 + 2 * pi + cc); };
    const int hb = tid >= 320;
    unsigned ep0 = 0;
    if (!spare) {
        const unsigned t = tid - 320 * hb, r32 = t / 10u, cc = t - r32 * 10u, row = r32 + 64 * hb;
        const unsigned go = (unsigned)(pi * 128 * 1280 + pg * 160) + row * 1280u + cc * 16u;
        const uint32_t so = sb + (row >> 4) * 32u + row * 160u + cc * 16u;
        const char* kb = (const char*)p.k + go;
        const char* vb = (const char*)p.v + go;
        if (hb) {
            if (tid < 328) {
                const char* a = lane < 5 ? (const char*)p.shift + pg * 640 + lane * 128 : (const char*)p.ssmD + pg * 160 + (lane - 5) * 64;
                asm volatile("prefetch.global.L2 [%0];" ::"l"(a));
            }
            if (tid >= 640 - NBARS) {
                const int i = 639 - tid;
                mbar_init(bars + i * 8, (i >= BAR_EB && i < BAR_K) ? 4 : ((i >= BAR_EA && i < BAR_EB) || i == BAR_XY) ? 2 : 1);
                asm volatile("fence.mbarrier_init.release.cluster;" ::: "memory");
            }
            bar_arrive(14, 640);
            if (tid >= 512) asm volatile("ld.volatile.global.u32 %0, [%1];" : "=r"(ep0) : "l"(p.epoch + smid) : "memory");
            if (B_DELAY) spin(B_DELAY);
        }
        cpasync16(so + SM_PK + 2592, kb, 16);
        cpasync16(so + SM_PV, vb, 16);
        cpasync16(so + SM_PK + 3 * 2592, kb + 32 * 1280, 16);
        cpasync16(so + SM_PV + 2 * 2592, vb + 32 * 1280, 16);
        if (tid < 30) cpasync16(so + SM_PK + 13 * 160, pi ? kb - 3 * 1280 : kb, pi ? 16 : 0);
        asm volatile("cp.async.commit_group;" ::: "memory");
    }
    const int warp = __shfl_sync(0xffffffffu, tid >> 5, 0);
    const int wg = warp >> 2, wq = warp & 3;

    if (spare) {
        const int sp = smid & 3;
        const unsigned ep1 = *(volatile unsigned*)&p.epoch[smid] + 1;
        if (tid == 32) { sts32(sb + SM_GV + 512, smid); asm volatile("fence.release.sync_restrict::shared::cta.cluster;" ::: "memory"); }
        asm volatile("barrier.cluster.arrive.relaxed.aligned;" ::: "memory");
        asm volatile("barrier.cluster.wait.aligned;" ::: "memory");
        if (tid == 0) {
            for (int i = 0; i < 4; i++) mbar_init(bars + i * 8, 1);
            asm volatile("fence.mbarrier_init.release.cluster;" ::: "memory");
        }
        if (warp == 0) { if (lane < 8) flag_wait(FL_P + lane, ep1 * 16); __syncwarp(); }
        __syncthreads();
        const int cq = tid % 54, rg = tid / 54;
        float a[8];
#pragma unroll
        for (int i = 0; i < 8; i++) a[i] = 0.f;
#pragma unroll 1
        for (int it = -4; it < 10; it++) {
            const uint32_t st = sb + (it & 3) * 55296, fb = bars + (it & 3) * 8;
            if (it >= 0) {
                mbar_wait(fb, (it >> 2) & 1);
                if (tid < 432) {
#pragma unroll 2
                    for (int i = 0; i < 8; i++) {
                        uint4 w = lds128(st + (cq >= 27 ? 27648 - 432 : 0) + (rg * 8 + i) * 432 + cq * 16);
                        a[0] += blo(w.x); a[1] += bhi(w.x); a[2] += blo(w.y); a[3] += bhi(w.y);
                        a[4] += blo(w.z); a[5] += bhi(w.z); a[6] += blo(w.w); a[7] += bhi(w.w);
                    }
                }
                __syncthreads();
            }
            if (it < 6 && warp == 19 && elect()) {
                mbar_expect(fb, 55296);
                tma2d(st, &maps.w3s, sp * 432, (it + 4) * 64, fb);
                tma2d(st + 27648, &maps.w3s, sp * 432 + 216, (it + 4) * 64, fb);
            }
        }
        if (warp == 19 && elect()) {
#pragma unroll 1
            for (int i = 0; i < 27; i++) bulk_prefetch((const char*)p.w4 + sp * 552960 + i * 20480, 20480);
        }
        if (tid < 432) {
            sts128f(sb + rg * 1728 + cq * 32, a[0], a[1], a[2], a[3]);
            sts128f(sb + rg * 1728 + cq * 32 + 16, a[4], a[5], a[6], a[7]);
        }
        __syncthreads();
        if (tid < 432) {
            float s = 0.f;
#pragma unroll
            for (int i = 0; i < 8; i++) s += __uint_as_float(lds32(sb + i * 1728 + tid * 4));
            g_cs[sp * 432 + tid] = s;
        }
        __syncthreads();
        if (tid == 0) { flag_release(FL_CS); p.epoch[smid] = ep1; TS(0); }
        if (warp == 0) TSFLUSH();
        return;
    }

    int gpc, idx;
    if (smid < 64) { gpc = (smid & 15) >> 1; idx = (smid >> 4) * 2 + (smid & 1); }
    else if (smid < 120) { int t = smid - 64; gpc = 1 + (t % 14) / 2; idx = 8 + (t / 14) * 2 + (smid & 1); }
    else { gpc = 0; idx = 8 + (smid - 124); }
    const int rb = 2 * gpc + (idx & 1), j = idx >> 1;
    const int g = lane >> 2, c = lane & 3;
    const int cm = 160 * (j >> 1) + 64 * (j & 1) + ((j & 2) ? 32 : 0), cr = 160 * (j >> 1) + 16 * (j & 1) + ((j & 2) ? 0 : 128);

    {
        if (warp == 5) TSW(61);
        const int w10 = warp - 10 * hb, h = w10 >= 5;
        const int pr = (w10 - 5 * h) * 8 + (lane >> 2), blk = 4 * hb + (lane & 3);
        const int ch = 80 * pg + 2 * pr;
        const uint4 sw = __ldg(reinterpret_cast<const uint4*>(p.shift + ch * 4));
        uint32_t dv = 0;
        if (warp == 9 && lane < 5) dv = __bfloat16_as_ushort(p.ssmD[chan(lane)]);
        if (tid == 512) { sts32(sb + SM_GV + 512, smid); asm volatile("fence.release.sync_restrict::shared::cta.cluster;" ::: "memory"); }
        asm volatile("barrier.cluster.arrive.relaxed.aligned;" ::: "memory");
        if (warp == 11 && lane < 13) prefetch_map(&maps.hn + lane);
        if (wg < 4) {
            const int t = tid & 127, cc = (wg == 3 && t >= 64) ? 4 : wg;
            if (t < 64 || wg == 3) sts128(sb + sm_u(cc) + ((t >> 5) & 1) * U_PLANE + 2048 + lane * 16, make_uint4(0, 0, 0, 0));
            if ((t & 63) < 4 && (t < 64 || wg == 3)) sts128(sb + sm_k(cc) + ((t >> 1) & 1) * 4160 + (t & 1) * 16, make_uint4(0, 0, 0, 0));
        }
        if (warp == 9 && lane < 5) sts32(sb + SM_GV + 520 + lane * 4, dv << 16);
        asm volatile("cp.async.wait_group 0;" ::: "memory");
        if (!hb) bar_arrive(12, 640);
        bar_sync(hb ? 12 : 14, 640);
        if (warp == 9) {
            if (SSM_DELAY) spin(SSM_DELAY);
            if (elect()) {
#pragma unroll
                for (int i = 0; i < SSM_N; i++) {
                    mbar_expect(bars + (BAR_K + i) * 8, 4096);
                    bulk_g2s(sb + sm_k(i) + 32, p.ssmk + (size_t)(chan(i)) * S_, 4096, bars + (BAR_K + i) * 8);
                }
            }
        }
        const uint32_t w0 = prmt(sw.x, sw.z, 0x5410), w1 = prmt(sw.x, sw.z, 0x7632), w2 = prmt(sw.y, sw.w, 0x5410), w3 = prmt(sw.y, sw.w, 0x7632);
        const uint32_t ka = sb + SM_PK + 2592 + blk * 2592 + h * 1280 + pr * 4;
        const uint32_t va = sb + SM_PV + blk * 2592 + h * 1280 + pr * 4;
        uint32_t kk[11], kv[8];
#pragma unroll
        for (int i = 0; i < 11; i++) kk[i] = lds32(ka + (i - 3) * 160 - ((i < 3 && h == 0) ? 32 : 0));
#pragma unroll
        for (int i = 0; i < 8; i++) {
            uint32_t t = badd2(badd2(badd2(bmul2(kk[i], w3), bmul2(kk[i + 1], w2)), bmul2(kk[i + 2], w1)), bmul2(kk[i + 3], w0));
            kv[i] = bmul2(t, lds32(va + i * 160));
        }
        uint4 o0, o1;
        o0.x = prmt(kv[1], kv[0], 0x5410); o0.y = prmt(kv[3], kv[2], 0x5410); o0.z = prmt(kv[5], kv[4], 0x5410); o0.w = prmt(kv[7], kv[6], 0x5410);
        o1.x = prmt(kv[1], kv[0], 0x7632); o1.y = prmt(kv[3], kv[2], 0x7632); o1.z = prmt(kv[5], kv[4], 0x7632); o1.w = prmt(kv[7], kv[6], 0x7632);
        uint4* dst = reinterpret_cast<uint4*>(g_kvT) + ch * 256 + h * 128 + (127 - (8 * pi + blk));
        dst[0] = o0;
        dst[256] = o1;
    }

    const int rho = 8 * rb + j;

    if (wg == 4) {
        asm volatile("setmaxnreg.dec.sync.aligned.u32 32;");
        const unsigned ep1 = __shfl_sync(0xffffffffu, ep0, 0) + 1;
        if (wq == 0) {
            bar_sync(13, 640);
            TSW(39);
            if (lane == 0) flag_release(FL_P + pg);
            __syncwarp();
            TSW(2);
            if (lane < 5) mbar_expect(bars + (BAR_U + lane) * 8, 4096);
            flag_wait(FL_P + pg, ep1 * 16);
            fence_async_global();
            TSW(3);
            if (elect()) {
#pragma unroll
                for (int i = 0; i < 5; i++) {
                    const char* us = (const char*)g_kvT + (size_t)(chan(i)) * 4096;
                    bulk_g2s(sb + sm_u(i), us, 2048, bars + (BAR_U + i) * 8);
                    bulk_g2s(sb + sm_u(i) + U_PLANE, us + 2048, 2048, bars + (BAR_U + i) * 8);
                }
            }
            __syncwarp();
            if (elect()) {
#pragma unroll
                for (int i = SSM_N; i < 5; i++) {
                    mbar_expect(bars + (BAR_K + i) * 8, 4096);
                    bulk_g2s(sb + sm_k(i) + 32, p.ssmk + (size_t)(chan(i)) * S_, 4096, bars + (BAR_K + i) * 8);
                }
                if (cta < 120) {
                    mbar_expect(bars + BAR_WM0 * 8, 3 * 8192);
                    mbar_expect(bars + BAR_WM * 8, 2 * 8192);
#pragma unroll 1
                    for (int i = 0; i < 5; i++) tma2d(sb + SM_WM + i * 8192, &maps.wm, cta * 32, i * 128, bars + (i < 3 ? BAR_WM0 : BAR_WM) * 8);
                }
                mbar_wait(bars + (cta < 120 ? BAR_WM0 : BAR_K + 4) * 8, 0);
                bulk_prefetch((const char*)p.q + cta * 20480, 20480);
                bulk_prefetch((const char*)p.w1 + cta * 6400, 6400);
                bulk_prefetch((const char*)p.w2 + cta * 6400, 6400);
            }
            __syncwarp();
        } else {
            bar_arrive(13, 640);
        }
        asm volatile("barrier.cluster.wait.aligned;" ::: "memory");
        uint32_t peer;
        asm volatile("ld.shared::cluster.u32 %0, [%1];" : "=r"(peer) : "r"(mapa(sb + SM_GV + 512, (blockIdx.x & 1) ^ 1)) : "memory");
        const bool paired = peer == (smid ^ 1) && !FORCE_UNPAIRED;
        if (tid == 639) sts32(sb + SM_GV + 516, paired);
        if (cta < 120) {
            float d[4];
            if (tid >= 544 && tid < 624) {
                const int t = tid - 544;
                mbar_wait(bars + BAR_U * 8, 0);
                uint4 cv = __ldg(reinterpret_cast<const uint4*>(p.c) + t);
                auto silu2 = [](uint32_t v) { float a = blo(v), b = bhi(v); return pack2(__fdividef(a, 1.0f + __expf(-a)), __fdividef(b, 1.0f + __expf(-b))); };
#pragma unroll 1
                for (int i = 0; i < 4; i++) { const uint32_t r = silu2(cv.x); cv.x = cv.y; cv.y = cv.z; cv.z = cv.w; cv.w = r; }
                sts128(sb + SM_Y + (t % 40) * 32 + (t / 40) * 16, cv);
                fence_async_smem();
            }
            bar_sync(5, 128);
            mbar_wait(bars + BAR_WM0 * 8, 0);
            mbar_wait(bars + BAR_WM * 8, 0);
            if (wq == 3) TSW(56);
            const uint32_t da = desc_lo(sb + SM_WM, 20480), db = desc_lo(sb + SM_Y, 32);
#pragma unroll 1
            for (int k0 = 0; k0 < 20; k0 += 4) {
                wg_fence();
#pragma unroll
                for (int k = k0; k < k0 + 4; k++) asm volatile("{.reg .pred p; .reg .b32 l,m; .reg .b64 da,db; setp.ne.b32 p,%10,0; add.u32 l,%4,%6; mov.b64 da,{l,%8}; add.u32 m,%5,%7; mov.b64 db,{m,%9};"
                             " wgmma.mma_async.sync.aligned.m64n8k16.f32.bf16.bf16 {%0,%1,%2,%3},da,db,p,1,1,1,0;}"
                             : "+f"(d[0]), "+f"(d[1]), "+f"(d[2]), "+f"(d[3])
                             : "r"(da), "r"(db), "r"(64 * k), "r"(4 * k), "n"(desc_hi(512, 2u)), "n"(desc_hi(128, 0)), "r"(k));
                wg_commit();
            }
            wg_wait<0>();
            reg_fence<4>(d);
            if (c == 0) {
                sts32(sb + SM_GV + (16 * wq + g) * 4, __float_as_uint(wq < 2 ? d[0] : d[1]));
                sts32(sb + SM_GV + (16 * wq + g + 8) * 4, __float_as_uint(wq < 2 ? d[2] : d[3]));
            }
            bar_sync(5, 128);
            if (wq == 2) {
                g_mod[cta * 32 + lane] = __float2bfloat16_rn(__uint_as_float(lds32(sb + SM_GV + lane * 4)) + __uint_as_float(lds32(sb + SM_GV + 128 + lane * 4)));
            }
        }
        if (wq == 2) {
            bar_sync(9, 320);
            if (lane == 0) flag_release(FL_M);
            __syncwarp();
            TSW(4);
            flag_wait(FL_M, ep1 * 128);
            fence_async_global();
            if (elect()) {
                mbar_expect(bars + BAR_M * 8, 7680);
                bulk_g2s(sb + SM_MOD, g_mod, 7680, bars + BAR_M * 8);
                mbar_wait(bars + BAR_CD * 8, 0);
                mbar_expect(bars + BAR_Y * 8, 12288);
#pragma unroll 1
                for (int i = 0; i < 8; i++) bulk_g2s(sb + SM_Y + i * 2560, g_yv + rho * 5120 + i * 640, 1536, bars + BAR_Y * 8);
            }
            __syncwarp();
            TSW(60);
            bar_sync(8, 576);  if (lane == 0) { flag_release(FL_R + rb); TS(23); }  __syncwarp();
            bar_sync(15, 288); if (lane == 0) { flag_release(FL_B1 + rb); TS(27); } __syncwarp();
            bar_sync(6, 288);  if (lane == 0) { flag_release(FL_B2 + rb); TS(31); } __syncwarp();
#pragma unroll 1
            for (int i = 0; i < 3; i++) { bar_sync(i ? i : 8, 288); if (lane == 0) { TS(53 + (i + 2) % 3); flag_release(FL_G + 16 * i + rb); TS(57 + (i + 2) % 3); } __syncwarp(); }
            if (lane == 0) p.epoch[smid] = ep1;
            return;
        }
        if (wq == 1) {
            bar_sync(9, 320);
            if (lane < 4 * NB) mbar_arrive_cl(mapa(bars + (BAR_EB + (lane >> 2)) * 8, paired ? lane & 1 : blockIdx.x & 1));
        }
        if (wq == 3) {
            bar_sync(7, 544);
            if (lane == 0) { flag_release(FL_C); mbar_expect(bars + BAR_CD * 8, 0); TS(20); }
            __syncwarp();
            if (lane == 0) mbar_expect(bars + BAR_Y2 * 8, 8192);
            flag_wait(FL_C, ep1 * 128);
            fence_async_global();
            TSW(21);
            if (elect()) {
#pragma unroll
                for (int i = 0; i < 8; i++) bulk_g2s(sb + SM_Y + i * 2560 + 1536, g_yv + rho * 5120 + i * 640 + 384, 1024, bars + BAR_Y2 * 8);
            }
            __syncwarp();
        }
        if (wq == 3) {
            mbar_wait(bars + BAR_Y2 * 8, 0);
            if (elect()) {
                mbar_expect(bars + BAR_XY * 8, 20480);
#pragma unroll 1
                for (int i = 0; i < 8; i++) {
                    bulk_g2s(sb + SM_YT + i * 2560, g_yv + (8 * rb + i) * 5120 + cm * 8, 2048, bars + BAR_XY * 8);
                    bulk_g2s(sb + SM_YT + i * 2560 + 2048, g_yv + (8 * rb + i) * 5120 + cr * 8, 512, bars + BAR_XY * 8);
                }
            }
            __syncwarp();
            bar_sync(8, 576);
            mbar_wait_warm(bars + BAR_FA * 8, 0);
            mbar_wait(bars + BAR_ME * 8, 0);
            mbar_wait_warm(bars + (BAR_FA + 11 % NA) * 8, (11 / NA) & 1);
            flag_wait(FL_CS, ep1 * 4);
            fence_async_global();
            if (elect()) {
                mbar_expect(bars + BAR_CS * 8, 864);
                bulk_g2s(sb + SM_CS, g_cs + 64 * j, 256, bars + BAR_CS * 8);
                bulk_g2s(sb + SM_CS + 256, g_cs + 512 + RA3 * j, 4 * RA3, bars + BAR_CS * 8);
                bulk_g2s(sb + SM_CS + 256 + 4 * RA3, g_cs + HB0 + 64 * j, 256, bars + BAR_CS * 8);
                bulk_g2s(sb + SM_CS + 512 + 4 * RA3, g_cs + HB0 + 512 + RB3 * j, 4 * RB3, bars + BAR_CS * 8);
            }
            __syncwarp();
            mbar_wait(bars + BAR_ME * 8, 1);
            mbar_wait_warm(bars + (BAR_FA + 21 % NA) * 8, (21 / NA) & 1);
#pragma unroll 1
            for (int i = 0; i < 3; i++) {
                if (i) {
                    mbar_wait(bars + BAR_ME * 8, (i + 1) & 1);
                    for (int n = i; n < NPING; n++) { spin(PING); n += tensor_ping(); }
                }
                flag_wait(FL_G + 16 * i + rb, ep1 * 8);
                if (lane == 0) { mbar_expect(bars + (BAR_G + i) * 8, 0); TS(35 + (i + 2) % 3); }
                __syncwarp();
            }
            return;
        }
        if (elect()) {
            if (wq == 1) {
                Ring<NB, SM_RB, BAR_FB, BAR_EB> r{sb, 0, 0};
#pragma unroll 1
                for (int ph = 0; ph < 7; ph++) {
                    const CUtensorMap* ma = ph == 0 ? &maps.w1a : ph == 1 ? &maps.w2a : ph == 6 ? &maps.w4a : &maps.w3a;
                    const bool b3b = ph == 2 || ph == 4 || ph == 5;
                    r.runw(paired, idx & 1, ma, ma + (b3b ? 2 : 1), ph == 3 ? 64 * j : b3b ? HB0 + 64 * j : cm,
                           ph == 3 ? 512 + RA3 * j : b3b ? HB0 + 512 + RB3 * j : cr, ph == 4 ? 10 - NA : ph == 5 ? 1 : 0,
                           ph == 6 ? 27 : ph == 5 ? 10 - NA : ph == 2 ? 1 : 10, ph == 0 ? 0 : ph == 6 ? OWNG * (HB0 / 64 + j) : cm >> 6,
                           ph == 3 ? 8192 + 128 * RA3 : b3b ? 8192 + 128 * RB3 : 10240,
                           ph == 1 ? GATE : ph == 3 ? GATE - 1 : -1, bars + (BAR_ST - (ph == 1)) * 8);
                }
            } else {
                Ring<NA, SM_RA, BAR_FA, BAR_EA> r{sb, 0, 0};
                if (cta >= 120) mbar_wait(bars + (BAR_K + 4) * 8, 0);
                mbar_expect(bars + BAR_XR * 8, 20480);
                bulk_g2s(sb + SM_XR, p.q + (size_t)rho * 16 * D_, 20480, bars + BAR_XR * 8);
                mbar_wait(bars + BAR_Y2 * 8, 0);
                mbar_expect(bars + BAR_XY * 8, 20480);
                tma2d(sb + SM_XT, &maps.xa, cm, rb * 128, bars + BAR_XY * 8);
                tma2d(sb + SM_XT2, &maps.xb, cr, rb * 128, bars + BAR_XY * 8);
                const int grp = j >> 1;
                const int delta = (grp & 1 ? 1 : -1) * (1 + (grp >> 1));
                const int nb = min(max(rb + (delta > 0 ? 1 : -1), 0), 15);
                uint32_t fb = r.acquire(SLOT), dst = r.slot();
                flag_wait2(FL_R + nb, FL_R + rb, ep1 * 8);
                fence_async_global();
                tma2d(dst, &maps.hn, 0, rb * 128 + delta, fb);
                TS(24);
                r.next();
                r.run2d(&maps.hn, rb * 128 + delta);
#pragma unroll 1
                for (int i = 0; i < 2; i++) {
                    const char* src = (const char*)(i ? g_x1 : g_h1) + (size_t)rb * 163840;
                    r.acquire(0); r.next();
                    fb = r.acquire(SLOT); dst = r.slot();
                    const char* src1 = src + (cm == 0 ? SLOT : 0);
                    flag_wait(FL_B1 + 16 * i + rb, ep1 * 8);
                    fence_async_global();
                    bulk_g2s(dst, src1, SLOT, fb);
                    TS(28 + 4 * i);
                    mbar_expect(bars + (BAR_ST - 1 + i) * 8, 0);
                    r.next();
                    r.run1d(src, 2, 10, cm >> 6);
                }
                r.run1d((const char*)g_x1 + (size_t)rb * 163840, 1, 10 - NA, cm >> 6);
                if (OWNG) { r.acquire(0); r.next(); }
#pragma unroll 1
                for (int i = 0; i < 2; i++) {
                    mbar_wait(bars + (BAR_G + 1 + i) * 8, 0); fence_async_global();
                    r.run1d((const char*)g_g + (size_t)rb * 442368, OWNG + HB0 / 64 * i, i ? 27 : OWNG + HB0 / 64, OWNG * (HB0 / 64 + j));
                }
            }
        }
        return;
    }
    bar_arrive(13, 640);
    asm volatile("setmaxnreg.inc.sync.aligned.u32 112;");
    const int rrow = 16 * rho + (warp >> 1) + 8 * (warp & 1);

    fence_async_smem();
    bar_sync(1 + wg, 128);
#pragma unroll 1
    for (int cc = wg; cc < wg + 1 + (wg == 3); cc++) {
        mbar_wait(bars + (BAR_K + cc) * 8, 0);
        if (cc == 2 && wq == 0) TSW(40);
        uint32_t a = sb + sm_k(cc) + 32 + (tid & 127) * 32;
        uint32_t pw = lds32(a - 4);
        uint4 x = lds128(a), y = lds128(a + 16), o;
        if ((tid & 127) == 0) {
            uint16_t k0 = __bfloat16_as_ushort(__float2bfloat16_rn(blo(x.x) + __uint_as_float(lds32(sb + SM_GV + 520 + cc * 4))));
            x.x = (x.x & 0xffff0000u) | k0;
            sts16(a, k0);
        }
        o.x = prmt(pw, x.x, 0x5432); o.y = prmt(x.x, x.y, 0x5432); o.z = prmt(x.y, x.z, 0x5432); o.w = prmt(x.z, x.w, 0x5432);
        sts128(a + 4160, o);
        o.x = prmt(x.w, y.x, 0x5432); o.y = prmt(y.x, y.y, 0x5432); o.z = prmt(y.y, y.z, 0x5432); o.w = prmt(y.z, y.w, 0x5432);
        sts128(a + 4176, o);
    }
    bar_sync(1 + wg, 128);
    if (wg == 3) bar_arrive(11, 256);
#pragma unroll 1
    for (int cc = wg; cc < 5; cc += 3) {
        if (cc == 3 && wg == 0) break;
        if (cc == 4) bar_sync(11, 256);
        const uint32_t kaddr = sb + sm_k(cc) + ((g & 1) ? 32 : 4192) + 4 * ((g >> 1) - c) + 64 * wq;
        const AFrag f0 = ldA(kaddr), f1 = ldA(kaddr + 256);
        if (STAG && cc == 3) bar_sync(12, 256);
        mbar_wait(bars + (BAR_U + cc) * 8, 0);
        if (wq == 0) TSW(5 + cc);
        float d[64];
        conv_two<0>(d, f0, f1, kaddr, desc_lo(sb + sm_u(cc), U_PLANE), sb + sm_red(cc) + wq * 4352 + g * 544 + c * 8, cc == 1);
        if (wq == 0) TSW(10 + cc);
        if (cc == 1) bar_arrive(6, 256);
    }
#pragma unroll 1
    for (int cc = wg == 1 ? 4 : wg;; cc++) {
        if (cc == 1) bar_sync(6, 256); else bar_sync(1 + wg, 128);
        const int ch = chan(cc);
        uint32_t* dst = g_yv + ch * 8 + ((g + (ch >> 2)) & 7) + (126 - 32 * wq - 2 * c) * 5120;
        uint2 v[16];
#pragma unroll
        for (int i = 0; i < 16; i++) v[i] = lds64(sb + sm_red(cc) + g * 544 + wq * 128 + c * 8 + (i >> 2) * 32 + (i & 3) * 4360);
#pragma unroll
        for (int w = 1; w < 4; w++)
            if (wq == 3 && c > 3 - w) v[12 + w] = make_uint2(0, 0);
#pragma unroll
        for (int q = 0; q < 4; q++) {
            const uint2* u = v + 4 * q;
            dst[-8 * q * 5120] = badd2(u[0].x, badd2(u[1].x, badd2(u[2].x, u[3].x)));
            dst[(-8 * q + 1) * 5120] = badd2(u[0].y, badd2(u[1].y, badd2(u[2].y, u[3].y)));
        }
        if (wq == 0) TSW(15 + cc);
        if (cc != 0) break;
    }
    fence_async_smem();
    if (!(wg & 1)) bar_arrive(9, 320);
    bar_arrive(7, 544);

    const uint32_t one2 = 0x3f803f80u;
    const unsigned ones = p.ones;
    {
        uint32_t x[10], a[10], cb[10], sbv[10];
        if (RPRE_WAIT) bar_sync(10, 512);
        mbar_wait(bars + BAR_XR * 8, 0);
#pragma unroll
        for (int i = 0; i < 10; i++) x[i] = lds32(sb + SM_XR + (rrow & 15) * 1280 + lane * 4 + i * 128);
        const uint3 s1 = row_stats(x, lane);
        const int up = lane >> 4, gg = warp >> 1, e = warp & 1;
        const uint32_t ya = sb + SM_Y + lane * 64 + ((gg + (lane >> 1)) & 7) * 4;
        const uint32_t sel = (up ? 0x1054u : 0x5410u) + (e ? 0x2222u : 0u);
        const uint32_t ma = sb + SM_MOD + lane * 4;
        mbar_wait(bars + BAR_M * 8, 0);
        uint32_t pin = 0;
#pragma unroll
        for (int i = 0; i < 10; i++) {
            uint32_t h = bfma2(ln_apply(x[i], s1.x, s1.y, s1.z), badd2(lds32(ma + 1280 + i * 128), one2), lds32(ma + i * 128));
            a[i] = bmul2(h, lds32(ma + 2560 + i * 128));
            sbv[i] = lds32(ma + 3840 + i * 128);
            cb[i] = badd2(lds32(ma + 5120 + i * 128), one2);
            pin ^= a[i] ^ cb[i];
        }
        if (pin & ~ones) sts32(sb + SM_GV, pin);
        if (warp == 4) TSW(52);
        mbar_wait(bars + BAR_Y * 8, 0);
        mbar_wait(bars + BAR_Y2 * 8, 0);
        if (warp == 0) TSW(22);
#pragma unroll
        for (int i = 0; i < 10; i++) {
            uint32_t y0 = lds32(ya + i * 2048 + up * 32), y1 = lds32(ya + i * 2048 + (up ^ 1) * 32);
            x[i] = bfma2(a[i], prmt(y0, y1, sel), x[i]);
        }
        const uint3 s2 = row_stats(x, lane);
#pragma unroll
        for (int i = 0; i < 10; i++) x[i] = bfma2(ln_apply(x[i], s2.x, s2.y, s2.z), cb[i], sbv[i]);
        const uint3 s3 = row_stats(x, lane);
        uint32_t* o = reinterpret_cast<uint32_t*>(g_hn + (size_t)rrow * D_) + lane;
#pragma unroll
        for (int i = 0; i < 10; i++) o[32 * i] = ln_apply(x[i], s3.x, s3.y, s3.z);
        if (lane < 2) g_rs[rrow * 2 + lane] = lane ? make_uint4(s2.x, s2.y, s2.z, 0) : make_uint4(s1.x, s1.y, s1.z, 0);
        if (warp == 0) TSW(34);
        bar_arrive(8, 576);
    }

    const int half = wg & 1;
    const int row = 64 * half + 16 * wq + g;
    const int tw0 = (rb * 80 + (cm >> 3)) * 512 + row * 4 + c, tw1 = (rb * 80 + (cr >> 3) - 8) * 512 + row * 4 + c;
    const uint32_t park = sb + SM_Y + (tid & 255) * 16;
    const uint32_t ms0 = sb + SM_MOD + (cm + 2 * c) * 2, ms1 = sb + SM_MOD + (cr - 64 + 2 * c) * 2;
    if (wg >= 2) {
        {
            float acc[40];
            gemm_loop<80, true, 10, 10, true>(acc, sb, half, 0, 0, 10, 0, 0, 25);
            if (tid == 256) mbar_expect(bars + BAR_ME * 8, 0);
#pragma unroll
            for (int k = 0; k < 10; k += CH) CHUNK(k) {
#pragma unroll
                for (int q = k; q < k + CH && q < 10; q++) {
                    uint32_t* dst = reinterpret_cast<uint32_t*>(g_h1) + (q < 8 ? tw0 : tw1);
                    const uint32_t u = gelu2_h(bmul2(pack2(acc[4 * q], acc[4 * q + 1]), 0x3f003f00u));
                    const uint32_t v = gelu2_h(bmul2(pack2(acc[4 * q + 2], acc[4 * q + 3]), 0x3f003f00u));
                    dst[q * 512] = u;
                    dst[q * 512 + 32] = v;
                    acc[4 * q] = __uint_as_float(u); acc[4 * q + 1] = __uint_as_float(v);
                }
            }
            bar_arrive(15, 288);
            mbar_wait(bars + (BAR_FA + 10 % NA) * 8, (10 / NA) & 1);
#pragma unroll
            for (int q = 0; q < 8; q++) {
                sts32(sb + SM_RA + (10 % NA) * SLOT + q * 2048 + row * 16 + c * 4, __float_as_uint(acc[4 * q]));
                sts32(sb + SM_RA + (10 % NA) * SLOT + q * 2048 + row * 16 + c * 4 + 128, __float_as_uint(acc[4 * q + 1]));
            }
            fence_async_smem();
            bar_arrive(14, 512);
        }
        gemm3<0>(sb, rb, j, half, row, c, ones);
        {
            float acc[40];
            uint32_t gbv[10], base[20];
#pragma unroll
            for (int q = 0; q < 10; q++) gbv[q] = lds32((q < 8 ? ms0 : ms1) + 6400 + q * 16);
#pragma unroll
            for (int q = 0; q < 5; q++) { const uint4 t = lds128(park + q * 4096); base[4 * q] = t.x; base[4 * q + 1] = t.y; base[4 * q + 2] = t.z; base[4 * q + 3] = t.w; }
            gemm_loop<80, false, 27, 27 - NB, true>(acc, sb, half, 39 - NA, 40, 27 - NA, 11, 0, 42);
            auto fin = [&](int q, int r) {
                return bfma2(gbv[q], pack2(acc[4 * q + 2 * r], acc[4 * q + 2 * r + 1]), base[2 * q + r]);
            };
            auto tr4 = [&](uint32_t t0, uint32_t t1, uint32_t t2, uint32_t t3) {
                const bool o1 = c & 1, o2 = c & 2;
                uint32_t a = __shfl_xor_sync(0xffffffffu, o1 ? t0 : t1, 1), b = __shfl_xor_sync(0xffffffffu, o1 ? t2 : t3, 1);
                uint32_t u0 = o1 ? a : t0, u1 = o1 ? t1 : a, u2 = o1 ? b : t2, u3 = o1 ? t3 : b;
                a = __shfl_xor_sync(0xffffffffu, o2 ? u0 : u2, 2); b = __shfl_xor_sync(0xffffffffu, o2 ? u1 : u3, 2);
                return o2 ? make_uint4(a, b, u2, u3) : make_uint4(u0, u1, a, b);
            };
            bf16* go = p.out + (size_t)(rb * 128 + row) * D_;
#pragma unroll
            for (int k = 0; k < 2; k++) CHUNK(k) {
#pragma unroll
                for (int r = 0; r < 2; r++)
                    *reinterpret_cast<uint4*>(go + r * 8 * D_ + cm + 32 * k + 8 * c) = tr4(fin(4 * k, r), fin(4 * k + 1, r), fin(4 * k + 2, r), fin(4 * k + 3, r));
            }
            CHUNK(2) *reinterpret_cast<uint4*>(go + (c >> 1) * 8 * D_ + cr + 8 * (c & 1)) = tr4(fin(8, 0), fin(9, 0), fin(8, 1), fin(9, 1));
            if (tid == 256) TS(44);
            if (warp == 8) TSFLUSH();
        }
    } else {
        {
            float acc[40];
            uint32_t x2[20];
            {
                uint32_t y[20];
                mbar_wait(bars + BAR_XY * 8, 0);
                const uint32_t xa = sb + SM_XT + row * 128 + c * 4, xb = sb + SM_XT2 + row * 32 + c * 4;
                const uint32_t ya = sb + SM_YT + (4 * half + wq) * 2560 + c * 64;
#pragma unroll
                for (int q = 0; q < 10; q++) {
                    const uint32_t a = q < 8 ? xa + ((q ^ g) << 4) : xb + (q - 8) * 16;
                    x2[2 * q] = lds32(a); x2[2 * q + 1] = lds32(a + (q < 8 ? 1024 : 256));
                    const int pos = (g + ((q < 8 ? cm : cr) >> 2) + 2 * q + (c >> 1)) & 7;
                    y[2 * q] = lds32(ya + q * 256 + pos * 4); y[2 * q + 1] = lds32(ya + q * 256 + 32 + pos * 4);
                }
                fence_async_smem();
                bar_sync(1 + wg, 128);
                if ((tid & 127) < NA) mbar_arrive_cl(mapa(bars + (BAR_EA + (tid & 127)) * 8, blockIdx.x & 1));
                mbar_wait(bars + (BAR_FA + 1) * 8, 0);
                const uint4* rp = g_rs + (rb * 128 + row) * 2;
                const uint4 ra = ldcg128(rp), rb2 = ldcg128(rp + 1), rc = ldcg128(rp + 16), rd = ldcg128(rp + 17);
                bar_sync(14, 512);
#pragma unroll
                for (int q = 0; q < 10; q++) {
                    const uint32_t ms = q < 8 ? ms0 : ms1;
                    const uint32_t sa = lds32(ms + 16 * q), ca = badd2(lds32(ms + 1280 + 16 * q), one2), ga = lds32(ms + 2560 + 16 * q);
                    const uint32_t sbv = lds32(ms + 3840 + 16 * q), cb = badd2(lds32(ms + 5120 + 16 * q), one2);
                    uint32_t u = x2[2 * q], v = x2[2 * q + 1];
                    u = bfma2(bmul2(bfma2(ln_apply(u, ra.x, ra.y, ra.z), ca, sa), ga), prmt(y[2 * q], y[2 * q + 1], 0x5410), u);
                    v = bfma2(bmul2(bfma2(ln_apply(v, rc.x, rc.y, rc.z), ca, sa), ga), prmt(y[2 * q], y[2 * q + 1], 0x7632), v);
                    x2[2 * q] = u; x2[2 * q + 1] = v;
                    u = bfma2(ln_apply(u, rb2.x, rb2.y, rb2.z), cb, sbv);
                    v = bfma2(ln_apply(v, rd.x, rd.y, rd.z), cb, sbv);
                    acc[4 * q] = blo(u); acc[4 * q + 1] = bhi(u); acc[4 * q + 2] = blo(v); acc[4 * q + 3] = bhi(v);
                }
            }
            reg_fence<40>(acc);
            if (tid == 0) TS(45);
            gemm_loop<80, false, 10, 10, false>(acc, sb, half, 10, 10, 10, 0, 0, 29);
            if (tid == 0) mbar_expect(bars + BAR_ME * 8, 0);
            uint32_t x1[20];
            float s0 = 0.f, q0 = 0.f, s1 = 0.f, q1 = 0.f;
#pragma unroll
            for (int q = 0; q < 10; q++) {
                uint32_t u = pack2(acc[4 * q], acc[4 * q + 1]);
                uint32_t v = pack2(acc[4 * q + 2], acc[4 * q + 3]);
                uint32_t* dst = reinterpret_cast<uint32_t*>(g_x1) + (q < 8 ? tw0 : tw1);
                dst[q * 512] = u;
                dst[q * 512 + 32] = v;
                x1[2 * q] = u; x1[2 * q + 1] = v;
            }
            bar_arrive(6, 288);
            CHUNK(0)
#pragma unroll
            for (int q = 0; q < 10; q++) {
                float a = blo(x1[2 * q]), b = bhi(x1[2 * q]), e = blo(x1[2 * q + 1]), f = bhi(x1[2 * q + 1]);
                s0 += a + b; q0 = fmaf(a, a, fmaf(b, b, q0));
                s1 += e + f; q1 = fmaf(e, e, fmaf(f, f, q1));
            }
#pragma unroll
            for (int m = 1; m <= 2; m <<= 1) {
                s0 += __shfl_xor_sync(0xffffffffu, s0, m); q0 += __shfl_xor_sync(0xffffffffu, q0, m);
                s1 += __shfl_xor_sync(0xffffffffu, s1, m); q1 += __shfl_xor_sync(0xffffffffu, q1, m);
            }
            if (c < 2) g_st[(rb * 8 + j) * 128 + row + 8 * c] = c ? make_float2(s1, q1) : make_float2(s0, q0);
            bar_arrive(8, 288);
            mbar_wait(bars + (BAR_FA + 20 % NA) * 8, (20 / NA) & 1);
#pragma unroll
            for (int q = 0; q < 8; q++) {
                sts32(sb + SM_RA + (20 % NA) * SLOT + q * 2048 + row * 16 + c * 4, x1[2 * q]);
                sts32(sb + SM_RA + (20 % NA) * SLOT + q * 2048 + row * 16 + c * 4 + 128, x1[2 * q + 1]);
            }
            fence_async_smem();
            bar_sync(3 + wg, 128);
#pragma unroll
            for (int q = 0; q < 5; q++) {
                const uint32_t ms = q < 4 ? ms0 : ms1;
                const uint32_t g0 = lds32(ms + 6400 + q * 32), g1 = lds32(ms + 6400 + q * 32 + 16);
                sts128(park + q * 4096, make_uint4(bfma2(g0, x1[4 * q], x2[4 * q]), bfma2(g0, x1[4 * q + 1], x2[4 * q + 1]),
                                                   bfma2(g1, x1[4 * q + 2], x2[4 * q + 2]), bfma2(g1, x1[4 * q + 3], x2[4 * q + 3])));
            }
        }
        gemm3<1>(sb, rb, j, half, row, c, ones);
    }
}

typedef CUresult (*EncFn)(CUtensorMap*, CUtensorMapDataType, cuuint32_t, void*, const cuuint64_t*, const cuuint64_t*,
                          const cuuint32_t*, const cuuint32_t*, CUtensorMapInterleave, CUtensorMapSwizzle,
                          CUtensorMapL2promotion, CUtensorMapFloatOOBfill);

void make_map(EncFn enc, CUtensorMap* m, const void* base, uint64_t inner, uint64_t outer, uint32_t bi, uint32_t bo,
              CUtensorMapSwizzle swz = CU_TENSOR_MAP_SWIZZLE_128B) {
    cuuint64_t dims[2] = {inner, outer};
    cuuint64_t st[1] = {inner * 2};
    cuuint32_t box[2] = {bi, bo};
    cuuint32_t es[2] = {1, 1};
    enc(m, CU_TENSOR_MAP_DATA_TYPE_BFLOAT16, 2, const_cast<void*>(base), dims, st, box, es, CU_TENSOR_MAP_INTERLEAVE_NONE,
        swz, CU_TENSOR_MAP_L2_PROMOTION_NONE, CU_TENSOR_MAP_FLOAT_OOB_FILL_NONE);
}

}

extern "C" void kernel_launch(void* const* d_in, const int* in_sizes, int n_in, void* d_out, int out_size) {
    (void)in_sizes; (void)n_in; (void)out_size;
    Params p;
    p.q = (const bf16*)d_in[0]; p.k = (const bf16*)d_in[1]; p.v = (const bf16*)d_in[2];
    p.shift = (const bf16*)d_in[3]; p.ssmk = (const bf16*)d_in[4]; p.ssmD = (const bf16*)d_in[5];
    p.w1 = (const bf16*)d_in[7]; p.w2 = (const bf16*)d_in[8]; p.w3 = (const bf16*)d_in[9]; p.w4 = (const bf16*)d_in[10];
    p.c = (const bf16*)d_in[11]; p.wmod = (const bf16*)d_in[12];
    p.out = (bf16*)d_out;
    p.ones = 0xffffffffu;
    cudaGetSymbolAddress((void**)&p.epoch, g_epoch);

    void* fn = nullptr;
    cudaDriverEntryPointQueryResult qr;
    cudaGetDriverEntryPoint("cuTensorMapEncodeTiled", &fn, cudaEnableDefault, &qr);
    EncFn enc = (EncFn)fn;
    void* hn = nullptr;
    cudaGetSymbolAddress(&hn, g_hn);
    Maps maps;
    make_map(enc, &maps.w3s, p.w3, F_, D_, 216, 64, CU_TENSOR_MAP_SWIZZLE_NONE);
    make_map(enc, &maps.wm, p.wmod, 6 * D_, D_, 32, 128, CU_TENSOR_MAP_SWIZZLE_64B);
    make_map(enc, &maps.xa, p.q, D_, S_, 64, 128);
    make_map(enc, &maps.xb, p.q, D_, S_, 16, 128, CU_TENSOR_MAP_SWIZZLE_NONE);
    make_map(enc, &maps.hn, hn, D_, S_, 64, 128);
    make_map(enc, &maps.w1a, p.w1, D_, D_, 64, 64);
    make_map(enc, &maps.w1b, p.w1, D_, D_, 16, 64);
    make_map(enc, &maps.w2a, p.w2, D_, D_, 64, 64);
    make_map(enc, &maps.w2b, p.w2, D_, D_, 16, 64);
    make_map(enc, &maps.w3a, p.w3, F_, D_, 64, 64);
    make_map(enc, &maps.w3b, p.w3, F_, D_, RA3, 64);
    make_map(enc, &maps.w3c, p.w3, F_, D_, RB3, 64);
    make_map(enc, &maps.w4a, p.w4, D_, F_, 64, 64);
    make_map(enc, &maps.w4b, p.w4, D_, F_, 16, 64);
    cudaFuncSetAttribute(fused_kernel, cudaFuncAttributeMaxDynamicSharedMemorySize, SMEM_BYTES);
    fused_kernel<<<132, NTHREADS, SMEM_BYTES>>>(p, maps);
}
```

```cpp
#include <cuda_runtime.h>
#include <cuda_bf16.h>
#include <cuda.h>
#include <stdint.h>
#include <string.h>

#define SEED 1
#define RING_A 6
#define CH 2
#define FAST_LN 2
#define STAG 12
#define PGELU 2
#define CH3 4
#define HO_A 16
#define HO_B 16
#define RA3 48
#define CSP 16
#define OWNG 1
#define GATE 5
#define SSM_DELAY 100
#define B_DELAY 220
#define RPRE_WAIT 1
#define PING 250
#define NPING 5
#define FORCE_UNPAIRED 0
#define WAFT 1
#define GATE0 3
#define GBAR0 BAR_Y2
#define TB1 0
#define GE 1
#define WMG 0
#define WMD 0
#define SPD 800
#define WMD2 600
#define SSM_N 3

namespace {

typedef __nv_bfloat16 bf16;
typedef __nv_bfloat162 bf162;

constexpr int S_ = 2048, D_ = 640, F_ = 1728;
constexpr int NTHREADS = 640;
constexpr int NA = RING_A, NB = 12 - RING_A;
constexpr int SLOT = 16384;
constexpr int RB3 = 88 - RA3, HB0 = 512 + 8 * RA3;
constexpr int SM_RA = 0, SM_RB = NA * SLOT;

static_assert(NA == 6, "smem map");
constexpr int RED_STRIDE = 17536;
constexpr int K_STRIDE = 8320;
constexpr int U_PLANE = 2560, U_STRIDE = 5120;
constexpr int SM_Y = 12 * SLOT;
__device__ __forceinline__ int sm_red(int cc) { return cc * RED_STRIDE + (cc < 3 ? SM_RB : -3 * RED_STRIDE); }
__device__ __forceinline__ int sm_k(int cc) { return cc * K_STRIDE + (cc < 3 ? SM_RB + 3 * RED_STRIDE : 2 * RED_STRIDE - 3 * K_STRIDE); }
__device__ __forceinline__ int sm_u(int cc) { return cc * U_STRIDE + (cc < 3 ? SM_RB + 3 * RED_STRIDE + 3 * K_STRIDE : SM_Y + 8192 - 3 * U_STRIDE); }
constexpr int SM_PK = SM_RB;
constexpr int SM_PV = SM_RB + 24576;
constexpr int SM_WM = 57344;
constexpr int SM_XT = TB1 ? 5 * SLOT : SM_WM, SM_XT2 = TB1 ? 0 : SM_WM + 16384, SM_XR = SM_WM + 20480;
constexpr int SM_YT = TB1 ? SM_Y : 0;
constexpr int SM_MOD = SM_Y + 20480;
constexpr int SM_GV = SM_MOD + 7680;
constexpr int SM_CS = SM_GV + 1024;
constexpr int SM_RP = SM_CS + 1024;
constexpr int SM_BAR = SM_RP + 1024;
constexpr int SM_PROF = SM_BAR + 512;
constexpr int SM_TOTAL = SM_PROF + 512;
constexpr int SMEM_BYTES = SM_TOTAL + 1024;
static_assert(SMEM_BYTES <= 232448, "smem");

constexpr int BAR_FA = 0, BAR_FB = NA, BAR_EA = 12, BAR_EB = 12 + NA, BAR_K = 24, BAR_U = 29, BAR_Y = 34, BAR_CS = 35, BAR_WM = 36, BAR_M = 37, BAR_XY = 38, BAR_Y2 = 39, BAR_G = 40, BAR_ST = 44, BAR_XR = 45, BAR_ME = 46, BAR_CD = 47, BAR_WM0 = 48, BAR_MR = 49, BAR_XD = 50, NBARS = 51;

__device__ __align__(1024) bf16 g_kvT[D_ * S_];
__device__ __align__(1024) uint32_t g_yv[128 * 5120];
__device__ __align__(1024) bf16 g_mod[6 * D_];
__device__ __align__(1024) bf16 g_hn[S_ * D_];
__device__ __align__(1024) uint4 g_rs[S_ * 2];
__device__ __align__(1024) bf16 g_h1[S_ * D_];
__device__ __align__(1024) bf16 g_x1[S_ * D_];
__device__ __align__(1024) bf16 g_g[S_ * F_];
__device__ __align__(1024) float2 g_st[S_ * 8];
__device__ __align__(1024) float g_cs[F_];
__device__ __align__(1024) unsigned g_flags[128 * 32];
__device__ __align__(1024) unsigned g_epoch[160];
constexpr int FL_P = 0, FL_C = 8, FL_CS = 9, FL_M = 10, FL_R = 16, FL_B1 = 32, FL_B2 = 48, FL_G = 64;

#define TS(i) do {} while (0)
#define TSW(i) do {} while (0)
#define TSD(i, dep) do {} while (0)
#define TSD2(i, dep) do {} while (0)
#define TSFLUSH() do {} while (0)

struct Params {
    const bf16 *q, *k, *v, *shift, *ssmk, *ssmD, *w1, *w2, *w3, *w4, *c, *wmod;
    bf16* out;
    unsigned* epoch;
    unsigned ones;
};
#define CHUNK(k) if (ones & (1u << (k)))
struct Maps { CUtensorMap hn, w1a, w1b, w2a, w2b, w3a, w3b, w3c, w4a, w4b, wm, xa, xb, w3s; };

template<int N> struct WgRs;
template<int N> struct WgSs;
template<> struct WgRs<32> { template<int OFF,int HI,int SC> static __device__ __forceinline__ void run(float* d,uint32_t a0,uint32_t a1,uint32_t a2,uint32_t a3,uint32_t blo){
 asm volatile("{.reg .b32 l; .reg .b64 db; add.u32 l,%20,%21; mov.b64 db,{l,%22}; wgmma.mma_async.sync.aligned.m64n32k16.f32.bf16.bf16 {%0,%1,%2,%3,%4,%5,%6,%7,%8,%9,%10,%11,%12,%13,%14,%15},{%16,%17,%18,%19},db,%23,1,1,0;}"
 :"+f"(d[0]),"+f"(d[1]),"+f"(d[2]),"+f"(d[3]),"+f"(d[4]),"+f"(d[5]),"+f"(d[6]),"+f"(d[7]),"+f"(d[8]),"+f"(d[9]),"+f"(d[10]),"+f"(d[11]),"+f"(d[12]),"+f"(d[13]),"+f"(d[14]),"+f"(d[15])
 :"r"(a0),"r"(a1),"r"(a2),"r"(a3),"r"(blo),"n"(OFF),"n"(HI),"n"(SC)); } };
template<> struct WgRs<48> { template<int OFF,int HI,int SC> static __device__ __forceinline__ void run(float* d,uint32_t a0,uint32_t a1,uint32_t a2,uint32_t a3,uint32_t blo){
 asm volatile("{.reg .b32 l; .reg .b64 db; add.u32 l,%28,%29; mov.b64 db,{l,%30}; wgmma.mma_async.sync.aligned.m64n48k16.f32.bf16.bf16 {%0,%1,%2,%3,%4,%5,%6,%7,%8,%9,%10,%11,%12,%13,%14,%15,%16,%17,%18,%19,%20,%21,%22,%23},{%24,%25,%26,%27},db,%31,1,1,0;}"
 :"+f"(d[0]),"+f"(d[1]),"+f"(d[2]),"+f"(d[3]),"+f"(d[4]),"+f"(d[5]),"+f"(d[6]),"+f"(d[7]),"+f"(d[8]),"+f"(d[9]),"+f"(d[10]),"+f"(d[11]),"+f"(d[12]),"+f"(d[13]),"+f"(d[14]),"+f"(d[15]),"+f"(d[16]),"+f"(d[17]),"+f"(d[18]),"+f"(d[19]),"+f"(d[20]),"+f"(d[21]),"+f"(d[22]),"+f"(d[23])
 :"r"(a0),"r"(a1),"r"(a2),"r"(a3),"r"(blo),"n"(OFF),"n"(HI),"n"(SC)); } };
template<> struct WgRs<64> { template<int OFF,int HI,int SC> static __device__ __forceinline__ void run(float* d,uint32_t a0,uint32_t a1,uint32_t a2,uint32_t a3,uint32_t blo){
 asm volatile("{.reg .b32 l; .reg .b64 db; add.u32 l,%36,%37; mov.b64 db,{l,%38}; wgmma.mma_async.sync.aligned.m64n64k16.f32.bf16.bf16 {%0,%1,%2,%3,%4,%5,%6,%7,%8,%9,%10,%11,%12,%13,%14,%15,%16,%17,%18,%19,%20,%21,%22,%23,%24,%25,%26,%27,%28,%29,%30,%31},{%32,%33,%34,%35},db,%39,1,1,0;}"
 :"+f"(d[0]),"+f"(d[1]),"+f"(d[2]),"+f"(d[3]),"+f"(d[4]),"+f"(d[5]),"+f"(d[6]),"+f"(d[7]),"+f"(d[8]),"+f"(d[9]),"+f"(d[10]),"+f"(d[11]),"+f"(d[12]),"+f"(d[13]),"+f"(d[14]),"+f"(d[15]),"+f"(d[16]),"+f"(d[17]),"+f"(d[18]),"+f"(d[19]),"+f"(d[20]),"+f"(d[21]),"+f"(d[22]),"+f"(d[23]),"+f"(d[24]),"+f"(d[25]),"+f"(d[26]),"+f"(d[27]),"+f"(d[28]),"+f"(d[29]),"+f"(d[30]),"+f"(d[31])
 :"r"(a0),"r"(a1),"r"(a2),"r"(a3),"r"(blo),"n"(OFF),"n"(HI),"n"(SC)); } };
template<> struct WgRs<80> { template<int OFF,int HI,int SC> static __device__ __forceinline__ void run(float* d,uint32_t a0,uint32_t a1,uint32_t a2,uint32_t a3,uint32_t blo){
 asm volatile("{.reg .b32 l; .reg .b64 db; add.u32 l,%44,%45; mov.b64 db,{l,%46}; wgmma.mma_async.sync.aligned.m64n80k16.f32.bf16.bf16 {%0,%1,%2,%3,%4,%5,%6,%7,%8,%9,%10,%11,%12,%13,%14,%15,%16,%17,%18,%19,%20,%21,%22,%23,%24,%25,%26,%27,%28,%29,%30,%31,%32,%33,%34,%35,%36,%37,%38,%39},{%40,%41,%42,%43},db,%47,1,1,0;}"
 :"+f"(d[0]),"+f"(d[1]),"+f"(d[2]),"+f"(d[3]),"+f"(d[4]),"+f"(d[5]),"+f"(d[6]),"+f"(d[7]),"+f"(d[8]),"+f"(d[9]),"+f"(d[10]),"+f"(d[11]),"+f"(d[12]),"+f"(d[13]),"+f"(d[14]),"+f"(d[15]),"+f"(d[16]),"+f"(d[17]),"+f"(d[18]),"+f"(d[19]),"+f"(d[20]),"+f"(d[21]),"+f"(d[22]),"+f"(d[23]),"+f"(d[24]),"+f"(d[25]),"+f"(d[26]),"+f"(d[27]),"+f"(d[28]),"+f"(d[29]),"+f"(d[30]),"+f"(d[31]),"+f"(d[32]),"+f"(d[33]),"+f"(d[34]),"+f"(d[35]),"+f"(d[36]),"+f"(d[37]),"+f"(d[38]),"+f"(d[39])
 :"r"(a0),"r"(a1),"r"(a2),"r"(a3),"r"(blo),"n"(OFF),"n"(HI),"n"(SC)); } };
template<> struct WgRs<96> { template<int OFF,int HI,int SC> static __device__ __forceinline__ void run(float* d,uint32_t a0,uint32_t a1,uint32_t a2,uint32_t a3,uint32_t blo){
 asm volatile("{.reg .b32 l; .reg .b64 db; add.u32 l,%52,%53; mov.b64 db,{l,%54}; wgmma.mma_async.sync.aligned.m64n96k16.f32.bf16.bf16 {%0,%1,%2,%3,%4,%5,%6,%7,%8,%9,%10,%11,%12,%13,%14,%15,%16,%17,%18,%19,%20,%21,%22,%23,%24,%25,%26,%27,%28,%29,%30,%31,%32,%33,%34,%35,%36,%37,%38,%39,%40,%41,%42,%43,%44,%45,%46,%47},{%48,%49,%50,%51},db,%55,1,1,0;}"
 :"+f"(d[0]),"+f"(d[1]),"+f"(d[2]),"+f"(d[3]),"+f"(d[4]),"+f"(d[5]),"+f"(d[6]),"+f"(d[7]),"+f"(d[8]),"+f"(d[9]),"+f"(d[10]),"+f"(d[11]),"+f"(d[12]),"+f"(d[13]),"+f"(d[14]),"+f"(d[15]),"+f"(d[16]),"+f"(d[17]),"+f"(d[18]),"+f"(d[19]),"+f"(d[20]),"+f"(d[21]),"+f"(d[22]),"+f"(d[23]),"+f"(d[24]),"+f"(d[25]),"+f"(d[26]),"+f"(d[27]),"+f"(d[28]),"+f"(d[29]),"+f"(d[30]),"+f"(d[31]),"+f"(d[32]),"+f"(d[33]),"+f"(d[34]),"+f"(d[35]),"+f"(d[36]),"+f"(d[37]),"+f"(d[38]),"+f"(d[39]),"+f"(d[40]),"+f"(d[41]),"+f"(d[42]),"+f"(d[43]),"+f"(d[44]),"+f"(d[45]),"+f"(d[46]),"+f"(d[47])
 :"r"(a0),"r"(a1),"r"(a2),"r"(a3),"r"(blo),"n"(OFF),"n"(HI),"n"(SC)); } };
template<> struct WgRs<112> { template<int OFF,int HI,int SC> static __device__ __forceinline__ void run(float* d,uint32_t a0,uint32_t a1,uint32_t a2,uint32_t a3,uint32_t blo){
 asm volatile("{.reg .b32 l; .reg .b64 db; add.u32 l,%60,%61; mov.b64 db,{l,%62}; wgmma.mma_async.sync.aligned.m64n112k16.f32.bf16.bf16 {%0,%1,%2,%3,%4,%5,%6,%7,%8,%9,%10,%11,%12,%13,%14,%15,%16,%17,%18,%19,%20,%21,%22,%23,%24,%25,%26,%27,%28,%29,%30,%31,%32,%33,%34,%35,%36,%37,%38,%39,%40,%41,%42,%43,%44,%45,%46,%47,%48,%49,%50,%51,%52,%53,%54,%55},{%56,%57,%58,%59},db,%63,1,1,0;}"
 :"+f"(d[0]),"+f"(d[1]),"+f"(d[2]),"+f"(d[3]),"+f"(d[4]),"+f"(d[5]),"+f"(d[6]),"+f"(d[7]),"+f"(d[8]),"+f"(d[9]),"+f"(d[10]),"+f"(d[11]),"+f"(d[12]),"+f"(d[13]),"+f"(d[14]),"+f"(d[15]),"+f"(d[16]),"+f"(d[17]),"+f"(d[18]),"+f"(d[19]),"+f"(d[20]),"+f"(d[21]),"+f"(d[22]),"+f"(d[23]),"+f"(d[24]),"+f"(d[25]),"+f"(d[26]),"+f"(d[27]),"+f"(d[28]),"+f"(d[29]),"+f"(d[30]),"+f"(d[31]),"+f"(d[32]),"+f"(d[33]),"+f"(d[34]),"+f"(d[35]),"+f"(d[36]),"+f"(d[37]),"+f"(d[38]),"+f"(d[39]),"+f"(d[40]),"+f"(d[41]),"+f"(d[42]),"+f"(d[43]),"+f"(d[44]),"+f"(d[45]),"+f"(d[46]),"+f"(d[47]),"+f"(d[48]),"+f"(d[49]),"+f"(d[50]),"+f"(d[51]),"+f"(d[52]),"+f"(d[53]),"+f"(d[54]),"+f"(d[55])
 :"r"(a0),"r"(a1),"r"(a2),"r"(a3),"r"(blo),"n"(OFF),"n"(HI),"n"(SC)); } };
template<> struct WgRs<128> { template<int OFF,int HI,int SC> static __device__ __forceinline__ void run(float* d,uint32_t a0,uint32_t a1,uint32_t a2,uint32_t a3,uint32_t blo){
 asm volatile("{.reg .b32 l; .reg .b64 db; add.u32 l,%68,%69; mov.b64 db,{l,%70}; wgmma.mma_async.sync.aligned.m64n128k16.f32.bf16.bf16 {%0,%1,%2,%3,%4,%5,%6,%7,%8,%9,%10,%11,%12,%13,%14,%15,%16,%17,%18,%19,%20,%21,%22,%23,%24,%25,%26,%27,%28,%29,%30,%31,%32,%33,%34,%35,%36,%37,%38,%39,%40,%41,%42,%43,%44,%45,%46,%47,%48,%49,%50,%51,%52,%53,%54,%55,%56,%57,%58,%59,%60,%61,%62,%63},{%64,%65,%66,%67},db,%71,1,1,0;}"
 :"+f"(d[0]),"+f"(d[1]),"+f"(d[2]),"+f"(d[3]),"+f"(d[4]),"+f"(d[5]),"+f"(d[6]),"+f"(d[7]),"+f"(d[8]),"+f"(d[9]),"+f"(d[10]),"+f"(d[11]),"+f"(d[12]),"+f"(d[13]),"+f"(d[14]),"+f"(d[15]),"+f"(d[16]),"+f"(d[17]),"+f"(d[18]),"+f"(d[19]),"+f"(d[20]),"+f"(d[21]),"+f"(d[22]),"+f"(d[23]),"+f"(d[24]),"+f"(d[25]),"+f"(d[26]),"+f"(d[27]),"+f"(d[28]),"+f"(d[29]),"+f"(d[30]),"+f"(d[31]),"+f"(d[32]),"+f"(d[33]),"+f"(d[34]),"+f"(d[35]),"+f"(d[36]),"+f"(d[37]),"+f"(d[38]),"+f"(d[39]),"+f"(d[40]),"+f"(d[41]),"+f"(d[42]),"+f"(d[43]),"+f"(d[44]),"+f"(d[45]),"+f"(d[46]),"+f"(d[47]),"+f"(d[48]),"+f"(d[49]),"+f"(d[50]),"+f"(d[51]),"+f"(d[52]),"+f"(d[53]),"+f"(d[54]),"+f"(d[55]),"+f"(d[56]),"+f"(d[57]),"+f"(d[58]),"+f"(d[59]),"+f"(d[60]),"+f"(d[61]),"+f"(d[62]),"+f"(d[63])
 :"r"(a0),"r"(a1),"r"(a2),"r"(a3),"r"(blo),"n"(OFF),"n"(HI),"n"(SC)); } };
template<> struct WgSs<80> { template<int AOFF,int AHI,int BOFF,int BHI,int SC> static __device__ __forceinline__ void run(float* d,uint32_t alo,uint32_t blo){
 asm volatile("{.reg .b32 l,m; .reg .b64 da,db; add.u32 l,%40,%42; mov.b64 da,{l,%43}; add.u32 m,%41,%44; mov.b64 db,{m,%45}; wgmma.mma_async.sync.aligned.m64n80k16.f32.bf16.bf16 {%0,%1,%2,%3,%4,%5,%6,%7,%8,%9,%10,%11,%12,%13,%14,%15,%16,%17,%18,%19,%20,%21,%22,%23,%24,%25,%26,%27,%28,%29,%30,%31,%32,%33,%34,%35,%36,%37,%38,%39},da,db,%46,1,1,0,1;}"
 :"+f"(d[0]),"+f"(d[1]),"+f"(d[2]),"+f"(d[3]),"+f"(d[4]),"+f"(d[5]),"+f"(d[6]),"+f"(d[7]),"+f"(d[8]),"+f"(d[9]),"+f"(d[10]),"+f"(d[11]),"+f"(d[12]),"+f"(d[13]),"+f"(d[14]),"+f"(d[15]),"+f"(d[16]),"+f"(d[17]),"+f"(d[18]),"+f"(d[19]),"+f"(d[20]),"+f"(d[21]),"+f"(d[22]),"+f"(d[23]),"+f"(d[24]),"+f"(d[25]),"+f"(d[26]),"+f"(d[27]),"+f"(d[28]),"+f"(d[29]),"+f"(d[30]),"+f"(d[31]),"+f"(d[32]),"+f"(d[33]),"+f"(d[34]),"+f"(d[35]),"+f"(d[36]),"+f"(d[37]),"+f"(d[38]),"+f"(d[39])
 :"r"(alo),"r"(blo),"n"(AOFF),"n"(AHI),"n"(BOFF),"n"(BHI),"n"(SC)); } };
template<> struct WgSs<104> { template<int AOFF,int AHI,int BOFF,int BHI,int SC> static __device__ __forceinline__ void run(float* d,uint32_t alo,uint32_t blo){
 asm volatile("{.reg .b32 l,m; .reg .b64 da,db; add.u32 l,%52,%54; mov.b64 da,{l,%55}; add.u32 m,%53,%56; mov.b64 db,{m,%57}; wgmma.mma_async.sync.aligned.m64n104k16.f32.bf16.bf16 {%0,%1,%2,%3,%4,%5,%6,%7,%8,%9,%10,%11,%12,%13,%14,%15,%16,%17,%18,%19,%20,%21,%22,%23,%24,%25,%26,%27,%28,%29,%30,%31,%32,%33,%34,%35,%36,%37,%38,%39,%40,%41,%42,%43,%44,%45,%46,%47,%48,%49,%50,%51},da,db,%58,1,1,0,1;}"
 :"+f"(d[0]),"+f"(d[1]),"+f"(d[2]),"+f"(d[3]),"+f"(d[4]),"+f"(d[5]),"+f"(d[6]),"+f"(d[7]),"+f"(d[8]),"+f"(d[9]),"+f"(d[10]),"+f"(d[11]),"+f"(d[12]),"+f"(d[13]),"+f"(d[14]),"+f"(d[15]),"+f"(d[16]),"+f"(d[17]),"+f"(d[18]),"+f"(d[19]),"+f"(d[20]),"+f"(d[21]),"+f"(d[22]),"+f"(d[23]),"+f"(d[24]),"+f"(d[25]),"+f"(d[26]),"+f"(d[27]),"+f"(d[28]),"+f"(d[29]),"+f"(d[30]),"+f"(d[31]),"+f"(d[32]),"+f"(d[33]),"+f"(d[34]),"+f"(d[35]),"+f"(d[36]),"+f"(d[37]),"+f"(d[38]),"+f"(d[39]),"+f"(d[40]),"+f"(d[41]),"+f"(d[42]),"+f"(d[43]),"+f"(d[44]),"+f"(d[45]),"+f"(d[46]),"+f"(d[47]),"+f"(d[48]),"+f"(d[49]),"+f"(d[50]),"+f"(d[51])
 :"r"(alo),"r"(blo),"n"(AOFF),"n"(AHI),"n"(BOFF),"n"(BHI),"n"(SC)); } };
template<> struct WgSs<112> { template<int AOFF,int AHI,int BOFF,int BHI,int SC> static __device__ __forceinline__ void run(float* d,uint32_t alo,uint32_t blo){
 asm volatile("{.reg .b32 l,m; .reg .b64 da,db; add.u32 l,%56,%58; mov.b64 da,{l,%59}; add.u32 m,%57,%60; mov.b64 db,{m,%61}; wgmma.mma_async.sync.aligned.m64n112k16.f32.bf16.bf16 {%0,%1,%2,%3,%4,%5,%6,%7,%8,%9,%10,%11,%12,%13,%14,%15,%16,%17,%18,%19,%20,%21,%22,%23,%24,%25,%26,%27,%28,%29,%30,%31,%32,%33,%34,%35,%36,%37,%38,%39,%40,%41,%42,%43,%44,%45,%46,%47,%48,%49,%50,%51,%52,%53,%54,%55},da,db,%62,1,1,0,1;}"
 :"+f"(d[0]),"+f"(d[1]),"+f"(d[2]),"+f"(d[3]),"+f"(d[4]),"+f"(d[5]),"+f"(d[6]),"+f"(d[7]),"+f"(d[8]),"+f"(d[9]),"+f"(d[10]),"+f"(d[11]),"+f"(d[12]),"+f"(d[13]),"+f"(d[14]),"+f"(d[15]),"+f"(d[16]),"+f"(d[17]),"+f"(d[18]),"+f"(d[19]),"+f"(d[20]),"+f"(d[21]),"+f"(d[22]),"+f"(d[23]),"+f"(d[24]),"+f"(d[25]),"+f"(d[26]),"+f"(d[27]),"+f"(d[28]),"+f"(d[29]),"+f"(d[30]),"+f"(d[31]),"+f"(d[32]),"+f"(d[33]),"+f"(d[34]),"+f"(d[35]),"+f"(d[36]),"+f"(d[37]),"+f"(d[38]),"+f"(d[39]),"+f"(d[40]),"+f"(d[41]),"+f"(d[42]),"+f"(d[43]),"+f"(d[44]),"+f"(d[45]),"+f"(d[46]),"+f"(d[47]),"+f"(d[48]),"+f"(d[49]),"+f"(d[50]),"+f"(d[51]),"+f"(d[52]),"+f"(d[53]),"+f"(d[54]),"+f"(d[55])
 :"r"(alo),"r"(blo),"n"(AOFF),"n"(AHI),"n"(BOFF),"n"(BHI),"n"(SC)); } };

__device__ __forceinline__ void wg_fence() { asm volatile("wgmma.fence.sync.aligned;" ::: "memory"); }
__device__ __forceinline__ void wg_commit() { asm volatile("wgmma.commit_group.sync.aligned;" ::: "memory"); }
template <int N> __device__ __forceinline__ void wg_wait() { asm volatile("wgmma.wait_group.sync.aligned %0;" ::"n"(N) : "memory"); }
template <int N> __device__ __forceinline__ void reg_fence(float* d) {
#pragma unroll
    for (int i = 0; i < N; i++) asm volatile("" : "+f"(d[i])::"memory");
}
__device__ __forceinline__ uint32_t desc_lo(uint32_t addr, uint32_t lbo) { return ((addr & 0x3FFFF) >> 4) | ((lbo >> 4) << 16); }
#define desc_hi(sbo, sw) (((sbo) >> 4) | ((sw) << 30))
__device__ __forceinline__ uint32_t smem_u32(const void* p) { return (uint32_t)__cvta_generic_to_shared(p); }
__device__ __forceinline__ bool elect() {
    uint32_t p;
    asm volatile("{.reg .pred P; elect.sync _|P, 0xffffffff; selp.u32 %0,1,0,P;}" : "=r"(p));
    return p;
}
__device__ __forceinline__ void mbar_init(uint32_t bar, uint32_t cnt) { asm volatile("mbarrier.init.shared::cta.b64 [%0], %1;" ::"r"(bar), "r"(cnt) : "memory"); }
__device__ __forceinline__ void mbar_expect(uint32_t bar, uint32_t bytes) { asm volatile("mbarrier.arrive.expect_tx.shared::cta.b64 _, [%0], %1;" ::"r"(bar), "r"(bytes) : "memory"); }
__device__ __forceinline__ bool mbar_try(uint32_t bar, uint32_t par) {
    uint32_t ok;
    asm volatile("{.reg .pred p; mbarrier.try_wait.parity.shared::cta.b64 p, [%1], %2; selp.u32 %0,1,0,p;}" : "=r"(ok) : "r"(bar), "r"(par) : "memory");
    return ok;
}
constexpr int SPIN_LIMIT = 1 << 18;
__device__ __forceinline__ void mbar_wait(uint32_t bar, uint32_t par) {
    if (mbar_try(bar, par)) return;
    asm volatile("{.reg .pred p, q; .reg .b32 n; mov.u32 n, 0;\n"
                 "W%=: mbarrier.try_wait.parity.shared::cta.b64 p, [%0], %1; add.u32 n, n, 1; setp.lt.and.u32 q, n, %2, !p; @q bra W%=;}"
                 ::"r"(bar), "r"(par), "n"(SPIN_LIMIT) : "memory");
}
__device__ __forceinline__ void bulk_g2s(uint32_t dst, const void* src, uint32_t bytes, uint32_t bar) {
    asm volatile("cp.async.bulk.shared::cluster.global.mbarrier::complete_tx::bytes [%0], [%1], %2, [%3];" ::"r"(dst), "l"(src), "r"(bytes), "r"(bar) : "memory");
}
__device__ __forceinline__ void bulk_s2g(void* dst, uint32_t src, uint32_t bytes) {
    asm volatile("cp.async.bulk.global.shared::cta.bulk_group [%0], [%1], %2;" ::"l"(dst), "r"(src), "r"(bytes) : "memory");
}
__device__ __forceinline__ void bulk_prefetch(const void* src, uint32_t bytes) {
    asm volatile("cp.async.bulk.prefetch.L2.global [%0], %1;" ::"l"(src), "r"(bytes) : "memory");
}
__device__ __forceinline__ void tma2d(uint32_t dst, const CUtensorMap* m, int c0, int c1, uint32_t bar) {
    asm volatile("cp.async.bulk.tensor.2d.shared::cluster.global.mbarrier::complete_tx::bytes [%0], [%1, {%3, %4}], [%2];" ::"r"(dst), "l"(m), "r"(bar), "r"(c0), "r"(c1) : "memory");
}
__device__ __forceinline__ void tma2d_mc(uint32_t dst, const CUtensorMap* m, int c0, int c1, uint32_t bar) {
    asm volatile("cp.async.bulk.tensor.2d.shared::cluster.global.mbarrier::complete_tx::bytes.multicast::cluster [%0], [%1, {%3, %4}], [%2], %5;" ::"r"(dst), "l"(m), "r"(bar), "r"(c0), "r"(c1), "h"((uint16_t)3) : "memory");
}
__device__ __forceinline__ uint32_t mapa(uint32_t a, uint32_t rank) { uint32_t r; asm("mapa.shared::cluster.u32 %0, %1, %2;" : "=r"(r) : "r"(a), "r"(rank)); return r; }
__device__ __forceinline__ void mbar_arrive_cl(uint32_t bar) { asm volatile("mbarrier.arrive.shared::cluster.b64 _, [%0];" ::"r"(bar) : "memory"); }
__device__ __forceinline__ void prefetch_map(const CUtensorMap* m) { asm volatile("prefetch.tensormap [%0];" ::"l"(m) : "memory"); }
__device__ __forceinline__ void cpasync16(uint32_t dst, const void* src, uint32_t srcsz) {
    asm volatile("cp.async.cg.shared.global [%0], [%1], 16, %2;" ::"r"(dst), "l"(src), "r"(srcsz) : "memory");
}
__device__ __forceinline__ void bar_sync(int id, int n) { asm volatile("bar.sync %0, %1;" ::"r"(id), "r"(n) : "memory"); }
__device__ __forceinline__ void bar_arrive(int id, int n) { asm volatile("bar.arrive %0, %1;" ::"r"(id), "r"(n) : "memory"); }
__device__ __forceinline__ void fence_async_smem() { asm volatile("fence.proxy.async.shared::cta;" ::: "memory"); }
__device__ __forceinline__ void fence_async_global() { asm volatile("fence.proxy.async.global;" ::: "memory"); }
__device__ __forceinline__ void flag_release(int f) { asm volatile("red.release.gpu.global.add.u32 [%0], 1;" ::"l"(&g_flags[f * 32]) : "memory"); }
__device__ __forceinline__ void flag_wait(int f, unsigned target) {
    const unsigned* p = &g_flags[f * 32];
    unsigned v; int n = 0;
    do {
        asm volatile("ld.relaxed.gpu.global.u32 %0, [%1];" : "=r"(v) : "l"(p) : "memory");
    } while ((int)(v - target) < 0 && ++n < SPIN_LIMIT);
    asm volatile("fence.acquire.gpu;" ::: "memory");
}
__device__ __forceinline__ unsigned ld_flag(const unsigned* p) { unsigned v; asm volatile("ld.relaxed.gpu.global.u32 %0, [%1];" : "=r"(v) : "l"(p) : "memory"); return v; }
__device__ __forceinline__ void spin(unsigned n) { unsigned t0, t1; asm volatile("mov.u32 %0, %%clock;" : "=r"(t0)); do { asm volatile("mov.u32 %0, %%clock;" : "=r"(t1)); } while (t1 - t0 < n); }
__device__ __forceinline__ int tensor_ping() {
    int r;
    asm volatile("{.reg .f32 a, b, c, d; mma.sync.aligned.m16n8k16.row.col.f32.bf16.bf16.f32 {a,b,c,d},{%1,%1,%1,%1},{%1,%1},{%2,%2,%2,%2}; mov.b32 %0, a;}" : "=r"(r) : "r"(0), "f"(0.f));
    return r;
}
__device__ __forceinline__ void mbar_wait_warm(uint32_t bar, uint32_t par) {
    for (int n = 0; n < SPIN_LIMIT; n++) {
        uint32_t ok;
        asm volatile("{.reg .pred p; mbarrier.test_wait.parity.shared::cta.b64 p, [%1], %2; selp.u32 %0,1,0,p;}" : "=r"(ok) : "r"(bar), "r"(par) : "memory");
        if (ok) break;
        n += tensor_ping();
        spin(PING);
    }
}
__device__ __forceinline__ void flag_wait2(int f0, int f1, unsigned target) {
    const unsigned *p = &g_flags[f0 * 32], *q = &g_flags[f1 * 32];
    unsigned v, w; int n = 0;
    do { v = ld_flag(p); w = ld_flag(q); } while ((int)((v - target) | (w - target)) < 0 && ++n < SPIN_LIMIT);
    asm volatile("fence.acquire.gpu;" ::: "memory");
}
__device__ __forceinline__ uint32_t lds32(uint32_t a) { uint32_t v; asm volatile("ld.shared.u32 %0, [%1];" : "=r"(v) : "r"(a)); return v; }
__device__ __forceinline__ float2 lds64f(uint32_t a) { float2 v; asm volatile("ld.shared.v2.f32 {%0,%1}, [%2];" : "=f"(v.x), "=f"(v.y) : "r"(a)); return v; }
__device__ __forceinline__ uint2 lds64(uint32_t a) { uint2 v; asm volatile("ld.shared.v2.u32 {%0,%1}, [%2];" : "=r"(v.x), "=r"(v.y) : "r"(a)); return v; }
__device__ __forceinline__ void sts64f(uint32_t a, float2 v) { asm volatile("st.shared.v2.f32 [%0], {%1,%2};" ::"r"(a), "f"(v.x), "f"(v.y) : "memory"); }
__device__ __forceinline__ void sts32(uint32_t a, uint32_t v) { asm volatile("st.shared.u32 [%0], %1;" ::"r"(a), "r"(v) : "memory"); }
__device__ __forceinline__ void sts64(uint32_t a, uint32_t x, uint32_t y) { asm volatile("st.shared.v2.u32 [%0], {%1,%2};" ::"r"(a), "r"(x), "r"(y) : "memory"); }
__device__ __forceinline__ void sts16(uint32_t a, uint16_t v) { asm volatile("st.shared.u16 [%0], %1;" ::"r"(a), "h"(v) : "memory"); }
__device__ __forceinline__ uint4 lds128(uint32_t a) { uint4 v; asm volatile("ld.shared.v4.u32 {%0,%1,%2,%3}, [%4];" : "=r"(v.x), "=r"(v.y), "=r"(v.z), "=r"(v.w) : "r"(a)); return v; }
__device__ __forceinline__ void sts128(uint32_t a, uint4 v) { asm volatile("st.shared.v4.u32 [%0], {%1,%2,%3,%4};" ::"r"(a), "r"(v.x), "r"(v.y), "r"(v.z), "r"(v.w) : "memory"); }
__device__ __forceinline__ void sts128f(uint32_t a, float x, float y, float z, float w) { asm volatile("st.shared.v4.f32 [%0], {%1,%2,%3,%4};" ::"r"(a), "f"(x), "f"(y), "f"(z), "f"(w) : "memory"); }
__device__ __forceinline__ uint32_t prmt(uint32_t a, uint32_t b, uint32_t s) { uint32_t r; asm("prmt.b32 %0,%1,%2,%3;" : "=r"(r) : "r"(a), "r"(b), "r"(s)); return r; }
__device__ __forceinline__ uint32_t pack2(float lo, float hi) { uint32_t r; asm("cvt.rn.bf16x2.f32 %0, %1, %2;" : "=r"(r) : "f"(hi), "f"(lo)); return r; }
__device__ __forceinline__ float blo(uint32_t v) { return __uint_as_float(v << 16); }
__device__ __forceinline__ float bhi(uint32_t v) { return __uint_as_float(v & 0xffff0000u); }
__device__ __forceinline__ uint32_t bmul2(uint32_t a, uint32_t b) { uint32_t r; asm("mul.rn.bf16x2 %0,%1,%2;" : "=r"(r) : "r"(a), "r"(b)); return r; }
__device__ __forceinline__ uint32_t badd2(uint32_t a, uint32_t b) { uint32_t r; asm("add.rn.bf16x2 %0,%1,%2;" : "=r"(r) : "r"(a), "r"(b)); return r; }
__device__ __forceinline__ float rbf(float x) { return __bfloat162float(__float2bfloat16_rn(x)); }
__device__ __forceinline__ uint32_t ldcg32(const void* p) { uint32_t v; asm volatile("ld.global.cg.u32 %0, [%1];" : "=r"(v) : "l"(p) : "memory"); return v; }
__device__ __forceinline__ uint4 ldcg128(const void* p) { uint4 v; asm volatile("ld.global.cg.v4.u32 {%0,%1,%2,%3}, [%4];" : "=r"(v.x), "=r"(v.y), "=r"(v.z), "=r"(v.w) : "l"(p) : "memory"); return v; }
__device__ __forceinline__ void stg32_if(void* p, uint32_t v, int on) { asm volatile("{.reg .pred q; setp.ne.b32 q, %2, 0; @q st.global.u32 [%0], %1;}" ::"l"(p), "r"(v), "r"(on) : "memory"); }
__device__ __forceinline__ uint2 ldcg64(const void* p) { uint2 v; asm volatile("ld.global.cg.v2.u32 {%0,%1}, [%2];" : "=r"(v.x), "=r"(v.y) : "l"(p) : "memory"); return v; }
__device__ __forceinline__ float gelu_h(float h) {
    float u = h * fmaf(h * h, 8.0f * 0.044715f * 0.7978845608028654f, 2.0f * 0.7978845608028654f);
    float th;
    asm("tanh.approx.f32 %0, %1;" : "=f"(th) : "f"(u));
    return fmaf(h, th, h);
}
__device__ __forceinline__ float gelu(float x) { return gelu_h(0.5f * x); }
__device__ __forceinline__ float half_rstd(float sum, float sq) {
    float mean = sum * (1.0f / D_), inv;
    asm("rsqrt.approx.ftz.f32 %0, %1;" : "=f"(inv) : "f"(fmaxf(fmaf(-mean, mean, fmaf(sq, 1.0f / D_, 1e-5f)), 1e-5f)));
    return 0.5f * inv;
}
__device__ __forceinline__ uint32_t bsub2(uint32_t a, uint32_t b) { uint32_t r; asm("sub.rn.bf16x2 %0,%1,%2;" : "=r"(r) : "r"(a), "r"(b)); return r; }
__device__ __forceinline__ uint32_t bfma2(uint32_t a, uint32_t b, uint32_t c) { uint32_t r; asm("fma.rn.bf16x2 %0,%1,%2,%3;" : "=r"(r) : "r"(a), "r"(b), "r"(c)); return r; }
__device__ __forceinline__ uint32_t gelu2_h(uint32_t h) {
    uint32_t u = bmul2(h, bfma2(bmul2(h, h), 0x3e923e92u, 0x3fcc3fccu)), th;
    asm("tanh.approx.bf16x2 %0, %1;" : "=r"(th) : "r"(u));
    return bfma2(h, th, h);
}
struct RowSum { float s = 0.f, q = 0.f, s_ = 0.f, q_ = 0.f;
    __device__ __forceinline__ void add(uint32_t v) { float a = blo(v), b = bhi(v); s += a; s_ += b; q = fmaf(a, a, q); q_ = fmaf(b, b, q_); } };
template <int I0>
__device__ __forceinline__ uint3 row_stats(const uint32_t* v, int lane, RowSum r0 = RowSum()) {
#pragma unroll
    for (int i = I0; i < 10; i++) r0.add(v[i]);
    float s = r0.s + r0.s_, q = r0.q + r0.q_;
    {
        float t = __shfl_xor_sync(0xffffffffu, (lane & 16) ? s : q, 16);
        t += (lane & 16) ? q : s;
#pragma unroll
        for (int m = 8; m; m >>= 1) t += __shfl_xor_sync(0xffffffffu, t, m);
        float o = __shfl_xor_sync(0xffffffffu, t, 16);
        s = (lane & 16) ? o : t; q = (lane & 16) ? t : o;
    }
    float mean = s * (1.0f / D_), inv;
    asm("rsqrt.approx.ftz.f32 %0, %1;" : "=f"(inv) : "f"(fmaxf(fmaf(-mean, mean, fmaf(q, 1.0f / D_, 1e-5f)), 1e-5f)));
    uint3 r;
    r.x = pack2(mean, mean);
    r.y = pack2(inv, inv);
    inv -= blo(r.y);
    r.z = pack2(inv, inv);
    return r;
}
__device__ __forceinline__ uint32_t ln_apply(uint32_t x, uint32_t m, uint32_t hi, uint32_t lo) {
    uint32_t xc = bsub2(x, m);
    return bmul2(xc, hi);
}

struct AFrag { uint32_t m, a, b, c, d; };
__device__ __forceinline__ AFrag ldA(uint32_t a) { AFrag f; f.m = lds32(a - 16); f.a = lds32(a); f.b = lds32(a + 16); f.c = lds32(a + 32); f.d = lds32(a + 48); return f; }
template <int N, int M> __device__ __forceinline__ void conv_pair(float* d, const AFrag& f, uint32_t descU) {
    WgRs<N>::template run<8 * M, desc_hi(128, 0), M ? 1 : 0>(d, f.a, f.b, f.m, f.a, descU);
    WgRs<N>::template run<8 * M + 1, desc_hi(128, 0), 1>(d, f.c, f.d, f.b, f.c, descU);
}
template <int Q> __device__ __forceinline__ void conv_put(float* d, uint32_t r0) {
    sts64(r0 + Q * 32, pack2(d[4 * Q + 1], d[4 * Q + 3]), pack2(d[4 * Q], d[4 * Q + 2]));
}
template <int M> __device__ __forceinline__ void conv_two(float* d, AFrag f0, AFrag f1, uint32_t kaddr, uint32_t descU, uint32_t r0, bool handoff) {
    constexpr int N = M < 14 ? 128 - 8 * M : 32;
    wg_fence();
    conv_pair<N, M>(d, f0, descU);
    wg_commit();
    if constexpr (M > 0) f1 = ldA(kaddr + 256 * (M + 1));
    wg_fence();
    conv_pair<N, M + 1>(d, f1, descU);
    wg_commit();
    if (STAG && M == STAG && handoff) bar_arrive(12, 256);
    if constexpr (M < 14) {
        if constexpr (M > 0) { conv_put<17 - M>(d, r0); conv_put<16 - M>(d, r0); }
        wg_wait<1>();
        f0 = ldA(kaddr + 256 * (M + 2));
        if constexpr (M < 12) wg_wait<0>();
        conv_two<M + 2>(d, f0, f1, kaddr, descU, r0, handoff);
    } else {
        wg_wait<0>();
        conv_put<3>(d, r0); conv_put<2>(d, r0); conv_put<1>(d, r0); conv_put<0>(d, r0);
    }
}
template <int N, bool ASWZ, int SC0>
__device__ __forceinline__ void gemm_issue(float* acc, uint32_t bars, int sa, int pa, int sw, int pw, uint32_t da0, uint32_t db0) {
    mbar_wait(bars + (BAR_FB + sw) * 8, pw);
    mbar_wait(bars + (BAR_FA + sa) * 8, pa);
    const uint32_t da = da0 + sa * (SLOT >> 4), db = db0 + sw * (SLOT >> 4);
    constexpr int AK = ASWZ ? 2 : 256, AH = ASWZ ? desc_hi(1024, 1) : desc_hi(128, 0), BH = desc_hi(1024, 1);
    wg_fence();
    WgSs<N>::template run<0, AH, 0, BH, SC0>(acc, da, db);
    WgSs<N>::template run<AK, AH, 128, BH, 1>(acc, da, db);
    WgSs<N>::template run<2 * AK, AH, 256, BH, 1>(acc, da, db);
    WgSs<N>::template run<3 * AK, AH, 384, BH, 1>(acc, da, db);
    wg_commit();
}
template <int N, bool ASWZ, int NKB, int RELB, bool ZERO>
__device__ __forceinline__ void gemm_loop(float* acc, uint32_t sb, int half, int ia0, int ib0, int rela, int wait_bar, int order_bar, int tsid) {
    int sa = ia0 % NA, pa = (ia0 / NA) & 1, sw = ib0 % NB, pw = (ib0 / NB) & 1;
    const uint32_t bars = sb + SM_BAR;
    const int t = threadIdx.x & 127;
    uint32_t ebar = mapa(bars + (t < 2 ? BAR_EB : BAR_EA) * 8, (t < 2 && lds32(sb + SM_GV + 516)) ? t : blockIdx.x & 1);
    const int nrel = t < 2 ? RELB : t == 2 ? rela : 0;
    const uint32_t da0 = ASWZ ? desc_lo(sb + SM_RA + half * 8192, 16) : desc_lo(sb + SM_RA + half * 1024, 2048), db0 = desc_lo(sb + SM_RB, 8192);
    asm volatile("" : "+r"(ebar));
    if (wait_bar) bar_sync(wait_bar, 512);
    gemm_issue<N, ASWZ, ZERO ? 0 : 1>(acc, bars, sa, pa, sw, pw, da0, db0);
    if ((threadIdx.x & 255) == 0) TS(tsid);
#pragma unroll 1
    for (int kb = 1; kb < NKB; kb++) {
        const int prev = t < 2 ? sw : sa;
        if (++sa == NA) { sa = 0; pa ^= 1; }
        if (++sw == NB) { sw = 0; pw ^= 1; }
        gemm_issue<N, ASWZ, 1>(acc, bars, sa, pa, sw, pw, da0, db0);
        if (order_bar && kb == NKB - 1) bar_arrive(order_bar, 512);
        wg_wait<1>();
        if (kb <= nrel) mbar_arrive_cl(ebar + prev * 8);
    }
    wg_wait<0>();
    if (nrel == NKB) mbar_arrive_cl(ebar + (t < 2 ? sw : sa) * 8);
    reg_fence<N / 2>(acc);
    if ((threadIdx.x & 255) == 0) TS(tsid + 1);
}

template <int PART>
__device__ __forceinline__ void gemm3(uint32_t sb, int rb, int j, int half, int row, int c, unsigned ones) {
    constexpr int N = 64 + (PART ? RB3 : RA3), NQ = N / 8;
    constexpr int HO = PART ? HO_B : HO_A;
    float acc[N / 2];
    float2 cr[NQ];
    if (PART) {
        gemm_loop<N, false, 1, 1, true>(acc, sb, half, 20, 20, 0, 0, 0, 50);
        bar_arrive(9, 512);
    }
    mbar_wait(sb + SM_BAR + BAR_CS * 8, 0);
    const uint32_t csa = sb + SM_CS + PART * (256 + 4 * RA3) + 8 * c;
#pragma unroll
    for (int q = 0; q < NQ; q++) if (q < CSP) cr[q] = lds64f(csa + 32 * q);
    uint4 rp;
    if (PART) {
        mbar_wait(sb + SM_BAR + BAR_G * 8, 0);
        const float2* sp = &g_st[(rb * 8 + 2 * c) * 128 + row];
        const uint2 s0 = ldcg64(sp), s1 = ldcg64(sp + 128), s2 = ldcg64(sp + 8), s3 = ldcg64(sp + 136);
        float a0 = __uint_as_float(s0.x) + __uint_as_float(s1.x), b0 = __uint_as_float(s0.y) + __uint_as_float(s1.y);
        float a1 = __uint_as_float(s2.x) + __uint_as_float(s3.x), b1 = __uint_as_float(s2.y) + __uint_as_float(s3.y);
#pragma unroll
        for (int m = 1; m <= 2; m <<= 1) {
            a0 += __shfl_xor_sync(0xffffffffu, a0, m); b0 += __shfl_xor_sync(0xffffffffu, b0, m);
            a1 += __shfl_xor_sync(0xffffffffu, a1, m); b1 += __shfl_xor_sync(0xffffffffu, b1, m);
        }
        const float inv0 = half_rstd(a0, b0), inv1 = half_rstd(a1, b1);
        rp = make_uint4(PGELU ? pack2(inv0, inv0) : __float_as_uint(inv0), __float_as_uint(a0 * (-1.0f / D_)),
                        PGELU ? pack2(inv1, inv1) : __float_as_uint(inv1), __float_as_uint(a1 * (-1.0f / D_)));
        if (c == 0) sts128(sb + SM_RP + ((threadIdx.x & 255) >> 2) * 16, rp);
        bar_arrive(13, 512);
    }
    gemm_loop<N, false, 10 - PART, 10 - PART, !PART>(acc, sb, half, 20 + (10 - NA) * PART, 21 + 10 * PART, PART ? 9 : 10 - NA, 9 + PART, HO < 0 ? 10 + PART : 0, 46 + 2 * PART);
    if ((threadIdx.x & 255) == 0) mbar_expect(sb + SM_BAR + BAR_ME * 8, 0);
    if (!PART) {
        bar_sync(13, 512);
        rp = lds128(sb + SM_RP + ((threadIdx.x & 255) >> 2) * 16);
    }
    const float nb0 = __uint_as_float(rp.y), nb1 = __uint_as_float(rp.w);
    const uint32_t own = sb + SM_RA + ((39 - NA) % NA) * SLOT + row * 16 + c * 4;
    if (PART && OWNG) mbar_wait(sb + SM_BAR + (BAR_FA + (39 - NA) % NA) * 8, ((39 - NA) / NA) & 1);
    uint32_t* dst = reinterpret_cast<uint32_t*>(g_g) + (rb * 216 + HB0 / 8 * PART + 8 * j) * 512 + row * 4 + c;
    auto act = [&](int q, int r) {
        const float nb = r ? nb1 : nb0;
        const uint32_t inv = r ? rp.z : rp.x;
        const float t0 = fmaf(nb, cr[q].x, acc[4 * q + 2 * r]), t1 = fmaf(nb, cr[q].y, acc[4 * q + 2 * r + 1]);
        return gelu2_h(bmul2(pack2(t0, t1), inv));
    };
    uint32_t* dst1 = dst + (56 - (16 - NQ) * j) * 512;
#pragma unroll
    for (int k = 0; k < NQ; k += CH3) {
        if (k == HO) bar_arrive(10 + PART, 512);
        CHUNK(k) {
#pragma unroll
            for (int q = k; q < k + CH3 && q < NQ; q++) {
                if (q + CSP < NQ) cr[q + CSP] = lds64f(csa + 32 * (q + CSP));
                const uint32_t u = act(q, 0), v = act(q, 1);
                (q < 8 ? dst : dst1)[q * 512] = u;
                (q < 8 ? dst : dst1)[q * 512 + 32] = v;
                if (PART && OWNG && q < 8) { sts32(own + q * 2048, u); sts32(own + q * 2048 + 128, v); }
            }
            if (PART && OWNG && k < 8 && k + CH3 >= 8) fence_async_smem();
        }
    }
    bar_arrive(1 + PART, 288);
    if (HO >= NQ) bar_arrive(10 + PART, 512);
}

template <int NS, int BASE, int BF, int BE> struct Ring {
    uint32_t sb, st, ph;
    __device__ __forceinline__ uint32_t acquire(uint32_t bytes) {
        mbar_wait(sb + SM_BAR + BE * 8 + st * 8, ph);
        uint32_t fb = sb + SM_BAR + BF * 8 + st * 8;
        mbar_expect(fb, bytes);
        return fb;
    }
    __device__ __forceinline__ uint32_t slot() { return sb + BASE + st * SLOT; }
    __device__ __forceinline__ void next() { if (++st == NS) { st = 0; ph ^= 1; } }
    __device__ __forceinline__ void run2d(const CUtensorMap* m, int c1) {
#pragma unroll 1
        for (int c0 = 64; c0 < D_; c0 += 64) {
            uint32_t fb = acquire(SLOT);
            tma2d(slot(), m, c0, c1, fb);
            next();
        }
    }
    static __device__ __forceinline__ int korder(int i, int own) { return i == 0 ? own : i > own ? i : i - 1; }
    __device__ __forceinline__ void runw(bool paired, int rk, const CUtensorMap* ma, const CUtensorMap* mb, int ca, int cb, int i0, int i1, int own, uint32_t bytes, int gate_at, uint32_t gate) {
        if (paired) {
            const CUtensorMap* m = rk ? mb : ma;
            const int c0 = rk ? cb : ca;
#pragma unroll 1
            for (int i = i0; i < i1; i++) {
                const int c1 = korder(i, own) * 64;
                if (i == gate_at) mbar_wait(gate, 0);
                uint32_t fb = acquire(bytes);
                tma2d_mc(slot() + 8192 * rk, m, c0, c1, fb);
                next();
            }
        } else {
#pragma unroll 1
            for (int i = i0; i < i1; i++) {
                const int c1 = korder(i, own) * 64;
                uint32_t fb = acquire(bytes);
                tma2d(slot(), ma, ca, c1, fb);
                tma2d(slot() + 8192, mb, cb, c1, fb);
                next();
            }
        }
    }
    __device__ __forceinline__ void run1d(const char* src, int i0, int i1, int own) {
#pragma unroll 1
        for (int i = i0; i < i1; i++) {
            const char* s = src + korder(i, own) * SLOT;
            uint32_t fb = acquire(SLOT);
            bulk_g2s(slot(), s, SLOT, fb);
            next();
        }
    }
};

__global__ void __cluster_dims__(2, 1, 1) __launch_bounds__(NTHREADS, 1) fused_kernel(const Params p, const __grid_constant__ Maps maps) {
    extern __shared__ __align__(1024) unsigned char smem_raw[];
    const uint32_t sb = (smem_u32(smem_raw) + 1023u) & ~1023u;
#pragma unroll
    for (int i = 0; i < SEED; i++) asm volatile("{.reg .b32 t; mov.u32 t, %laneid;}");
    const uint32_t bars = sb + SM_BAR;
    const int tid = threadIdx.x, lane = tid & 31;
    unsigned smid;
    asm volatile("mov.u32 %0, %%smid;" : "=r"(smid));
    const bool spare = (smid >> 2) == 30;
    const int cta = smid < 120 ? smid : smid - 4;
    const int pg = cta >> 4, pi = cta & 15;
    auto chan = [&](int cc) { return GE ? (cc < 3 ? 3 * cta + cc : 381 + 2 * cta + cc) : 80 * pg + (cc < 3 ? 3 * pi + cc : 45 + 2 * pi + cc); };
    const int hb = tid >= 320;
    unsigned ep0 = 0;
    if (!spare) {
        const unsigned t = tid - 320 * hb, r32 = t / 10u, cc = t - r32 * 10u, row = r32 + 64 * hb;
        const unsigned go = (unsigned)(pi * 128 * 1280) + row * 1280u + cc * 16u + (!GE ? pg * 160 : cc < 6 ? pg * 96 : 672 + pg * 64);
        const uint32_t so = sb + (row >> 4) * 32u + row * 160u + cc * 16u;
        const char* kb = (const char*)p.k + go;
        const char* vb = (const char*)p.v + go;
        if (hb) {
            if (tid < 328) {
                const char* a = !GE ? (lane < 5 ? (const char*)p.shift + pg * 640 + lane * 128 : (const char*)p.ssmD + pg * 160 + (lane - 5) * 64)
                              : lane < 5 ? (const char*)p.shift + lane * 128 + (lane < 3 ? pg * 384 : 2688 + pg * 256) : (const char*)(p.ssmD + chan(2 * lane - 10));
                asm volatile("prefetch.global.L2 [%0];" ::"l"(a));
            }
            if (tid >= 640 - NBARS) {
                const int i = 639 - tid;
                mbar_init(bars + i * 8, (i >= BAR_EB && i < BAR_K) ? 4 : ((i >= BAR_EA && i < BAR_EB) || i == (TB1 ? BAR_XD : BAR_XY)) ? 2 : 1);
                asm volatile("fence.mbarrier_init.release.cluster;" ::: "memory");
            }
            bar_arrive(14, 640);
            if (tid >= 512) asm volatile("ld.volatile.global.u32 %0, [%1];" : "=r"(ep0) : "l"(p.epoch + smid) : "memory");
            if (B_DELAY) spin(B_DELAY);
        }
        cpasync16(so + SM_PK + 2592, kb, 16);
        cpasync16(so + SM_PV, vb, 16);
        cpasync16(so + SM_PK + 3 * 2592, kb + 32 * 1280, 16);
        cpasync16(so + SM_PV + 2 * 2592, vb + 32 * 1280, 16);
        if (tid < 30) cpasync16(so + SM_PK + 13 * 160, pi ? kb - 3 * 1280 : kb, pi ? 16 : 0);
        asm volatile("cp.async.commit_group;" ::: "memory");
    }
    const int warp = __shfl_sync(0xffffffffu, tid >> 5, 0);
    const int wg = warp >> 2, wq = warp & 3;

    if (spare) {
        const int sp = smid & 3;
        const unsigned ep1 = *(volatile unsigned*)&p.epoch[smid] + 1;
        if (tid == 32) { sts32(sb + SM_GV + 512, smid); asm volatile("fence.release.sync_restrict::shared::cta.cluster;" ::: "memory"); }
        asm volatile("barrier.cluster.arrive.relaxed.aligned;" ::: "memory");
        asm volatile("barrier.cluster.wait.aligned;" ::: "memory");
        if (tid == 0) {
            for (int i = 0; i < 4; i++) mbar_init(bars + i * 8, 1);
            asm volatile("fence.mbarrier_init.release.cluster;" ::: "memory");
        }
        if (warp == 0) { if (lane < 8) flag_wait(FL_P + lane, ep1 * 16); __syncwarp(); if (SPD) spin(SPD); }
        __syncthreads();
        const int cq = tid % 54, rg = tid / 54;
        float a[8];
#pragma unroll
        for (int i = 0; i < 8; i++) a[i] = 0.f;
#pragma unroll 1
        for (int it = -4; it < 10; it++) {
            const uint32_t st = sb + (it & 3) * 55296, fb = bars + (it & 3) * 8;
            if (it >= 0) {
                mbar_wait(fb, (it >> 2) & 1);
                if (tid < 432) {
#pragma unroll 2
                    for (int i = 0; i < 8; i++) {
                        uint4 w = lds128(st + (cq >= 27 ? 27648 - 432 : 0) + (rg * 8 + i) * 432 + cq * 16);
                        a[0] += blo(w.x); a[1] += bhi(w.x); a[2] += blo(w.y); a[3] += bhi(w.y);
                        a[4] += blo(w.z); a[5] += bhi(w.z); a[6] += blo(w.w); a[7] += bhi(w.w);
                    }
                }
                __syncthreads();
            }
            if (it < 6 && warp == 19 && elect()) {
                mbar_expect(fb, 55296);
                tma2d(st, &maps.w3s, sp * 432, (it + 4) * 64, fb);
                tma2d(st + 27648, &maps.w3s, sp * 432 + 216, (it + 4) * 64, fb);
            }
        }
        if (warp == 19 && elect()) {
#pragma unroll 1
            for (int i = 0; i < 27; i++) bulk_prefetch((const char*)p.w4 + sp * 552960 + i * 20480, 20480);
        }
        if (tid < 432) {
            sts128f(sb + rg * 1728 + cq * 32, a[0], a[1], a[2], a[3]);
            sts128f(sb + rg * 1728 + cq * 32 + 16, a[4], a[5], a[6], a[7]);
        }
        __syncthreads();
        if (tid < 432) {
            float s = 0.f;
#pragma unroll
            for (int i = 0; i < 8; i++) s += __uint_as_float(lds32(sb + i * 1728 + tid * 4));
            g_cs[sp * 432 + tid] = s;
        }
        __syncthreads();
        if (tid == 0) { flag_release(FL_CS); p.epoch[smid] = ep1; TS(0); }
        if (warp == 0) TSFLUSH();
        return;
    }

    int gpc, idx;
    if (smid < 64) { gpc = (smid & 15) >> 1; idx = (smid >> 4) * 2 + (smid & 1); }
    else if (smid < 120) { int t = smid - 64; gpc = 1 + (t % 14) / 2; idx = 8 + (t / 14) * 2 + (smid & 1); }
    else { gpc = 0; idx = 8 + (smid - 124); }
    const int rb = 2 * gpc + (idx & 1), j = idx >> 1;
    const int g = lane >> 2, c = lane & 3;
    const int cm = 160 * (j >> 1) + 64 * (j & 1) + ((j & 2) ? 32 : 0), cr = 160 * (j >> 1) + 16 * (j & 1) + ((j & 2) ? 0 : 128);

    {
        if (warp == 5) TSW(61);
        const int w10 = warp - 10 * hb, h = w10 >= 5;
        const int pr = (w10 - 5 * h) * 8 + (lane >> 2), blk = 4 * hb + (lane & 3);
        const int ch = 2 * pr + (!GE ? 80 * pg : pr < 24 ? 48 * pg : 336 + 32 * pg);
        const uint4 sw = __ldg(reinterpret_cast<const uint4*>(p.shift + ch * 4));
        uint32_t dv = 0;
        if (warp == 9 && lane < 5) dv = __bfloat16_as_ushort(p.ssmD[chan(lane)]);
        if (tid == 512) { sts32(sb + SM_GV + 512, smid); asm volatile("fence.release.sync_restrict::shared::cta.cluster;" ::: "memory"); }
        asm volatile("barrier.cluster.arrive.relaxed.aligned;" ::: "memory");
        if (warp == 11 && lane < 13) prefetch_map(&maps.hn + lane);
        if (wg < 4) {
            const int t = tid & 127, cc = (wg == 3 && t >= 64) ? 4 : wg;
            if (t < 64 || wg == 3) sts128(sb + sm_u(cc) + ((t >> 5) & 1) * U_PLANE + 2048 + lane * 16, make_uint4(0, 0, 0, 0));
            if ((t & 63) < 4 && (t < 64 || wg == 3)) sts128(sb + sm_k(cc) + ((t >> 1) & 1) * 4160 + (t & 1) * 16, make_uint4(0, 0, 0, 0));
        }
        if (warp == 9 && lane < 5) sts32(sb + SM_GV + 520 + lane * 4, dv << 16);
        asm volatile("cp.async.wait_group 0;" ::: "memory");
        if (!hb) bar_arrive(12, 640);
        bar_sync(hb ? 12 : 14, 640);
        if (warp == 9) {
            if (SSM_DELAY) spin(SSM_DELAY);
            if (elect()) {
#pragma unroll
                for (int i = 0; i < SSM_N; i++) {
                    mbar_expect(bars + (BAR_K + i) * 8, 4096);
                    bulk_g2s(sb + sm_k(i) + 32, p.ssmk + (size_t)(chan(i)) * S_, 4096, bars + (BAR_K + i) * 8);
                }
            }
        }
        const uint32_t w0 = prmt(sw.x, sw.z, 0x5410), w1 = prmt(sw.x, sw.z, 0x7632), w2 = prmt(sw.y, sw.w, 0x5410), w3 = prmt(sw.y, sw.w, 0x7632);
        const uint32_t ka = sb + SM_PK + 2592 + blk * 2592 + h * 1280 + pr * 4;
        const uint32_t va = sb + SM_PV + blk * 2592 + h * 1280 + pr * 4;
        uint32_t kk[11], kv[8];
#pragma unroll
        for (int i = 0; i < 11; i++) kk[i] = lds32(ka + (i - 3) * 160 - ((i < 3 && h == 0) ? 32 : 0));
#pragma unroll
        for (int i = 0; i < 8; i++) {
            uint32_t t = badd2(badd2(badd2(bmul2(kk[i], w3), bmul2(kk[i + 1], w2)), bmul2(kk[i + 2], w1)), bmul2(kk[i + 3], w0));
            kv[i] = bmul2(t, lds32(va + i * 160));
        }
        uint4 o0, o1;
        o0.x = prmt(kv[1], kv[0], 0x5410); o0.y = prmt(kv[3], kv[2], 0x5410); o0.z = prmt(kv[5], kv[4], 0x5410); o0.w = prmt(kv[7], kv[6], 0x5410);
        o1.x = prmt(kv[1], kv[0], 0x7632); o1.y = prmt(kv[3], kv[2], 0x7632); o1.z = prmt(kv[5], kv[4], 0x7632); o1.w = prmt(kv[7], kv[6], 0x7632);
        uint4* dst = reinterpret_cast<uint4*>(g_kvT) + ch * 256 + h * 128 + (127 - (8 * pi + blk));
        dst[0] = o0;
        dst[256] = o1;
    }

    const int rho = 8 * rb + j;

    if (wg == 4) {
        asm volatile("setmaxnreg.dec.sync.aligned.u32 32;");
        const unsigned ep1 = __shfl_sync(0xffffffffu, ep0, 0) + 1;
        if (wq == 0) {
            bar_sync(13, 640);
            TSW(39);
            if (lane == 0) flag_release(FL_P + pg);
            __syncwarp();
            TSW(2);
            if (lane < 5) mbar_expect(bars + (BAR_U + lane) * 8, 4096);
            flag_wait(FL_P + pg, ep1 * 16);
            fence_async_global();
            TSW(3);
            if (elect()) {
#pragma unroll
                for (int i = 0; i < 5; i++) {
                    const char* us = (const char*)g_kvT + (size_t)(chan(i)) * 4096;
                    bulk_g2s(sb + sm_u(i), us, 2048, bars + (BAR_U + i) * 8);
                    bulk_g2s(sb + sm_u(i) + U_PLANE, us + 2048, 2048, bars + (BAR_U + i) * 8);
                }
            }
            __syncwarp();
            if (WMG == 1) { if (lane < 8) flag_wait(FL_P + lane, ep1 * 16); __syncwarp(); }
            if (WMD) spin(WMD);
            if (elect()) {
#pragma unroll
                for (int i = SSM_N; i < 5; i++) {
                    mbar_expect(bars + (BAR_K + i) * 8, 4096);
                    bulk_g2s(sb + sm_k(i) + 32, p.ssmk + (size_t)(chan(i)) * S_, 4096, bars + (BAR_K + i) * 8);
                }
                if (WMD2) spin(WMD2);
                if (cta < 120) {
                    mbar_expect(bars + BAR_WM0 * 8, 3 * 8192);
                    mbar_expect(bars + BAR_WM * 8, 2 * 8192);
#pragma unroll 1
                    for (int i = 0; i < 5; i++) tma2d(sb + SM_WM + i * 8192, &maps.wm, cta * 32, i * 128, bars + (i < 3 ? BAR_WM0 : BAR_WM) * 8);
                }
                mbar_wait(bars + (cta < 120 ? BAR_WM0 : BAR_K + 4) * 8, 0);
                bulk_prefetch((const char*)p.q + cta * 20480, 20480);
                bulk_prefetch((const char*)p.w1 + cta * 6400, 6400);
                bulk_prefetch((const char*)p.w2 + cta * 6400, 6400);
            }
            __syncwarp();
        } else {
            bar_arrive(13, 640);
        }
        asm volatile("barrier.cluster.wait.aligned;" ::: "memory");
        uint32_t peer;
        asm volatile("ld.shared::cluster.u32 %0, [%1];" : "=r"(peer) : "r"(mapa(sb + SM_GV + 512, (blockIdx.x & 1) ^ 1)) : "memory");
        const bool paired = peer == (smid ^ 1) && !FORCE_UNPAIRED;
        if (tid == 639) sts32(sb + SM_GV + 516, paired);
        if (cta < 120) {
            float d[4];
            if (tid >= 544 && tid < 624) {
                const int t = tid - 544;
                mbar_wait(bars + BAR_U * 8, 0);
                uint4 cv = __ldg(reinterpret_cast<const uint4*>(p.c) + t);
                auto silu2 = [](uint32_t v) { float a = blo(v), b = bhi(v); return pack2(__fdividef(a, 1.0f + __expf(-a)), __fdividef(b, 1.0f + __expf(-b))); };
#pragma unroll 1
                for (int i = 0; i < 4; i++) { const uint32_t r = silu2(cv.x); cv.x = cv.y; cv.y = cv.z; cv.z = cv.w; cv.w = r; }
                sts128(sb + SM_Y + (t % 40) * 32 + (t / 40) * 16, cv);
                fence_async_smem();
            }
            bar_sync(5, 128);
            mbar_wait(bars + BAR_WM0 * 8, 0);
            mbar_wait(bars + BAR_WM * 8, 0);
            if (wq == 3) TSW(56);
            const uint32_t da = desc_lo(sb + SM_WM, 20480), db = desc_lo(sb + SM_Y, 32);
#pragma unroll 1
            for (int k0 = 0; k0 < 20; k0 += 4) {
                wg_fence();
#pragma unroll
                for (int k = k0; k < k0 + 4; k++) asm volatile("{.reg .pred p; .reg .b32 l,m; .reg .b64 da,db; setp.ne.b32 p,%10,0; add.u32 l,%4,%6; mov.b64 da,{l,%8}; add.u32 m,%5,%7; mov.b64 db,{m,%9};"
                             " wgmma.mma_async.sync.aligned.m64n8k16.f32.bf16.bf16 {%0,%1,%2,%3},da,db,p,1,1,1,0;}"
                             : "+f"(d[0]), "+f"(d[1]), "+f"(d[2]), "+f"(d[3])
                             : "r"(da), "r"(db), "r"(64 * k), "r"(4 * k), "n"(desc_hi(512, 2u)), "n"(desc_hi(128, 0)), "r"(k));
                wg_commit();
            }
            wg_wait<0>();
            reg_fence<4>(d);
            if (c == 0) {
                sts32(sb + SM_GV + (16 * wq + g) * 4, __float_as_uint(wq < 2 ? d[0] : d[1]));
                sts32(sb + SM_GV + (16 * wq + g + 8) * 4, __float_as_uint(wq < 2 ? d[2] : d[3]));
            }
            bar_sync(5, 128);
            if (wq == 2) {
                g_mod[cta * 32 + lane] = __float2bfloat16_rn(__uint_as_float(lds32(sb + SM_GV + lane * 4)) + __uint_as_float(lds32(sb + SM_GV + 128 + lane * 4)));
            }
        }
        if (wq == 2) {
            bar_sync(9, 320);
            if (lane == 0) { flag_release(FL_M); mbar_expect(bars + BAR_MR * 8, 0); }
            __syncwarp();
            TSW(4);
            flag_wait(FL_M, ep1 * 128);
            fence_async_global();
            if (elect()) {
                mbar_expect(bars + BAR_M * 8, 7680);
                bulk_g2s(sb + SM_MOD, g_mod, 7680, bars + BAR_M * 8);
                mbar_wait(bars + BAR_CD * 8, 0);
                mbar_expect(bars + BAR_Y * 8, 12288);
                if (GE) bulk_g2s(sb + SM_Y, g_yv + rho * 5120, 12288, bars + BAR_Y * 8);
                else
#pragma unroll 1
                for (int i = 0; i < 8; i++) bulk_g2s(sb + SM_Y + i * 2560, g_yv + rho * 5120 + i * 640, 1536, bars + BAR_Y * 8);
            }
            __syncwarp();
            TSW(60);
            bar_sync(8, 576);  if (lane == 0) { flag_release(FL_R + rb); TS(23); }  __syncwarp();
            bar_sync(15, 288); if (lane == 0) { flag_release(FL_B1 + rb); TS(27); } __syncwarp();
            bar_sync(6, 288);  if (lane == 0) { flag_release(FL_B2 + rb); TS(31); } __syncwarp();
#pragma unroll 1
            for (int i = 0; i < 3; i++) { bar_sync(i ? i : 8, 288); if (lane == 0) { TS(53 + (i + 2) % 3); flag_release(FL_G + 16 * i + rb); TS(57 + (i + 2) % 3); } __syncwarp(); }
            if (lane == 0) p.epoch[smid] = ep1;
            return;
        }
        if (wq == 1) {
            bar_sync(9, 320);
            if (WAFT) mbar_wait(bars + BAR_MR * 8, 0);
            if (lane < 4 * NB) mbar_arrive_cl(mapa(bars + (BAR_EB + (lane >> 2)) * 8, paired ? lane & 1 : blockIdx.x & 1));
        }
        if (wq == 3) {
            bar_sync(7, 544);
            if (lane == 0) { flag_release(FL_C); mbar_expect(bars + BAR_CD * 8, 0); TS(20); }
            __syncwarp();
            if (lane == 0) mbar_expect(bars + BAR_Y2 * 8, 8192);
            flag_wait(FL_C, ep1 * 128);
            fence_async_global();
            TSW(21);
            if (elect()) {
                if (GE) bulk_g2s(sb + SM_Y + 12288, g_yv + rho * 5120 + 3072, 8192, bars + BAR_Y2 * 8);
                else
#pragma unroll
                for (int i = 0; i < 8; i++) bulk_g2s(sb + SM_Y + i * 2560 + 1536, g_yv + rho * 5120 + i * 640 + 384, 1024, bars + BAR_Y2 * 8);
            }
            __syncwarp();
        }
        if (wq == 3) {
            mbar_wait(bars + BAR_Y2 * 8, 0);
            if (elect()) {
                mbar_expect(bars + BAR_XY * 8, 20480);
#pragma unroll 1
                for (int i = 0; i < 8; i++) {
                    bulk_g2s(sb + SM_YT + i * 2560, g_yv + (8 * rb + i) * 5120 + cm * 8, 2048, bars + BAR_XY * 8);
                    bulk_g2s(sb + SM_YT + i * 2560 + 2048, g_yv + (8 * rb + i) * 5120 + cr * 8, 512, bars + BAR_XY * 8);
                }
            }
            __syncwarp();
            bar_sync(8, 576);
            mbar_wait_warm(bars + BAR_FA * 8, 0);
            mbar_wait(bars + BAR_ME * 8, 0);
            mbar_wait_warm(bars + (BAR_FA + 11 % NA) * 8, (11 / NA) & 1);
            flag_wait(FL_CS, ep1 * 4);
            fence_async_global();
            if (elect()) {
                mbar_expect(bars + BAR_CS * 8, 864);
                bulk_g2s(sb + SM_CS, g_cs + 64 * j, 256, bars + BAR_CS * 8);
                bulk_g2s(sb + SM_CS + 256, g_cs + 512 + RA3 * j, 4 * RA3, bars + BAR_CS * 8);
                bulk_g2s(sb + SM_CS + 256 + 4 * RA3, g_cs + HB0 + 64 * j, 256, bars + BAR_CS * 8);
                bulk_g2s(sb + SM_CS + 512 + 4 * RA3, g_cs + HB0 + 512 + RB3 * j, 4 * RB3, bars + BAR_CS * 8);
            }
            __syncwarp();
            mbar_wait(bars + BAR_ME * 8, 1);
            mbar_wait_warm(bars + (BAR_FA + 21 % NA) * 8, (21 / NA) & 1);
#pragma unroll 1
            for (int i = 0; i < 3; i++) {
                if (i) {
                    mbar_wait(bars + BAR_ME * 8, (i + 1) & 1);
                    for (int n = i; n < NPING; n++) { spin(PING); n += tensor_ping(); }
                }
                flag_wait(FL_G + 16 * i + rb, ep1 * 8);
                if (lane == 0) { mbar_expect(bars + (BAR_G + i) * 8, 0); TS(35 + (i + 2) % 3); }
                __syncwarp();
            }
            return;
        }
        if (elect()) {
            if (wq == 1) {
                Ring<NB, SM_RB, BAR_FB, BAR_EB> r{sb, 0, 0};
#pragma unroll 1
                for (int ph = 0; ph < 7; ph++) {
                    const CUtensorMap* ma = ph == 0 ? &maps.w1a : ph == 1 ? &maps.w2a : ph == 6 ? &maps.w4a : &maps.w3a;
                    const bool b3b = ph == 2 || ph == 4 || ph == 5;
                    r.runw(paired, idx & 1, ma, ma + (b3b ? 2 : 1), ph == 3 ? 64 * j : b3b ? HB0 + 64 * j : cm,
                           ph == 3 ? 512 + RA3 * j : b3b ? HB0 + 512 + RB3 * j : cr, ph == 4 ? 10 - NA : ph == 5 ? 1 : 0,
                           ph == 6 ? 27 : ph == 5 ? 10 - NA : ph == 2 ? 1 : 10, ph == 0 ? 0 : ph == 6 ? OWNG * (HB0 / 64 + j) : cm >> 6,
                           ph == 3 ? 8192 + 128 * RA3 : b3b ? 8192 + 128 * RB3 : 10240,
                           ph == 0 ? GATE0 : ph == 1 ? GATE : ph == 3 ? GATE - 1 : -1, bars + (ph == 0 ? GBAR0 : BAR_ST - (ph == 1)) * 8);
                }
            } else {
                Ring<NA, SM_RA, BAR_FA, BAR_EA> r{sb, 0, TB1};
                if (cta >= 120) mbar_wait(bars + (BAR_K + 4) * 8, 0);
                mbar_expect(bars + BAR_XR * 8, 20480);
                bulk_g2s(sb + SM_XR, p.q + (size_t)rho * 16 * D_, 20480, bars + BAR_XR * 8);
                mbar_wait(bars + BAR_Y2 * 8, 0);
                mbar_expect(bars + BAR_XY * 8, 20480);
                tma2d(sb + SM_XT, &maps.xa, cm, rb * 128, bars + BAR_XY * 8);
                tma2d(sb + SM_XT2, &maps.xb, cr, rb * 128, bars + BAR_XY * 8);
                const int grp = j >> 1;
                const int delta = (grp & 1 ? 1 : -1) * (1 + (grp >> 1));
                const int nb = min(max(rb + (delta > 0 ? 1 : -1), 0), 15);
                uint32_t fb = r.acquire(SLOT), dst = r.slot();
                flag_wait2(FL_R + nb, FL_R + rb, ep1 * 8);
                fence_async_global();
                tma2d(dst, &maps.hn, 0, rb * 128 + delta, fb);
                TS(24);
                r.next();
                r.run2d(&maps.hn, rb * 128 + delta);
#pragma unroll 1
                for (int i = 0; i < 2; i++) {
                    const char* src = (const char*)(i ? g_x1 : g_h1) + (size_t)rb * 163840;
                    r.acquire(0); r.next();
                    if (TB1) mbar_wait(bars + BAR_XD * 8, 0);
                    fb = r.acquire(SLOT); dst = r.slot();
                    const char* src1 = src + (cm == 0 ? SLOT : 0);
                    flag_wait(FL_B1 + 16 * i + rb, ep1 * 8);
                    fence_async_global();
                    bulk_g2s(dst, src1, SLOT, fb);
                    TS(28 + 4 * i);
                    mbar_expect(bars + (BAR_ST - 1 + i) * 8, 0);
                    r.next();
                    r.run1d(src, 2, 10, cm >> 6);
                }
                r.run1d((const char*)g_x1 + (size_t)rb * 163840, 1, 10 - NA, cm >> 6);
                if (OWNG) { r.acquire(0); r.next(); }
#pragma unroll 1
                for (int i = 0; i < 2; i++) {
                    mbar_wait(bars + (BAR_G + 1 + i) * 8, 0); fence_async_global();
                    r.run1d((const char*)g_g + (size_t)rb * 442368, OWNG + HB0 / 64 * i, i ? 27 : OWNG + HB0 / 64, OWNG * (HB0 / 64 + j));
                }
            }
        }
        return;
    }
    bar_arrive(13, 640);
    asm volatile("setmaxnreg.inc.sync.aligned.u32 112;");
    const int rrow = 16 * rho + (warp >> 1) + 8 * (warp & 1);

    fence_async_smem();
    bar_sync(1 + wg, 128);
#pragma unroll 1
    for (int cc = wg; cc < wg + 1 + (wg == 3); cc++) {
        mbar_wait(bars + (BAR_K + cc) * 8, 0);
        if (cc == 2 && wq == 0) TSW(40);
        uint32_t a = sb + sm_k(cc) + 32 + (tid & 127) * 32;
        uint32_t pw = lds32(a - 4);
        uint4 x = lds128(a), y = lds128(a + 16), o;
        if ((tid & 127) == 0) {
            uint16_t k0 = __bfloat16_as_ushort(__float2bfloat16_rn(blo(x.x) + __uint_as_float(lds32(sb + SM_GV + 520 + cc * 4))));
            x.x = (x.x & 0xffff0000u) | k0;
            sts16(a, k0);
        }
        o.x = prmt(pw, x.x, 0x5432); o.y = prmt(x.x, x.y, 0x5432); o.z = prmt(x.y, x.z, 0x5432); o.w = prmt(x.z, x.w, 0x5432);
        sts128(a + 4160, o);
        o.x = prmt(x.w, y.x, 0x5432); o.y = prmt(y.x, y.y, 0x5432); o.z = prmt(y.y, y.z, 0x5432); o.w = prmt(y.z, y.w, 0x5432);
        sts128(a + 4176, o);
    }
    bar_sync(1 + wg, 128);
    if (wg == 3) bar_arrive(11, 256);
#pragma unroll 1
    for (int cc = wg; cc < 5; cc += 3) {
        if (cc == 3 && wg == 0) break;
        if (cc == 4) bar_sync(11, 256);
        const uint32_t kaddr = sb + sm_k(cc) + ((g & 1) ? 32 : 4192) + 4 * ((g >> 1) - c) + 64 * wq;
        const AFrag f0 = ldA(kaddr), f1 = ldA(kaddr + 256);
        if (STAG && cc == 3) bar_sync(12, 256);
        mbar_wait(bars + (BAR_U + cc) * 8, 0);
        if (wq == 0) TSW(5 + cc);
        float d[64];
        conv_two<0>(d, f0, f1, kaddr, desc_lo(sb + sm_u(cc), U_PLANE), sb + sm_red(cc) + wq * 4352 + g * 544 + c * 8, cc == 1);
        if (wq == 0) TSW(10 + cc);
        if (cc == 1) bar_arrive(6, 256);
    }
#pragma unroll 1
    for (int cc = wg == 1 ? 4 : wg;; cc++) {
        if (cc == 1) bar_sync(6, 256); else bar_sync(1 + wg, 128);
        const int ch = chan(cc);
        uint32_t* dst = g_yv + ch * 8 + ((g + (ch >> 2)) & 7) + (126 - 32 * wq - 2 * c) * 5120;
        uint2 v[16];
#pragma unroll
        for (int i = 0; i < 16; i++) v[i] = lds64(sb + sm_red(cc) + g * 544 + wq * 128 + c * 8 + (i >> 2) * 32 + (i & 3) * 4360);
#pragma unroll
        for (int w = 1; w < 4; w++)
            if (wq == 3 && c > 3 - w) v[12 + w] = make_uint2(0, 0);
#pragma unroll
        for (int q = 0; q < 4; q++) {
            const uint2* u = v + 4 * q;
            dst[-8 * q * 5120] = badd2(u[0].x, badd2(u[1].x, badd2(u[2].x, u[3].x)));
            dst[(-8 * q + 1) * 5120] = badd2(u[0].y, badd2(u[1].y, badd2(u[2].y, u[3].y)));
        }
        if (wq == 0) TSW(15 + cc);
        if (cc != 0) break;
    }
    fence_async_smem();
    if (!(wg & 1)) bar_arrive(9, 320);
    bar_arrive(7, 544);

    const uint32_t one2 = 0x3f803f80u;
    const unsigned ones = p.ones;
    {
        uint32_t x[10], a[10], cb[10], sbv[10];
        if (RPRE_WAIT) bar_sync(10, 512);
        mbar_wait(bars + BAR_XR * 8, 0);
#pragma unroll
        for (int i = 0; i < 10; i++) x[i] = lds32(sb + SM_XR + (rrow & 15) * 1280 + lane * 4 + i * 128);
        const uint3 s1 = row_stats<0>(x, lane);
        const int up = lane >> 4, gg = warp >> 1, e = warp & 1;
        const uint32_t ya = sb + SM_Y + lane * 64 + ((gg + (lane >> 1)) & 7) * 4;
        const uint32_t sel = (up ? 0x1054u : 0x5410u) + (e ? 0x2222u : 0u);
        const uint32_t ma = sb + SM_MOD + lane * 4;
        mbar_wait(bars + BAR_M * 8, 0);
        uint32_t pin = 0;
#pragma unroll
        for (int i = 0; i < 10; i++) {
            uint32_t h = bfma2(ln_apply(x[i], s1.x, s1.y, s1.z), badd2(lds32(ma + 1280 + i * 128), one2), lds32(ma + i * 128));
            a[i] = bmul2(h, lds32(ma + 2560 + i * 128));
            sbv[i] = lds32(ma + 3840 + i * 128);
            cb[i] = badd2(lds32(ma + 5120 + i * 128), one2);
            pin ^= a[i] ^ cb[i];
        }
        if (pin & ~ones) sts32(sb + SM_GV, pin);
        if (warp == 4) TSW(52);
        mbar_wait(bars + BAR_Y * 8, 0);
        RowSum part;
#pragma unroll
        for (int i = 0; i < 10; i++) {
            if (i == 6 * GE) {
                if (GE && (__float_as_uint(part.s + part.s_ + part.q + part.q_) & ~ones)) sts32(sb + SM_GV, pin);
                mbar_wait(bars + BAR_Y2 * 8, 0);
                if (warp == 0) TSW(22);
            }
            uint32_t y0 = lds32(ya + i * 2048 + up * 32), y1 = lds32(ya + i * 2048 + (up ^ 1) * 32);
            x[i] = bfma2(a[i], prmt(y0, y1, sel), x[i]);
            if (i < 6 * GE) part.add(x[i]);
        }
        const uint3 s2 = row_stats<6 * GE>(x, lane, part);
#pragma unroll
        for (int i = 0; i < 10; i++) x[i] = bfma2(ln_apply(x[i], s2.x, s2.y, s2.z), cb[i], sbv[i]);
        const uint3 s3 = row_stats<0>(x, lane);
        uint32_t* o = reinterpret_cast<uint32_t*>(g_hn + (size_t)rrow * D_) + lane;
#pragma unroll
        for (int i = 0; i < 10; i++) o[32 * i] = ln_apply(x[i], s3.x, s3.y, s3.z);
        if (lane < 2) g_rs[rrow * 2 + lane] = lane ? make_uint4(s2.x, s2.y, s2.z, 0) : make_uint4(s1.x, s1.y, s1.z, 0);
        if (warp == 0) TSW(34);
        bar_arrive(8, 576);
    }

    const int half = wg & 1;
    const int row = 64 * half + 16 * wq + g;
    const int tw0 = (rb * 80 + (cm >> 3)) * 512 + row * 4 + c, tw1 = (rb * 80 + (cr >> 3) - 8) * 512 + row * 4 + c;
    const uint32_t park = sb + SM_Y + (tid & 255) * 16;
    const uint32_t ms0 = sb + SM_MOD + (cm + 2 * c) * 2, ms1 = sb + SM_MOD + (cr - 64 + 2 * c) * 2;
    if (wg >= 2) {
        {
            float acc[40];
            gemm_loop<80, true, 10, 10, true>(acc, sb, half, 0, 0, 10, 0, 0, 25);
            if (tid == 256) mbar_expect(bars + BAR_ME * 8, 0);
#pragma unroll
            for (int k = 0; k < 10; k += CH) CHUNK(k) {
#pragma unroll
                for (int q = k; q < k + CH && q < 10; q++) {
                    uint32_t* dst = reinterpret_cast<uint32_t*>(g_h1) + (q < 8 ? tw0 : tw1);
                    const uint32_t u = gelu2_h(bmul2(pack2(acc[4 * q], acc[4 * q + 1]), 0x3f003f00u));
                    const uint32_t v = gelu2_h(bmul2(pack2(acc[4 * q + 2], acc[4 * q + 3]), 0x3f003f00u));
                    dst[q * 512] = u;
                    dst[q * 512 + 32] = v;
                    acc[4 * q] = __uint_as_float(u); acc[4 * q + 1] = __uint_as_float(v);
                }
            }
            bar_arrive(15, 288);
            mbar_wait(bars + (BAR_FA + 10 % NA) * 8, (10 / NA) & 1);
#pragma unroll
            for (int q = 0; q < 8; q++) {
                sts32(sb + SM_RA + (10 % NA) * SLOT + q * 2048 + row * 16 + c * 4, __float_as_uint(acc[4 * q]));
                sts32(sb + SM_RA + (10 % NA) * SLOT + q * 2048 + row * 16 + c * 4 + 128, __float_as_uint(acc[4 * q + 1]));
            }
            fence_async_smem();
            bar_arrive(14, 512);
        }
        gemm3<0>(sb, rb, j, half, row, c, ones);
        {
            float acc[40];
            uint32_t gbv[10], base[20];
#pragma unroll
            for (int q = 0; q < 10; q++) gbv[q] = lds32((q < 8 ? ms0 : ms1) + 6400 + q * 16);
#pragma unroll
            for (int q = 0; q < 5; q++) { const uint4 t = lds128(park + q * 4096); base[4 * q] = t.x; base[4 * q + 1] = t.y; base[4 * q + 2] = t.z; base[4 * q + 3] = t.w; }
            gemm_loop<80, false, 27, 27 - NB, true>(acc, sb, half, 39 - NA, 40, 27 - NA, 11, 0, 42);
            auto fin = [&](int q, int r) {
                return bfma2(gbv[q], pack2(acc[4 * q + 2 * r], acc[4 * q + 2 * r + 1]), base[2 * q + r]);
            };
            auto tr4 = [&](uint32_t t0, uint32_t t1, uint32_t t2, uint32_t t3) {
                const bool o1 = c & 1, o2 = c & 2;
                uint32_t a = __shfl_xor_sync(0xffffffffu, o1 ? t0 : t1, 1), b = __shfl_xor_sync(0xffffffffu, o1 ? t2 : t3, 1);
                uint32_t u0 = o1 ? a : t0, u1 = o1 ? t1 : a, u2 = o1 ? b : t2, u3 = o1 ? t3 : b;
                a = __shfl_xor_sync(0xffffffffu, o2 ? u0 : u2, 2); b = __shfl_xor_sync(0xffffffffu, o2 ? u1 : u3, 2);
                return o2 ? make_uint4(a, b, u2, u3) : make_uint4(u0, u1, a, b);
            };
            bf16* go = p.out + (size_t)(rb * 128 + row) * D_;
#pragma unroll
            for (int k = 0; k < 2; k++) CHUNK(k) {
#pragma unroll
                for (int r = 0; r < 2; r++)
                    *reinterpret_cast<uint4*>(go + r * 8 * D_ + cm + 32 * k + 8 * c) = tr4(fin(4 * k, r), fin(4 * k + 1, r), fin(4 * k + 2, r), fin(4 * k + 3, r));
            }
            CHUNK(2) *reinterpret_cast<uint4*>(go + (c >> 1) * 8 * D_ + cr + 8 * (c & 1)) = tr4(fin(8, 0), fin(9, 0), fin(8, 1), fin(9, 1));
            if (tid == 256) TS(44);
            if (warp == 8) TSFLUSH();
        }
    } else {
        {
            float acc[40];
            uint32_t x2[20];
            {
                uint32_t y[20];
                mbar_wait(bars + BAR_XY * 8, 0);
                const uint32_t xa = sb + SM_XT + row * 128 + c * 4, xb = sb + SM_XT2 + row * 32 + c * 4;
                const uint32_t ya = sb + SM_YT + (4 * half + wq) * 2560 + c * 64;
#pragma unroll
                for (int q = 0; q < 10; q++) {
                    const uint32_t a = q < 8 ? xa + ((q ^ g) << 4) : xb + (q - 8) * 16;
                    x2[2 * q] = lds32(a); x2[2 * q + 1] = lds32(a + (q < 8 ? 1024 : 256));
                    const int pos = (g + ((q < 8 ? cm : cr) >> 2) + 2 * q + (c >> 1)) & 7;
                    y[2 * q] = lds32(ya + q * 256 + pos * 4); y[2 * q + 1] = lds32(ya + q * 256 + 32 + pos * 4);
                }
                fence_async_smem();
                bar_sync(1 + wg, 128);
                if ((tid & 127) < NA) mbar_arrive_cl(mapa(bars + (BAR_EA + (tid & 127)) * 8, blockIdx.x & 1));
                mbar_wait(bars + (BAR_FA + 1) * 8, 0);
                const uint4* rp = g_rs + (rb * 128 + row) * 2;
                const uint4 ra = ldcg128(rp), rb2 = ldcg128(rp + 1), rc = ldcg128(rp + 16), rd = ldcg128(rp + 17);
                bar_sync(14, 512);
#pragma unroll
                for (int q = 0; q < 10; q++) {
                    const uint32_t ms = q < 8 ? ms0 : ms1;
                    const uint32_t sa = lds32(ms + 16 * q), ca = badd2(lds32(ms + 1280 + 16 * q), one2), ga = lds32(ms + 2560 + 16 * q);
                    const uint32_t sbv = lds32(ms + 3840 + 16 * q), cb = badd2(lds32(ms + 5120 + 16 * q), one2);
                    uint32_t u = x2[2 * q], v = x2[2 * q + 1];
                    u = bfma2(bmul2(bfma2(ln_apply(u, ra.x, ra.y, ra.z), ca, sa), ga), prmt(y[2 * q], y[2 * q + 1], 0x5410), u);
                    v = bfma2(bmul2(bfma2(ln_apply(v, rc.x, rc.y, rc.z), ca, sa), ga), prmt(y[2 * q], y[2 * q + 1], 0x7632), v);
                    x2[2 * q] = u; x2[2 * q + 1] = v;
                    u = bfma2(ln_apply(u, rb2.x, rb2.y, rb2.z), cb, sbv);
                    v = bfma2(ln_apply(v, rd.x, rd.y, rd.z), cb, sbv);
                    acc[4 * q] = blo(u); acc[4 * q + 1] = bhi(u); acc[4 * q + 2] = blo(v); acc[4 * q + 3] = bhi(v);
                }
            }
            reg_fence<40>(acc);
            if (tid == 0) TS(45);
            gemm_loop<80, false, 10, 10, false>(acc, sb, half, 10, 10, 10, 0, 0, 29);
            if (tid == 0) mbar_expect(bars + BAR_ME * 8, 0);
            uint32_t x1[20];
            float s0 = 0.f, q0 = 0.f, s1 = 0.f, q1 = 0.f;
#pragma unroll
            for (int q = 0; q < 10; q++) {
                uint32_t u = pack2(acc[4 * q], acc[4 * q + 1]);
                uint32_t v = pack2(acc[4 * q + 2], acc[4 * q + 3]);
                uint32_t* dst = reinterpret_cast<uint32_t*>(g_x1) + (q < 8 ? tw0 : tw1);
                dst[q * 512] = u;
                dst[q * 512 + 32] = v;
                x1[2 * q] = u; x1[2 * q + 1] = v;
            }
            bar_arrive(6, 288);
            CHUNK(0)
#pragma unroll
            for (int q = 0; q < 10; q++) {
                float a = blo(x1[2 * q]), b = bhi(x1[2 * q]), e = blo(x1[2 * q + 1]), f = bhi(x1[2 * q + 1]);
                s0 += a + b; q0 = fmaf(a, a, fmaf(b, b, q0));
                s1 += e + f; q1 = fmaf(e, e, fmaf(f, f, q1));
            }
#pragma unroll
            for (int m = 1; m <= 2; m <<= 1) {
                s0 += __shfl_xor_sync(0xffffffffu, s0, m); q0 += __shfl_xor_sync(0xffffffffu, q0, m);
                s1 += __shfl_xor_sync(0xffffffffu, s1, m); q1 += __shfl_xor_sync(0xffffffffu, q1, m);
            }
            if (c < 2) g_st[(rb * 8 + j) * 128 + row + 8 * c] = c ? make_float2(s1, q1) : make_float2(s0, q0);
            bar_arrive(8, 288);
            mbar_wait(bars + (BAR_FA + 20 % NA) * 8, (20 / NA) & 1);
#pragma unroll
            for (int q = 0; q < 8; q++) {
                sts32(sb + SM_RA + (20 % NA) * SLOT + q * 2048 + row * 16 + c * 4, x1[2 * q]);
                sts32(sb + SM_RA + (20 % NA) * SLOT + q * 2048 + row * 16 + c * 4 + 128, x1[2 * q + 1]);
            }
            fence_async_smem();
            bar_sync(3 + wg, 128);
#pragma unroll
            for (int q = 0; q < 5; q++) {
                const uint32_t ms = q < 4 ? ms0 : ms1;
                const uint32_t g0 = lds32(ms + 6400 + q * 32), g1 = lds32(ms + 6400 + q * 32 + 16);
                sts128(park + q * 4096, make_uint4(bfma2(g0, x1[4 * q], x2[4 * q]), bfma2(g0, x1[4 * q + 1], x2[4 * q + 1]),
                                                   bfma2(g1, x1[4 * q + 2], x2[4 * q + 2]), bfma2(g1, x1[4 * q + 3], x2[4 * q + 3])));
            }
        }
        gemm3<1>(sb, rb, j, half, row, c, ones);
    }
}

typedef CUresult (*EncFn)(CUtensorMap*, CUtensorMapDataType, cuuint32_t, void*, const cuuint64_t*, const cuuint64_t*,
                          const cuuint32_t*, const cuuint32_t*, CUtensorMapInterleave, CUtensorMapSwizzle,
                          CUtensorMapL2promotion, CUtensorMapFloatOOBfill);

void make_map(EncFn enc, CUtensorMap* m, const void* base, uint64_t inner, uint64_t outer, uint32_t bi, uint32_t bo,
              CUtensorMapSwizzle swz = CU_TENSOR_MAP_SWIZZLE_128B) {
    cuuint64_t dims[2] = {inner, outer};
    cuuint64_t st[1] = {inner * 2};
    cuuint32_t box[2] = {bi, bo};
    cuuint32_t es[2] = {1, 1};
    enc(m, CU_TENSOR_MAP_DATA_TYPE_BFLOAT16, 2, const_cast<void*>(base), dims, st, box, es, CU_TENSOR_MAP_INTERLEAVE_NONE,
        swz, CU_TENSOR_MAP_L2_PROMOTION_NONE, CU_TENSOR_MAP_FLOAT_OOB_FILL_NONE);
}

}

extern "C" void kernel_launch(void* const* d_in, const int* in_sizes, int n_in, void* d_out, int out_size) {
    (void)in_sizes; (void)n_in; (void)out_size;
    Params p;
    p.q = (const bf16*)d_in[0]; p.k = (const bf16*)d_in[1]; p.v = (const bf16*)d_in[2];
    p.shift = (const bf16*)d_in[3]; p.ssmk = (const bf16*)d_in[4]; p.ssmD = (const bf16*)d_in[5];
    p.w1 = (const bf16*)d_in[7]; p.w2 = (const bf16*)d_in[8]; p.w3 = (const bf16*)d_in[9]; p.w4 = (const bf16*)d_in[10];
    p.c = (const bf16*)d_in[11]; p.wmod = (const bf16*)d_in[12];
    p.out = (bf16*)d_out;
    p.ones = 0xffffffffu;
    cudaGetSymbolAddress((void**)&p.epoch, g_epoch);

    void* fn = nullptr;
    cudaDriverEntryPointQueryResult qr;
    cudaGetDriverEntryPoint("cuTensorMapEncodeTiled", &fn, cudaEnableDefault, &qr);
    EncFn enc = (EncFn)fn;
    void* hn = nullptr;
    cudaGetSymbolAddress(&hn, g_hn);
    Maps maps;
    make_map(enc, &maps.w3s, p.w3, F_, D_, 216, 64, CU_TENSOR_MAP_SWIZZLE_NONE);
    make_map(enc, &maps.wm, p.wmod, 6 * D_, D_, 32, 128, CU_TENSOR_MAP_SWIZZLE_64B);
    make_map(enc, &maps.xa, p.q, D_, S_, 64, 128);
    make_map(enc, &maps.xb, p.q, D_, S_, 16, 128, CU_TENSOR_MAP_SWIZZLE_NONE);
    make_map(enc, &maps.hn, hn, D_, S_, 64, 128);
    make_map(enc, &maps.w1a, p.w1, D_, D_, 64, 64);
    make_map(enc, &maps.w1b, p.w1, D_, D_, 16, 64);
    make_map(enc, &maps.w2a, p.w2, D_, D_, 64, 64);
    make_map(enc, &maps.w2b, p.w2, D_, D_, 16, 64);
    make_map(enc, &maps.w3a, p.w3, F_, D_, 64, 64);
    make_map(enc, &maps.w3b, p.w3, F_, D_, RA3, 64);
    make_map(enc, &maps.w3c, p.w3, F_, D_, RB3, 64);
    make_map(enc, &maps.w4a, p.w4, D_, F_, 64, 64);
    make_map(enc, &maps.w4b, p.w4, D_, F_, 16, 64);
    cudaFuncSetAttribute(fused_kernel, cudaFuncAttributeMaxDynamicSharedMemorySize, SMEM_BYTES);
    fused_kernel<<<132, NTHREADS, SMEM_BYTES>>>(p, maps);
}
```

```cpp
#include <cuda_runtime.h>
#include <cuda_bf16.h>
#include <cuda.h>
#include <stdint.h>
#include <string.h>

#define SEED 1
#define RING_A 6
#define CH 2
#define FAST_LN 2
#define STAG 12
#define PGELU 2
#define CH3 4
#define HO_A 16
#define HO_B 16
#define RA3 48
#define CSP 16
#define OWNG 1
#define GATE 5
#define SSM_DELAY 100
#define B_DELAY 220
#define PING 250
#define FORCE_UNPAIRED 0
#define GATE0 3
#define SPD 800
#define WMD2 600
#define SSM_N 3

namespace {

typedef __nv_bfloat16 bf16;
typedef __nv_bfloat162 bf162;

constexpr int S_ = 2048, D_ = 640, F_ = 1728;
constexpr int NTHREADS = 640;
constexpr int NA = RING_A, NB = 12 - RING_A;
constexpr int SLOT = 16384;
constexpr int RB3 = 88 - RA3, HB0 = 512 + 8 * RA3;
constexpr int SM_RA = 0, SM_RB = NA * SLOT;

static_assert(NA == 6, "smem map");
constexpr int RED_STRIDE = 17536;
constexpr int K_STRIDE = 8320;
constexpr int U_PLANE = 2560, U_STRIDE = 5120;
constexpr int SM_Y = 12 * SLOT;
__device__ __forceinline__ int sm_red(int cc) { return cc * RED_STRIDE + (cc < 3 ? SM_RB : -3 * RED_STRIDE); }
__device__ __forceinline__ int sm_k(int cc) { return cc * K_STRIDE + (cc < 3 ? SM_RB + 3 * RED_STRIDE : 2 * RED_STRIDE - 3 * K_STRIDE); }
__device__ __forceinline__ int sm_u(int cc) { return cc * U_STRIDE + (cc < 3 ? SM_RB + 3 * RED_STRIDE + 3 * K_STRIDE : SM_Y + 8192 - 3 * U_STRIDE); }
constexpr int SM_PK = SM_RB;
constexpr int SM_PV = SM_RB + 24576;
constexpr int SM_WM = 57344;
constexpr int SM_XT = SM_WM, SM_XT2 = SM_WM + 16384, SM_XR = SM_WM + 20480;
constexpr int SM_YT = 0;
constexpr int SM_MOD = SM_Y + 20480;
constexpr int SM_GV = SM_MOD + 7680;
constexpr int SM_CS = SM_GV + 1024;
constexpr int SM_RP = SM_CS + 1024;
constexpr int SM_BAR = SM_RP + 1024;
constexpr int SM_PROF = SM_BAR + 512;
constexpr int SM_TOTAL = SM_PROF + 512;
constexpr int SMEM_BYTES = SM_TOTAL + 1024;
static_assert(SMEM_BYTES <= 232448, "smem");

constexpr int BAR_FA = 0, BAR_FB = NA, BAR_EA = 12, BAR_EB = 12 + NA, BAR_K = 24, BAR_U = 29, BAR_Y = 34, BAR_CS = 35, BAR_WM = 36, BAR_M = 37, BAR_XY = 38, BAR_Y2 = 39, BAR_G = 40, BAR_ST = 44, BAR_XR = 45, BAR_ME = 46, BAR_CD = 47, BAR_WM0 = 48, BAR_MR = 49, BAR_MC = 50, NBARS = 51;

__device__ __align__(1024) bf16 g_kvT[D_ * S_];
__device__ __align__(1024) uint32_t g_yv[128 * 5120];
__device__ __align__(1024) bf16 g_mod[6 * D_];
__device__ __align__(1024) bf16 g_hn[S_ * D_];
__device__ __align__(1024) uint4 g_rs[S_ * 2];
__device__ __align__(1024) bf16 g_h1[S_ * D_];
__device__ __align__(1024) bf16 g_x1[S_ * D_];
__device__ __align__(1024) bf16 g_g[S_ * F_];
__device__ __align__(1024) float2 g_st[S_ * 8];
__device__ __align__(1024) float g_cs[F_];
__device__ __align__(1024) unsigned g_flags[128 * 32];
__device__ __align__(1024) unsigned g_epoch[160];
constexpr int FL_P = 0, FL_C = 8, FL_CS = 9, FL_M = 10, FL_R = 16, FL_B1 = 32, FL_B2 = 48, FL_G = 64;

#define TS(i) do {} while (0)
#define TSW(i) do {} while (0)
#define TSD(i, dep) do {} while (0)
#define TSD2(i, dep) do {} while (0)
#define TSFLUSH() do {} while (0)

struct Params {
    const bf16 *q, *k, *v, *shift, *ssmk, *ssmD, *w1, *w2, *w3, *w4, *c, *wmod;
    bf16* out;
    unsigned* epoch;
    unsigned ones;
};
#define CHUNK(k) if (ones & (1u << (k)))
struct Maps { CUtensorMap hn, w1a, w1b, w2a, w2b, w3a, w3b, w3c, w4a, w4b, wm, xa, xb, w3s; };

template<int N> struct WgRs;
template<int N> struct WgSs;
template<> struct WgRs<32> { template<int OFF,int HI,int SC> static __device__ __forceinline__ void run(float* d,uint32_t a0,uint32_t a1,uint32_t a2,uint32_t a3,uint32_t blo){
 asm volatile("{.reg .b32 l; .reg .b64 db; add.u32 l,%20,%21; mov.b64 db,{l,%22}; wgmma.mma_async.sync.aligned.m64n32k16.f32.bf16.bf16 {%0,%1,%2,%3,%4,%5,%6,%7,%8,%9,%10,%11,%12,%13,%14,%15},{%16,%17,%18,%19},db,%23,1,1,0;}"
 :"+f"(d[0]),"+f"(d[1]),"+f"(d[2]),"+f"(d[3]),"+f"(d[4]),"+f"(d[5]),"+f"(d[6]),"+f"(d[7]),"+f"(d[8]),"+f"(d[9]),"+f"(d[10]),"+f"(d[11]),"+f"(d[12]),"+f"(d[13]),"+f"(d[14]),"+f"(d[15])
 :"r"(a0),"r"(a1),"r"(a2),"r"(a3),"r"(blo),"n"(OFF),"n"(HI),"n"(SC)); } };
template<> struct WgRs<48> { template<int OFF,int HI,int SC> static __device__ __forceinline__ void run(float* d,uint32_t a0,uint32_t a1,uint32_t a2,uint32_t a3,uint32_t blo){
 asm volatile("{.reg .b32 l; .reg .b64 db; add.u32 l,%28,%29; mov.b64 db,{l,%30}; wgmma.mma_async.sync.aligned.m64n48k16.f32.bf16.bf16 {%0,%1,%2,%3,%4,%5,%6,%7,%8,%9,%10,%11,%12,%13,%14,%15,%16,%17,%18,%19,%20,%21,%22,%23},{%24,%25,%26,%27},db,%31,1,1,0;}"
 :"+f"(d[0]),"+f"(d[1]),"+f"(d[2]),"+f"(d[3]),"+f"(d[4]),"+f"(d[5]),"+f"(d[6]),"+f"(d[7]),"+f"(d[8]),"+f"(d[9]),"+f"(d[10]),"+f"(d[11]),"+f"(d[12]),"+f"(d[13]),"+f"(d[14]),"+f"(d[15]),"+f"(d[16]),"+f"(d[17]),"+f"(d[18]),"+f"(d[19]),"+f"(d[20]),"+f"(d[21]),"+f"(d[22]),"+f"(d[23])
 :"r"(a0),"r"(a1),"r"(a2),"r"(a3),"r"(blo),"n"(OFF),"n"(HI),"n"(SC)); } };
template<> struct WgRs<64> { template<int OFF,int HI,int SC> static __device__ __forceinline__ void run(float* d,uint32_t a0,uint32_t a1,uint32_t a2,uint32_t a3,uint32_t blo){
 asm volatile("{.reg .b32 l; .reg .b64 db; add.u32 l,%36,%37; mov.b64 db,{l,%38}; wgmma.mma_async.sync.aligned.m64n64k16.f32.bf16.bf16 {%0,%1,%2,%3,%4,%5,%6,%7,%8,%9,%10,%11,%12,%13,%14,%15,%16,%17,%18,%19,%20,%21,%22,%23,%24,%25,%26,%27,%28,%29,%30,%31},{%32,%33,%34,%35},db,%39,1,1,0;}"
 :"+f"(d[0]),"+f"(d[1]),"+f"(d[2]),"+f"(d[3]),"+f"(d[4]),"+f"(d[5]),"+f"(d[6]),"+f"(d[7]),"+f"(d[8]),"+f"(d[9]),"+f"(d[10]),"+f"(d[11]),"+f"(d[12]),"+f"(d[13]),"+f"(d[14]),"+f"(d[15]),"+f"(d[16]),"+f"(d[17]),"+f"(d[18]),"+f"(d[19]),"+f"(d[20]),"+f"(d[21]),"+f"(d[22]),"+f"(d[23]),"+f"(d[24]),"+f"(d[25]),"+f"(d[26]),"+f"(d[27]),"+f"(d[28]),"+f"(d[29]),"+f"(d[30]),"+f"(d[31])
 :"r"(a0),"r"(a1),"r"(a2),"r"(a3),"r"(blo),"n"(OFF),"n"(HI),"n"(SC)); } };
template<> struct WgRs<80> { template<int OFF,int HI,int SC> static __device__ __forceinline__ void run(float* d,uint32_t a0,uint32_t a1,uint32_t a2,uint32_t a3,uint32_t blo){
 asm volatile("{.reg .b32 l; .reg .b64 db; add.u32 l,%44,%45; mov.b64 db,{l,%46}; wgmma.mma_async.sync.aligned.m64n80k16.f32.bf16.bf16 {%0,%1,%2,%3,%4,%5,%6,%7,%8,%9,%10,%11,%12,%13,%14,%15,%16,%17,%18,%19,%20,%21,%22,%23,%24,%25,%26,%27,%28,%29,%30,%31,%32,%33,%34,%35,%36,%37,%38,%39},{%40,%41,%42,%43},db,%47,1,1,0;}"
 :"+f"(d[0]),"+f"(d[1]),"+f"(d[2]),"+f"(d[3]),"+f"(d[4]),"+f"(d[5]),"+f"(d[6]),"+f"(d[7]),"+f"(d[8]),"+f"(d[9]),"+f"(d[10]),"+f"(d[11]),"+f"(d[12]),"+f"(d[13]),"+f"(d[14]),"+f"(d[15]),"+f"(d[16]),"+f"(d[17]),"+f"(d[18]),"+f"(d[19]),"+f"(d[20]),"+f"(d[21]),"+f"(d[22]),"+f"(d[23]),"+f"(d[24]),"+f"(d[25]),"+f"(d[26]),"+f"(d[27]),"+f"(d[28]),"+f"(d[29]),"+f"(d[30]),"+f"(d[31]),"+f"(d[32]),"+f"(d[33]),"+f"(d[34]),"+f"(d[35]),"+f"(d[36]),"+f"(d[37]),"+f"(d[38]),"+f"(d[39])
 :"r"(a0),"r"(a1),"r"(a2),"r"(a3),"r"(blo),"n"(OFF),"n"(HI),"n"(SC)); } };
template<> struct WgRs<96> { template<int OFF,int HI,int SC> static __device__ __forceinline__ void run(float* d,uint32_t a0,uint32_t a1,uint32_t a2,uint32_t a3,uint32_t blo){
 asm volatile("{.reg .b32 l; .reg .b64 db; add.u32 l,%52,%53; mov.b64 db,{l,%54}; wgmma.mma_async.sync.aligned.m64n96k16.f32.bf16.bf16 {%0,%1,%2,%3,%4,%5,%6,%7,%8,%9,%10,%11,%12,%13,%14,%15,%16,%17,%18,%19,%20,%21,%22,%23,%24,%25,%26,%27,%28,%29,%30,%31,%32,%33,%34,%35,%36,%37,%38,%39,%40,%41,%42,%43,%44,%45,%46,%47},{%48,%49,%50,%51},db,%55,1,1,0;}"
 :"+f"(d[0]),"+f"(d[1]),"+f"(d[2]),"+f"(d[3]),"+f"(d[4]),"+f"(d[5]),"+f"(d[6]),"+f"(d[7]),"+f"(d[8]),"+f"(d[9]),"+f"(d[10]),"+f"(d[11]),"+f"(d[12]),"+f"(d[13]),"+f"(d[14]),"+f"(d[15]),"+f"(d[16]),"+f"(d[17]),"+f"(d[18]),"+f"(d[19]),"+f"(d[20]),"+f"(d[21]),"+f"(d[22]),"+f"(d[23]),"+f"(d[24]),"+f"(d[25]),"+f"(d[26]),"+f"(d[27]),"+f"(d[28]),"+f"(d[29]),"+f"(d[30]),"+f"(d[31]),"+f"(d[32]),"+f"(d[33]),"+f"(d[34]),"+f"(d[35]),"+f"(d[36]),"+f"(d[37]),"+f"(d[38]),"+f"(d[39]),"+f"(d[40]),"+f"(d[41]),"+f"(d[42]),"+f"(d[43]),"+f"(d[44]),"+f"(d[45]),"+f"(d[46]),"+f"(d[47])
 :"r"(a0),"r"(a1),"r"(a2),"r"(a3),"r"(blo),"n"(OFF),"n"(HI),"n"(SC)); } };
template<> struct WgRs<112> { template<int OFF,int HI,int SC> static __device__ __forceinline__ void run(float* d,uint32_t a0,uint32_t a1,uint32_t a2,uint32_t a3,uint32_t blo){
 asm volatile("{.reg .b32 l; .reg .b64 db; add.u32 l,%60,%61; mov.b64 db,{l,%62}; wgmma.mma_async.sync.aligned.m64n112k16.f32.bf16.bf16 {%0,%1,%2,%3,%4,%5,%6,%7,%8,%9,%10,%11,%12,%13,%14,%15,%16,%17,%18,%19,%20,%21,%22,%23,%24,%25,%26,%27,%28,%29,%30,%31,%32,%33,%34,%35,%36,%37,%38,%39,%40,%41,%42,%43,%44,%45,%46,%47,%48,%49,%50,%51,%52,%53,%54,%55},{%56,%57,%58,%59},db,%63,1,1,0;}"
 :"+f"(d[0]),"+f"(d[1]),"+f"(d[2]),"+f"(d[3]),"+f"(d[4]),"+f"(d[5]),"+f"(d[6]),"+f"(d[7]),"+f"(d[8]),"+f"(d[9]),"+f"(d[10]),"+f"(d[11]),"+f"(d[12]),"+f"(d[13]),"+f"(d[14]),"+f"(d[15]),"+f"(d[16]),"+f"(d[17]),"+f"(d[18]),"+f"(d[19]),"+f"(d[20]),"+f"(d[21]),"+f"(d[22]),"+f"(d[23]),"+f"(d[24]),"+f"(d[25]),"+f"(d[26]),"+f"(d[27]),"+f"(d[28]),"+f"(d[29]),"+f"(d[30]),"+f"(d[31]),"+f"(d[32]),"+f"(d[33]),"+f"(d[34]),"+f"(d[35]),"+f"(d[36]),"+f"(d[37]),"+f"(d[38]),"+f"(d[39]),"+f"(d[40]),"+f"(d[41]),"+f"(d[42]),"+f"(d[43]),"+f"(d[44]),"+f"(d[45]),"+f"(d[46]),"+f"(d[47]),"+f"(d[48]),"+f"(d[49]),"+f"(d[50]),"+f"(d[51]),"+f"(d[52]),"+f"(d[53]),"+f"(d[54]),"+f"(d[55])
 :"r"(a0),"r"(a1),"r"(a2),"r"(a3),"r"(blo),"n"(OFF),"n"(HI),"n"(SC)); } };
template<> struct WgRs<128> { template<int OFF,int HI,int SC> static __device__ __forceinline__ void run(float* d,uint32_t a0,uint32_t a1,uint32_t a2,uint32_t a3,uint32_t blo){
 asm volatile("{.reg .b32 l; .reg .b64 db; add.u32 l,%68,%69; mov.b64 db,{l,%70}; wgmma.mma_async.sync.aligned.m64n128k16.f32.bf16.bf16 {%0,%1,%2,%3,%4,%5,%6,%7,%8,%9,%10,%11,%12,%13,%14,%15,%16,%17,%18,%19,%20,%21,%22,%23,%24,%25,%26,%27,%28,%29,%30,%31,%32,%33,%34,%35,%36,%37,%38,%39,%40,%41,%42,%43,%44,%45,%46,%47,%48,%49,%50,%51,%52,%53,%54,%55,%56,%57,%58,%59,%60,%61,%62,%63},{%64,%65,%66,%67},db,%71,1,1,0;}"
 :"+f"(d[0]),"+f"(d[1]),"+f"(d[2]),"+f"(d[3]),"+f"(d[4]),"+f"(d[5]),"+f"(d[6]),"+f"(d[7]),"+f"(d[8]),"+f"(d[9]),"+f"(d[10]),"+f"(d[11]),"+f"(d[12]),"+f"(d[13]),"+f"(d[14]),"+f"(d[15]),"+f"(d[16]),"+f"(d[17]),"+f"(d[18]),"+f"(d[19]),"+f"(d[20]),"+f"(d[21]),"+f"(d[22]),"+f"(d[23]),"+f"(d[24]),"+f"(d[25]),"+f"(d[26]),"+f"(d[27]),"+f"(d[28]),"+f"(d[29]),"+f"(d[30]),"+f"(d[31]),"+f"(d[32]),"+f"(d[33]),"+f"(d[34]),"+f"(d[35]),"+f"(d[36]),"+f"(d[37]),"+f"(d[38]),"+f"(d[39]),"+f"(d[40]),"+f"(d[41]),"+f"(d[42]),"+f"(d[43]),"+f"(d[44]),"+f"(d[45]),"+f"(d[46]),"+f"(d[47]),"+f"(d[48]),"+f"(d[49]),"+f"(d[50]),"+f"(d[51]),"+f"(d[52]),"+f"(d[53]),"+f"(d[54]),"+f"(d[55]),"+f"(d[56]),"+f"(d[57]),"+f"(d[58]),"+f"(d[59]),"+f"(d[60]),"+f"(d[61]),"+f"(d[62]),"+f"(d[63])
 :"r"(a0),"r"(a1),"r"(a2),"r"(a3),"r"(blo),"n"(OFF),"n"(HI),"n"(SC)); } };
template<> struct WgSs<80> { template<int AOFF,int AHI,int BOFF,int BHI,int SC> static __device__ __forceinline__ void run(float* d,uint32_t alo,uint32_t blo){
 asm volatile("{.reg .b32 l,m; .reg .b64 da,db; add.u32 l,%40,%42; mov.b64 da,{l,%43}; add.u32 m,%41,%44; mov.b64 db,{m,%45}; wgmma.mma_async.sync.aligned.m64n80k16.f32.bf16.bf16 {%0,%1,%2,%3,%4,%5,%6,%7,%8,%9,%10,%11,%12,%13,%14,%15,%16,%17,%18,%19,%20,%21,%22,%23,%24,%25,%26,%27,%28,%29,%30,%31,%32,%33,%34,%35,%36,%37,%38,%39},da,db,%46,1,1,0,1;}"
 :"+f"(d[0]),"+f"(d[1]),"+f"(d[2]),"+f"(d[3]),"+f"(d[4]),"+f"(d[5]),"+f"(d[6]),"+f"(d[7]),"+f"(d[8]),"+f"(d[9]),"+f"(d[10]),"+f"(d[11]),"+f"(d[12]),"+f"(d[13]),"+f"(d[14]),"+f"(d[15]),"+f"(d[16]),"+f"(d[17]),"+f"(d[18]),"+f"(d[19]),"+f"(d[20]),"+f"(d[21]),"+f"(d[22]),"+f"(d[23]),"+f"(d[24]),"+f"(d[25]),"+f"(d[26]),"+f"(d[27]),"+f"(d[28]),"+f"(d[29]),"+f"(d[30]),"+f"(d[31]),"+f"(d[32]),"+f"(d[33]),"+f"(d[34]),"+f"(d[35]),"+f"(d[36]),"+f"(d[37]),"+f"(d[38]),"+f"(d[39])
 :"r"(alo),"r"(blo),"n"(AOFF),"n"(AHI),"n"(BOFF),"n"(BHI),"n"(SC)); } };
template<> struct WgSs<104> { template<int AOFF,int AHI,int BOFF,int BHI,int SC> static __device__ __forceinline__ void run(float* d,uint32_t alo,uint32_t blo){
 asm volatile("{.reg .b32 l,m; .reg .b64 da,db; add.u32 l,%52,%54; mov.b64 da,{l,%55}; add.u32 m,%53,%56; mov.b64 db,{m,%57}; wgmma.mma_async.sync.aligned.m64n104k16.f32.bf16.bf16 {%0,%1,%2,%3,%4,%5,%6,%7,%8,%9,%10,%11,%12,%13,%14,%15,%16,%17,%18,%19,%20,%21,%22,%23,%24,%25,%26,%27,%28,%29,%30,%31,%32,%33,%34,%35,%36,%37,%38,%39,%40,%41,%42,%43,%44,%45,%46,%47,%48,%49,%50,%51},da,db,%58,1,1,0,1;}"
 :"+f"(d[0]),"+f"(d[1]),"+f"(d[2]),"+f"(d[3]),"+f"(d[4]),"+f"(d[5]),"+f"(d[6]),"+f"(d[7]),"+f"(d[8]),"+f"(d[9]),"+f"(d[10]),"+f"(d[11]),"+f"(d[12]),"+f"(d[13]),"+f"(d[14]),"+f"(d[15]),"+f"(d[16]),"+f"(d[17]),"+f"(d[18]),"+f"(d[19]),"+f"(d[20]),"+f"(d[21]),"+f"(d[22]),"+f"(d[23]),"+f"(d[24]),"+f"(d[25]),"+f"(d[26]),"+f"(d[27]),"+f"(d[28]),"+f"(d[29]),"+f"(d[30]),"+f"(d[31]),"+f"(d[32]),"+f"(d[33]),"+f"(d[34]),"+f"(d[35]),"+f"(d[36]),"+f"(d[37]),"+f"(d[38]),"+f"(d[39]),"+f"(d[40]),"+f"(d[41]),"+f"(d[42]),"+f"(d[43]),"+f"(d[44]),"+f"(d[45]),"+f"(d[46]),"+f"(d[47]),"+f"(d[48]),"+f"(d[49]),"+f"(d[50]),"+f"(d[51])
 :"r"(alo),"r"(blo),"n"(AOFF),"n"(AHI),"n"(BOFF),"n"(BHI),"n"(SC)); } };
template<> struct WgSs<112> { template<int AOFF,int AHI,int BOFF,int BHI,int SC> static __device__ __forceinline__ void run(float* d,uint32_t alo,uint32_t blo){
 asm volatile("{.reg .b32 l,m; .reg .b64 da,db; add.u32 l,%56,%58; mov.b64 da,{l,%59}; add.u32 m,%57,%60; mov.b64 db,{m,%61}; wgmma.mma_async.sync.aligned.m64n112k16.f32.bf16.bf16 {%0,%1,%2,%3,%4,%5,%6,%7,%8,%9,%10,%11,%12,%13,%14,%15,%16,%17,%18,%19,%20,%21,%22,%23,%24,%25,%26,%27,%28,%29,%30,%31,%32,%33,%34,%35,%36,%37,%38,%39,%40,%41,%42,%43,%44,%45,%46,%47,%48,%49,%50,%51,%52,%53,%54,%55},da,db,%62,1,1,0,1;}"
 :"+f"(d[0]),"+f"(d[1]),"+f"(d[2]),"+f"(d[3]),"+f"(d[4]),"+f"(d[5]),"+f"(d[6]),"+f"(d[7]),"+f"(d[8]),"+f"(d[9]),"+f"(d[10]),"+f"(d[11]),"+f"(d[12]),"+f"(d[13]),"+f"(d[14]),"+f"(d[15]),"+f"(d[16]),"+f"(d[17]),"+f"(d[18]),"+f"(d[19]),"+f"(d[20]),"+f"(d[21]),"+f"(d[22]),"+f"(d[23]),"+f"(d[24]),"+f"(d[25]),"+f"(d[26]),"+f"(d[27]),"+f"(d[28]),"+f"(d[29]),"+f"(d[30]),"+f"(d[31]),"+f"(d[32]),"+f"(d[33]),"+f"(d[34]),"+f"(d[35]),"+f"(d[36]),"+f"(d[37]),"+f"(d[38]),"+f"(d[39]),"+f"(d[40]),"+f"(d[41]),"+f"(d[42]),"+f"(d[43]),"+f"(d[44]),"+f"(d[45]),"+f"(d[46]),"+f"(d[47]),"+f"(d[48]),"+f"(d[49]),"+f"(d[50]),"+f"(d[51]),"+f"(d[52]),"+f"(d[53]),"+f"(d[54]),"+f"(d[55])
 :"r"(alo),"r"(blo),"n"(AOFF),"n"(AHI),"n"(BOFF),"n"(BHI),"n"(SC)); } };

__device__ __forceinline__ void wg_fence() { asm volatile("wgmma.fence.sync.aligned;" ::: "memory"); }
__device__ __forceinline__ void wg_commit() { asm volatile("wgmma.commit_group.sync.aligned;" ::: "memory"); }
template <int N> __device__ __forceinline__ void wg_wait() { asm volatile("wgmma.wait_group.sync.aligned %0;" ::"n"(N) : "memory"); }
template <int N> __device__ __forceinline__ void reg_fence(float* d) {
#pragma unroll
    for (int i = 0; i < N; i++) asm volatile("" : "+f"(d[i])::"memory");
}
__device__ __forceinline__ uint32_t desc_lo(uint32_t addr, uint32_t lbo) { return ((addr & 0x3FFFF) >> 4) | ((lbo >> 4) << 16); }
#define desc_hi(sbo, sw) (((sbo) >> 4) | ((sw) << 30))
__device__ __forceinline__ uint32_t smem_u32(const void* p) { return (uint32_t)__cvta_generic_to_shared(p); }
__device__ __forceinline__ bool elect() {
    uint32_t p;
    asm volatile("{.reg .pred P; elect.sync _|P, 0xffffffff; selp.u32 %0,1,0,P;}" : "=r"(p));
    return p;
}
__device__ __forceinline__ void mbar_init(uint32_t bar, uint32_t cnt) { asm volatile("mbarrier.init.shared::cta.b64 [%0], %1;" ::"r"(bar), "r"(cnt) : "memory"); }
__device__ __forceinline__ void mbar_expect(uint32_t bar, uint32_t bytes) { asm volatile("mbarrier.arrive.expect_tx.shared::cta.b64 _, [%0], %1;" ::"r"(bar), "r"(bytes) : "memory"); }
__device__ __forceinline__ bool mbar_try(uint32_t bar, uint32_t par) {
    uint32_t ok;
    asm volatile("{.reg .pred p; mbarrier.try_wait.parity.shared::cta.b64 p, [%1], %2; selp.u32 %0,1,0,p;}" : "=r"(ok) : "r"(bar), "r"(par) : "memory");
    return ok;
}
constexpr int SPIN_LIMIT = 1 << 18;
__device__ __forceinline__ void mbar_wait(uint32_t bar, uint32_t par) {
    if (mbar_try(bar, par)) return;
    asm volatile("{.reg .pred p, q; .reg .b32 n; mov.u32 n, 0;\n"
                 "W%=: mbarrier.try_wait.parity.shared::cta.b64 p, [%0], %1; add.u32 n, n, 1; setp.lt.and.u32 q, n, %2, !p; @q bra W%=;}"
                 ::"r"(bar), "r"(par), "n"(SPIN_LIMIT) : "memory");
}
__device__ __forceinline__ void bulk_g2s(uint32_t dst, const void* src, uint32_t bytes, uint32_t bar) {
    asm volatile("cp.async.bulk.shared::cluster.global.mbarrier::complete_tx::bytes [%0], [%1], %2, [%3];" ::"r"(dst), "l"(src), "r"(bytes), "r"(bar) : "memory");
}
__device__ __forceinline__ void bulk_s2g(void* dst, uint32_t src, uint32_t bytes) {
    asm volatile("cp.async.bulk.global.shared::cta.bulk_group [%0], [%1], %2;" ::"l"(dst), "r"(src), "r"(bytes) : "memory");
}
__device__ __forceinline__ void bulk_prefetch(const void* src, uint32_t bytes) {
    asm volatile("cp.async.bulk.prefetch.L2.global [%0], %1;" ::"l"(src), "r"(bytes) : "memory");
}
__device__ __forceinline__ void tma2d(uint32_t dst, const CUtensorMap* m, int c0, int c1, uint32_t bar) {
    asm volatile("cp.async.bulk.tensor.2d.shared::cluster.global.mbarrier::complete_tx::bytes [%0], [%1, {%3, %4}], [%2];" ::"r"(dst), "l"(m), "r"(bar), "r"(c0), "r"(c1) : "memory");
}
__device__ __forceinline__ void tma2d_mc(uint32_t dst, const CUtensorMap* m, int c0, int c1, uint32_t bar) {
    asm volatile("cp.async.bulk.tensor.2d.shared::cluster.global.mbarrier::complete_tx::bytes.multicast::cluster [%0], [%1, {%3, %4}], [%2], %5;" ::"r"(dst), "l"(m), "r"(bar), "r"(c0), "r"(c1), "h"((uint16_t)3) : "memory");
}
__device__ __forceinline__ uint32_t mapa(uint32_t a, uint32_t rank) { uint32_t r; asm("mapa.shared::cluster.u32 %0, %1, %2;" : "=r"(r) : "r"(a), "r"(rank)); return r; }
__device__ __forceinline__ void mbar_arrive_cl(uint32_t bar) { asm volatile("mbarrier.arrive.shared::cluster.b64 _, [%0];" ::"r"(bar) : "memory"); }
__device__ __forceinline__ void prefetch_map(const CUtensorMap* m) { asm volatile("prefetch.tensormap [%0];" ::"l"(m) : "memory"); }
__device__ __forceinline__ void cpasync16(uint32_t dst, const void* src, uint32_t srcsz) {
    asm volatile("cp.async.cg.shared.global [%0], [%1], 16, %2;" ::"r"(dst), "l"(src), "r"(srcsz) : "memory");
}
__device__ __forceinline__ void bar_sync(int id, int n) { asm volatile("bar.sync %0, %1;" ::"r"(id), "r"(n) : "memory"); }
__device__ __forceinline__ void bar_arrive(int id, int n) { asm volatile("bar.arrive %0, %1;" ::"r"(id), "r"(n) : "memory"); }
__device__ __forceinline__ void fence_async_smem() { asm volatile("fence.proxy.async.shared::cta;" ::: "memory"); }
__device__ __forceinline__ void fence_async_global() { asm volatile("fence.proxy.async.global;" ::: "memory"); }
__device__ __forceinline__ void flag_release(int f) { asm volatile("red.release.gpu.global.add.u32 [%0], 1;" ::"l"(&g_flags[f * 32]) : "memory"); }
__device__ __forceinline__ void flag_wait(int f, unsigned target) {
    const unsigned* p = &g_flags[f * 32];
    unsigned v; int n = 0;
    do {
        asm volatile("ld.relaxed.gpu.global.u32 %0, [%1];" : "=r"(v) : "l"(p) : "memory");
    } while ((int)(v - target) < 0 && ++n < SPIN_LIMIT);
    asm volatile("fence.acquire.gpu;" ::: "memory");
}
__device__ __forceinline__ unsigned ld_flag(const unsigned* p) { unsigned v; asm volatile("ld.relaxed.gpu.global.u32 %0, [%1];" : "=r"(v) : "l"(p) : "memory"); return v; }
__device__ __forceinline__ void spin(unsigned n) { unsigned t0, t1; asm volatile("mov.u32 %0, %%clock;" : "=r"(t0)); do { asm volatile("mov.u32 %0, %%clock;" : "=r"(t1)); } while (t1 - t0 < n); }
__device__ __forceinline__ int tensor_ping() {
    int r;
    asm volatile("{.reg .f32 a, b, c, d; mma.sync.aligned.m16n8k16.row.col.f32.bf16.bf16.f32 {a,b,c,d},{%1,%1,%1,%1},{%1,%1},{%2,%2,%2,%2}; mov.b32 %0, a;}" : "=r"(r) : "r"(0), "f"(0.f));
    return r;
}
__device__ __forceinline__ void mbar_wait_warm(uint32_t bar, uint32_t par) {
    for (int n = 0; n < SPIN_LIMIT; n++) {
        uint32_t ok;
        asm volatile("{.reg .pred p; mbarrier.test_wait.parity.shared::cta.b64 p, [%1], %2; selp.u32 %0,1,0,p;}" : "=r"(ok) : "r"(bar), "r"(par) : "memory");
        if (ok) break;
        n += tensor_ping();
        spin(PING);
    }
}
__device__ __forceinline__ void flag_wait2(int f0, int f1, unsigned target) {
    const unsigned *p = &g_flags[f0 * 32], *q = &g_flags[f1 * 32];
    unsigned v, w; int n = 0;
    do { v = ld_flag(p); w = ld_flag(q); } while ((int)((v - target) | (w - target)) < 0 && ++n < SPIN_LIMIT);
    asm volatile("fence.acquire.gpu;" ::: "memory");
}
__device__ __forceinline__ uint32_t lds32(uint32_t a) { uint32_t v; asm volatile("ld.shared.u32 %0, [%1];" : "=r"(v) : "r"(a)); return v; }
__device__ __forceinline__ float2 lds64f(uint32_t a) { float2 v; asm volatile("ld.shared.v2.f32 {%0,%1}, [%2];" : "=f"(v.x), "=f"(v.y) : "r"(a)); return v; }
__device__ __forceinline__ uint2 lds64(uint32_t a) { uint2 v; asm volatile("ld.shared.v2.u32 {%0,%1}, [%2];" : "=r"(v.x), "=r"(v.y) : "r"(a)); return v; }
__device__ __forceinline__ void sts64f(uint32_t a, float2 v) { asm volatile("st.shared.v2.f32 [%0], {%1,%2};" ::"r"(a), "f"(v.x), "f"(v.y) : "memory"); }
__device__ __forceinline__ void sts32(uint32_t a, uint32_t v) { asm volatile("st.shared.u32 [%0], %1;" ::"r"(a), "r"(v) : "memory"); }
__device__ __forceinline__ void sts64(uint32_t a, uint32_t x, uint32_t y) { asm volatile("st.shared.v2.u32 [%0], {%1,%2};" ::"r"(a), "r"(x), "r"(y) : "memory"); }
__device__ __forceinline__ void sts16(uint32_t a, uint16_t v) { asm volatile("st.shared.u16 [%0], %1;" ::"r"(a), "h"(v) : "memory"); }
__device__ __forceinline__ uint4 lds128(uint32_t a) { uint4 v; asm volatile("ld.shared.v4.u32 {%0,%1,%2,%3}, [%4];" : "=r"(v.x), "=r"(v.y), "=r"(v.z), "=r"(v.w) : "r"(a)); return v; }
__device__ __forceinline__ void sts128(uint32_t a, uint4 v) { asm volatile("st.shared.v4.u32 [%0], {%1,%2,%3,%4};" ::"r"(a), "r"(v.x), "r"(v.y), "r"(v.z), "r"(v.w) : "memory"); }
__device__ __forceinline__ void sts128f(uint32_t a, float x, float y, float z, float w) { asm volatile("st.shared.v4.f32 [%0], {%1,%2,%3,%4};" ::"r"(a), "f"(x), "f"(y), "f"(z), "f"(w) : "memory"); }
__device__ __forceinline__ uint32_t prmt(uint32_t a, uint32_t b, uint32_t s) { uint32_t r; asm("prmt.b32 %0,%1,%2,%3;" : "=r"(r) : "r"(a), "r"(b), "r"(s)); return r; }
__device__ __forceinline__ uint32_t pack2(float lo, float hi) { uint32_t r; asm("cvt.rn.bf16x2.f32 %0, %1, %2;" : "=r"(r) : "f"(hi), "f"(lo)); return r; }
__device__ __forceinline__ float blo(uint32_t v) { return __uint_as_float(v << 16); }
__device__ __forceinline__ float bhi(uint32_t v) { return __uint_as_float(v & 0xffff0000u); }
__device__ __forceinline__ uint32_t bmul2(uint32_t a, uint32_t b) { uint32_t r; asm("mul.rn.bf16x2 %0,%1,%2;" : "=r"(r) : "r"(a), "r"(b)); return r; }
__device__ __forceinline__ uint32_t badd2(uint32_t a, uint32_t b) { uint32_t r; asm("add.rn.bf16x2 %0,%1,%2;" : "=r"(r) : "r"(a), "r"(b)); return r; }
__device__ __forceinline__ float rbf(float x) { return __bfloat162float(__float2bfloat16_rn(x)); }
__device__ __forceinline__ uint32_t ldcg32(const void* p) { uint32_t v; asm volatile("ld.global.cg.u32 %0, [%1];" : "=r"(v) : "l"(p) : "memory"); return v; }
__device__ __forceinline__ uint4 ldcg128(const void* p) { uint4 v; asm volatile("ld.global.cg.v4.u32 {%0,%1,%2,%3}, [%4];" : "=r"(v.x), "=r"(v.y), "=r"(v.z), "=r"(v.w) : "l"(p) : "memory"); return v; }
__device__ __forceinline__ void stg32_if(void* p, uint32_t v, int on) { asm volatile("{.reg .pred q; setp.ne.b32 q, %2, 0; @q st.global.u32 [%0], %1;}" ::"l"(p), "r"(v), "r"(on) : "memory"); }
__device__ __forceinline__ uint2 ldcg64(const void* p) { uint2 v; asm volatile("ld.global.cg.v2.u32 {%0,%1}, [%2];" : "=r"(v.x), "=r"(v.y) : "l"(p) : "memory"); return v; }
__device__ __forceinline__ float gelu_h(float h) {
    float u = h * fmaf(h * h, 8.0f * 0.044715f * 0.7978845608028654f, 2.0f * 0.7978845608028654f);
    float th;
    asm("tanh.approx.f32 %0, %1;" : "=f"(th) : "f"(u));
    return fmaf(h, th, h);
}
__device__ __forceinline__ float gelu(float x) { return gelu_h(0.5f * x); }
__device__ __forceinline__ float half_rstd(float sum, float sq) {
    float mean = sum * (1.0f / D_), inv;
    asm("rsqrt.approx.ftz.f32 %0, %1;" : "=f"(inv) : "f"(fmaxf(fmaf(-mean, mean, fmaf(sq, 1.0f / D_, 1e-5f)), 1e-5f)));
    return 0.5f * inv;
}
__device__ __forceinline__ uint32_t bsub2(uint32_t a, uint32_t b) { uint32_t r; asm("sub.rn.bf16x2 %0,%1,%2;" : "=r"(r) : "r"(a), "r"(b)); return r; }
__device__ __forceinline__ uint32_t bfma2(uint32_t a, uint32_t b, uint32_t c) { uint32_t r; asm("fma.rn.bf16x2 %0,%1,%2,%3;" : "=r"(r) : "r"(a), "r"(b), "r"(c)); return r; }
__device__ __forceinline__ uint32_t gelu2_h(uint32_t h) {
    uint32_t u = bmul2(h, bfma2(bmul2(h, h), 0x3e923e92u, 0x3fcc3fccu)), th;
    asm("tanh.approx.bf16x2 %0, %1;" : "=r"(th) : "r"(u));
    return bfma2(h, th, h);
}
struct RowSum { float s = 0.f, q = 0.f, s_ = 0.f, q_ = 0.f;
    __device__ __forceinline__ void add(uint32_t v) { float a = blo(v), b = bhi(v); s += a; s_ += b; q = fmaf(a, a, q); q_ = fmaf(b, b, q_); } };
template <int I0>
__device__ __forceinline__ uint3 row_stats(const uint32_t* v, int lane, RowSum r0 = RowSum()) {
#pragma unroll
    for (int i = I0; i < 10; i++) r0.add(v[i]);
    float s = r0.s + r0.s_, q = r0.q + r0.q_;
    {
        float t = __shfl_xor_sync(0xffffffffu, (lane & 16) ? s : q, 16);
        t += (lane & 16) ? q : s;
#pragma unroll
        for (int m = 8; m; m >>= 1) t += __shfl_xor_sync(0xffffffffu, t, m);
        float o = __shfl_xor_sync(0xffffffffu, t, 16);
        s = (lane & 16) ? o : t; q = (lane & 16) ? t : o;
    }
    float mean = s * (1.0f / D_), inv;
    asm("rsqrt.approx.ftz.f32 %0, %1;" : "=f"(inv) : "f"(fmaxf(fmaf(-mean, mean, fmaf(q, 1.0f / D_, 1e-5f)), 1e-5f)));
    uint3 r;
    r.x = pack2(mean, mean);
    r.y = pack2(inv, inv);
    inv -= blo(r.y);
    r.z = pack2(inv, inv);
    return r;
}
__device__ __forceinline__ uint32_t ln_apply(uint32_t x, uint32_t m, uint32_t hi, uint32_t lo) {
    uint32_t xc = bsub2(x, m);
    return bmul2(xc, hi);
}

struct AFrag { uint32_t m, a, b, c, d; };
__device__ __forceinline__ AFrag ldA(uint32_t a) { AFrag f; f.m = lds32(a - 16); f.a = lds32(a); f.b = lds32(a + 16); f.c = lds32(a + 32); f.d = lds32(a + 48); return f; }
template <int N, int M> __device__ __forceinline__ void conv_pair(float* d, const AFrag& f, uint32_t descU) {
    WgRs<N>::template run<8 * M, desc_hi(128, 0), M ? 1 : 0>(d, f.a, f.b, f.m, f.a, descU);
    WgRs<N>::template run<8 * M + 1, desc_hi(128, 0), 1>(d, f.c, f.d, f.b, f.c, descU);
}
template <int Q> __device__ __forceinline__ void conv_put(float* d, uint32_t r0) {
    sts64(r0 + Q * 32, pack2(d[4 * Q + 1], d[4 * Q + 3]), pack2(d[4 * Q], d[4 * Q + 2]));
}
template <int M> __device__ __forceinline__ void conv_two(float* d, AFrag f0, AFrag f1, uint32_t kaddr, uint32_t descU, uint32_t r0, bool handoff) {
    constexpr int N = M < 14 ? 128 - 8 * M : 32;
    wg_fence();
    conv_pair<N, M>(d, f0, descU);
    wg_commit();
    if constexpr (M > 0) f1 = ldA(kaddr + 256 * (M + 1));
    wg_fence();
    conv_pair<N, M + 1>(d, f1, descU);
    wg_commit();
    if (STAG && M == STAG && handoff) bar_arrive(12, 256);
    if constexpr (M < 14) {
        if constexpr (M > 0) { conv_put<17 - M>(d, r0); conv_put<16 - M>(d, r0); }
        wg_wait<1>();
        f0 = ldA(kaddr + 256 * (M + 2));
        if constexpr (M < 12) wg_wait<0>();
        conv_two<M + 2>(d, f0, f1, kaddr, descU, r0, handoff);
    } else {
        wg_wait<0>();
        conv_put<3>(d, r0); conv_put<2>(d, r0); conv_put<1>(d, r0); conv_put<0>(d, r0);
    }
}
template <int N, bool ASWZ, int SC0>
__device__ __forceinline__ void gemm_issue(float* acc, uint32_t bars, int sa, int pa, int sw, int pw, uint32_t da0, uint32_t db0) {
    mbar_wait(bars + (BAR_FB + sw) * 8, pw);
    mbar_wait(bars + (BAR_FA + sa) * 8, pa);
    const uint32_t da = da0 + sa * (SLOT >> 4), db = db0 + sw * (SLOT >> 4);
    constexpr int AK = ASWZ ? 2 : 256, AH = ASWZ ? desc_hi(1024, 1) : desc_hi(128, 0), BH = desc_hi(1024, 1);
    wg_fence();
    WgSs<N>::template run<0, AH, 0, BH, SC0>(acc, da, db);
    WgSs<N>::template run<AK, AH, 128, BH, 1>(acc, da, db);
    WgSs<N>::template run<2 * AK, AH, 256, BH, 1>(acc, da, db);
    WgSs<N>::template run<3 * AK, AH, 384, BH, 1>(acc, da, db);
    wg_commit();
}
template <int N, bool ASWZ, int NKB, int RELB, bool ZERO>
__device__ __forceinline__ void gemm_loop(float* acc, uint32_t sb, int half, int ia0, int ib0, int rela, int wait_bar, int order_bar, int tsid) {
    int sa = ia0 % NA, pa = (ia0 / NA) & 1, sw = ib0 % NB, pw = (ib0 / NB) & 1;
    const uint32_t bars = sb + SM_BAR;
    const int t = threadIdx.x & 127;
    uint32_t ebar = mapa(bars + (t < 2 ? BAR_EB : BAR_EA) * 8, (t < 2 && lds32(sb + SM_GV + 516)) ? t : blockIdx.x & 1);
    const int nrel = t < 2 ? RELB : t == 2 ? rela : 0;
    const uint32_t da0 = ASWZ ? desc_lo(sb + SM_RA + half * 8192, 16) : desc_lo(sb + SM_RA + half * 1024, 2048), db0 = desc_lo(sb + SM_RB, 8192);
    asm volatile("" : "+r"(ebar));
    if (wait_bar) bar_sync(wait_bar, 512);
    gemm_issue<N, ASWZ, ZERO ? 0 : 1>(acc, bars, sa, pa, sw, pw, da0, db0);
    if ((threadIdx.x & 255) == 0) TS(tsid);
#pragma unroll 1
    for (int kb = 1; kb < NKB; kb++) {
        const int prev = t < 2 ? sw : sa;
        if (++sa == NA) { sa = 0; pa ^= 1; }
        if (++sw == NB) { sw = 0; pw ^= 1; }
        gemm_issue<N, ASWZ, 1>(acc, bars, sa, pa, sw, pw, da0, db0);
        if (order_bar && kb == NKB - 1) bar_arrive(order_bar, 512);
        wg_wait<1>();
        if (kb <= nrel) mbar_arrive_cl(ebar + prev * 8);
    }
    wg_wait<0>();
    if (nrel == NKB) mbar_arrive_cl(ebar + (t < 2 ? sw : sa) * 8);
    reg_fence<N / 2>(acc);
    if ((threadIdx.x & 255) == 0) TS(tsid + 1);
}

template <int PART>
__device__ __forceinline__ void gemm3(uint32_t sb, int rb, int j, int half, int row, int c, unsigned ones) {
    constexpr int N = 64 + (PART ? RB3 : RA3), NQ = N / 8;
    constexpr int HO = PART ? HO_B : HO_A;
    float acc[N / 2];
    float2 cr[NQ];
    if (PART) {
        gemm_loop<N, false, 1, 1, true>(acc, sb, half, 20, 20, 0, 0, 0, 50);
        bar_arrive(9, 512);
    }
    mbar_wait(sb + SM_BAR + BAR_CS * 8, 0);
    const uint32_t csa = sb + SM_CS + PART * (256 + 4 * RA3) + 8 * c;
#pragma unroll
    for (int q = 0; q < NQ; q++) if (q < CSP) cr[q] = lds64f(csa + 32 * q);
    uint4 rp;
    if (PART) {
        mbar_wait(sb + SM_BAR + BAR_G * 8, 0);
        const float2* sp = &g_st[(rb * 8 + 2 * c) * 128 + row];
        const uint2 s0 = ldcg64(sp), s1 = ldcg64(sp + 128), s2 = ldcg64(sp + 8), s3 = ldcg64(sp + 136);
        float a0 = __uint_as_float(s0.x) + __uint_as_float(s1.x), b0 = __uint_as_float(s0.y) + __uint_as_float(s1.y);
        float a1 = __uint_as_float(s2.x) + __uint_as_float(s3.x), b1 = __uint_as_float(s2.y) + __uint_as_float(s3.y);
#pragma unroll
        for (int m = 1; m <= 2; m <<= 1) {
            a0 += __shfl_xor_sync(0xffffffffu, a0, m); b0 += __shfl_xor_sync(0xffffffffu, b0, m);
            a1 += __shfl_xor_sync(0xffffffffu, a1, m); b1 += __shfl_xor_sync(0xffffffffu, b1, m);
        }
        const float inv0 = half_rstd(a0, b0), inv1 = half_rstd(a1, b1);
        rp = make_uint4(PGELU ? pack2(inv0, inv0) : __float_as_uint(inv0), __float_as_uint(a0 * (-1.0f / D_)),
                        PGELU ? pack2(inv1, inv1) : __float_as_uint(inv1), __float_as_uint(a1 * (-1.0f / D_)));
        if (c == 0) sts128(sb + SM_RP + ((threadIdx.x & 255) >> 2) * 16, rp);
        bar_arrive(13, 512);
    }
    gemm_loop<N, false, 10 - PART, 10 - PART, !PART>(acc, sb, half, 20 + (10 - NA) * PART, 21 + 10 * PART, PART ? 9 : 10 - NA, 9 + PART, HO < 0 ? 10 + PART : 0, 46 + 2 * PART);
    if (!PART) {
        bar_sync(13, 512);
        rp = lds128(sb + SM_RP + ((threadIdx.x & 255) >> 2) * 16);
    }
    const float nb0 = __uint_as_float(rp.y), nb1 = __uint_as_float(rp.w);
    const uint32_t own = sb + SM_RA + ((39 - NA) % NA) * SLOT + row * 16 + c * 4;
    if (PART && OWNG) mbar_wait(sb + SM_BAR + (BAR_FA + (39 - NA) % NA) * 8, ((39 - NA) / NA) & 1);
    uint32_t* dst = reinterpret_cast<uint32_t*>(g_g) + (rb * 216 + HB0 / 8 * PART + 8 * j) * 512 + row * 4 + c;
    auto act = [&](int q, int r) {
        const float nb = r ? nb1 : nb0;
        const uint32_t inv = r ? rp.z : rp.x;
        const float t0 = fmaf(nb, cr[q].x, acc[4 * q + 2 * r]), t1 = fmaf(nb, cr[q].y, acc[4 * q + 2 * r + 1]);
        return gelu2_h(bmul2(pack2(t0, t1), inv));
    };
    uint32_t* dst1 = dst + (56 - (16 - NQ) * j) * 512;
#pragma unroll
    for (int k = 0; k < NQ; k += CH3) {
        if (k == HO) bar_arrive(10 + PART, 512);
        CHUNK(k) {
#pragma unroll
            for (int q = k; q < k + CH3 && q < NQ; q++) {
                if (q + CSP < NQ) cr[q + CSP] = lds64f(csa + 32 * (q + CSP));
                const uint32_t u = act(q, 0), v = act(q, 1);
                (q < 8 ? dst : dst1)[q * 512] = u;
                (q < 8 ? dst : dst1)[q * 512 + 32] = v;
                if (PART && OWNG && q < 8) { sts32(own + q * 2048, u); sts32(own + q * 2048 + 128, v); }
            }
            if (PART && OWNG && k < 8 && k + CH3 >= 8) fence_async_smem();
        }
    }
    bar_arrive(1 + PART, 288);
    if (HO >= NQ) bar_arrive(10 + PART, 512);
}

template <int NS, int BASE, int BF, int BE> struct Ring {
    uint32_t sb, st, ph;
    __device__ __forceinline__ uint32_t acquire(uint32_t bytes) {
        mbar_wait(sb + SM_BAR + BE * 8 + st * 8, ph);
        uint32_t fb = sb + SM_BAR + BF * 8 + st * 8;
        mbar_expect(fb, bytes);
        return fb;
    }
    __device__ __forceinline__ uint32_t slot() { return sb + BASE + st * SLOT; }
    __device__ __forceinline__ void next() { if (++st == NS) { st = 0; ph ^= 1; } }
    __device__ __forceinline__ void run2d(const CUtensorMap* m, int c1) {
#pragma unroll 1
        for (int c0 = 64; c0 < D_; c0 += 64) {
            uint32_t fb = acquire(SLOT);
            tma2d(slot(), m, c0, c1, fb);
            next();
        }
    }
    static __device__ __forceinline__ int korder(int i, int own) { return i == 0 ? own : i > own ? i : i - 1; }
    __device__ __forceinline__ void runw(bool paired, int rk, const CUtensorMap* ma, const CUtensorMap* mb, int ca, int cb, int i0, int i1, int own, uint32_t bytes, int gate_at, uint32_t gate) {
        if (paired) {
            const CUtensorMap* m = rk ? mb : ma;
            const int c0 = rk ? cb : ca;
#pragma unroll 1
            for (int i = i0; i < i1; i++) {
                const int c1 = korder(i, own) * 64;
                if (i == gate_at) mbar_wait(gate, 0);
                uint32_t fb = acquire(bytes);
                tma2d_mc(slot() + 8192 * rk, m, c0, c1, fb);
                next();
            }
        } else {
#pragma unroll 1
            for (int i = i0; i < i1; i++) {
                const int c1 = korder(i, own) * 64;
                uint32_t fb = acquire(bytes);
                tma2d(slot(), ma, ca, c1, fb);
                tma2d(slot() + 8192, mb, cb, c1, fb);
                next();
            }
        }
    }
    __device__ __forceinline__ void run1d(const char* src, int i0, int i1, int own) {
#pragma unroll 1
        for (int i = i0; i < i1; i++) {
            const char* s = src + korder(i, own) * SLOT;
            uint32_t fb = acquire(SLOT);
            bulk_g2s(slot(), s, SLOT, fb);
            next();
        }
    }
};

__global__ void __cluster_dims__(2, 1, 1) __launch_bounds__(NTHREADS, 1) fused_kernel(const Params p, const __grid_constant__ Maps maps) {
    extern __shared__ __align__(1024) unsigned char smem_raw[];
    const uint32_t sb = (smem_u32(smem_raw) + 1023u) & ~1023u;
#pragma unroll
    for (int i = 0; i < SEED; i++) asm volatile("{.reg .b32 t; mov.u32 t, %laneid;}");
    const uint32_t bars = sb + SM_BAR;
    const int tid = threadIdx.x, lane = tid & 31;
    unsigned smid;
    asm volatile("mov.u32 %0, %%smid;" : "=r"(smid));
    const bool spare = (smid >> 2) == 30;
    const int cta = smid < 120 ? smid : smid - 4;
    const int pg = cta >> 4, pi = cta & 15;
    auto chan = [&](int cc) { return cc < 3 ? 3 * cta + cc : 381 + 2 * cta + cc; };
    const int hb = tid >= 320;
    unsigned ep0 = 0;
    if (!spare) {
        const unsigned t = tid - 320 * hb, r32 = t / 10u, cc = t - r32 * 10u, row = r32 + 64 * hb;
        const unsigned go = (unsigned)(pi * 128 * 1280) + row * 1280u + cc * 16u + (cc < 6 ? pg * 96 : 672 + pg * 64);
        const uint32_t so = sb + (row >> 4) * 32u + row * 160u + cc * 16u;
        const char* kb = (const char*)p.k + go;
        const char* vb = (const char*)p.v + go;
        if (hb) {
            if (tid < 328) {
                const char* a = lane < 5 ? (const char*)p.shift + lane * 128 + (lane < 3 ? pg * 384 : 2688 + pg * 256) : (const char*)(p.ssmD + chan(2 * lane - 10));
                asm volatile("prefetch.global.L2 [%0];" ::"l"(a));
            }
            if (tid >= 640 - NBARS) {
                const int i = 639 - tid;
                mbar_init(bars + i * 8, (i >= BAR_EB && i < BAR_K) ? 4 : ((i >= BAR_EA && i < BAR_EB) || i == BAR_XY) ? 2 : 1);
                asm volatile("fence.mbarrier_init.release.cluster;" ::: "memory");
            }
            bar_arrive(14, 640);
            if (tid >= 512) asm volatile("ld.volatile.global.u32 %0, [%1];" : "=r"(ep0) : "l"(p.epoch + smid) : "memory");
            if (B_DELAY) spin(B_DELAY);
        }
        cpasync16(so + SM_PK + 2592, kb, 16);
        cpasync16(so + SM_PV, vb, 16);
        cpasync16(so + SM_PK + 3 * 2592, kb + 32 * 1280, 16);
        cpasync16(so + SM_PV + 2 * 2592, vb + 32 * 1280, 16);
        if (tid < 30) cpasync16(so + SM_PK + 13 * 160, pi ? kb - 3 * 1280 : kb, pi ? 16 : 0);
        asm volatile("cp.async.commit_group;" ::: "memory");
    }
    const int warp = __shfl_sync(0xffffffffu, tid >> 5, 0);
    const int wg = warp >> 2, wq = warp & 3;

    if (spare) {
        const int sp = smid & 3;
        const unsigned ep1 = *(volatile unsigned*)&p.epoch[smid] + 1;
        if (tid == 32) { sts32(sb + SM_GV + 512, smid); asm volatile("fence.release.sync_restrict::shared::cta.cluster;" ::: "memory"); }
        asm volatile("barrier.cluster.arrive.relaxed.aligned;" ::: "memory");
        asm volatile("barrier.cluster.wait.aligned;" ::: "memory");
        if (tid == 0) {
            for (int i = 0; i < 4; i++) mbar_init(bars + i * 8, 1);
            asm volatile("fence.mbarrier_init.release.cluster;" ::: "memory");
        }
        if (warp == 0) { if (lane < 8) flag_wait(FL_P + lane, ep1 * 16); __syncwarp(); if (SPD) spin(SPD); }
        __syncthreads();
        const int cq = tid % 54, rg = tid / 54;
        float a[8];
#pragma unroll
        for (int i = 0; i < 8; i++) a[i] = 0.f;
#pragma unroll 1
        for (int it = -4; it < 10; it++) {
            const uint32_t st = sb + (it & 3) * 55296, fb = bars + (it & 3) * 8;
            if (it >= 0) {
                mbar_wait(fb, (it >> 2) & 1);
                if (tid < 432) {
#pragma unroll 2
                    for (int i = 0; i < 8; i++) {
                        uint4 w = lds128(st + (cq >= 27 ? 27648 - 432 : 0) + (rg * 8 + i) * 432 + cq * 16);
                        a[0] += blo(w.x); a[1] += bhi(w.x); a[2] += blo(w.y); a[3] += bhi(w.y);
                        a[4] += blo(w.z); a[5] += bhi(w.z); a[6] += blo(w.w); a[7] += bhi(w.w);
                    }
                }
                __syncthreads();
            }
            if (it < 6 && warp == 19 && elect()) {
                mbar_expect(fb, 55296);
                tma2d(st, &maps.w3s, sp * 432, (it + 4) * 64, fb);
                tma2d(st + 27648, &maps.w3s, sp * 432 + 216, (it + 4) * 64, fb);
            }
        }
        if (warp == 19 && elect()) {
#pragma unroll 1
            for (int i = 0; i < 27; i++) bulk_prefetch((const char*)p.w4 + sp * 552960 + i * 20480, 20480);
        }
        if (tid < 432) {
            sts128f(sb + rg * 1728 + cq * 32, a[0], a[1], a[2], a[3]);
            sts128f(sb + rg * 1728 + cq * 32 + 16, a[4], a[5], a[6], a[7]);
        }
        __syncthreads();
        if (tid < 432) {
            float s = 0.f;
#pragma unroll
            for (int i = 0; i < 8; i++) s += __uint_as_float(lds32(sb + i * 1728 + tid * 4));
            g_cs[sp * 432 + tid] = s;
        }
        __syncthreads();
        if (tid == 0) { flag_release(FL_CS); p.epoch[smid] = ep1; TS(0); }
        if (warp == 0) TSFLUSH();
        return;
    }

    int gpc, idx;
    if (smid < 64) { gpc = (smid & 15) >> 1; idx = (smid >> 4) * 2 + (smid & 1); }
    else if (smid < 120) { int t = smid - 64; gpc = 1 + (t % 14) / 2; idx = 8 + (t / 14) * 2 + (smid & 1); }
    else { gpc = 0; idx = 8 + (smid - 124); }
    const int rb = 2 * gpc + (idx & 1), j = idx >> 1;
    const int g = lane >> 2, c = lane & 3;
    const int cm = 160 * (j >> 1) + 64 * (j & 1) + ((j & 2) ? 32 : 0), cr = 160 * (j >> 1) + 16 * (j & 1) + ((j & 2) ? 0 : 128);

    {
        if (warp == 5) TSW(61);
        const int w10 = warp - 10 * hb, h = w10 >= 5;
        const int pr = (w10 - 5 * h) * 8 + (lane >> 2), blk = 4 * hb + (lane & 3);
        const int ch = 2 * pr + (pr < 24 ? 48 * pg : 336 + 32 * pg);
        const uint4 sw = __ldg(reinterpret_cast<const uint4*>(p.shift + ch * 4));
        uint32_t dv = 0;
        if (warp == 9 && lane < 5) dv = __bfloat16_as_ushort(p.ssmD[chan(lane)]);
        if (tid == 512) { sts32(sb + SM_GV + 512, smid); asm volatile("fence.release.sync_restrict::shared::cta.cluster;" ::: "memory"); }
        asm volatile("barrier.cluster.arrive.relaxed.aligned;" ::: "memory");
        if (warp == 11 && lane < 13) prefetch_map(&maps.hn + lane);
        if (wg < 4) {
            const int t = tid & 127, cc = (wg == 3 && t >= 64) ? 4 : wg;
            if (t < 64 || wg == 3) sts128(sb + sm_u(cc) + ((t >> 5) & 1) * U_PLANE + 2048 + lane * 16, make_uint4(0, 0, 0, 0));
            if ((t & 63) < 4 && (t < 64 || wg == 3)) sts128(sb + sm_k(cc) + ((t >> 1) & 1) * 4160 + (t & 1) * 16, make_uint4(0, 0, 0, 0));
        }
        if (warp == 9 && lane < 5) sts32(sb + SM_GV + 520 + lane * 4, dv << 16);
        asm volatile("cp.async.wait_group 0;" ::: "memory");
        if (!hb) bar_arrive(12, 640);
        bar_sync(hb ? 12 : 14, 640);
        if (warp == 9) {
            if (SSM_DELAY) spin(SSM_DELAY);
            if (elect()) {
#pragma unroll
                for (int i = 0; i < SSM_N; i++) {
                    mbar_expect(bars + (BAR_K + i) * 8, 4096);
                    bulk_g2s(sb + sm_k(i) + 32, p.ssmk + (size_t)(chan(i)) * S_, 4096, bars + (BAR_K + i) * 8);
                }
            }
        }
        const uint32_t w0 = prmt(sw.x, sw.z, 0x5410), w1 = prmt(sw.x, sw.z, 0x7632), w2 = prmt(sw.y, sw.w, 0x5410), w3 = prmt(sw.y, sw.w, 0x7632);
        const uint32_t ka = sb + SM_PK + 2592 + blk * 2592 + h * 1280 + pr * 4;
        const uint32_t va = sb + SM_PV + blk * 2592 + h * 1280 + pr * 4;
        uint32_t kk[11], kv[8];
#pragma unroll
        for (int i = 0; i < 11; i++) kk[i] = lds32(ka + (i - 3) * 160 - ((i < 3 && h == 0) ? 32 : 0));
#pragma unroll
        for (int i = 0; i < 8; i++) {
            uint32_t t = badd2(badd2(badd2(bmul2(kk[i], w3), bmul2(kk[i + 1], w2)), bmul2(kk[i + 2], w1)), bmul2(kk[i + 3], w0));
            kv[i] = bmul2(t, lds32(va + i * 160));
        }
        uint4 o0, o1;
        o0.x = prmt(kv[1], kv[0], 0x5410); o0.y = prmt(kv[3], kv[2], 0x5410); o0.z = prmt(kv[5], kv[4], 0x5410); o0.w = prmt(kv[7], kv[6], 0x5410);
        o1.x = prmt(kv[1], kv[0], 0x7632); o1.y = prmt(kv[3], kv[2], 0x7632); o1.z = prmt(kv[5], kv[4], 0x7632); o1.w = prmt(kv[7], kv[6], 0x7632);
        uint4* dst = reinterpret_cast<uint4*>(g_kvT) + ch * 256 + h * 128 + (127 - (8 * pi + blk));
        dst[0] = o0;
        dst[256] = o1;
    }

    const int rho = 8 * rb + j;

    if (wg == 4) {
        asm volatile("setmaxnreg.dec.sync.aligned.u32 32;");
        const unsigned ep1 = __shfl_sync(0xffffffffu, ep0, 0) + 1;
        if (wq == 0) {
            bar_sync(13, 640);
            TSW(39);
            if (lane == 0) flag_release(FL_P + pg);
            __syncwarp();
            TSW(2);
            if (lane < 5) mbar_expect(bars + (BAR_U + lane) * 8, 4096);
            flag_wait(FL_P + pg, ep1 * 16);
            fence_async_global();
            TSW(3);
            if (elect()) {
#pragma unroll
                for (int i = 0; i < 5; i++) {
                    const char* us = (const char*)g_kvT + (size_t)(chan(i)) * 4096;
                    bulk_g2s(sb + sm_u(i), us, 2048, bars + (BAR_U + i) * 8);
                    bulk_g2s(sb + sm_u(i) + U_PLANE, us + 2048, 2048, bars + (BAR_U + i) * 8);
                }
            }
            __syncwarp();
            if (elect()) {
#pragma unroll
                for (int i = SSM_N; i < 5; i++) {
                    mbar_expect(bars + (BAR_K + i) * 8, 4096);
                    bulk_g2s(sb + sm_k(i) + 32, p.ssmk + (size_t)(chan(i)) * S_, 4096, bars + (BAR_K + i) * 8);
                }
                if (WMD2) spin(WMD2);
                if (cta < 120) {
                    mbar_expect(bars + BAR_WM0 * 8, 3 * 8192);
                    mbar_expect(bars + BAR_WM * 8, 2 * 8192);
#pragma unroll 1
                    for (int i = 0; i < 5; i++) tma2d(sb + SM_WM + i * 8192, &maps.wm, cta * 32, i * 128, bars + (i < 3 ? BAR_WM0 : BAR_WM) * 8);
                }
                mbar_wait(bars + (cta < 120 ? BAR_WM0 : BAR_K + 4) * 8, 0);
                bulk_prefetch((const char*)p.q + cta * 20480, 20480);
                bulk_prefetch((const char*)p.w1 + cta * 6400, 6400);
                bulk_prefetch((const char*)p.w2 + cta * 6400, 6400);
            }
            __syncwarp();
        } else {
            bar_arrive(13, 640);
        }
        asm volatile("barrier.cluster.wait.aligned;" ::: "memory");
        uint32_t peer;
        asm volatile("ld.shared::cluster.u32 %0, [%1];" : "=r"(peer) : "r"(mapa(sb + SM_GV + 512, (blockIdx.x & 1) ^ 1)) : "memory");
        const bool paired = peer == (smid ^ 1) && !FORCE_UNPAIRED;
        if (tid == 639) sts32(sb + SM_GV + 516, paired);
        if (cta < 120) {
            float d[4];
            if (tid >= 544 && tid < 624) {
                const int t = tid - 544;
                mbar_wait(bars + BAR_U * 8, 0);
                uint4 cv = __ldg(reinterpret_cast<const uint4*>(p.c) + t);
                auto silu2 = [](uint32_t v) { float a = blo(v), b = bhi(v); return pack2(__fdividef(a, 1.0f + __expf(-a)), __fdividef(b, 1.0f + __expf(-b))); };
#pragma unroll 1
                for (int i = 0; i < 4; i++) { const uint32_t r = silu2(cv.x); cv.x = cv.y; cv.y = cv.z; cv.z = cv.w; cv.w = r; }
                sts128(sb + SM_Y + (t % 40) * 32 + (t / 40) * 16, cv);
                fence_async_smem();
            }
            bar_sync(5, 128);
            mbar_wait(bars + BAR_WM0 * 8, 0);
            mbar_wait(bars + BAR_WM * 8, 0);
            if (wq == 3) TSW(56);
            const uint32_t da = desc_lo(sb + SM_WM, 20480), db = desc_lo(sb + SM_Y, 32);
#pragma unroll 1
            for (int k0 = 0; k0 < 20; k0 += 4) {
                wg_fence();
#pragma unroll
                for (int k = k0; k < k0 + 4; k++) asm volatile("{.reg .pred p; .reg .b32 l,m; .reg .b64 da,db; setp.ne.b32 p,%10,0; add.u32 l,%4,%6; mov.b64 da,{l,%8}; add.u32 m,%5,%7; mov.b64 db,{m,%9};"
                             " wgmma.mma_async.sync.aligned.m64n8k16.f32.bf16.bf16 {%0,%1,%2,%3},da,db,p,1,1,1,0;}"
                             : "+f"(d[0]), "+f"(d[1]), "+f"(d[2]), "+f"(d[3])
                             : "r"(da), "r"(db), "r"(64 * k), "r"(4 * k), "n"(desc_hi(512, 2u)), "n"(desc_hi(128, 0)), "r"(k));
                wg_commit();
            }
            wg_wait<0>();
            reg_fence<4>(d);
            if (c == 0) {
                sts32(sb + SM_GV + (16 * wq + g) * 4, __float_as_uint(wq < 2 ? d[0] : d[1]));
                sts32(sb + SM_GV + (16 * wq + g + 8) * 4, __float_as_uint(wq < 2 ? d[2] : d[3]));
            }
            bar_sync(5, 128);
            if (wq == 2) {
                g_mod[cta * 32 + lane] = __float2bfloat16_rn(__uint_as_float(lds32(sb + SM_GV + lane * 4)) + __uint_as_float(lds32(sb + SM_GV + 128 + lane * 4)));
            }
        }
        if (wq == 2) {
            bar_sync(9, 320);
            if (lane == 0) { flag_release(FL_M); mbar_expect(bars + BAR_MR * 8, 0); }
            __syncwarp();
            TSW(4);
            flag_wait(FL_M, ep1 * 128);
            fence_async_global();
            if (elect()) {
                mbar_expect(bars + BAR_M * 8, 7680);
                bulk_g2s(sb + SM_MOD, g_mod, 7680, bars + BAR_M * 8);
                mbar_wait(bars + BAR_CD * 8, 0);
                mbar_expect(bars + BAR_Y * 8, 12288);
                bulk_g2s(sb + SM_Y, g_yv + rho * 5120, 12288, bars + BAR_Y * 8);
            }
            __syncwarp();
            TSW(60);
            bar_sync(8, 576);  if (lane == 0) { flag_release(FL_R + rb); TS(23); }  __syncwarp();
            bar_sync(15, 288); if (lane == 0) { flag_release(FL_B1 + rb); TS(27); } __syncwarp();
            bar_sync(6, 288);  if (lane == 0) { flag_release(FL_B2 + rb); TS(31); } __syncwarp();
#pragma unroll 1
            for (int i = 0; i < 3; i++) { bar_sync(i ? i : 8, 288); if (lane == 0) { TS(53 + (i + 2) % 3); flag_release(FL_G + 16 * i + rb); TS(57 + (i + 2) % 3); } __syncwarp(); }
            if (lane == 0) p.epoch[smid] = ep1;
            return;
        }
        if (wq == 1) {
            bar_sync(9, 320);
            mbar_wait(bars + BAR_MR * 8, 0);
            if (lane < 4 * NB) mbar_arrive_cl(mapa(bars + (BAR_EB + (lane >> 2)) * 8, paired ? lane & 1 : blockIdx.x & 1));
        }
        if (wq == 3) {
            bar_sync(7, 544);
            if (lane == 0) { flag_release(FL_C); mbar_expect(bars + BAR_CD * 8, 0); TS(20); }
            __syncwarp();
            if (lane == 0) mbar_expect(bars + BAR_Y2 * 8, 8192);
            flag_wait(FL_C, ep1 * 128);
            fence_async_global();
            TSW(21);
            if (elect()) {
                bulk_g2s(sb + SM_Y + 12288, g_yv + rho * 5120 + 3072, 8192, bars + BAR_Y2 * 8);
            }
            __syncwarp();
        }
        if (wq == 3) {
            mbar_wait(bars + BAR_Y2 * 8, 0);
            if (elect()) {
                mbar_expect(bars + BAR_XY * 8, 20480);
#pragma unroll 1
                for (int i = 0; i < 8; i++) {
                    bulk_g2s(sb + SM_YT + i * 2560, g_yv + (8 * rb + i) * 5120 + cm * 8, 2048, bars + BAR_XY * 8);
                    bulk_g2s(sb + SM_YT + i * 2560 + 2048, g_yv + (8 * rb + i) * 5120 + cr * 8, 512, bars + BAR_XY * 8);
                }
            }
            __syncwarp();
            bar_sync(8, 576);
            mbar_wait_warm(bars + BAR_FA * 8, 0);
            mbar_wait(bars + BAR_ME * 8, 0);
            mbar_wait_warm(bars + (BAR_FA + 11 % NA) * 8, (11 / NA) & 1);
            flag_wait(FL_CS, ep1 * 4);
            fence_async_global();
            if (elect()) {
                mbar_expect(bars + BAR_CS * 8, 864);
                bulk_g2s(sb + SM_CS, g_cs + 64 * j, 256, bars + BAR_CS * 8);
                bulk_g2s(sb + SM_CS + 256, g_cs + 512 + RA3 * j, 4 * RA3, bars + BAR_CS * 8);
                bulk_g2s(sb + SM_CS + 256 + 4 * RA3, g_cs + HB0 + 64 * j, 256, bars + BAR_CS * 8);
                bulk_g2s(sb + SM_CS + 512 + 4 * RA3, g_cs + HB0 + 512 + RB3 * j, 4 * RB3, bars + BAR_CS * 8);
            }
            __syncwarp();
            mbar_wait(bars + BAR_ME * 8, 1);
            mbar_wait_warm(bars + (BAR_FA + 21 % NA) * 8, (21 / NA) & 1);
#pragma unroll 1
            for (int i = 0; i < 3; i++) {
                flag_wait(FL_G + 16 * i + rb, ep1 * 8);
                if (lane == 0) { mbar_expect(bars + (BAR_G + i) * 8, 0); TS(35 + (i + 2) % 3); }
                __syncwarp();
            }
            return;
        }
        if (elect()) {
            if (wq == 1) {
                Ring<NB, SM_RB, BAR_FB, BAR_EB> r{sb, 0, 0};
#pragma unroll 1
                for (int ph = 0; ph < 7; ph++) {
                    const CUtensorMap* ma = ph == 0 ? &maps.w1a : ph == 1 ? &maps.w2a : ph == 6 ? &maps.w4a : &maps.w3a;
                    const bool b3b = ph == 2 || ph == 4 || ph == 5;
                    r.runw(paired, idx & 1, ma, ma + (b3b ? 2 : 1), ph == 3 ? 64 * j : b3b ? HB0 + 64 * j : cm,
                           ph == 3 ? 512 + RA3 * j : b3b ? HB0 + 512 + RB3 * j : cr, ph == 4 ? 10 - NA : ph == 5 ? 1 : 0,
                           ph == 6 ? 27 : ph == 5 ? 10 - NA : ph == 2 ? 1 : 10, ph == 0 ? 0 : ph == 6 ? OWNG * (HB0 / 64 + j) : cm >> 6,
                           ph == 3 ? 8192 + 128 * RA3 : b3b ? 8192 + 128 * RB3 : 10240,
                           ph == 0 ? GATE0 : ph == 1 ? GATE : ph == 3 ? GATE - 1 : -1, bars + (ph == 0 ? BAR_Y2 : BAR_ST - (ph == 1)) * 8);
                }
            } else {
                Ring<NA, SM_RA, BAR_FA, BAR_EA> r{sb, 0, 0};
                if (cta >= 120) mbar_wait(bars + (BAR_K + 4) * 8, 0);
                mbar_expect(bars + BAR_XR * 8, 20480);
                bulk_g2s(sb + SM_XR, p.q + (size_t)rho * 16 * D_, 20480, bars + BAR_XR * 8);
                mbar_wait(bars + BAR_Y2 * 8, 0);
                mbar_expect(bars + BAR_XY * 8, 20480);
                tma2d(sb + SM_XT, &maps.xa, cm, rb * 128, bars + BAR_XY * 8);
                tma2d(sb + SM_XT2, &maps.xb, cr, rb * 128, bars + BAR_XY * 8);
                const int grp = j >> 1;
                const int delta = (grp & 1 ? 1 : -1) * (1 + (grp >> 1));
                const int nb = min(max(rb + (delta > 0 ? 1 : -1), 0), 15);
                uint32_t fb = r.acquire(SLOT), dst = r.slot();
                flag_wait2(FL_R + nb, FL_R + rb, ep1 * 8);
                fence_async_global();
                tma2d(dst, &maps.hn, 0, rb * 128 + delta, fb);
                TS(24);
                r.next();
                r.run2d(&maps.hn, rb * 128 + delta);
#pragma unroll 1
                for (int i = 0; i < 2; i++) {
                    const char* src = (const char*)(i ? g_x1 : g_h1) + (size_t)rb * 163840;
                    r.acquire(0); r.next();
                    fb = r.acquire(SLOT); dst = r.slot();
                    const char* src1 = src + (cm == 0 ? SLOT : 0);
                    flag_wait(FL_B1 + 16 * i + rb, ep1 * 8);
                    fence_async_global();
                    bulk_g2s(dst, src1, SLOT, fb);
                    TS(28 + 4 * i);
                    mbar_expect(bars + (BAR_ST - 1 + i) * 8, 0);
                    r.next();
                    r.run1d(src, 2, 10, cm >> 6);
                }
                r.run1d((const char*)g_x1 + (size_t)rb * 163840, 1, 10 - NA, cm >> 6);
                if (OWNG) { r.acquire(0); r.next(); }
#pragma unroll 1
                for (int i = 0; i < 2; i++) {
                    mbar_wait(bars + (BAR_G + 1 + i) * 8, 0); fence_async_global();
                    r.run1d((const char*)g_g + (size_t)rb * 442368, OWNG + HB0 / 64 * i, i ? 27 : OWNG + HB0 / 64, OWNG * (HB0 / 64 + j));
                }
            }
        }
        return;
    }
    bar_arrive(13, 640);
    asm volatile("setmaxnreg.inc.sync.aligned.u32 112;");
    const int rrow = 16 * rho + (warp >> 1) + 8 * (warp & 1);

    fence_async_smem();
    bar_sync(1 + wg, 128);
#pragma unroll 1
    for (int cc = wg; cc < wg + 1 + (wg == 3); cc++) {
        mbar_wait(bars + (BAR_K + cc) * 8, 0);
        if (cc == 2 && wq == 0) TSW(40);
        uint32_t a = sb + sm_k(cc) + 32 + (tid & 127) * 32;
        uint32_t pw = lds32(a - 4);
        uint4 x = lds128(a), y = lds128(a + 16), o;
        if ((tid & 127) == 0) {
            uint16_t k0 = __bfloat16_as_ushort(__float2bfloat16_rn(blo(x.x) + __uint_as_float(lds32(sb + SM_GV + 520 + cc * 4))));
            x.x = (x.x & 0xffff0000u) | k0;
            sts16(a, k0);
        }
        o.x = prmt(pw, x.x, 0x5432); o.y = prmt(x.x, x.y, 0x5432); o.z = prmt(x.y, x.z, 0x5432); o.w = prmt(x.z, x.w, 0x5432);
        sts128(a + 4160, o);
        o.x = prmt(x.w, y.x, 0x5432); o.y = prmt(y.x, y.y, 0x5432); o.z = prmt(y.y, y.z, 0x5432); o.w = prmt(y.z, y.w, 0x5432);
        sts128(a + 4176, o);
    }
    bar_sync(1 + wg, 128);
    if (wg == 3) bar_arrive(11, 256);
#pragma unroll 1
    for (int cc = wg; cc < 5; cc += 3) {
        if (cc == 3 && wg == 0) break;
        if (cc == 4) bar_sync(11, 256);
        const uint32_t kaddr = sb + sm_k(cc) + ((g & 1) ? 32 : 4192) + 4 * ((g >> 1) - c) + 64 * wq;
        const AFrag f0 = ldA(kaddr), f1 = ldA(kaddr + 256);
        if (STAG && cc == 3) bar_sync(12, 256);
        mbar_wait(bars + (BAR_U + cc) * 8, 0);
        if (wq == 0) TSW(5 + cc);
        float d[64];
        conv_two<0>(d, f0, f1, kaddr, desc_lo(sb + sm_u(cc), U_PLANE), sb + sm_red(cc) + wq * 4352 + g * 544 + c * 8, cc == 1);
        if (wq == 0) TSW(10 + cc);
        if (cc == 1) bar_arrive(6, 256);
    }
#pragma unroll 1
    for (int cc = wg == 1 ? 4 : wg;; cc++) {
        if (cc == 1) bar_sync(6, 256); else bar_sync(1 + wg, 128);
        const int ch = chan(cc);
        uint32_t* dst = g_yv + ch * 8 + ((g + (ch >> 2)) & 7) + (126 - 32 * wq - 2 * c) * 5120;
        uint2 v[16];
#pragma unroll
        for (int i = 0; i < 16; i++) v[i] = lds64(sb + sm_red(cc) + g * 544 + wq * 128 + c * 8 + (i >> 2) * 32 + (i & 3) * 4360);
#pragma unroll
        for (int w = 1; w < 4; w++)
            if (wq == 3 && c > 3 - w) v[12 + w] = make_uint2(0, 0);
#pragma unroll
        for (int q = 0; q < 4; q++) {
            const uint2* u = v + 4 * q;
            dst[-8 * q * 5120] = badd2(u[0].x, badd2(u[1].x, badd2(u[2].x, u[3].x)));
            dst[(-8 * q + 1) * 5120] = badd2(u[0].y, badd2(u[1].y, badd2(u[2].y, u[3].y)));
        }
        if (wq == 0) TSW(15 + cc);
        if (cc != 0) break;
    }
    fence_async_smem();
    if (!(wg & 1)) bar_arrive(9, 320);
    bar_arrive(7, 544);

    const uint32_t one2 = 0x3f803f80u;
    const unsigned ones = p.ones;
    {
        uint32_t x[10], a[10], cb[10], sbv[10];
        bar_sync(10, 512);
        mbar_wait(bars + BAR_XR * 8, 0);
#pragma unroll
        for (int i = 0; i < 10; i++) x[i] = lds32(sb + SM_XR + (rrow & 15) * 1280 + lane * 4 + i * 128);
        const uint3 s1 = row_stats<0>(x, lane);
        const int up = lane >> 4, gg = warp >> 1, e = warp & 1;
        const uint32_t ya = sb + SM_Y + lane * 64 + ((gg + (lane >> 1)) & 7) * 4;
        const uint32_t sel = (up ? 0x1054u : 0x5410u) + (e ? 0x2222u : 0u);
        const uint32_t ma = sb + SM_MOD + lane * 4;
        mbar_wait(bars + BAR_M * 8, 0);
        uint32_t pin = 0;
#pragma unroll
        for (int i = 0; i < 10; i++) {
            uint32_t h = bfma2(ln_apply(x[i], s1.x, s1.y, s1.z), badd2(lds32(ma + 1280 + i * 128), one2), lds32(ma + i * 128));
            a[i] = bmul2(h, lds32(ma + 2560 + i * 128));
            sbv[i] = lds32(ma + 3840 + i * 128);
            cb[i] = badd2(lds32(ma + 5120 + i * 128), one2);
            pin ^= a[i] ^ cb[i];
        }
        if (pin & ~ones) sts32(sb + SM_GV, pin);
        if (warp == 4) TSW(52);
        mbar_wait(bars + BAR_Y * 8, 0);
        RowSum part;
#pragma unroll
        for (int i = 0; i < 10; i++) {
            if (i == 6) {
                if ((__float_as_uint(part.s + part.s_ + part.q + part.q_) & ~ones)) sts32(sb + SM_GV, pin);
                mbar_wait(bars + BAR_Y2 * 8, 0);
                if (warp == 0) TSW(22);
            }
            uint32_t y0 = lds32(ya + i * 2048 + up * 32), y1 = lds32(ya + i * 2048 + (up ^ 1) * 32);
            x[i] = bfma2(a[i], prmt(y0, y1, sel), x[i]);
            if (i < 6) part.add(x[i]);
        }
        const uint3 s2 = row_stats<6>(x, lane, part);
#pragma unroll
        for (int i = 0; i < 10; i++) x[i] = bfma2(ln_apply(x[i], s2.x, s2.y, s2.z), cb[i], sbv[i]);
        const uint3 s3 = row_stats<0>(x, lane);
        uint32_t* o = reinterpret_cast<uint32_t*>(g_hn + (size_t)rrow * D_) + lane;
#pragma unroll
        for (int i = 0; i < 10; i++) o[32 * i] = ln_apply(x[i], s3.x, s3.y, s3.z);
        if (lane < 2) g_rs[rrow * 2 + lane] = lane ? make_uint4(s2.x, s2.y, s2.z, 0) : make_uint4(s1.x, s1.y, s1.z, 0);
        if (warp == 0) TSW(34);
        bar_arrive(8, 576);
    }

    const int half = wg & 1;
    const int row = 64 * half + 16 * wq + g;
    const int tw0 = (rb * 80 + (cm >> 3)) * 512 + row * 4 + c, tw1 = (rb * 80 + (cr >> 3) - 8) * 512 + row * 4 + c;
    const uint32_t park = sb + SM_Y + (tid & 255) * 16;
    const uint32_t ms0 = sb + SM_MOD + (cm + 2 * c) * 2, ms1 = sb + SM_MOD + (cr - 64 + 2 * c) * 2;
    if (wg >= 2) {
        {
            float acc[40];
            gemm_loop<80, true, 10, 10, true>(acc, sb, half, 0, 0, 10, 0, 0, 25);
            if (tid == 256) mbar_expect(bars + BAR_ME * 8, 0);
#pragma unroll
            for (int k = 0; k < 10; k += CH) CHUNK(k) {
#pragma unroll
                for (int q = k; q < k + CH && q < 10; q++) {
                    uint32_t* dst = reinterpret_cast<uint32_t*>(g_h1) + (q < 8 ? tw0 : tw1);
                    const uint32_t u = gelu2_h(bmul2(pack2(acc[4 * q], acc[4 * q + 1]), 0x3f003f00u));
                    const uint32_t v = gelu2_h(bmul2(pack2(acc[4 * q + 2], acc[4 * q + 3]), 0x3f003f00u));
                    dst[q * 512] = u;
                    dst[q * 512 + 32] = v;
                    acc[4 * q] = __uint_as_float(u); acc[4 * q + 1] = __uint_as_float(v);
                }
            }
            bar_arrive(15, 288);
            mbar_wait(bars + (BAR_FA + 10 % NA) * 8, (10 / NA) & 1);
#pragma unroll
            for (int q = 0; q < 8; q++) {
                sts32(sb + SM_RA + (10 % NA) * SLOT + q * 2048 + row * 16 + c * 4, __float_as_uint(acc[4 * q]));
                sts32(sb + SM_RA + (10 % NA) * SLOT + q * 2048 + row * 16 + c * 4 + 128, __float_as_uint(acc[4 * q + 1]));
            }
            fence_async_smem();
            bar_arrive(14, 512);
        }
        gemm3<0>(sb, rb, j, half, row, c, ones);
        {
            float acc[40];
            uint32_t gbv[10], base[20];
#pragma unroll
            for (int q = 0; q < 10; q++) gbv[q] = lds32((q < 8 ? ms0 : ms1) + 6400 + q * 16);
#pragma unroll
            for (int q = 0; q < 5; q++) { const uint4 t = lds128(park + q * 4096); base[4 * q] = t.x; base[4 * q + 1] = t.y; base[4 * q + 2] = t.z; base[4 * q + 3] = t.w; }
            gemm_loop<80, false, 27, 27 - NB, true>(acc, sb, half, 39 - NA, 40, 27 - NA, 11, 0, 42);
            auto fin = [&](int q, int r) {
                return bfma2(gbv[q], pack2(acc[4 * q + 2 * r], acc[4 * q + 2 * r + 1]), base[2 * q + r]);
            };
            auto tr4 = [&](uint32_t t0, uint32_t t1, uint32_t t2, uint32_t t3) {
                const bool o1 = c & 1, o2 = c & 2;
                uint32_t a = __shfl_xor_sync(0xffffffffu, o1 ? t0 : t1, 1), b = __shfl_xor_sync(0xffffffffu, o1 ? t2 : t3, 1);
                uint32_t u0 = o1 ? a : t0, u1 = o1 ? t1 : a, u2 = o1 ? b : t2, u3 = o1 ? t3 : b;
                a = __shfl_xor_sync(0xffffffffu, o2 ? u0 : u2, 2); b = __shfl_xor_sync(0xffffffffu, o2 ? u1 : u3, 2);
                return o2 ? make_uint4(a, b, u2, u3) : make_uint4(u0, u1, a, b);
            };
            bf16* go = p.out + (size_t)(rb * 128 + row) * D_;
#pragma unroll
            for (int k = 0; k < 2; k++) CHUNK(k) {
#pragma unroll
                for (int r = 0; r < 2; r++)
                    *reinterpret_cast<uint4*>(go + r * 8 * D_ + cm + 32 * k + 8 * c) = tr4(fin(4 * k, r), fin(4 * k + 1, r), fin(4 * k + 2, r), fin(4 * k + 3, r));
            }
            CHUNK(2) *reinterpret_cast<uint4*>(go + (c >> 1) * 8 * D_ + cr + 8 * (c & 1)) = tr4(fin(8, 0), fin(9, 0), fin(8, 1), fin(9, 1));
            if (tid == 256) TS(44);
            if (warp == 8) TSFLUSH();
        }
    } else {
        {
            float acc[40];
            uint32_t x2[20];
            {
                uint32_t y[20];
                mbar_wait(bars + BAR_XY * 8, 0);
                const uint32_t xa = sb + SM_XT + row * 128 + c * 4, xb = sb + SM_XT2 + row * 32 + c * 4;
                const uint32_t ya = sb + SM_YT + (4 * half + wq) * 2560 + c * 64;
#pragma unroll
                for (int q = 0; q < 10; q++) {
                    const uint32_t a = q < 8 ? xa + ((q ^ g) << 4) : xb + (q - 8) * 16;
                    x2[2 * q] = lds32(a); x2[2 * q + 1] = lds32(a + (q < 8 ? 1024 : 256));
                    const int pos = (g + ((q < 8 ? cm : cr) >> 2) + 2 * q + (c >> 1)) & 7;
                    y[2 * q] = lds32(ya + q * 256 + pos * 4); y[2 * q + 1] = lds32(ya + q * 256 + 32 + pos * 4);
                }
                fence_async_smem();
                bar_sync(1 + wg, 128);
                if ((tid & 127) < NA) mbar_arrive_cl(mapa(bars + (BAR_EA + (tid & 127)) * 8, blockIdx.x & 1));
                mbar_wait(bars + (BAR_FA + 1) * 8, 0);
                const uint4* rp = g_rs + (rb * 128 + row) * 2;
                const uint4 ra = ldcg128(rp), rb2 = ldcg128(rp + 1), rc = ldcg128(rp + 16), rd = ldcg128(rp + 17);
                bar_sync(14, 512);
#pragma unroll
                for (int q = 0; q < 10; q++) {
                    const uint32_t ms = q < 8 ? ms0 : ms1;
                    const uint32_t sa = lds32(ms + 16 * q), ca = badd2(lds32(ms + 1280 + 16 * q), one2), ga = lds32(ms + 2560 + 16 * q);
                    const uint32_t sbv = lds32(ms + 3840 + 16 * q), cb = badd2(lds32(ms + 5120 + 16 * q), one2);
                    uint32_t u = x2[2 * q], v = x2[2 * q + 1];
                    u = bfma2(bmul2(bfma2(ln_apply(u, ra.x, ra.y, ra.z), ca, sa), ga), prmt(y[2 * q], y[2 * q + 1], 0x5410), u);
                    v = bfma2(bmul2(bfma2(ln_apply(v, rc.x, rc.y, rc.z), ca, sa), ga), prmt(y[2 * q], y[2 * q + 1], 0x7632), v);
                    x2[2 * q] = u; x2[2 * q + 1] = v;
                    u = bfma2(ln_apply(u, rb2.x, rb2.y, rb2.z), cb, sbv);
                    v = bfma2(ln_apply(v, rd.x, rd.y, rd.z), cb, sbv);
                    acc[4 * q] = blo(u); acc[4 * q + 1] = bhi(u); acc[4 * q + 2] = blo(v); acc[4 * q + 3] = bhi(v);
                }
            }
            reg_fence<40>(acc);
            if (tid == 0) TS(45);
            gemm_loop<80, false, 10, 10, false>(acc, sb, half, 10, 10, 10, 0, 0, 29);
            if (tid == 0) mbar_expect(bars + BAR_ME * 8, 0);
            uint32_t x1[20];
            float s0 = 0.f, q0 = 0.f, s1 = 0.f, q1 = 0.f;
#pragma unroll
            for (int q = 0; q < 10; q++) {
                uint32_t u = pack2(acc[4 * q], acc[4 * q + 1]);
                uint32_t v = pack2(acc[4 * q + 2], acc[4 * q + 3]);
                uint32_t* dst = reinterpret_cast<uint32_t*>(g_x1) + (q < 8 ? tw0 : tw1);
                dst[q * 512] = u;
                dst[q * 512 + 32] = v;
                x1[2 * q] = u; x1[2 * q + 1] = v;
            }
            bar_arrive(6, 288);
            CHUNK(0)
#pragma unroll
            for (int q = 0; q < 10; q++) {
                float a = blo(x1[2 * q]), b = bhi(x1[2 * q]), e = blo(x1[2 * q + 1]), f = bhi(x1[2 * q + 1]);
                s0 += a + b; q0 = fmaf(a, a, fmaf(b, b, q0));
                s1 += e + f; q1 = fmaf(e, e, fmaf(f, f, q1));
            }
#pragma unroll
            for (int m = 1; m <= 2; m <<= 1) {
                s0 += __shfl_xor_sync(0xffffffffu, s0, m); q0 += __shfl_xor_sync(0xffffffffu, q0, m);
                s1 += __shfl_xor_sync(0xffffffffu, s1, m); q1 += __shfl_xor_sync(0xffffffffu, q1, m);
            }
            if (c < 2) g_st[(rb * 8 + j) * 128 + row + 8 * c] = c ? make_float2(s1, q1) : make_float2(s0, q0);
            bar_arrive(8, 288);
            mbar_wait(bars + (BAR_FA + 20 % NA) * 8, (20 / NA) & 1);
#pragma unroll
            for (int q = 0; q < 8; q++) {
                sts32(sb + SM_RA + (20 % NA) * SLOT + q * 2048 + row * 16 + c * 4, x1[2 * q]);
                sts32(sb + SM_RA + (20 % NA) * SLOT + q * 2048 + row * 16 + c * 4 + 128, x1[2 * q + 1]);
            }
            fence_async_smem();
            bar_sync(3 + wg, 128);
#pragma unroll
            for (int q = 0; q < 5; q++) {
                const uint32_t ms = q < 4 ? ms0 : ms1;
                const uint32_t g0 = lds32(ms + 6400 + q * 32), g1 = lds32(ms + 6400 + q * 32 + 16);
                sts128(park + q * 4096, make_uint4(bfma2(g0, x1[4 * q], x2[4 * q]), bfma2(g0, x1[4 * q + 1], x2[4 * q + 1]),
                                                   bfma2(g1, x1[4 * q + 2], x2[4 * q + 2]), bfma2(g1, x1[4 * q + 3], x2[4 * q + 3])));
            }
        }
        gemm3<1>(sb, rb, j, half, row, c, ones);
    }
}

typedef CUresult (*EncFn)(CUtensorMap*, CUtensorMapDataType, cuuint32_t, void*, const cuuint64_t*, const cuuint64_t*,
                          const cuuint32_t*, const cuuint32_t*, CUtensorMapInterleave, CUtensorMapSwizzle,
                          CUtensorMapL2promotion, CUtensorMapFloatOOBfill);

void make_map(EncFn enc, CUtensorMap* m, const void* base, uint64_t inner, uint64_t outer, uint32_t bi, uint32_t bo,
              CUtensorMapSwizzle swz = CU_TENSOR_MAP_SWIZZLE_128B) {
    cuuint64_t dims[2] = {inner, outer};
    cuuint64_t st[1] = {inner * 2};
    cuuint32_t box[2] = {bi, bo};
    cuuint32_t es[2] = {1, 1};
    enc(m, CU_TENSOR_MAP_DATA_TYPE_BFLOAT16, 2, const_cast<void*>(base), dims, st, box, es, CU_TENSOR_MAP_INTERLEAVE_NONE,
        swz, CU_TENSOR_MAP_L2_PROMOTION_NONE, CU_TENSOR_MAP_FLOAT_OOB_FILL_NONE);
}

}

extern "C" void kernel_launch(void* const* d_in, const int* in_sizes, int n_in, void* d_out, int out_size) {
    (void)in_sizes; (void)n_in; (void)out_size;
    Params p;
    p.q = (const bf16*)d_in[0]; p.k = (const bf16*)d_in[1]; p.v = (const bf16*)d_in[2];
    p.shift = (const bf16*)d_in[3]; p.ssmk = (const bf16*)d_in[4]; p.ssmD = (const bf16*)d_in[5];
    p.w1 = (const bf16*)d_in[7]; p.w2 = (const bf16*)d_in[8]; p.w3 = (const bf16*)d_in[9]; p.w4 = (const bf16*)d_in[10];
    p.c = (const bf16*)d_in[11]; p.wmod = (const bf16*)d_in[12];
    p.out = (bf16*)d_out;
    p.ones = 0xffffffffu;
    cudaGetSymbolAddress((void**)&p.epoch, g_epoch);

    void* fn = nullptr;
    cudaDriverEntryPointQueryResult qr;
    cudaGetDriverEntryPoint("cuTensorMapEncodeTiled", &fn, cudaEnableDefault, &qr);
    EncFn enc = (EncFn)fn;
    void* hn = nullptr;
    cudaGetSymbolAddress(&hn, g_hn);
    Maps maps;
    make_map(enc, &maps.w3s, p.w3, F_, D_, 216, 64, CU_TENSOR_MAP_SWIZZLE_NONE);
    make_map(enc, &maps.wm, p.wmod, 6 * D_, D_, 32, 128, CU_TENSOR_MAP_SWIZZLE_64B);
    make_map(enc, &maps.xa, p.q, D_, S_, 64, 128);
    make_map(enc, &maps.xb, p.q, D_, S_, 16, 128, CU_TENSOR_MAP_SWIZZLE_NONE);
    make_map(enc, &maps.hn, hn, D_, S_, 64, 128);
    make_map(enc, &maps.w1a, p.w1, D_, D_, 64, 64);
    make_map(enc, &maps.w1b, p.w1, D_, D_, 16, 64);
    make_map(enc, &maps.w2a, p.w2, D_, D_, 64, 64);
    make_map(enc, &maps.w2b, p.w2, D_, D_, 16, 64);
    make_map(enc, &maps.w3a, p.w3, F_, D_, 64, 64);
    make_map(enc, &maps.w3b, p.w3, F_, D_, RA3, 64);
    make_map(enc, &maps.w3c, p.w3, F_, D_, RB3, 64);
    make_map(enc, &maps.w4a, p.w4, D_, F_, 64, 64);
    make_map(enc, &maps.w4b, p.w4, D_, F_, 16, 64);
    cudaFuncSetAttribute(fused_kernel, cudaFuncAttributeMaxDynamicSharedMemorySize, SMEM_BYTES);
    fused_kernel<<<132, NTHREADS, SMEM_BYTES>>>(p, maps);
}
```

```cpp
#include <cuda_runtime.h>
#include <cuda_bf16.h>
#include <cuda.h>
#include <stdint.h>
#include <string.h>

#define SEED 2
#define RING_A 6
#define CH 2
#define FAST_LN 2
#define STAG 12
#define PGELU 2
#define CH3 4
#define HO_A 16
#define HO_B 16
#define RA3 48
#define CSP 16
#define OWNG 1
#define GATE 5
#define SSM_DELAY 100
#define B_DELAY 220
#define PING 250
#define FORCE_UNPAIRED 0
#define GATE0 3
#define SPD 800
#define WMD2 600
#define SSM_N 3

namespace {

typedef __nv_bfloat16 bf16;
typedef __nv_bfloat162 bf162;

constexpr int S_ = 2048, D_ = 640, F_ = 1728;
constexpr int NTHREADS = 640;
constexpr int NA = RING_A, NB = 12 - RING_A;
constexpr int SLOT = 16384;
constexpr int RB3 = 88 - RA3, HB0 = 512 + 8 * RA3;
constexpr int SM_RA = 0, SM_RB = NA * SLOT;

static_assert(NA == 6, "smem map");
constexpr int RED_STRIDE = 17536;
constexpr int K_STRIDE = 8320;
constexpr int U_PLANE = 2560, U_STRIDE = 5120;
constexpr int SM_Y = 12 * SLOT;
__device__ __forceinline__ int sm_red(int cc) { return cc * RED_STRIDE + (cc < 3 ? SM_RB : -3 * RED_STRIDE); }
__device__ __forceinline__ int sm_k(int cc) { return cc * K_STRIDE + (cc < 3 ? SM_RB + 3 * RED_STRIDE : 2 * RED_STRIDE - 3 * K_STRIDE); }
__device__ __forceinline__ int sm_u(int cc) { return cc * U_STRIDE + (cc < 3 ? SM_RB + 3 * RED_STRIDE + 3 * K_STRIDE : SM_Y + 8192 - 3 * U_STRIDE); }
constexpr int SM_PK = SM_RB;
constexpr int SM_PV = SM_RB + 24576;
constexpr int SM_WM = 57344;
constexpr int SM_XT = SM_WM, SM_XT2 = SM_WM + 16384, SM_XR = SM_WM + 20480;
constexpr int SM_YT = 0;
constexpr int SM_MOD = SM_Y + 20480;
constexpr int SM_GV = SM_MOD + 7680;
constexpr int SM_CS = SM_GV + 1024;
constexpr int SM_RP = SM_CS + 1024;
constexpr int SM_BAR = SM_RP + 1024;
constexpr int SM_PROF = SM_BAR + 512;
constexpr int SM_TOTAL = SM_PROF + 512;
constexpr int SMEM_BYTES = SM_TOTAL + 1024;
static_assert(SMEM_BYTES <= 232448, "smem");

constexpr int BAR_FA = 0, BAR_FB = NA, BAR_EA = 12, BAR_EB = 12 + NA, BAR_K = 24, BAR_U = 29, BAR_Y = 34, BAR_CS = 35, BAR_WM = 36, BAR_M = 37, BAR_XY = 38, BAR_Y2 = 39, BAR_G = 40, BAR_ST = 44, BAR_XR = 45, BAR_ME = 46, BAR_CD = 47, BAR_WM0 = 48, BAR_MR = 49, BAR_MC = 50, NBARS = 51;

__device__ __align__(1024) bf16 g_kvT[D_ * S_];
__device__ __align__(1024) uint32_t g_yv[128 * 5120];
__device__ __align__(1024) bf16 g_mod[6 * D_];
__device__ __align__(1024) bf16 g_hn[S_ * D_];
__device__ __align__(1024) uint4 g_rs[S_ * 2];
__device__ __align__(1024) bf16 g_h1[S_ * D_];
__device__ __align__(1024) bf16 g_x1[S_ * D_];
__device__ __align__(1024) bf16 g_g[S_ * F_];
__device__ __align__(1024) float2 g_st[S_ * 8];
__device__ __align__(1024) float g_cs[F_];
__device__ __align__(1024) unsigned g_flags[128 * 32];
__device__ __align__(1024) unsigned g_epoch[160];
constexpr int FL_P = 0, FL_C = 8, FL_CS = 9, FL_M = 10, FL_R = 16, FL_B1 = 32, FL_B2 = 48, FL_G = 64;

#define TS(i) do {} while (0)
#define TSW(i) do {} while (0)
#define TSD(i, dep) do {} while (0)
#define TSD2(i, dep) do {} while (0)
#define TSFLUSH() do {} while (0)

struct Params {
    const bf16 *q, *k, *v, *shift, *ssmk, *ssmD, *w1, *w2, *w3, *w4, *c, *wmod;
    bf16* out;
    unsigned* epoch;
    unsigned ones;
};
#define CHUNK(k) if (ones & (1u << (k)))
struct Maps { CUtensorMap hn, w1a, w1b, w2a, w2b, w3a, w3b, w3c, w4a, w4b, wm, xa, xb, w3s; };

template<int N> struct WgRs;
template<int N> struct WgSs;
template<> struct WgRs<32> { template<int OFF,int HI,int SC> static __device__ __forceinline__ void run(float* d,uint32_t a0,uint32_t a1,uint32_t a2,uint32_t a3,uint32_t blo){
 asm volatile("{.reg .b32 l; .reg .b64 db; add.u32 l,%20,%21; mov.b64 db,{l,%22}; wgmma.mma_async.sync.aligned.m64n32k16.f32.bf16.bf16 {%0,%1,%2,%3,%4,%5,%6,%7,%8,%9,%10,%11,%12,%13,%14,%15},{%16,%17,%18,%19},db,%23,1,1,0;}"
 :"+f"(d[0]),"+f"(d[1]),"+f"(d[2]),"+f"(d[3]),"+f"(d[4]),"+f"(d[5]),"+f"(d[6]),"+f"(d[7]),"+f"(d[8]),"+f"(d[9]),"+f"(d[10]),"+f"(d[11]),"+f"(d[12]),"+f"(d[13]),"+f"(d[14]),"+f"(d[15])
 :"r"(a0),"r"(a1),"r"(a2),"r"(a3),"r"(blo),"n"(OFF),"n"(HI),"n"(SC)); } };
template<> struct WgRs<48> { template<int OFF,int HI,int SC> static __device__ __forceinline__ void run(float* d,uint32_t a0,uint32_t a1,uint32_t a2,uint32_t a3,uint32_t blo){
 asm volatile("{.reg .b32 l; .reg .b64 db; add.u32 l,%28,%29; mov.b64 db,{l,%30}; wgmma.mma_async.sync.aligned.m64n48k16.f32.bf16.bf16 {%0,%1,%2,%3,%4,%5,%6,%7,%8,%9,%10,%11,%12,%13,%14,%15,%16,%17,%18,%19,%20,%21,%22,%23},{%24,%25,%26,%27},db,%31,1,1,0;}"
 :"+f"(d[0]),"+f"(d[1]),"+f"(d[2]),"+f"(d[3]),"+f"(d[4]),"+f"(d[5]),"+f"(d[6]),"+f"(d[7]),"+f"(d[8]),"+f"(d[9]),"+f"(d[10]),"+f"(d[11]),"+f"(d[12]),"+f"(d[13]),"+f"(d[14]),"+f"(d[15]),"+f"(d[16]),"+f"(d[17]),"+f"(d[18]),"+f"(d[19]),"+f"(d[20]),"+f"(d[21]),"+f"(d[22]),"+f"(d[23])
 :"r"(a0),"r"(a1),"r"(a2),"r"(a3),"r"(blo),"n"(OFF),"n"(HI),"n"(SC)); } };
template<> struct WgRs<64> { template<int OFF,int HI,int SC> static __device__ __forceinline__ void run(float* d,uint32_t a0,uint32_t a1,uint32_t a2,uint32_t a3,uint32_t blo){
 asm volatile("{.reg .b32 l; .reg .b64 db; add.u32 l,%36,%37; mov.b64 db,{l,%38}; wgmma.mma_async.sync.aligned.m64n64k16.f32.bf16.bf16 {%0,%1,%2,%3,%4,%5,%6,%7,%8,%9,%10,%11,%12,%13,%14,%15,%16,%17,%18,%19,%20,%21,%22,%23,%24,%25,%26,%27,%28,%29,%30,%31},{%32,%33,%34,%35},db,%39,1,1,0;}"
 :"+f"(d[0]),"+f"(d[1]),"+f"(d[2]),"+f"(d[3]),"+f"(d[4]),"+f"(d[5]),"+f"(d[6]),"+f"(d[7]),"+f"(d[8]),"+f"(d[9]),"+f"(d[10]),"+f"(d[11]),"+f"(d[12]),"+f"(d[13]),"+f"(d[14]),"+f"(d[15]),"+f"(d[16]),"+f"(d[17]),"+f"(d[18]),"+f"(d[19]),"+f"(d[20]),"+f"(d[21]),"+f"(d[22]),"+f"(d[23]),"+f"(d[24]),"+f"(d[25]),"+f"(d[26]),"+f"(d[27]),"+f"(d[28]),"+f"(d[29]),"+f"(d[30]),"+f"(d[31])
 :"r"(a0),"r"(a1),"r"(a2),"r"(a3),"r"(blo),"n"(OFF),"n"(HI),"n"(SC)); } };
template<> struct WgRs<80> { template<int OFF,int HI,int SC> static __device__ __forceinline__ void run(float* d,uint32_t a0,uint32_t a1,uint32_t a2,uint32_t a3,uint32_t blo){
 asm volatile("{.reg .b32 l; .reg .b64 db; add.u32 l,%44,%45; mov.b64 db,{l,%46}; wgmma.mma_async.sync.aligned.m64n80k16.f32.bf16.bf16 {%0,%1,%2,%3,%4,%5,%6,%7,%8,%9,%10,%11,%12,%13,%14,%15,%16,%17,%18,%19,%20,%21,%22,%23,%24,%25,%26,%27,%28,%29,%30,%31,%32,%33,%34,%35,%36,%37,%38,%39},{%40,%41,%42,%43},db,%47,1,1,0;}"
 :"+f"(d[0]),"+f"(d[1]),"+f"(d[2]),"+f"(d[3]),"+f"(d[4]),"+f"(d[5]),"+f"(d[6]),"+f"(d[7]),"+f"(d[8]),"+f"(d[9]),"+f"(d[10]),"+f"(d[11]),"+f"(d[12]),"+f"(d[13]),"+f"(d[14]),"+f"(d[15]),"+f"(d[16]),"+f"(d[17]),"+f"(d[18]),"+f"(d[19]),"+f"(d[20]),"+f"(d[21]),"+f"(d[22]),"+f"(d[23]),"+f"(d[24]),"+f"(d[25]),"+f"(d[26]),"+f"(d[27]),"+f"(d[28]),"+f"(d[29]),"+f"(d[30]),"+f"(d[31]),"+f"(d[32]),"+f"(d[33]),"+f"(d[34]),"+f"(d[35]),"+f"(d[36]),"+f"(d[37]),"+f"(d[38]),"+f"(d[39])
 :"r"(a0),"r"(a1),"r"(a2),"r"(a3),"r"(blo),"n"(OFF),"n"(HI),"n"(SC)); } };
template<> struct WgRs<96> { template<int OFF,int HI,int SC> static __device__ __forceinline__ void run(float* d,uint32_t a0,uint32_t a1,uint32_t a2,uint32_t a3,uint32_t blo){
 asm volatile("{.reg .b32 l; .reg .b64 db; add.u32 l,%52,%53; mov.b64 db,{l,%54}; wgmma.mma_async.sync.aligned.m64n96k16.f32.bf16.bf16 {%0,%1,%2,%3,%4,%5,%6,%7,%8,%9,%10,%11,%12,%13,%14,%15,%16,%17,%18,%19,%20,%21,%22,%23,%24,%25,%26,%27,%28,%29,%30,%31,%32,%33,%34,%35,%36,%37,%38,%39,%40,%41,%42,%43,%44,%45,%46,%47},{%48,%49,%50,%51},db,%55,1,1,0;}"
 :"+f"(d[0]),"+f"(d[1]),"+f"(d[2]),"+f"(d[3]),"+f"(d[4]),"+f"(d[5]),"+f"(d[6]),"+f"(d[7]),"+f"(d[8]),"+f"(d[9]),"+f"(d[10]),"+f"(d[11]),"+f"(d[12]),"+f"(d[13]),"+f"(d[14]),"+f"(d[15]),"+f"(d[16]),"+f"(d[17]),"+f"(d[18]),"+f"(d[19]),"+f"(d[20]),"+f"(d[21]),"+f"(d[22]),"+f"(d[23]),"+f"(d[24]),"+f"(d[25]),"+f"(d[26]),"+f"(d[27]),"+f"(d[28]),"+f"(d[29]),"+f"(d[30]),"+f"(d[31]),"+f"(d[32]),"+f"(d[33]),"+f"(d[34]),"+f"(d[35]),"+f"(d[36]),"+f"(d[37]),"+f"(d[38]),"+f"(d[39]),"+f"(d[40]),"+f"(d[41]),"+f"(d[42]),"+f"(d[43]),"+f"(d[44]),"+f"(d[45]),"+f"(d[46]),"+f"(d[47])
 :"r"(a0),"r"(a1),"r"(a2),"r"(a3),"r"(blo),"n"(OFF),"n"(HI),"n"(SC)); } };
template<> struct WgRs<112> { template<int OFF,int HI,int SC> static __device__ __forceinline__ void run(float* d,uint32_t a0,uint32_t a1,uint32_t a2,uint32_t a3,uint32_t blo){
 asm volatile("{.reg .b32 l; .reg .b64 db; add.u32 l,%60,%61; mov.b64 db,{l,%62}; wgmma.mma_async.sync.aligned.m64n112k16.f32.bf16.bf16 {%0,%1,%2,%3,%4,%5,%6,%7,%8,%9,%10,%11,%12,%13,%14,%15,%16,%17,%18,%19,%20,%21,%22,%23,%24,%25,%26,%27,%28,%29,%30,%31,%32,%33,%34,%35,%36,%37,%38,%39,%40,%41,%42,%43,%44,%45,%46,%47,%48,%49,%50,%51,%52,%53,%54,%55},{%56,%57,%58,%59},db,%63,1,1,0;}"
 :"+f"(d[0]),"+f"(d[1]),"+f"(d[2]),"+f"(d[3]),"+f"(d[4]),"+f"(d[5]),"+f"(d[6]),"+f"(d[7]),"+f"(d[8]),"+f"(d[9]),"+f"(d[10]),"+f"(d[11]),"+f"(d[12]),"+f"(d[13]),"+f"(d[14]),"+f"(d[15]),"+f"(d[16]),"+f"(d[17]),"+f"(d[18]),"+f"(d[19]),"+f"(d[20]),"+f"(d[21]),"+f"(d[22]),"+f"(d[23]),"+f"(d[24]),"+f"(d[25]),"+f"(d[26]),"+f"(d[27]),"+f"(d[28]),"+f"(d[29]),"+f"(d[30]),"+f"(d[31]),"+f"(d[32]),"+f"(d[33]),"+f"(d[34]),"+f"(d[35]),"+f"(d[36]),"+f"(d[37]),"+f"(d[38]),"+f"(d[39]),"+f"(d[40]),"+f"(d[41]),"+f"(d[42]),"+f"(d[43]),"+f"(d[44]),"+f"(d[45]),"+f"(d[46]),"+f"(d[47]),"+f"(d[48]),"+f"(d[49]),"+f"(d[50]),"+f"(d[51]),"+f"(d[52]),"+f"(d[53]),"+f"(d[54]),"+f"(d[55])
 :"r"(a0),"r"(a1),"r"(a2),"r"(a3),"r"(blo),"n"(OFF),"n"(HI),"n"(SC)); } };
template<> struct WgRs<128> { template<int OFF,int HI,int SC> static __device__ __forceinline__ void run(float* d,uint32_t a0,uint32_t a1,uint32_t a2,uint32_t a3,uint32_t blo){
 asm volatile("{.reg .b32 l; .reg .b64 db; add.u32 l,%68,%69; mov.b64 db,{l,%70}; wgmma.mma_async.sync.aligned.m64n128k16.f32.bf16.bf16 {%0,%1,%2,%3,%4,%5,%6,%7,%8,%9,%10,%11,%12,%13,%14,%15,%16,%17,%18,%19,%20,%21,%22,%23,%24,%25,%26,%27,%28,%29,%30,%31,%32,%33,%34,%35,%36,%37,%38,%39,%40,%41,%42,%43,%44,%45,%46,%47,%48,%49,%50,%51,%52,%53,%54,%55,%56,%57,%58,%59,%60,%61,%62,%63},{%64,%65,%66,%67},db,%71,1,1,0;}"
 :"+f"(d[0]),"+f"(d[1]),"+f"(d[2]),"+f"(d[3]),"+f"(d[4]),"+f"(d[5]),"+f"(d[6]),"+f"(d[7]),"+f"(d[8]),"+f"(d[9]),"+f"(d[10]),"+f"(d[11]),"+f"(d[12]),"+f"(d[13]),"+f"(d[14]),"+f"(d[15]),"+f"(d[16]),"+f"(d[17]),"+f"(d[18]),"+f"(d[19]),"+f"(d[20]),"+f"(d[21]),"+f"(d[22]),"+f"(d[23]),"+f"(d[24]),"+f"(d[25]),"+f"(d[26]),"+f"(d[27]),"+f"(d[28]),"+f"(d[29]),"+f"(d[30]),"+f"(d[31]),"+f"(d[32]),"+f"(d[33]),"+f"(d[34]),"+f"(d[35]),"+f"(d[36]),"+f"(d[37]),"+f"(d[38]),"+f"(d[39]),"+f"(d[40]),"+f"(d[41]),"+f"(d[42]),"+f"(d[43]),"+f"(d[44]),"+f"(d[45]),"+f"(d[46]),"+f"(d[47]),"+f"(d[48]),"+f"(d[49]),"+f"(d[50]),"+f"(d[51]),"+f"(d[52]),"+f"(d[53]),"+f"(d[54]),"+f"(d[55]),"+f"(d[56]),"+f"(d[57]),"+f"(d[58]),"+f"(d[59]),"+f"(d[60]),"+f"(d[61]),"+f"(d[62]),"+f"(d[63])
 :"r"(a0),"r"(a1),"r"(a2),"r"(a3),"r"(blo),"n"(OFF),"n"(HI),"n"(SC)); } };
template<> struct WgSs<80> { template<int AOFF,int AHI,int BOFF,int BHI,int SC> static __device__ __forceinline__ void run(float* d,uint32_t alo,uint32_t blo){
 asm volatile("{.reg .b32 l,m; .reg .b64 da,db; add.u32 l,%40,%42; mov.b64 da,{l,%43}; add.u32 m,%41,%44; mov.b64 db,{m,%45}; wgmma.mma_async.sync.aligned.m64n80k16.f32.bf16.bf16 {%0,%1,%2,%3,%4,%5,%6,%7,%8,%9,%10,%11,%12,%13,%14,%15,%16,%17,%18,%19,%20,%21,%22,%23,%24,%25,%26,%27,%28,%29,%30,%31,%32,%33,%34,%35,%36,%37,%38,%39},da,db,%46,1,1,0,1;}"
 :"+f"(d[0]),"+f"(d[1]),"+f"(d[2]),"+f"(d[3]),"+f"(d[4]),"+f"(d[5]),"+f"(d[6]),"+f"(d[7]),"+f"(d[8]),"+f"(d[9]),"+f"(d[10]),"+f"(d[11]),"+f"(d[12]),"+f"(d[13]),"+f"(d[14]),"+f"(d[15]),"+f"(d[16]),"+f"(d[17]),"+f"(d[18]),"+f"(d[19]),"+f"(d[20]),"+f"(d[21]),"+f"(d[22]),"+f"(d[23]),"+f"(d[24]),"+f"(d[25]),"+f"(d[26]),"+f"(d[27]),"+f"(d[28]),"+f"(d[29]),"+f"(d[30]),"+f"(d[31]),"+f"(d[32]),"+f"(d[33]),"+f"(d[34]),"+f"(d[35]),"+f"(d[36]),"+f"(d[37]),"+f"(d[38]),"+f"(d[39])
 :"r"(alo),"r"(blo),"n"(AOFF),"n"(AHI),"n"(BOFF),"n"(BHI),"n"(SC)); } };
template<> struct WgSs<104> { template<int AOFF,int AHI,int BOFF,int BHI,int SC> static __device__ __forceinline__ void run(float* d,uint32_t alo,uint32_t blo){
 asm volatile("{.reg .b32 l,m; .reg .b64 da,db; add.u32 l,%52,%54; mov.b64 da,{l,%55}; add.u32 m,%53,%56; mov.b64 db,{m,%57}; wgmma.mma_async.sync.aligned.m64n104k16.f32.bf16.bf16 {%0,%1,%2,%3,%4,%5,%6,%7,%8,%9,%10,%11,%12,%13,%14,%15,%16,%17,%18,%19,%20,%21,%22,%23,%24,%25,%26,%27,%28,%29,%30,%31,%32,%33,%34,%35,%36,%37,%38,%39,%40,%41,%42,%43,%44,%45,%46,%47,%48,%49,%50,%51},da,db,%58,1,1,0,1;}"
 :"+f"(d[0]),"+f"(d[1]),"+f"(d[2]),"+f"(d[3]),"+f"(d[4]),"+f"(d[5]),"+f"(d[6]),"+f"(d[7]),"+f"(d[8]),"+f"(d[9]),"+f"(d[10]),"+f"(d[11]),"+f"(d[12]),"+f"(d[13]),"+f"(d[14]),"+f"(d[15]),"+f"(d[16]),"+f"(d[17]),"+f"(d[18]),"+f"(d[19]),"+f"(d[20]),"+f"(d[21]),"+f"(d[22]),"+f"(d[23]),"+f"(d[24]),"+f"(d[25]),"+f"(d[26]),"+f"(d[27]),"+f"(d[28]),"+f"(d[29]),"+f"(d[30]),"+f"(d[31]),"+f"(d[32]),"+f"(d[33]),"+f"(d[34]),"+f"(d[35]),"+f"(d[36]),"+f"(d[37]),"+f"(d[38]),"+f"(d[39]),"+f"(d[40]),"+f"(d[41]),"+f"(d[42]),"+f"(d[43]),"+f"(d[44]),"+f"(d[45]),"+f"(d[46]),"+f"(d[47]),"+f"(d[48]),"+f"(d[49]),"+f"(d[50]),"+f"(d[51])
 :"r"(alo),"r"(blo),"n"(AOFF),"n"(AHI),"n"(BOFF),"n"(BHI),"n"(SC)); } };
template<> struct WgSs<112> { template<int AOFF,int AHI,int BOFF,int BHI,int SC> static __device__ __forceinline__ void run(float* d,uint32_t alo,uint32_t blo){
 asm volatile("{.reg .b32 l,m; .reg .b64 da,db; add.u32 l,%56,%58; mov.b64 da,{l,%59}; add.u32 m,%57,%60; mov.b64 db,{m,%61}; wgmma.mma_async.sync.aligned.m64n112k16.f32.bf16.bf16 {%0,%1,%2,%3,%4,%5,%6,%7,%8,%9,%10,%11,%12,%13,%14,%15,%16,%17,%18,%19,%20,%21,%22,%23,%24,%25,%26,%27,%28,%29,%30,%31,%32,%33,%34,%35,%36,%37,%38,%39,%40,%41,%42,%43,%44,%45,%46,%47,%48,%49,%50,%51,%52,%53,%54,%55},da,db,%62,1,1,0,1;}"
 :"+f"(d[0]),"+f"(d[1]),"+f"(d[2]),"+f"(d[3]),"+f"(d[4]),"+f"(d[5]),"+f"(d[6]),"+f"(d[7]),"+f"(d[8]),"+f"(d[9]),"+f"(d[10]),"+f"(d[11]),"+f"(d[12]),"+f"(d[13]),"+f"(d[14]),"+f"(d[15]),"+f"(d[16]),"+f"(d[17]),"+f"(d[18]),"+f"(d[19]),"+f"(d[20]),"+f"(d[21]),"+f"(d[22]),"+f"(d[23]),"+f"(d[24]),"+f"(d[25]),"+f"(d[26]),"+f"(d[27]),"+f"(d[28]),"+f"(d[29]),"+f"(d[30]),"+f"(d[31]),"+f"(d[32]),"+f"(d[33]),"+f"(d[34]),"+f"(d[35]),"+f"(d[36]),"+f"(d[37]),"+f"(d[38]),"+f"(d[39]),"+f"(d[40]),"+f"(d[41]),"+f"(d[42]),"+f"(d[43]),"+f"(d[44]),"+f"(d[45]),"+f"(d[46]),"+f"(d[47]),"+f"(d[48]),"+f"(d[49]),"+f"(d[50]),"+f"(d[51]),"+f"(d[52]),"+f"(d[53]),"+f"(d[54]),"+f"(d[55])
 :"r"(alo),"r"(blo),"n"(AOFF),"n"(AHI),"n"(BOFF),"n"(BHI),"n"(SC)); } };

__device__ __forceinline__ void wg_fence() { asm volatile("wgmma.fence.sync.aligned;" ::: "memory"); }
__device__ __forceinline__ void wg_commit() { asm volatile("wgmma.commit_group.sync.aligned;" ::: "memory"); }
template <int N> __device__ __forceinline__ void wg_wait() { asm volatile("wgmma.wait_group.sync.aligned %0;" ::"n"(N) : "memory"); }
template <int N> __device__ __forceinline__ void reg_fence(float* d) {
#pragma unroll
    for (int i = 0; i < N; i++) asm volatile("" : "+f"(d[i])::"memory");
}
__device__ __forceinline__ uint32_t desc_lo(uint32_t addr, uint32_t lbo) { return ((addr & 0x3FFFF) >> 4) | ((lbo >> 4) << 16); }
#define desc_hi(sbo, sw) (((sbo) >> 4) | ((sw) << 30))
__device__ __forceinline__ uint32_t smem_u32(const void* p) { return (uint32_t)__cvta_generic_to_shared(p); }
__device__ __forceinline__ bool elect() {
    uint32_t p;
    asm volatile("{.reg .pred P; elect.sync _|P, 0xffffffff; selp.u32 %0,1,0,P;}" : "=r"(p));
    return p;
}
__device__ __forceinline__ void mbar_init(uint32_t bar, uint32_t cnt) { asm volatile("mbarrier.init.shared::cta.b64 [%0], %1;" ::"r"(bar), "r"(cnt) : "memory"); }
__device__ __forceinline__ void mbar_expect(uint32_t bar, uint32_t bytes) { asm volatile("mbarrier.arrive.expect_tx.shared::cta.b64 _, [%0], %1;" ::"r"(bar), "r"(bytes) : "memory"); }
__device__ __forceinline__ bool mbar_try(uint32_t bar, uint32_t par) {
    uint32_t ok;
    asm volatile("{.reg .pred p; mbarrier.try_wait.parity.shared::cta.b64 p, [%1], %2; selp.u32 %0,1,0,p;}" : "=r"(ok) : "r"(bar), "r"(par) : "memory");
    return ok;
}
constexpr int SPIN_LIMIT = 1 << 18;
__device__ __forceinline__ void mbar_wait(uint32_t bar, uint32_t par) {
    if (mbar_try(bar, par)) return;
    asm volatile("{.reg .pred p, q; .reg .b32 n; mov.u32 n, 0;\n"
                 "W%=: mbarrier.try_wait.parity.shared::cta.b64 p, [%0], %1; add.u32 n, n, 1; setp.lt.and.u32 q, n, %2, !p; @q bra W%=;}"
                 ::"r"(bar), "r"(par), "n"(SPIN_LIMIT) : "memory");
}
__device__ __forceinline__ void bulk_g2s(uint32_t dst, const void* src, uint32_t bytes, uint32_t bar) {
    asm volatile("cp.async.bulk.shared::cluster.global.mbarrier::complete_tx::bytes [%0], [%1], %2, [%3];" ::"r"(dst), "l"(src), "r"(bytes), "r"(bar) : "memory");
}
__device__ __forceinline__ void bulk_s2g(void* dst, uint32_t src, uint32_t bytes) {
    asm volatile("cp.async.bulk.global.shared::cta.bulk_group [%0], [%1], %2;" ::"l"(dst), "r"(src), "r"(bytes) : "memory");
}
__device__ __forceinline__ void bulk_prefetch(const void* src, uint32_t bytes) {
    asm volatile("cp.async.bulk.prefetch.L2.global [%0], %1;" ::"l"(src), "r"(bytes) : "memory");
}
__device__ __forceinline__ void tma2d(uint32_t dst, const CUtensorMap* m, int c0, int c1, uint32_t bar) {
    asm volatile("cp.async.bulk.tensor.2d.shared::cluster.global.mbarrier::complete_tx::bytes [%0], [%1, {%3, %4}], [%2];" ::"r"(dst), "l"(m), "r"(bar), "r"(c0), "r"(c1) : "memory");
}
__device__ __forceinline__ void tma2d_mc(uint32_t dst, const CUtensorMap* m, int c0, int c1, uint32_t bar) {
    asm volatile("cp.async.bulk.tensor.2d.shared::cluster.global.mbarrier::complete_tx::bytes.multicast::cluster [%0], [%1, {%3, %4}], [%2], %5;" ::"r"(dst), "l"(m), "r"(bar), "r"(c0), "r"(c1), "h"((uint16_t)3) : "memory");
}
__device__ __forceinline__ uint32_t mapa(uint32_t a, uint32_t rank) { uint32_t r; asm("mapa.shared::cluster.u32 %0, %1, %2;" : "=r"(r) : "r"(a), "r"(rank)); return r; }
__device__ __forceinline__ void mbar_arrive_cl(uint32_t bar) { asm volatile("mbarrier.arrive.shared::cluster.b64 _, [%0];" ::"r"(bar) : "memory"); }
__device__ __forceinline__ void prefetch_map(const CUtensorMap* m) { asm volatile("prefetch.tensormap [%0];" ::"l"(m) : "memory"); }
__device__ __forceinline__ void cpasync16(uint32_t dst, const void* src, uint32_t srcsz) {
    asm volatile("cp.async.cg.shared.global [%0], [%1], 16, %2;" ::"r"(dst), "l"(src), "r"(srcsz) : "memory");
}
__device__ __forceinline__ void bar_sync(int id, int n) { asm volatile("bar.sync %0, %1;" ::"r"(id), "r"(n) : "memory"); }
__device__ __forceinline__ void bar_arrive(int id, int n) { asm volatile("bar.arrive %0, %1;" ::"r"(id), "r"(n) : "memory"); }
__device__ __forceinline__ void fence_async_smem() { asm volatile("fence.proxy.async.shared::cta;" ::: "memory"); }
__device__ __forceinline__ void fence_async_global() { asm volatile("fence.proxy.async.global;" ::: "memory"); }
__device__ __forceinline__ unsigned* flag_ptr(int f) {
    return f < 16 ? &g_flags[(f & 7) * 32 + (f >> 3)] : &g_flags[f * 32];
}
__device__ __forceinline__ void flag_release(int f) { asm volatile("red.release.gpu.global.add.u32 [%0], 1;" ::"l"(flag_ptr(f)) : "memory"); }
__device__ __forceinline__ void flag_wait(int f, unsigned target) {
    const unsigned* p = flag_ptr(f);
    unsigned v; int n = 0;
    do {
        asm volatile("ld.relaxed.gpu.global.u32 %0, [%1];" : "=r"(v) : "l"(p) : "memory");
    } while ((int)(v - target) < 0 && ++n < SPIN_LIMIT);
    asm volatile("fence.acquire.gpu;" ::: "memory");
}
__device__ __forceinline__ unsigned ld_flag(const unsigned* p) { unsigned v; asm volatile("ld.relaxed.gpu.global.u32 %0, [%1];" : "=r"(v) : "l"(p) : "memory"); return v; }
__device__ __forceinline__ void spin(unsigned n) { unsigned t0, t1; asm volatile("mov.u32 %0, %%clock;" : "=r"(t0)); do { asm volatile("mov.u32 %0, %%clock;" : "=r"(t1)); } while (t1 - t0 < n); }
__device__ __forceinline__ int tensor_ping() {
    int r;
    asm volatile("{.reg .f32 a, b, c, d; mma.sync.aligned.m16n8k16.row.col.f32.bf16.bf16.f32 {a,b,c,d},{%1,%1,%1,%1},{%1,%1},{%2,%2,%2,%2}; mov.b32 %0, a;}" : "=r"(r) : "r"(0), "f"(0.f));
    return r;
}
__device__ __forceinline__ void mbar_wait_warm(uint32_t bar, uint32_t par) {
    for (int n = 0; n < SPIN_LIMIT; n++) {
        uint32_t ok;
        asm volatile("{.reg .pred p; mbarrier.test_wait.parity.shared::cta.b64 p, [%1], %2; selp.u32 %0,1,0,p;}" : "=r"(ok) : "r"(bar), "r"(par) : "memory");
        if (ok) break;
        n += tensor_ping();
        spin(PING);
    }
}
__device__ __forceinline__ void flag_wait2(int f0, int f1, unsigned target) {
    const unsigned *p = flag_ptr(f0), *q = flag_ptr(f1);
    unsigned v, w; int n = 0;
    do { v = ld_flag(p); w = ld_flag(q); } while ((int)((v - target) | (w - target)) < 0 && ++n < SPIN_LIMIT);
    asm volatile("fence.acquire.gpu;" ::: "memory");
}
__device__ __forceinline__ uint32_t lds32(uint32_t a) { uint32_t v; asm volatile("ld.shared.u32 %0, [%1];" : "=r"(v) : "r"(a)); return v; }
__device__ __forceinline__ float2 lds64f(uint32_t a) { float2 v; asm volatile("ld.shared.v2.f32 {%0,%1}, [%2];" : "=f"(v.x), "=f"(v.y) : "r"(a)); return v; }
__device__ __forceinline__ uint2 lds64(uint32_t a) { uint2 v; asm volatile("ld.shared.v2.u32 {%0,%1}, [%2];" : "=r"(v.x), "=r"(v.y) : "r"(a)); return v; }
__device__ __forceinline__ void sts64f(uint32_t a, float2 v) { asm volatile("st.shared.v2.f32 [%0], {%1,%2};" ::"r"(a), "f"(v.x), "f"(v.y) : "memory"); }
__device__ __forceinline__ void sts32(uint32_t a, uint32_t v) { asm volatile("st.shared.u32 [%0], %1;" ::"r"(a), "r"(v) : "memory"); }
__device__ __forceinline__ void sts64(uint32_t a, uint32_t x, uint32_t y) { asm volatile("st.shared.v2.u32 [%0], {%1,%2};" ::"r"(a), "r"(x), "r"(y) : "memory"); }
__device__ __forceinline__ void sts16(uint32_t a, uint16_t v) { asm volatile("st.shared.u16 [%0], %1;" ::"r"(a), "h"(v) : "memory"); }
__device__ __forceinline__ uint4 lds128(uint32_t a) { uint4 v; asm volatile("ld.shared.v4.u32 {%0,%1,%2,%3}, [%4];" : "=r"(v.x), "=r"(v.y), "=r"(v.z), "=r"(v.w) : "r"(a)); return v; }
__device__ __forceinline__ void sts128(uint32_t a, uint4 v) { asm volatile("st.shared.v4.u32 [%0], {%1,%2,%3,%4};" ::"r"(a), "r"(v.x), "r"(v.y), "r"(v.z), "r"(v.w) : "memory"); }
__device__ __forceinline__ void sts128f(uint32_t a, float x, float y, float z, float w) { asm volatile("st.shared.v4.f32 [%0], {%1,%2,%3,%4};" ::"r"(a), "f"(x), "f"(y), "f"(z), "f"(w) : "memory"); }
__device__ __forceinline__ uint32_t prmt(uint32_t a, uint32_t b, uint32_t s) { uint32_t r; asm("prmt.b32 %0,%1,%2,%3;" : "=r"(r) : "r"(a), "r"(b), "r"(s)); return r; }
__device__ __forceinline__ uint32_t pack2(float lo, float hi) { uint32_t r; asm("cvt.rn.bf16x2.f32 %0, %1, %2;" : "=r"(r) : "f"(hi), "f"(lo)); return r; }
__device__ __forceinline__ float blo(uint32_t v) { return __uint_as_float(v << 16); }
__device__ __forceinline__ float bhi(uint32_t v) { return __uint_as_float(v & 0xffff0000u); }
__device__ __forceinline__ uint32_t bmul2(uint32_t a, uint32_t b) { uint32_t r; asm("mul.rn.bf16x2 %0,%1,%2;" : "=r"(r) : "r"(a), "r"(b)); return r; }
__device__ __forceinline__ uint32_t badd2(uint32_t a, uint32_t b) { uint32_t r; asm("add.rn.bf16x2 %0,%1,%2;" : "=r"(r) : "r"(a), "r"(b)); return r; }
__device__ __forceinline__ float rbf(float x) { return __bfloat162float(__float2bfloat16_rn(x)); }
__device__ __forceinline__ uint32_t ldcg32(const void* p) { uint32_t v; asm volatile("ld.global.cg.u32 %0, [%1];" : "=r"(v) : "l"(p) : "memory"); return v; }
__device__ __forceinline__ uint4 ldcg128(const void* p) { uint4 v; asm volatile("ld.global.cg.v4.u32 {%0,%1,%2,%3}, [%4];" : "=r"(v.x), "=r"(v.y), "=r"(v.z), "=r"(v.w) : "l"(p) : "memory"); return v; }
__device__ __forceinline__ void stg32_if(void* p, uint32_t v, int on) { asm volatile("{.reg .pred q; setp.ne.b32 q, %2, 0; @q st.global.u32 [%0], %1;}" ::"l"(p), "r"(v), "r"(on) : "memory"); }
__device__ __forceinline__ uint2 ldcg64(const void* p) { uint2 v; asm volatile("ld.global.cg.v2.u32 {%0,%1}, [%2];" : "=r"(v.x), "=r"(v.y) : "l"(p) : "memory"); return v; }
__device__ __forceinline__ float gelu_h(float h) {
    float u = h * fmaf(h * h, 8.0f * 0.044715f * 0.7978845608028654f, 2.0f * 0.7978845608028654f);
    float th;
    asm("tanh.approx.f32 %0, %1;" : "=f"(th) : "f"(u));
    return fmaf(h, th, h);
}
__device__ __forceinline__ float gelu(float x) { return gelu_h(0.5f * x); }
__device__ __forceinline__ float half_rstd(float sum, float sq) {
    float mean = sum * (1.0f / D_), inv;
    asm("rsqrt.approx.ftz.f32 %0, %1;" : "=f"(inv) : "f"(fmaxf(fmaf(-mean, mean, fmaf(sq, 1.0f / D_, 1e-5f)), 1e-5f)));
    return 0.5f * inv;
}
__device__ __forceinline__ uint32_t bsub2(uint32_t a, uint32_t b) { uint32_t r; asm("sub.rn.bf16x2 %0,%1,%2;" : "=r"(r) : "r"(a), "r"(b)); return r; }
__device__ __forceinline__ uint32_t bfma2(uint32_t a, uint32_t b, uint32_t c) { uint32_t r; asm("fma.rn.bf16x2 %0,%1,%2,%3;" : "=r"(r) : "r"(a), "r"(b), "r"(c)); return r; }
__device__ __forceinline__ uint32_t gelu2_h(uint32_t h) {
    uint32_t u = bmul2(h, bfma2(bmul2(h, h), 0x3e923e92u, 0x3fcc3fccu)), th;
    asm("tanh.approx.bf16x2 %0, %1;" : "=r"(th) : "r"(u));
    return bfma2(h, th, h);
}
struct RowSum { float s = 0.f, q = 0.f, s_ = 0.f, q_ = 0.f;
    __device__ __forceinline__ void add(uint32_t v) { float a = blo(v), b = bhi(v); s += a; s_ += b; q = fmaf(a, a, q); q_ = fmaf(b, b, q_); } };
template <int I0>
__device__ __forceinline__ uint3 row_stats(const uint32_t* v, int lane, RowSum r0 = RowSum()) {
#pragma unroll
    for (int i = I0; i < 10; i++) r0.add(v[i]);
    float s = r0.s + r0.s_, q = r0.q + r0.q_;
    {
        float t = __shfl_xor_sync(0xffffffffu, (lane & 16) ? s : q, 16);
        t += (lane & 16) ? q : s;
#pragma unroll
        for (int m = 8; m; m >>= 1) t += __shfl_xor_sync(0xffffffffu, t, m);
        float o = __shfl_xor_sync(0xffffffffu, t, 16);
        s = (lane & 16) ? o : t; q = (lane & 16) ? t : o;
    }
    float mean = s * (1.0f / D_), inv;
    asm("rsqrt.approx.ftz.f32 %0, %1;" : "=f"(inv) : "f"(fmaxf(fmaf(-mean, mean, fmaf(q, 1.0f / D_, 1e-5f)), 1e-5f)));
    uint3 r;
    r.x = pack2(mean, mean);
    r.y = pack2(inv, inv);
    inv -= blo(r.y);
    r.z = pack2(inv, inv);
    return r;
}
__device__ __forceinline__ uint32_t ln_apply(uint32_t x, uint32_t m, uint32_t hi, uint32_t lo) {
    uint32_t xc = bsub2(x, m);
    return bmul2(xc, hi);
}

struct AFrag { uint32_t m, a, b, c, d; };
__device__ __forceinline__ AFrag ldA(uint32_t a) { AFrag f; f.m = lds32(a - 16); f.a = lds32(a); f.b = lds32(a + 16); f.c = lds32(a + 32); f.d = lds32(a + 48); return f; }
template <int N, int M> __device__ __forceinline__ void conv_pair(float* d, const AFrag& f, uint32_t descU) {
    WgRs<N>::template run<8 * M, desc_hi(128, 0), M ? 1 : 0>(d, f.a, f.b, f.m, f.a, descU);
    WgRs<N>::template run<8 * M + 1, desc_hi(128, 0), 1>(d, f.c, f.d, f.b, f.c, descU);
}
template <int Q> __device__ __forceinline__ void conv_put(float* d, uint32_t r0) {
    sts64(r0 + Q * 32, pack2(d[4 * Q + 1], d[4 * Q + 3]), pack2(d[4 * Q], d[4 * Q + 2]));
}
template <int M> __device__ __forceinline__ void conv_two(float* d, AFrag f0, AFrag f1, uint32_t kaddr, uint32_t descU, uint32_t r0, bool handoff) {
    constexpr int N = M < 14 ? 128 - 8 * M : 32;
    wg_fence();
    conv_pair<N, M>(d, f0, descU);
    wg_commit();
    if constexpr (M > 0) f1 = ldA(kaddr + 256 * (M + 1));
    wg_fence();
    conv_pair<N, M + 1>(d, f1, descU);
    wg_commit();
    if (STAG && M == STAG && handoff) bar_arrive(12, 256);
    if constexpr (M < 14) {
        if constexpr (M > 0) { conv_put<17 - M>(d, r0); conv_put<16 - M>(d, r0); }
        wg_wait<1>();
        f0 = ldA(kaddr + 256 * (M + 2));
        if constexpr (M < 12) wg_wait<0>();
        conv_two<M + 2>(d, f0, f1, kaddr, descU, r0, handoff);
    } else {
        wg_wait<0>();
        conv_put<3>(d, r0); conv_put<2>(d, r0); conv_put<1>(d, r0); conv_put<0>(d, r0);
    }
}
template <int N, bool ASWZ, int SC0>
__device__ __forceinline__ void gemm_issue(float* acc, uint32_t bars, int sa, int pa, int sw, int pw, uint32_t da0, uint32_t db0) {
    mbar_wait(bars + (BAR_FB + sw) * 8, pw);
    mbar_wait(bars + (BAR_FA + sa) * 8, pa);
    const uint32_t da = da0 + sa * (SLOT >> 4), db = db0 + sw * (SLOT >> 4);
    constexpr int AK = ASWZ ? 2 : 256, AH = ASWZ ? desc_hi(1024, 1) : desc_hi(128, 0), BH = desc_hi(1024, 1);
    wg_fence();
    WgSs<N>::template run<0, AH, 0, BH, SC0>(acc, da, db);
    WgSs<N>::template run<AK, AH, 128, BH, 1>(acc, da, db);
    WgSs<N>::template run<2 * AK, AH, 256, BH, 1>(acc, da, db);
    WgSs<N>::template run<3 * AK, AH, 384, BH, 1>(acc, da, db);
    wg_commit();
}
template <int N, bool ASWZ, int NKB, int RELB, bool ZERO>
__device__ __forceinline__ void gemm_loop(float* acc, uint32_t sb, int half, int ia0, int ib0, int rela, int wait_bar, int order_bar, int tsid) {
    int sa = ia0 % NA, pa = (ia0 / NA) & 1, sw = ib0 % NB, pw = (ib0 / NB) & 1;
    const uint32_t bars = sb + SM_BAR;
    const int t = threadIdx.x & 127;
    uint32_t ebar = mapa(bars + (t < 2 ? BAR_EB : BAR_EA) * 8, (t < 2 && lds32(sb + SM_GV + 516)) ? t : blockIdx.x & 1);
    const int nrel = t < 2 ? RELB : t == 2 ? rela : 0;
    const uint32_t da0 = ASWZ ? desc_lo(sb + SM_RA + half * 8192, 16) : desc_lo(sb + SM_RA + half * 1024, 2048), db0 = desc_lo(sb + SM_RB, 8192);
    asm volatile("" : "+r"(ebar));
    if (wait_bar) bar_sync(wait_bar, 512);
    gemm_issue<N, ASWZ, ZERO ? 0 : 1>(acc, bars, sa, pa, sw, pw, da0, db0);
    if ((threadIdx.x & 255) == 0) TS(tsid);
#pragma unroll 1
    for (int kb = 1; kb < NKB; kb++) {
        const int prev = t < 2 ? sw : sa;
        if (++sa == NA) { sa = 0; pa ^= 1; }
        if (++sw == NB) { sw = 0; pw ^= 1; }
        gemm_issue<N, ASWZ, 1>(acc, bars, sa, pa, sw, pw, da0, db0);
        if (order_bar && kb == NKB - 1) bar_arrive(order_bar, 512);
        wg_wait<1>();
        if (kb <= nrel) mbar_arrive_cl(ebar + prev * 8);
    }
    wg_wait<0>();
    if (nrel == NKB) mbar_arrive_cl(ebar + (t < 2 ? sw : sa) * 8);
    reg_fence<N / 2>(acc);
    if ((threadIdx.x & 255) == 0) TS(tsid + 1);
}

template <int PART>
__device__ __forceinline__ void gemm3(uint32_t sb, int rb, int j, int half, int row, int c, unsigned ones) {
    constexpr int N = 64 + (PART ? RB3 : RA3), NQ = N / 8;
    constexpr int HO = PART ? HO_B : HO_A;
    float acc[N / 2];
    float2 cr[NQ];
    if (PART) {
        gemm_loop<N, false, 1, 1, true>(acc, sb, half, 20, 20, 0, 0, 0, 50);
        bar_arrive(9, 512);
    }
    mbar_wait(sb + SM_BAR + BAR_CS * 8, 0);
    const uint32_t csa = sb + SM_CS + PART * (256 + 4 * RA3) + 8 * c;
#pragma unroll
    for (int q = 0; q < NQ; q++) if (q < CSP) cr[q] = lds64f(csa + 32 * q);
    uint4 rp;
    if (PART) {
        mbar_wait(sb + SM_BAR + BAR_G * 8, 0);
        const float2* sp = &g_st[(rb * 8 + 2 * c) * 128 + row];
        const uint2 s0 = ldcg64(sp), s1 = ldcg64(sp + 128), s2 = ldcg64(sp + 8), s3 = ldcg64(sp + 136);
        float a0 = __uint_as_float(s0.x) + __uint_as_float(s1.x), b0 = __uint_as_float(s0.y) + __uint_as_float(s1.y);
        float a1 = __uint_as_float(s2.x) + __uint_as_float(s3.x), b1 = __uint_as_float(s2.y) + __uint_as_float(s3.y);
#pragma unroll
        for (int m = 1; m <= 2; m <<= 1) {
            a0 += __shfl_xor_sync(0xffffffffu, a0, m); b0 += __shfl_xor_sync(0xffffffffu, b0, m);
            a1 += __shfl_xor_sync(0xffffffffu, a1, m); b1 += __shfl_xor_sync(0xffffffffu, b1, m);
        }
        const float inv0 = half_rstd(a0, b0), inv1 = half_rstd(a1, b1);
        rp = make_uint4(PGELU ? pack2(inv0, inv0) : __float_as_uint(inv0), __float_as_uint(a0 * (-1.0f / D_)),
                        PGELU ? pack2(inv1, inv1) : __float_as_uint(inv1), __float_as_uint(a1 * (-1.0f / D_)));
        if (c == 0) sts128(sb + SM_RP + ((threadIdx.x & 255) >> 2) * 16, rp);
        bar_arrive(13, 512);
    }
    gemm_loop<N, false, 10 - PART, 10 - PART, !PART>(acc, sb, half, 20 + (10 - NA) * PART, 21 + 10 * PART, PART ? 9 : 10 - NA, 9 + PART, HO < 0 ? 10 + PART : 0, 46 + 2 * PART);
    if ((threadIdx.x & 255) == 0) mbar_expect(sb + SM_BAR + BAR_ME * 8, 0);
    if (!PART) {
        bar_sync(13, 512);
        rp = lds128(sb + SM_RP + ((threadIdx.x & 255) >> 2) * 16);
    }
    const float nb0 = __uint_as_float(rp.y), nb1 = __uint_as_float(rp.w);
    const uint32_t own = sb + SM_RA + ((39 - NA) % NA) * SLOT + row * 16 + c * 4;
    if (PART && OWNG) mbar_wait(sb + SM_BAR + (BAR_FA + (39 - NA) % NA) * 8, ((39 - NA) / NA) & 1);
    uint32_t* dst = reinterpret_cast<uint32_t*>(g_g) + (rb * 216 + HB0 / 8 * PART + 8 * j) * 512 + row * 4 + c;
    auto act = [&](int q, int r) {
        const float nb = r ? nb1 : nb0;
        const uint32_t inv = r ? rp.z : rp.x;
        const float t0 = fmaf(nb, cr[q].x, acc[4 * q + 2 * r]), t1 = fmaf(nb, cr[q].y, acc[4 * q + 2 * r + 1]);
        return gelu2_h(bmul2(pack2(t0, t1), inv));
    };
    uint32_t* dst1 = dst + (56 - (16 - NQ) * j) * 512;
#pragma unroll
    for (int k = 0; k < NQ; k += CH3) {
        if (k == HO) bar_arrive(10 + PART, 512);
        CHUNK(k) {
#pragma unroll
            for (int q = k; q < k + CH3 && q < NQ; q++) {
                if (q + CSP < NQ) cr[q + CSP] = lds64f(csa + 32 * (q + CSP));
                const uint32_t u = act(q, 0), v = act(q, 1);
                (q < 8 ? dst : dst1)[q * 512] = u;
                (q < 8 ? dst : dst1)[q * 512 + 32] = v;
                if (PART && OWNG && q < 8) { sts32(own + q * 2048, u); sts32(own + q * 2048 + 128, v); }
            }
            if (PART && OWNG && k < 8 && k + CH3 >= 8) fence_async_smem();
        }
    }
    bar_arrive(1 + PART, 288);
    if (HO >= NQ) bar_arrive(10 + PART, 512);
}

template <int NS, int BASE, int BF, int BE> struct Ring {
    uint32_t sb, st, ph;
    __device__ __forceinline__ uint32_t acquire(uint32_t bytes) {
        mbar_wait(sb + SM_BAR + BE * 8 + st * 8, ph);
        uint32_t fb = sb + SM_BAR + BF * 8 + st * 8;
        mbar_expect(fb, bytes);
        return fb;
    }
    __device__ __forceinline__ uint32_t slot() { return sb + BASE + st * SLOT; }
    __device__ __forceinline__ void next() { if (++st == NS) { st = 0; ph ^= 1; } }
    __device__ __forceinline__ void run2d(const CUtensorMap* m, int c1) {
#pragma unroll 1
        for (int c0 = 64; c0 < D_; c0 += 64) {
            uint32_t fb = acquire(SLOT);
            tma2d(slot(), m, c0, c1, fb);
            next();
        }
    }
    static __device__ __forceinline__ int korder(int i, int own) { return i == 0 ? own : i > own ? i : i - 1; }
    __device__ __forceinline__ void runw(bool paired, int rk, const CUtensorMap* ma, const CUtensorMap* mb, int ca, int cb, int i0, int i1, int own, uint32_t bytes, int gate_at, uint32_t gate) {
        if (paired) {
            const CUtensorMap* m = rk ? mb : ma;
            const int c0 = rk ? cb : ca;
#pragma unroll 1
            for (int i = i0; i < i1; i++) {
                const int c1 = korder(i, own) * 64;
                if (i == gate_at) mbar_wait(gate, 0);
                uint32_t fb = acquire(bytes);
                tma2d_mc(slot() + 8192 * rk, m, c0, c1, fb);
                next();
            }
        } else {
#pragma unroll 1
            for (int i = i0; i < i1; i++) {
                const int c1 = korder(i, own) * 64;
                uint32_t fb = acquire(bytes);
                tma2d(slot(), ma, ca, c1, fb);
                tma2d(slot() + 8192, mb, cb, c1, fb);
                next();
            }
        }
    }
    __device__ __forceinline__ void run1d(const char* src, int i0, int i1, int own) {
#pragma unroll 1
        for (int i = i0; i < i1; i++) {
            const char* s = src + korder(i, own) * SLOT;
            uint32_t fb = acquire(SLOT);
            bulk_g2s(slot(), s, SLOT, fb);
            next();
        }
    }
};

__global__ void __cluster_dims__(2, 1, 1) __launch_bounds__(NTHREADS, 1) fused_kernel(const Params p, const __grid_constant__ Maps maps) {
    extern __shared__ __align__(1024) unsigned char smem_raw[];
    const uint32_t sb = (smem_u32(smem_raw) + 1023u) & ~1023u;
#pragma unroll
    for (int i = 0; i < SEED; i++) asm volatile("{.reg .b32 t; mov.u32 t, %laneid;}");
    const uint32_t bars = sb + SM_BAR;
    const int tid = threadIdx.x, lane = tid & 31;
    unsigned smid;
    asm volatile("mov.u32 %0, %%smid;" : "=r"(smid));
    const bool spare = (smid >> 2) == 30;
    const int cta = smid < 120 ? smid : smid - 4;
    const int pg = cta >> 4, pi = cta & 15;
    auto chan = [&](int cc) { return cc < 3 ? 3 * cta + cc : 381 + 2 * cta + cc; };
    const int hb = tid >= 320;
    unsigned ep0 = 0;
    if (!spare) {
        const unsigned t = tid - 320 * hb, r32 = t / 10u, cc = t - r32 * 10u, row = r32 + 64 * hb;
        const unsigned go = (unsigned)(pi * 128 * 1280) + row * 1280u + cc * 16u + (cc < 6 ? pg * 96 : 672 + pg * 64);
        const uint32_t so = sb + (row >> 4) * 32u + row * 160u + cc * 16u;
        const char* kb = (const char*)p.k + go;
        const char* vb = (const char*)p.v + go;
        if (hb) {
            if (tid < 328) {
                const char* a = lane < 5 ? (const char*)p.shift + lane * 128 + (lane < 3 ? pg * 384 : 2688 + pg * 256) : (const char*)(p.ssmD + chan(2 * lane - 10));
                asm volatile("prefetch.global.L2 [%0];" ::"l"(a));
            }
            if (tid >= 640 - NBARS) {
                const int i = 639 - tid;
                mbar_init(bars + i * 8, (i >= BAR_EB && i < BAR_K) ? 4 : ((i >= BAR_EA && i < BAR_EB) || i == BAR_XY) ? 2 : 1);
                asm volatile("fence.mbarrier_init.release.cluster;" ::: "memory");
            }
            bar_arrive(14, 640);
            if (tid >= 512) asm volatile("ld.volatile.global.u32 %0, [%1];" : "=r"(ep0) : "l"(p.epoch + smid) : "memory");
            if (B_DELAY) spin(B_DELAY);
        }
        cpasync16(so + SM_PK + 2592, kb, 16);
        cpasync16(so + SM_PV, vb, 16);
        cpasync16(so + SM_PK + 3 * 2592, kb + 32 * 1280, 16);
        cpasync16(so + SM_PV + 2 * 2592, vb + 32 * 1280, 16);
        if (tid < 30) cpasync16(so + SM_PK + 13 * 160, pi ? kb - 3 * 1280 : kb, pi ? 16 : 0);
        asm volatile("cp.async.commit_group;" ::: "memory");
    }
    const int warp = __shfl_sync(0xffffffffu, tid >> 5, 0);
    const int wg = warp >> 2, wq = warp & 3;

    if (spare) {
        const int sp = smid & 3;
        const unsigned ep1 = *(volatile unsigned*)&p.epoch[smid] + 1;
        if (tid == 32) { sts32(sb + SM_GV + 512, smid); asm volatile("fence.release.sync_restrict::shared::cta.cluster;" ::: "memory"); }
        asm volatile("barrier.cluster.arrive.relaxed.aligned;" ::: "memory");
        asm volatile("barrier.cluster.wait.aligned;" ::: "memory");
        if (tid == 0) {
            for (int i = 0; i < 4; i++) mbar_init(bars + i * 8, 1);
            asm volatile("fence.mbarrier_init.release.cluster;" ::: "memory");
        }
        if (warp == 0) { if (lane < 8) flag_wait(FL_P + lane, ep1 * 16); __syncwarp(); if (SPD) spin(SPD); }
        __syncthreads();
        const int cq = tid % 54, rg = tid / 54;
        float a[8];
#pragma unroll
        for (int i = 0; i < 8; i++) a[i] = 0.f;
#pragma unroll 1
        for (int it = -4; it < 10; it++) {
            const uint32_t st = sb + (it & 3) * 55296, fb = bars + (it & 3) * 8;
            if (it >= 0) {
                mbar_wait(fb, (it >> 2) & 1);
                if (tid < 432) {
#pragma unroll 2
                    for (int i = 0; i < 8; i++) {
                        uint4 w = lds128(st + (cq >= 27 ? 27648 - 432 : 0) + (rg * 8 + i) * 432 + cq * 16);
                        a[0] += blo(w.x); a[1] += bhi(w.x); a[2] += blo(w.y); a[3] += bhi(w.y);
                        a[4] += blo(w.z); a[5] += bhi(w.z); a[6] += blo(w.w); a[7] += bhi(w.w);
                    }
                }
                __syncthreads();
            }
            if (it < 6 && warp == 19 && elect()) {
                mbar_expect(fb, 55296);
                tma2d(st, &maps.w3s, sp * 432, (it + 4) * 64, fb);
                tma2d(st + 27648, &maps.w3s, sp * 432 + 216, (it + 4) * 64, fb);
            }
        }
        if (warp == 19 && elect()) {
#pragma unroll 1
            for (int i = 0; i < 27; i++) bulk_prefetch((const char*)p.w4 + sp * 552960 + i * 20480, 20480);
        }
        if (tid < 432) {
            sts128f(sb + rg * 1728 + cq * 32, a[0], a[1], a[2], a[3]);
            sts128f(sb + rg * 1728 + cq * 32 + 16, a[4], a[5], a[6], a[7]);
        }
        __syncthreads();
        if (tid < 432) {
            float s = 0.f;
#pragma unroll
            for (int i = 0; i < 8; i++) s += __uint_as_float(lds32(sb + i * 1728 + tid * 4));
            g_cs[sp * 432 + tid] = s;
        }
        __syncthreads();
        if (tid == 0) { flag_release(FL_CS); p.epoch[smid] = ep1; TS(0); }
        if (warp == 0) TSFLUSH();
        return;
    }

    int gpc, idx;
    if (smid < 64) { gpc = (smid & 15) >> 1; idx = (smid >> 4) * 2 + (smid & 1); }
    else if (smid < 120) { int t = smid - 64; gpc = 1 + (t % 14) / 2; idx = 8 + (t / 14) * 2 + (smid & 1); }
    else { gpc = 0; idx = 8 + (smid - 124); }
    const int rb = 2 * gpc + (idx & 1), j = idx >> 1;
    const int g = lane >> 2, c = lane & 3;
    const int cm = 160 * (j >> 1) + 64 * (j & 1) + ((j & 2) ? 32 : 0), cr = 160 * (j >> 1) + 16 * (j & 1) + ((j & 2) ? 0 : 128);

    {
        if (warp == 5) TSW(61);
        const int w10 = warp - 10 * hb, h = w10 >= 5;
        const int pr = (w10 - 5 * h) * 8 + (lane >> 2), blk = 4 * hb + (lane & 3);
        const int ch = 2 * pr + (pr < 24 ? 48 * pg : 336 + 32 * pg);
        const uint4 sw = __ldg(reinterpret_cast<const uint4*>(p.shift + ch * 4));
        uint32_t dv = 0;
        if (warp == 9 && lane < 5) dv = __bfloat16_as_ushort(p.ssmD[chan(lane)]);
        if (tid == 512) { sts32(sb + SM_GV + 512, smid); asm volatile("fence.release.sync_restrict::shared::cta.cluster;" ::: "memory"); }
        asm volatile("barrier.cluster.arrive.relaxed.aligned;" ::: "memory");
        if (warp == 11 && lane < 13) prefetch_map(&maps.hn + lane);
        if (wg < 4) {
            const int t = tid & 127, cc = (wg == 3 && t >= 64) ? 4 : wg;
            if (t < 64 || wg == 3) sts128(sb + sm_u(cc) + ((t >> 5) & 1) * U_PLANE + 2048 + lane * 16, make_uint4(0, 0, 0, 0));
            if ((t & 63) < 4 && (t < 64 || wg == 3)) sts128(sb + sm_k(cc) + ((t >> 1) & 1) * 4160 + (t & 1) * 16, make_uint4(0, 0, 0, 0));
        }
        if (warp == 9 && lane < 5) sts32(sb + SM_GV + 520 + lane * 4, dv << 16);
        asm volatile("cp.async.wait_group 0;" ::: "memory");
        if (!hb) bar_arrive(12, 640);
        bar_sync(hb ? 12 : 14, 640);
        if (warp == 9) {
            if (SSM_DELAY) spin(SSM_DELAY);
            if (elect()) {
#pragma unroll
                for (int i = 0; i < SSM_N; i++) {
                    mbar_expect(bars + (BAR_K + i) * 8, 4096);
                    bulk_g2s(sb + sm_k(i) + 32, p.ssmk + (size_t)(chan(i)) * S_, 4096, bars + (BAR_K + i) * 8);
                }
            }
        }
        const uint32_t w0 = prmt(sw.x, sw.z, 0x5410), w1 = prmt(sw.x, sw.z, 0x7632), w2 = prmt(sw.y, sw.w, 0x5410), w3 = prmt(sw.y, sw.w, 0x7632);
        const uint32_t ka = sb + SM_PK + 2592 + blk * 2592 + h * 1280 + pr * 4;
        const uint32_t va = sb + SM_PV + blk * 2592 + h * 1280 + pr * 4;
        uint32_t kk[11], kv[8];
#pragma unroll
        for (int i = 0; i < 11; i++) kk[i] = lds32(ka + (i - 3) * 160 - ((i < 3 && h == 0) ? 32 : 0));
#pragma unroll
        for (int i = 0; i < 8; i++) {
            uint32_t t = badd2(badd2(badd2(bmul2(kk[i], w3), bmul2(kk[i + 1], w2)), bmul2(kk[i + 2], w1)), bmul2(kk[i + 3], w0));
            kv[i] = bmul2(t, lds32(va + i * 160));
        }
        uint4 o0, o1;
        o0.x = prmt(kv[1], kv[0], 0x5410); o0.y = prmt(kv[3], kv[2], 0x5410); o0.z = prmt(kv[5], kv[4], 0x5410); o0.w = prmt(kv[7], kv[6], 0x5410);
        o1.x = prmt(kv[1], kv[0], 0x7632); o1.y = prmt(kv[3], kv[2], 0x7632); o1.z = prmt(kv[5], kv[4], 0x7632); o1.w = prmt(kv[7], kv[6], 0x7632);
        uint4* dst = reinterpret_cast<uint4*>(g_kvT) + ch * 256 + h * 128 + (127 - (8 * pi + blk));
        dst[0] = o0;
        dst[256] = o1;
    }

    const int rho = 8 * rb + j;

    if (wg == 4) {
        asm volatile("setmaxnreg.dec.sync.aligned.u32 32;");
        const unsigned ep1 = __shfl_sync(0xffffffffu, ep0, 0) + 1;
        if (wq == 0) {
            bar_sync(13, 640);
            TSW(39);
            if (lane == 0) flag_release(FL_P + pg);
            __syncwarp();
            TSW(2);
            if (lane < 5) mbar_expect(bars + (BAR_U + lane) * 8, 4096);
            flag_wait(FL_P + pg, ep1 * 16);
            fence_async_global();
            TSW(3);
            if (elect()) {
#pragma unroll
                for (int i = 0; i < 5; i++) {
                    const char* us = (const char*)g_kvT + (size_t)(chan(i)) * 4096;
                    bulk_g2s(sb + sm_u(i), us, 2048, bars + (BAR_U + i) * 8);
                    bulk_g2s(sb + sm_u(i) + U_PLANE, us + 2048, 2048, bars + (BAR_U + i) * 8);
                }
            }
            __syncwarp();
            if (elect()) {
#pragma unroll
                for (int i = SSM_N; i < 5; i++) {
                    mbar_expect(bars + (BAR_K + i) * 8, 4096);
                    bulk_g2s(sb + sm_k(i) + 32, p.ssmk + (size_t)(chan(i)) * S_, 4096, bars + (BAR_K + i) * 8);
                }
                if (WMD2) spin(WMD2);
                if (cta < 120) {
                    mbar_expect(bars + BAR_WM0 * 8, 3 * 8192);
                    mbar_expect(bars + BAR_WM * 8, 2 * 8192);
#pragma unroll 1
                    for (int i = 0; i < 5; i++) tma2d(sb + SM_WM + i * 8192, &maps.wm, cta * 32, i * 128, bars + (i < 3 ? BAR_WM0 : BAR_WM) * 8);
                }
                mbar_wait(bars + (cta < 120 ? BAR_WM0 : BAR_K + 4) * 8, 0);
                bulk_prefetch((const char*)p.q + cta * 20480, 20480);
                bulk_prefetch((const char*)p.w1 + cta * 6400, 6400);
                bulk_prefetch((const char*)p.w2 + cta * 6400, 6400);
            }
            __syncwarp();
        } else {
            bar_arrive(13, 640);
        }
        asm volatile("barrier.cluster.wait.aligned;" ::: "memory");
        uint32_t peer;
        asm volatile("ld.shared::cluster.u32 %0, [%1];" : "=r"(peer) : "r"(mapa(sb + SM_GV + 512, (blockIdx.x & 1) ^ 1)) : "memory");
        const bool paired = peer == (smid ^ 1) && !FORCE_UNPAIRED;
        if (tid == 639) sts32(sb + SM_GV + 516, paired);
        if (cta < 120) {
            float d[4];
            if (tid >= 544 && tid < 624) {
                const int t = tid - 544;
                mbar_wait(bars + BAR_U * 8, 0);
                uint4 cv = __ldg(reinterpret_cast<const uint4*>(p.c) + t);
                auto silu2 = [](uint32_t v) { float a = blo(v), b = bhi(v); return pack2(__fdividef(a, 1.0f + __expf(-a)), __fdividef(b, 1.0f + __expf(-b))); };
#pragma unroll 1
                for (int i = 0; i < 4; i++) { const uint32_t r = silu2(cv.x); cv.x = cv.y; cv.y = cv.z; cv.z = cv.w; cv.w = r; }
                sts128(sb + SM_Y + (t % 40) * 32 + (t / 40) * 16, cv);
                fence_async_smem();
            }
            bar_sync(5, 128);
            mbar_wait(bars + BAR_WM0 * 8, 0);
            mbar_wait(bars + BAR_WM * 8, 0);
            if (wq == 3) TSW(56);
            const uint32_t da = desc_lo(sb + SM_WM, 20480), db = desc_lo(sb + SM_Y, 32);
#pragma unroll 1
            for (int k0 = 0; k0 < 20; k0 += 4) {
                wg_fence();
#pragma unroll
                for (int k = k0; k < k0 + 4; k++) asm volatile("{.reg .pred p; .reg .b32 l,m; .reg .b64 da,db; setp.ne.b32 p,%10,0; add.u32 l,%4,%6; mov.b64 da,{l,%8}; add.u32 m,%5,%7; mov.b64 db,{m,%9};"
                             " wgmma.mma_async.sync.aligned.m64n8k16.f32.bf16.bf16 {%0,%1,%2,%3},da,db,p,1,1,1,0;}"
                             : "+f"(d[0]), "+f"(d[1]), "+f"(d[2]), "+f"(d[3])
                             : "r"(da), "r"(db), "r"(64 * k), "r"(4 * k), "n"(desc_hi(512, 2u)), "n"(desc_hi(128, 0)), "r"(k));
                wg_commit();
            }
            wg_wait<0>();
            reg_fence<4>(d);
            if (c == 0) {
                sts32(sb + SM_GV + (16 * wq + g) * 4, __float_as_uint(wq < 2 ? d[0] : d[1]));
                sts32(sb + SM_GV + (16 * wq + g + 8) * 4, __float_as_uint(wq < 2 ? d[2] : d[3]));
            }
            bar_sync(5, 128);
            if (wq == 2) {
                g_mod[cta * 32 + lane] = __float2bfloat16_rn(__uint_as_float(lds32(sb + SM_GV + lane * 4)) + __uint_as_float(lds32(sb + SM_GV + 128 + lane * 4)));
            }
        }
        if (wq == 2) {
            bar_sync(9, 320);
            if (lane == 0) { flag_release(FL_M); mbar_expect(bars + BAR_MR * 8, 0); }
            __syncwarp();
            TSW(4);
            flag_wait(FL_M, ep1 * 128);
            fence_async_global();
            if (elect()) {
                mbar_expect(bars + BAR_M * 8, 7680);
                bulk_g2s(sb + SM_MOD, g_mod, 7680, bars + BAR_M * 8);
                mbar_wait(bars + BAR_CD * 8, 0);
                mbar_expect(bars + BAR_Y * 8, 12288);
                bulk_g2s(sb + SM_Y, g_yv + rho * 5120, 12288, bars + BAR_Y * 8);
            }
            __syncwarp();
            TSW(60);
            bar_sync(8, 576);  if (lane == 0) { flag_release(FL_R + rb); TS(23); }  __syncwarp();
            bar_sync(15, 288); if (lane == 0) { flag_release(FL_B1 + rb); TS(27); } __syncwarp();
            bar_sync(6, 288);  if (lane == 0) { flag_release(FL_B2 + rb); TS(31); } __syncwarp();
#pragma unroll 1
            for (int i = 0; i < 3; i++) { bar_sync(i ? i : 8, 288); if (lane == 0) { TS(53 + (i + 2) % 3); flag_release(FL_G + 16 * i + rb); TS(57 + (i + 2) % 3); } __syncwarp(); }
            if (lane == 0) p.epoch[smid] = ep1;
            return;
        }
        if (wq == 1) {
            bar_sync(9, 320);
            mbar_wait(bars + BAR_MR * 8, 0);
            if (lane < 4 * NB) mbar_arrive_cl(mapa(bars + (BAR_EB + (lane >> 2)) * 8, paired ? lane & 1 : blockIdx.x & 1));
        }
        if (wq == 3) {
            bar_sync(7, 544);
            if (lane == 0) { flag_release(FL_C); mbar_expect(bars + BAR_CD * 8, 0); TS(20); }
            __syncwarp();
            if (lane == 0) mbar_expect(bars + BAR_Y2 * 8, 8192);
            flag_wait(FL_C, ep1 * 128);
            fence_async_global();
            TSW(21);
            if (elect()) {
                bulk_g2s(sb + SM_Y + 12288, g_yv + rho * 5120 + 3072, 8192, bars + BAR_Y2 * 8);
            }
            __syncwarp();
        }
        if (wq == 3) {
            mbar_wait(bars + BAR_Y2 * 8, 0);
            if (elect()) {
                mbar_expect(bars + BAR_XY * 8, 20480);
#pragma unroll 1
                for (int i = 0; i < 8; i++) {
                    bulk_g2s(sb + SM_YT + i * 2560, g_yv + (8 * rb + i) * 5120 + cm * 8, 2048, bars + BAR_XY * 8);
                    bulk_g2s(sb + SM_YT + i * 2560 + 2048, g_yv + (8 * rb + i) * 5120 + cr * 8, 512, bars + BAR_XY * 8);
                }
            }
            __syncwarp();
            bar_sync(8, 576);
            mbar_wait_warm(bars + BAR_FA * 8, 0);
            mbar_wait(bars + BAR_ME * 8, 0);
            mbar_wait_warm(bars + (BAR_FA + 11 % NA) * 8, (11 / NA) & 1);
            flag_wait(FL_CS, ep1 * 4);
            fence_async_global();
            if (elect()) {
                mbar_expect(bars + BAR_CS * 8, 864);
                bulk_g2s(sb + SM_CS, g_cs + 64 * j, 256, bars + BAR_CS * 8);
                bulk_g2s(sb + SM_CS + 256, g_cs + 512 + RA3 * j, 4 * RA3, bars + BAR_CS * 8);
                bulk_g2s(sb + SM_CS + 256 + 4 * RA3, g_cs + HB0 + 64 * j, 256, bars + BAR_CS * 8);
                bulk_g2s(sb + SM_CS + 512 + 4 * RA3, g_cs + HB0 + 512 + RB3 * j, 4 * RB3, bars + BAR_CS * 8);
            }
            __syncwarp();
            mbar_wait(bars + BAR_ME * 8, 1);
            mbar_wait_warm(bars + (BAR_FA + 21 % NA) * 8, (21 / NA) & 1);
#pragma unroll 1
            for (int i = 0; i < 3; i++) {
                if (i) {
                    mbar_wait(bars + BAR_ME * 8, (i + 1) & 1);
                    for (int n = i; n < 5; n++) { spin(PING); n += tensor_ping(); }
                }
                flag_wait(FL_G + 16 * i + rb, ep1 * 8);
                if (lane == 0) { mbar_expect(bars + (BAR_G + i) * 8, 0); TS(35 + (i + 2) % 3); }
                __syncwarp();
            }
            return;
        }
        if (elect()) {
            if (wq == 1) {
                Ring<NB, SM_RB, BAR_FB, BAR_EB> r{sb, 0, 0};
#pragma unroll 1
                for (int ph = 0; ph < 7; ph++) {
                    const CUtensorMap* ma = ph == 0 ? &maps.w1a : ph == 1 ? &maps.w2a : ph == 6 ? &maps.w4a : &maps.w3a;
                    const bool b3b = ph == 2 || ph == 4 || ph == 5;
                    r.runw(paired, idx & 1, ma, ma + (b3b ? 2 : 1), ph == 3 ? 64 * j : b3b ? HB0 + 64 * j : cm,
                           ph == 3 ? 512 + RA3 * j : b3b ? HB0 + 512 + RB3 * j : cr, ph == 4 ? 10 - NA : ph == 5 ? 1 : 0,
                           ph == 6 ? 27 : ph == 5 ? 10 - NA : ph == 2 ? 1 : 10, ph == 0 ? 0 : ph == 6 ? OWNG * (HB0 / 64 + j) : cm >> 6,
                           ph == 3 ? 8192 + 128 * RA3 : b3b ? 8192 + 128 * RB3 : 10240,
                           ph == 0 ? GATE0 : ph == 1 ? GATE : ph == 3 ? GATE - 1 : -1, bars + (ph == 0 ? BAR_Y2 : BAR_ST - (ph == 1)) * 8);
                }
            } else {
                Ring<NA, SM_RA, BAR_FA, BAR_EA> r{sb, 0, 0};
                if (cta >= 120) mbar_wait(bars + (BAR_K + 4) * 8, 0);
                mbar_expect(bars + BAR_XR * 8, 20480);
                bulk_g2s(sb + SM_XR, p.q + (size_t)rho * 16 * D_, 20480, bars + BAR_XR * 8);
                mbar_wait(bars + BAR_Y2 * 8, 0);
                mbar_expect(bars + BAR_XY * 8, 20480);
                tma2d(sb + SM_XT, &maps.xa, cm, rb * 128, bars + BAR_XY * 8);
                tma2d(sb + SM_XT2, &maps.xb, cr, rb * 128, bars + BAR_XY * 8);
                const int grp = j >> 1;
                const int delta = (grp & 1 ? 1 : -1) * (1 + (grp >> 1));
                const int nb = min(max(rb + (delta > 0 ? 1 : -1), 0), 15);
                uint32_t fb = r.acquire(SLOT), dst = r.slot();
                flag_wait2(FL_R + nb, FL_R + rb, ep1 * 8);
                fence_async_global();
                tma2d(dst, &maps.hn, 0, rb * 128 + delta, fb);
                TS(24);
                r.next();
                r.run2d(&maps.hn, rb * 128 + delta);
#pragma unroll 1
                for (int i = 0; i < 2; i++) {
                    const char* src = (const char*)(i ? g_x1 : g_h1) + (size_t)rb * 163840;
                    r.acquire(0); r.next();
                    fb = r.acquire(SLOT); dst = r.slot();
                    const char* src1 = src + (cm == 0 ? SLOT : 0);
                    flag_wait(FL_B1 + 16 * i + rb, ep1 * 8);
                    fence_async_global();
                    bulk_g2s(dst, src1, SLOT, fb);
                    TS(28 + 4 * i);
                    mbar_expect(bars + (BAR_ST - 1 + i) * 8, 0);
                    r.next();
                    r.run1d(src, 2, 10, cm >> 6);
                }
                r.run1d((const char*)g_x1 + (size_t)rb * 163840, 1, 10 - NA, cm >> 6);
                if (OWNG) { r.acquire(0); r.next(); }
#pragma unroll 1
                for (int i = 0; i < 2; i++) {
                    mbar_wait(bars + (BAR_G + 1 + i) * 8, 0); fence_async_global();
                    r.run1d((const char*)g_g + (size_t)rb * 442368, OWNG + HB0 / 64 * i, i ? 27 : OWNG + HB0 / 64, OWNG * (HB0 / 64 + j));
                }
            }
        }
        return;
    }
    bar_arrive(13, 640);
    asm volatile("setmaxnreg.inc.sync.aligned.u32 112;");
    const int rrow = 16 * rho + (warp >> 1) + 8 * (warp & 1);

    fence_async_smem();
    bar_sync(1 + wg, 128);
#pragma unroll 1
    for (int cc = wg; cc < wg + 1 + (wg == 3); cc++) {
        mbar_wait(bars + (BAR_K + cc) * 8, 0);
        if (cc == 2 && wq == 0) TSW(40);
        uint32_t a = sb + sm_k(cc) + 32 + (tid & 127) * 32;
        uint32_t pw = lds32(a - 4);
        uint4 x = lds128(a), y = lds128(a + 16), o;
        if ((tid & 127) == 0) {
            uint16_t k0 = __bfloat16_as_ushort(__float2bfloat16_rn(blo(x.x) + __uint_as_float(lds32(sb + SM_GV + 520 + cc * 4))));
            x.x = (x.x & 0xffff0000u) | k0;
            sts16(a, k0);
        }
        o.x = prmt(pw, x.x, 0x5432); o.y = prmt(x.x, x.y, 0x5432); o.z = prmt(x.y, x.z, 0x5432); o.w = prmt(x.z, x.w, 0x5432);
        sts128(a + 4160, o);
        o.x = prmt(x.w, y.x, 0x5432); o.y = prmt(y.x, y.y, 0x5432); o.z = prmt(y.y, y.z, 0x5432); o.w = prmt(y.z, y.w, 0x5432);
        sts128(a + 4176, o);
    }
    bar_sync(1 + wg, 128);
    if (wg == 3) bar_arrive(11, 256);
#pragma unroll 1
    for (int cc = wg; cc < 5; cc += 3) {
        if (cc == 3 && wg == 0) break;
        if (cc == 4) bar_sync(11, 256);
        const uint32_t kaddr = sb + sm_k(cc) + ((g & 1) ? 32 : 4192) + 4 * ((g >> 1) - c) + 64 * wq;
        const AFrag f0 = ldA(kaddr), f1 = ldA(kaddr + 256);
        if (STAG && cc == 3) bar_sync(12, 256);
        mbar_wait(bars + (BAR_U + cc) * 8, 0);
        if (wq == 0) TSW(5 + cc);
        float d[64];
        conv_two<0>(d, f0, f1, kaddr, desc_lo(sb + sm_u(cc), U_PLANE), sb + sm_red(cc) + wq * 4352 + g * 544 + c * 8, cc == 1);
        if (wq == 0) TSW(10 + cc);
        if (cc == 1) bar_arrive(6, 256);
    }
#pragma unroll 1
    for (int cc = wg == 1 ? 4 : wg;; cc++) {
        if (cc == 1) bar_sync(6, 256); else bar_sync(1 + wg, 128);
        const int ch = chan(cc);
        uint32_t* dst = g_yv + ch * 8 + ((g + (ch >> 2)) & 7) + (126 - 32 * wq - 2 * c) * 5120;
        uint2 v[16];
#pragma unroll
        for (int i = 0; i < 16; i++) v[i] = lds64(sb + sm_red(cc) + g * 544 + wq * 128 + c * 8 + (i >> 2) * 32 + (i & 3) * 4360);
#pragma unroll
        for (int w = 1; w < 4; w++)
            if (wq == 3 && c > 3 - w) v[12 + w] = make_uint2(0, 0);
#pragma unroll
        for (int q = 0; q < 4; q++) {
            const uint2* u = v + 4 * q;
            dst[-8 * q * 5120] = badd2(u[0].x, badd2(u[1].x, badd2(u[2].x, u[3].x)));
            dst[(-8 * q + 1) * 5120] = badd2(u[0].y, badd2(u[1].y, badd2(u[2].y, u[3].y)));
        }
        if (wq == 0) TSW(15 + cc);
        if (cc != 0) break;
    }
    fence_async_smem();
    if (!(wg & 1)) bar_arrive(9, 320);
    bar_arrive(7, 544);

    const uint32_t one2 = 0x3f803f80u;
    const unsigned ones = p.ones;
    {
        uint32_t x[10], a[10], cb[10], sbv[10];
        bar_sync(10, 512);
        mbar_wait(bars + BAR_XR * 8, 0);
#pragma unroll
        for (int i = 0; i < 10; i++) x[i] = lds32(sb + SM_XR + (rrow & 15) * 1280 + lane * 4 + i * 128);
        const uint3 s1 = row_stats<0>(x, lane);
        const int up = lane >> 4, gg = warp >> 1, e = warp & 1;
        const uint32_t ya = sb + SM_Y + lane * 64 + ((gg + (lane >> 1)) & 7) * 4;
        const uint32_t sel = (up ? 0x1054u : 0x5410u) + (e ? 0x2222u : 0u);
        const uint32_t ma = sb + SM_MOD + lane * 4;
        mbar_wait(bars + BAR_M * 8, 0);
        uint32_t pin = 0;
#pragma unroll
        for (int i = 0; i < 10; i++) {
            uint32_t h = bfma2(ln_apply(x[i], s1.x, s1.y, s1.z), badd2(lds32(ma + 1280 + i * 128), one2), lds32(ma + i * 128));
            a[i] = bmul2(h, lds32(ma + 2560 + i * 128));
            sbv[i] = lds32(ma + 3840 + i * 128);
            cb[i] = badd2(lds32(ma + 5120 + i * 128), one2);
            pin ^= a[i] ^ cb[i];
        }
        if (pin & ~ones) sts32(sb + SM_GV, pin);
        if (warp == 4) TSW(52);
        mbar_wait(bars + BAR_Y * 8, 0);
        RowSum part;
#pragma unroll
        for (int i = 0; i < 10; i++) {
            if (i == 6) {
                if ((__float_as_uint(part.s + part.s_ + part.q + part.q_) & ~ones)) sts32(sb + SM_GV, pin);
                mbar_wait(bars + BAR_Y2 * 8, 0);
                if (warp == 0) TSW(22);
            }
            uint32_t y0 = lds32(ya + i * 2048 + up * 32), y1 = lds32(ya + i * 2048 + (up ^ 1) * 32);
            x[i] = bfma2(a[i], prmt(y0, y1, sel), x[i]);
            if (i < 6) part.add(x[i]);
        }
        const uint3 s2 = row_stats<6>(x, lane, part);
#pragma unroll
        for (int i = 0; i < 10; i++) x[i] = bfma2(ln_apply(x[i], s2.x, s2.y, s2.z), cb[i], sbv[i]);
        const uint3 s3 = row_stats<0>(x, lane);
        uint32_t* o = reinterpret_cast<uint32_t*>(g_hn + (size_t)rrow * D_) + lane;
#pragma unroll
        for (int i = 0; i < 10; i++) o[32 * i] = ln_apply(x[i], s3.x, s3.y, s3.z);
        if (lane < 2) g_rs[rrow * 2 + lane] = lane ? make_uint4(s2.x, s2.y, s2.z, 0) : make_uint4(s1.x, s1.y, s1.z, 0);
        if (warp == 0) TSW(34);
        bar_arrive(8, 576);
    }

    const int half = wg & 1;
    const int row = 64 * half + 16 * wq + g;
    const int tw0 = (rb * 80 + (cm >> 3)) * 512 + row * 4 + c, tw1 = (rb * 80 + (cr >> 3) - 8) * 512 + row * 4 + c;
    const uint32_t park = sb + SM_Y + (tid & 255) * 16;
    const uint32_t ms0 = sb + SM_MOD + (cm + 2 * c) * 2, ms1 = sb + SM_MOD + (cr - 64 + 2 * c) * 2;
    if (wg >= 2) {
        {
            float acc[40];
            gemm_loop<80, true, 10, 10, true>(acc, sb, half, 0, 0, 10, 0, 0, 25);
            if (tid == 256) mbar_expect(bars + BAR_ME * 8, 0);
#pragma unroll
            for (int k = 0; k < 10; k += CH) CHUNK(k) {
#pragma unroll
                for (int q = k; q < k + CH && q < 10; q++) {
                    uint32_t* dst = reinterpret_cast<uint32_t*>(g_h1) + (q < 8 ? tw0 : tw1);
                    const uint32_t u = gelu2_h(bmul2(pack2(acc[4 * q], acc[4 * q + 1]), 0x3f003f00u));
                    const uint32_t v = gelu2_h(bmul2(pack2(acc[4 * q + 2], acc[4 * q + 3]), 0x3f003f00u));
                    dst[q * 512] = u;
                    dst[q * 512 + 32] = v;
                    acc[4 * q] = __uint_as_float(u); acc[4 * q + 1] = __uint_as_float(v);
                }
            }
            bar_arrive(15, 288);
            mbar_wait(bars + (BAR_FA + 10 % NA) * 8, (10 / NA) & 1);
#pragma unroll
            for (int q = 0; q < 8; q++) {
                sts32(sb + SM_RA + (10 % NA) * SLOT + q * 2048 + row * 16 + c * 4, __float_as_uint(acc[4 * q]));
                sts32(sb + SM_RA + (10 % NA) * SLOT + q * 2048 + row * 16 + c * 4 + 128, __float_as_uint(acc[4 * q + 1]));
            }
            fence_async_smem();
            bar_arrive(14, 512);
        }
        gemm3<0>(sb, rb, j, half, row, c, ones);
        {
            float acc[40];
            uint32_t gbv[10], base[20];
#pragma unroll
            for (int q = 0; q < 10; q++) gbv[q] = lds32((q < 8 ? ms0 : ms1) + 6400 + q * 16);
#pragma unroll
            for (int q = 0; q < 5; q++) { const uint4 t = lds128(park + q * 4096); base[4 * q] = t.x; base[4 * q + 1] = t.y; base[4 * q + 2] = t.z; base[4 * q + 3] = t.w; }
            gemm_loop<80, false, 27, 27 - NB, true>(acc, sb, half, 39 - NA, 40, 27 - NA, 11, 0, 42);
            auto fin = [&](int q, int r) {
                return bfma2(gbv[q], pack2(acc[4 * q + 2 * r], acc[4 * q + 2 * r + 1]), base[2 * q + r]);
            };
            auto tr4 = [&](uint32_t t0, uint32_t t1, uint32_t t2, uint32_t t3) {
                const bool o1 = c & 1, o2 = c & 2;
                uint32_t a = __shfl_xor_sync(0xffffffffu, o1 ? t0 : t1, 1), b = __shfl_xor_sync(0xffffffffu, o1 ? t2 : t3, 1);
                uint32_t u0 = o1 ? a : t0, u1 = o1 ? t1 : a, u2 = o1 ? b : t2, u3 = o1 ? t3 : b;
                a = __shfl_xor_sync(0xffffffffu, o2 ? u0 : u2, 2); b = __shfl_xor_sync(0xffffffffu, o2 ? u1 : u3, 2);
                return o2 ? make_uint4(a, b, u2, u3) : make_uint4(u0, u1, a, b);
            };
            bf16* go = p.out + (size_t)(rb * 128 + row) * D_;
#pragma unroll
            for (int k = 0; k < 2; k++) CHUNK(k) {
#pragma unroll
                for (int r = 0; r < 2; r++)
                    *reinterpret_cast<uint4*>(go + r * 8 * D_ + cm + 32 * k + 8 * c) = tr4(fin(4 * k, r), fin(4 * k + 1, r), fin(4 * k + 2, r), fin(4 * k + 3, r));
            }
            CHUNK(2) *reinterpret_cast<uint4*>(go + (c >> 1) * 8 * D_ + cr + 8 * (c & 1)) = tr4(fin(8, 0), fin(9, 0), fin(8, 1), fin(9, 1));
            if (tid == 256) TS(44);
            if (warp == 8) TSFLUSH();
        }
    } else {
        {
            float acc[40];
            uint32_t x2[20];
            {
                uint32_t y[20];
                mbar_wait(bars + BAR_XY * 8, 0);
                const uint32_t xa = sb + SM_XT + row * 128 + c * 4, xb = sb + SM_XT2 + row * 32 + c * 4;
                const uint32_t ya = sb + SM_YT + (4 * half + wq) * 2560 + c * 64;
#pragma unroll
                for (int q = 0; q < 10; q++) {
                    const uint32_t a = q < 8 ? xa + ((q ^ g) << 4) : xb + (q - 8) * 16;
                    x2[2 * q] = lds32(a); x2[2 * q + 1] = lds32(a + (q < 8 ? 1024 : 256));
                    const int pos = (g + ((q < 8 ? cm : cr) >> 2) + 2 * q + (c >> 1)) & 7;
                    y[2 * q] = lds32(ya + q * 256 + pos * 4); y[2 * q + 1] = lds32(ya + q * 256 + 32 + pos * 4);
                }
                fence_async_smem();
                bar_sync(1 + wg, 128);
                if ((tid & 127) < NA) mbar_arrive_cl(mapa(bars + (BAR_EA + (tid & 127)) * 8, blockIdx.x & 1));
                mbar_wait(bars + (BAR_FA + 1) * 8, 0);
                const uint4* rp = g_rs + (rb * 128 + row) * 2;
                const uint4 ra = ldcg128(rp), rb2 = ldcg128(rp + 1), rc = ldcg128(rp + 16), rd = ldcg128(rp + 17);
                bar_sync(14, 512);
#pragma unroll
                for (int q = 0; q < 10; q++) {
                    const uint32_t ms = q < 8 ? ms0 : ms1;
                    const uint32_t sa = lds32(ms + 16 * q), ca = badd2(lds32(ms + 1280 + 16 * q), one2), ga = lds32(ms + 2560 + 16 * q);
                    const uint32_t sbv = lds32(ms + 3840 + 16 * q), cb = badd2(lds32(ms + 5120 + 16 * q), one2);
                    uint32_t u = x2[2 * q], v = x2[2 * q + 1];
                    u = bfma2(bmul2(bfma2(ln_apply(u, ra.x, ra.y, ra.z), ca, sa), ga), prmt(y[2 * q], y[2 * q + 1], 0x5410), u);
                    v = bfma2(bmul2(bfma2(ln_apply(v, rc.x, rc.y, rc.z), ca, sa), ga), prmt(y[2 * q], y[2 * q + 1], 0x7632), v);
                    x2[2 * q] = u; x2[2 * q + 1] = v;
                    u = bfma2(ln_apply(u, rb2.x, rb2.y, rb2.z), cb, sbv);
                    v = bfma2(ln_apply(v, rd.x, rd.y, rd.z), cb, sbv);
                    acc[4 * q] = blo(u); acc[4 * q + 1] = bhi(u); acc[4 * q + 2] = blo(v); acc[4 * q + 3] = bhi(v);
                }
            }
            reg_fence<40>(acc);
            if (tid == 0) TS(45);
            gemm_loop<80, false, 10, 10, false>(acc, sb, half, 10, 10, 10, 0, 0, 29);
            if (tid == 0) mbar_expect(bars + BAR_ME * 8, 0);
            uint32_t x1[20];
            float s0 = 0.f, q0 = 0.f, s1 = 0.f, q1 = 0.f;
#pragma unroll
            for (int q = 0; q < 10; q++) {
                uint32_t u = pack2(acc[4 * q], acc[4 * q + 1]);
                uint32_t v = pack2(acc[4 * q + 2], acc[4 * q + 3]);
                uint32_t* dst = reinterpret_cast<uint32_t*>(g_x1) + (q < 8 ? tw0 : tw1);
                dst[q * 512] = u;
                dst[q * 512 + 32] = v;
                x1[2 * q] = u; x1[2 * q + 1] = v;
            }
            bar_arrive(6, 288);
            CHUNK(0)
#pragma unroll
            for (int q = 0; q < 10; q++) {
                float a = blo(x1[2 * q]), b = bhi(x1[2 * q]), e = blo(x1[2 * q + 1]), f = bhi(x1[2 * q + 1]);
                s0 += a + b; q0 = fmaf(a, a, fmaf(b, b, q0));
                s1 += e + f; q1 = fmaf(e, e, fmaf(f, f, q1));
            }
#pragma unroll
            for (int m = 1; m <= 2; m <<= 1) {
                s0 += __shfl_xor_sync(0xffffffffu, s0, m); q0 += __shfl_xor_sync(0xffffffffu, q0, m);
                s1 += __shfl_xor_sync(0xffffffffu, s1, m); q1 += __shfl_xor_sync(0xffffffffu, q1, m);
            }
            if (c < 2) g_st[(rb * 8 + j) * 128 + row + 8 * c] = c ? make_float2(s1, q1) : make_float2(s0, q0);
            bar_arrive(8, 288);
            mbar_wait(bars + (BAR_FA + 20 % NA) * 8, (20 / NA) & 1);
#pragma unroll
            for (int q = 0; q < 8; q++) {
                sts32(sb + SM_RA + (20 % NA) * SLOT + q * 2048 + row * 16 + c * 4, x1[2 * q]);
                sts32(sb + SM_RA + (20 % NA) * SLOT + q * 2048 + row * 16 + c * 4 + 128, x1[2 * q + 1]);
            }
            fence_async_smem();
            bar_sync(3 + wg, 128);
#pragma unroll
            for (int q = 0; q < 5; q++) {
                const uint32_t ms = q < 4 ? ms0 : ms1;
                const uint32_t g0 = lds32(ms + 6400 + q * 32), g1 = lds32(ms + 6400 + q * 32 + 16);
                sts128(park + q * 4096, make_uint4(bfma2(g0, x1[4 * q], x2[4 * q]), bfma2(g0, x1[4 * q + 1], x2[4 * q + 1]),
                                                   bfma2(g1, x1[4 * q + 2], x2[4 * q + 2]), bfma2(g1, x1[4 * q + 3], x2[4 * q + 3])));
            }
        }
        gemm3<1>(sb, rb, j, half, row, c, ones);
    }
}

typedef CUresult (*EncFn)(CUtensorMap*, CUtensorMapDataType, cuuint32_t, void*, const cuuint64_t*, const cuuint64_t*,
                          const cuuint32_t*, const cuuint32_t*, CUtensorMapInterleave, CUtensorMapSwizzle,
                          CUtensorMapL2promotion, CUtensorMapFloatOOBfill);

void make_map(EncFn enc, CUtensorMap* m, const void* base, uint64_t inner, uint64_t outer, uint32_t bi, uint32_t bo,
              CUtensorMapSwizzle swz = CU_TENSOR_MAP_SWIZZLE_128B) {
    cuuint64_t dims[2] = {inner, outer};
    cuuint64_t st[1] = {inner * 2};
    cuuint32_t box[2] = {bi, bo};
    cuuint32_t es[2] = {1, 1};
    enc(m, CU_TENSOR_MAP_DATA_TYPE_BFLOAT16, 2, const_cast<void*>(base), dims, st, box, es, CU_TENSOR_MAP_INTERLEAVE_NONE,
        swz, CU_TENSOR_MAP_L2_PROMOTION_NONE, CU_TENSOR_MAP_FLOAT_OOB_FILL_NONE);
}

}

extern "C" void kernel_launch(void* const* d_in, const int* in_sizes, int n_in, void* d_out, int out_size) {
    (void)in_sizes; (void)n_in; (void)out_size;
    Params p;
    p.q = (const bf16*)d_in[0]; p.k = (const bf16*)d_in[1]; p.v = (const bf16*)d_in[2];
    p.shift = (const bf16*)d_in[3]; p.ssmk = (const bf16*)d_in[4]; p.ssmD = (const bf16*)d_in[5];
    p.w1 = (const bf16*)d_in[7]; p.w2 = (const bf16*)d_in[8]; p.w3 = (const bf16*)d_in[9]; p.w4 = (const bf16*)d_in[10];
    p.c = (const bf16*)d_in[11]; p.wmod = (const bf16*)d_in[12];
    p.out = (bf16*)d_out;
    p.ones = 0xffffffffu;
    cudaGetSymbolAddress((void**)&p.epoch, g_epoch);

    void* fn = nullptr;
    cudaDriverEntryPointQueryResult qr;
    cudaGetDriverEntryPoint("cuTensorMapEncodeTiled", &fn, cudaEnableDefault, &qr);
    EncFn enc = (EncFn)fn;
    void* hn = nullptr;
    cudaGetSymbolAddress(&hn, g_hn);
    Maps maps;
    make_map(enc, &maps.w3s, p.w3, F_, D_, 216, 64, CU_TENSOR_MAP_SWIZZLE_NONE);
    make_map(enc, &maps.wm, p.wmod, 6 * D_, D_, 32, 128, CU_TENSOR_MAP_SWIZZLE_64B);
    make_map(enc, &maps.xa, p.q, D_, S_, 64, 128);
    make_map(enc, &maps.xb, p.q, D_, S_, 16, 128, CU_TENSOR_MAP_SWIZZLE_NONE);
    make_map(enc, &maps.hn, hn, D_, S_, 64, 128);
    make_map(enc, &maps.w1a, p.w1, D_, D_, 64, 64);
    make_map(enc, &maps.w1b, p.w1, D_, D_, 16, 64);
    make_map(enc, &maps.w2a, p.w2, D_, D_, 64, 64);
    make_map(enc, &maps.w2b, p.w2, D_, D_, 16, 64);
    make_map(enc, &maps.w3a, p.w3, F_, D_, 64, 64);
    make_map(enc, &maps.w3b, p.w3, F_, D_, RA3, 64);
    make_map(enc, &maps.w3c, p.w3, F_, D_, RB3, 64);
    make_map(enc, &maps.w4a, p.w4, D_, F_, 64, 64);
    make_map(enc, &maps.w4b, p.w4, D_, F_, 16, 64);
    cudaFuncSetAttribute(fused_kernel, cudaFuncAttributeMaxDynamicSharedMemorySize, SMEM_BYTES);
    fused_kernel<<<132, NTHREADS, SMEM_BYTES>>>(p, maps);
}
```

```cpp
#include <cuda_runtime.h>
#include <cuda_bf16.h>
#include <cuda.h>
#include <stdint.h>
#include <string.h>

#define SEED 0
#define RING_A 6
#define CH 2
#define FAST_LN 2
#define STAG 12
#define PGELU 2
#define CH3 4
#define HO_A 16
#define HO_B 16
#define RA3 48
#define CSP 16
#define OWNG 1
#define GATE 5
#define SSM_DELAY 100
#define B_DELAY 220
#define PING 250
#define FORCE_UNPAIRED 0
#define GATE0 1
#define SPD 800
#define WMD2 600
#define SSM_N 3

namespace {

typedef __nv_bfloat16 bf16;
typedef __nv_bfloat162 bf162;

constexpr int S_ = 2048, D_ = 640, F_ = 1728;
constexpr int NTHREADS = 640;
constexpr int NA = RING_A, NB = 12 - RING_A;
constexpr int SLOT = 16384;
constexpr int RB3 = 88 - RA3, HB0 = 512 + 8 * RA3;
constexpr int SM_RA = 0, SM_RB = NA * SLOT;

static_assert(NA == 6, "smem map");
constexpr int RED_STRIDE = 17536;
constexpr int K_STRIDE = 8320;
constexpr int U_PLANE = 2560, U_STRIDE = 5120;
constexpr int SM_Y = 12 * SLOT;
__device__ __forceinline__ int sm_red(int cc) { return cc * RED_STRIDE + (cc < 3 ? SM_RB : -3 * RED_STRIDE); }
__device__ __forceinline__ int sm_k(int cc) { return cc * K_STRIDE + (cc < 3 ? SM_RB + 3 * RED_STRIDE : 2 * RED_STRIDE - 3 * K_STRIDE); }
__device__ __forceinline__ int sm_u(int cc) { return cc * U_STRIDE + (cc < 3 ? SM_RB + 3 * RED_STRIDE + 3 * K_STRIDE : SM_Y + 8192 - 3 * U_STRIDE); }
constexpr int SM_PK = SM_RB;
constexpr int SM_PV = SM_RB + 24576;
constexpr int SM_WM = 57344;
constexpr int SM_XT = SM_WM, SM_XT2 = SM_WM + 16384, SM_XR = SM_WM + 20480;
constexpr int SM_YT = 0;
constexpr int SM_MOD = SM_Y + 20480;
constexpr int SM_GV = SM_MOD + 7680;
constexpr int SM_CS = SM_GV + 1024;
constexpr int SM_RP = SM_CS + 1024;
constexpr int SM_BAR = SM_RP + 1024;
constexpr int SM_PROF = SM_BAR + 512;
constexpr int SM_TOTAL = SM_PROF + 512;
constexpr int SMEM_BYTES = SM_TOTAL + 1024;
static_assert(SMEM_BYTES <= 232448, "smem");

constexpr int BAR_FA = 0, BAR_FB = NA, BAR_EA = 12, BAR_EB = 12 + NA, BAR_K = 24, BAR_U = 29, BAR_Y = 34, BAR_CS = 35, BAR_WM = 36, BAR_M = 37, BAR_XY = 38, BAR_Y2 = 39, BAR_G = 40, BAR_ST = 44, BAR_XR = 45, BAR_ME = 46, BAR_CD = 47, BAR_WM0 = 48, BAR_MR = 49, BAR_MC = 50, NBARS = 51;

__device__ __align__(1024) bf16 g_kvT[D_ * S_];
__device__ __align__(1024) uint32_t g_yv[128 * 5120];
__device__ __align__(1024) bf16 g_mod[6 * D_];
__device__ __align__(1024) bf16 g_hn[S_ * D_];
__device__ __align__(1024) uint4 g_rs[S_ * 2];
__device__ __align__(1024) bf16 g_h1[S_ * D_];
__device__ __align__(1024) bf16 g_x1[S_ * D_];
__device__ __align__(1024) bf16 g_g[S_ * F_];
__device__ __align__(1024) float2 g_st[S_ * 8];
__device__ __align__(1024) float g_cs[F_];
__device__ __align__(1024) unsigned g_flags[128 * 32];
__device__ __align__(1024) unsigned g_epoch[160];
constexpr int FL_P = 0, FL_C = 8, FL_CS = 9, FL_M = 10, FL_R = 16, FL_B1 = 32, FL_B2 = 48, FL_G = 64;

#define TS(i) do {} while (0)
#define TSW(i) do {} while (0)
#define TSD(i, dep) do {} while (0)
#define TSD2(i, dep) do {} while (0)
#define TSFLUSH() do {} while (0)

struct Params {
    const bf16 *q, *k, *v, *shift, *ssmk, *ssmD, *w1, *w2, *w3, *w4, *c, *wmod;
    bf16* out;
    unsigned* epoch;
    unsigned ones;
};
#define CHUNK(k) if (ones & (1u << (k)))
struct Maps { CUtensorMap hn, w1a, w1b, w2a, w2b, w3a, w3b, w3c, w4a, w4b, wm, xa, xb, w3s; };

template<int N> struct WgRs;
template<int N> struct WgSs;
template<> struct WgRs<32> { template<int OFF,int HI,int SC> static __device__ __forceinline__ void run(float* d,uint32_t a0,uint32_t a1,uint32_t a2,uint32_t a3,uint32_t blo){
 asm volatile("{.reg .b32 l; .reg .b64 db; add.u32 l,%20,%21; mov.b64 db,{l,%22}; wgmma.mma_async.sync.aligned.m64n32k16.f32.bf16.bf16 {%0,%1,%2,%3,%4,%5,%6,%7,%8,%9,%10,%11,%12,%13,%14,%15},{%16,%17,%18,%19},db,%23,1,1,0;}"
 :"+f"(d[0]),"+f"(d[1]),"+f"(d[2]),"+f"(d[3]),"+f"(d[4]),"+f"(d[5]),"+f"(d[6]),"+f"(d[7]),"+f"(d[8]),"+f"(d[9]),"+f"(d[10]),"+f"(d[11]),"+f"(d[12]),"+f"(d[13]),"+f"(d[14]),"+f"(d[15])
 :"r"(a0),"r"(a1),"r"(a2),"r"(a3),"r"(blo),"n"(OFF),"n"(HI),"n"(SC)); } };
template<> struct WgRs<48> { template<int OFF,int HI,int SC> static __device__ __forceinline__ void run(float* d,uint32_t a0,uint32_t a1,uint32_t a2,uint32_t a3,uint32_t blo){
 asm volatile("{.reg .b32 l; .reg .b64 db; add.u32 l,%28,%29; mov.b64 db,{l,%30}; wgmma.mma_async.sync.aligned.m64n48k16.f32.bf16.bf16 {%0,%1,%2,%3,%4,%5,%6,%7,%8,%9,%10,%11,%12,%13,%14,%15,%16,%17,%18,%19,%20,%21,%22,%23},{%24,%25,%26,%27},db,%31,1,1,0;}"
 :"+f"(d[0]),"+f"(d[1]),"+f"(d[2]),"+f"(d[3]),"+f"(d[4]),"+f"(d[5]),"+f"(d[6]),"+f"(d[7]),"+f"(d[8]),"+f"(d[9]),"+f"(d[10]),"+f"(d[11]),"+f"(d[12]),"+f"(d[13]),"+f"(d[14]),"+f"(d[15]),"+f"(d[16]),"+f"(d[17]),"+f"(d[18]),"+f"(d[19]),"+f"(d[20]),"+f"(d[21]),"+f"(d[22]),"+f"(d[23])
 :"r"(a0),"r"(a1),"r"(a2),"r"(a3),"r"(blo),"n"(OFF),"n"(HI),"n"(SC)); } };
template<> struct WgRs<64> { template<int OFF,int HI,int SC> static __device__ __forceinline__ void run(float* d,uint32_t a0,uint32_t a1,uint32_t a2,uint32_t a3,uint32_t blo){
 asm volatile("{.reg .b32 l; .reg .b64 db; add.u32 l,%36,%37; mov.b64 db,{l,%38}; wgmma.mma_async.sync.aligned.m64n64k16.f32.bf16.bf16 {%0,%1,%2,%3,%4,%5,%6,%7,%8,%9,%10,%11,%12,%13,%14,%15,%16,%17,%18,%19,%20,%21,%22,%23,%24,%25,%26,%27,%28,%29,%30,%31},{%32,%33,%34,%35},db,%39,1,1,0;}"
 :"+f"(d[0]),"+f"(d[1]),"+f"(d[2]),"+f"(d[3]),"+f"(d[4]),"+f"(d[5]),"+f"(d[6]),"+f"(d[7]),"+f"(d[8]),"+f"(d[9]),"+f"(d[10]),"+f"(d[11]),"+f"(d[12]),"+f"(d[13]),"+f"(d[14]),"+f"(d[15]),"+f"(d[16]),"+f"(d[17]),"+f"(d[18]),"+f"(d[19]),"+f"(d[20]),"+f"(d[21]),"+f"(d[22]),"+f"(d[23]),"+f"(d[24]),"+f"(d[25]),"+f"(d[26]),"+f"(d[27]),"+f"(d[28]),"+f"(d[29]),"+f"(d[30]),"+f"(d[31])
 :"r"(a0),"r"(a1),"r"(a2),"r"(a3),"r"(blo),"n"(OFF),"n"(HI),"n"(SC)); } };
template<> struct WgRs<80> { template<int OFF,int HI,int SC> static __device__ __forceinline__ void run(float* d,uint32_t a0,uint32_t a1,uint32_t a2,uint32_t a3,uint32_t blo){
 asm volatile("{.reg .b32 l; .reg .b64 db; add.u32 l,%44,%45; mov.b64 db,{l,%46}; wgmma.mma_async.sync.aligned.m64n80k16.f32.bf16.bf16 {%0,%1,%2,%3,%4,%5,%6,%7,%8,%9,%10,%11,%12,%13,%14,%15,%16,%17,%18,%19,%20,%21,%22,%23,%24,%25,%26,%27,%28,%29,%30,%31,%32,%33,%34,%35,%36,%37,%38,%39},{%40,%41,%42,%43},db,%47,1,1,0;}"
 :"+f"(d[0]),"+f"(d[1]),"+f"(d[2]),"+f"(d[3]),"+f"(d[4]),"+f"(d[5]),"+f"(d[6]),"+f"(d[7]),"+f"(d[8]),"+f"(d[9]),"+f"(d[10]),"+f"(d[11]),"+f"(d[12]),"+f"(d[13]),"+f"(d[14]),"+f"(d[15]),"+f"(d[16]),"+f"(d[17]),"+f"(d[18]),"+f"(d[19]),"+f"(d[20]),"+f"(d[21]),"+f"(d[22]),"+f"(d[23]),"+f"(d[24]),"+f"(d[25]),"+f"(d[26]),"+f"(d[27]),"+f"(d[28]),"+f"(d[29]),"+f"(d[30]),"+f"(d[31]),"+f"(d[32]),"+f"(d[33]),"+f"(d[34]),"+f"(d[35]),"+f"(d[36]),"+f"(d[37]),"+f"(d[38]),"+f"(d[39])
 :"r"(a0),"r"(a1),"r"(a2),"r"(a3),"r"(blo),"n"(OFF),"n"(HI),"n"(SC)); } };
template<> struct WgRs<96> { template<int OFF,int HI,int SC> static __device__ __forceinline__ void run(float* d,uint32_t a0,uint32_t a1,uint32_t a2,uint32_t a3,uint32_t blo){
 asm volatile("{.reg .b32 l; .reg .b64 db; add.u32 l,%52,%53; mov.b64 db,{l,%54}; wgmma.mma_async.sync.aligned.m64n96k16.f32.bf16.bf16 {%0,%1,%2,%3,%4,%5,%6,%7,%8,%9,%10,%11,%12,%13,%14,%15,%16,%17,%18,%19,%20,%21,%22,%23,%24,%25,%26,%27,%28,%29,%30,%31,%32,%33,%34,%35,%36,%37,%38,%39,%40,%41,%42,%43,%44,%45,%46,%47},{%48,%49,%50,%51},db,%55,1,1,0;}"
 :"+f"(d[0]),"+f"(d[1]),"+f"(d[2]),"+f"(d[3]),"+f"(d[4]),"+f"(d[5]),"+f"(d[6]),"+f"(d[7]),"+f"(d[8]),"+f"(d[9]),"+f"(d[10]),"+f"(d[11]),"+f"(d[12]),"+f"(d[13]),"+f"(d[14]),"+f"(d[15]),"+f"(d[16]),"+f"(d[17]),"+f"(d[18]),"+f"(d[19]),"+f"(d[20]),"+f"(d[21]),"+f"(d[22]),"+f"(d[23]),"+f"(d[24]),"+f"(d[25]),"+f"(d[26]),"+f"(d[27]),"+f"(d[28]),"+f"(d[29]),"+f"(d[30]),"+f"(d[31]),"+f"(d[32]),"+f"(d[33]),"+f"(d[34]),"+f"(d[35]),"+f"(d[36]),"+f"(d[37]),"+f"(d[38]),"+f"(d[39]),"+f"(d[40]),"+f"(d[41]),"+f"(d[42]),"+f"(d[43]),"+f"(d[44]),"+f"(d[45]),"+f"(d[46]),"+f"(d[47])
 :"r"(a0),"r"(a1),"r"(a2),"r"(a3),"r"(blo),"n"(OFF),"n"(HI),"n"(SC)); } };
template<> struct WgRs<112> { template<int OFF,int HI,int SC> static __device__ __forceinline__ void run(float* d,uint32_t a0,uint32_t a1,uint32_t a2,uint32_t a3,uint32_t blo){
 asm volatile("{.reg .b32 l; .reg .b64 db; add.u32 l,%60,%61; mov.b64 db,{l,%62}; wgmma.mma_async.sync.aligned.m64n112k16.f32.bf16.bf16 {%0,%1,%2,%3,%4,%5,%6,%7,%8,%9,%10,%11,%12,%13,%14,%15,%16,%17,%18,%19,%20,%21,%22,%23,%24,%25,%26,%27,%28,%29,%30,%31,%32,%33,%34,%35,%36,%37,%38,%39,%40,%41,%42,%43,%44,%45,%46,%47,%48,%49,%50,%51,%52,%53,%54,%55},{%56,%57,%58,%59},db,%63,1,1,0;}"
 :"+f"(d[0]),"+f"(d[1]),"+f"(d[2]),"+f"(d[3]),"+f"(d[4]),"+f"(d[5]),"+f"(d[6]),"+f"(d[7]),"+f"(d[8]),"+f"(d[9]),"+f"(d[10]),"+f"(d[11]),"+f"(d[12]),"+f"(d[13]),"+f"(d[14]),"+f"(d[15]),"+f"(d[16]),"+f"(d[17]),"+f"(d[18]),"+f"(d[19]),"+f"(d[20]),"+f"(d[21]),"+f"(d[22]),"+f"(d[23]),"+f"(d[24]),"+f"(d[25]),"+f"(d[26]),"+f"(d[27]),"+f"(d[28]),"+f"(d[29]),"+f"(d[30]),"+f"(d[31]),"+f"(d[32]),"+f"(d[33]),"+f"(d[34]),"+f"(d[35]),"+f"(d[36]),"+f"(d[37]),"+f"(d[38]),"+f"(d[39]),"+f"(d[40]),"+f"(d[41]),"+f"(d[42]),"+f"(d[43]),"+f"(d[44]),"+f"(d[45]),"+f"(d[46]),"+f"(d[47]),"+f"(d[48]),"+f"(d[49]),"+f"(d[50]),"+f"(d[51]),"+f"(d[52]),"+f"(d[53]),"+f"(d[54]),"+f"(d[55])
 :"r"(a0),"r"(a1),"r"(a2),"r"(a3),"r"(blo),"n"(OFF),"n"(HI),"n"(SC)); } };
template<> struct WgRs<128> { template<int OFF,int HI,int SC> static __device__ __forceinline__ void run(float* d,uint32_t a0,uint32_t a1,uint32_t a2,uint32_t a3,uint32_t blo){
 asm volatile("{.reg .b32 l; .reg .b64 db; add.u32 l,%68,%69; mov.b64 db,{l,%70}; wgmma.mma_async.sync.aligned.m64n128k16.f32.bf16.bf16 {%0,%1,%2,%3,%4,%5,%6,%7,%8,%9,%10,%11,%12,%13,%14,%15,%16,%17,%18,%19,%20,%21,%22,%23,%24,%25,%26,%27,%28,%29,%30,%31,%32,%33,%34,%35,%36,%37,%38,%39,%40,%41,%42,%43,%44,%45,%46,%47,%48,%49,%50,%51,%52,%53,%54,%55,%56,%57,%58,%59,%60,%61,%62,%63},{%64,%65,%66,%67},db,%71,1,1,0;}"
 :"+f"(d[0]),"+f"(d[1]),"+f"(d[2]),"+f"(d[3]),"+f"(d[4]),"+f"(d[5]),"+f"(d[6]),"+f"(d[7]),"+f"(d[8]),"+f"(d[9]),"+f"(d[10]),"+f"(d[11]),"+f"(d[12]),"+f"(d[13]),"+f"(d[14]),"+f"(d[15]),"+f"(d[16]),"+f"(d[17]),"+f"(d[18]),"+f"(d[19]),"+f"(d[20]),"+f"(d[21]),"+f"(d[22]),"+f"(d[23]),"+f"(d[24]),"+f"(d[25]),"+f"(d[26]),"+f"(d[27]),"+f"(d[28]),"+f"(d[29]),"+f"(d[30]),"+f"(d[31]),"+f"(d[32]),"+f"(d[33]),"+f"(d[34]),"+f"(d[35]),"+f"(d[36]),"+f"(d[37]),"+f"(d[38]),"+f"(d[39]),"+f"(d[40]),"+f"(d[41]),"+f"(d[42]),"+f"(d[43]),"+f"(d[44]),"+f"(d[45]),"+f"(d[46]),"+f"(d[47]),"+f"(d[48]),"+f"(d[49]),"+f"(d[50]),"+f"(d[51]),"+f"(d[52]),"+f"(d[53]),"+f"(d[54]),"+f"(d[55]),"+f"(d[56]),"+f"(d[57]),"+f"(d[58]),"+f"(d[59]),"+f"(d[60]),"+f"(d[61]),"+f"(d[62]),"+f"(d[63])
 :"r"(a0),"r"(a1),"r"(a2),"r"(a3),"r"(blo),"n"(OFF),"n"(HI),"n"(SC)); } };
template<> struct WgSs<80> { template<int AOFF,int AHI,int BOFF,int BHI,int SC> static __device__ __forceinline__ void run(float* d,uint32_t alo,uint32_t blo){
 asm volatile("{.reg .b32 l,m; .reg .b64 da,db; add.u32 l,%40,%42; mov.b64 da,{l,%43}; add.u32 m,%41,%44; mov.b64 db,{m,%45}; wgmma.mma_async.sync.aligned.m64n80k16.f32.bf16.bf16 {%0,%1,%2,%3,%4,%5,%6,%7,%8,%9,%10,%11,%12,%13,%14,%15,%16,%17,%18,%19,%20,%21,%22,%23,%24,%25,%26,%27,%28,%29,%30,%31,%32,%33,%34,%35,%36,%37,%38,%39},da,db,%46,1,1,0,1;}"
 :"+f"(d[0]),"+f"(d[1]),"+f"(d[2]),"+f"(d[3]),"+f"(d[4]),"+f"(d[5]),"+f"(d[6]),"+f"(d[7]),"+f"(d[8]),"+f"(d[9]),"+f"(d[10]),"+f"(d[11]),"+f"(d[12]),"+f"(d[13]),"+f"(d[14]),"+f"(d[15]),"+f"(d[16]),"+f"(d[17]),"+f"(d[18]),"+f"(d[19]),"+f"(d[20]),"+f"(d[21]),"+f"(d[22]),"+f"(d[23]),"+f"(d[24]),"+f"(d[25]),"+f"(d[26]),"+f"(d[27]),"+f"(d[28]),"+f"(d[29]),"+f"(d[30]),"+f"(d[31]),"+f"(d[32]),"+f"(d[33]),"+f"(d[34]),"+f"(d[35]),"+f"(d[36]),"+f"(d[37]),"+f"(d[38]),"+f"(d[39])
 :"r"(alo),"r"(blo),"n"(AOFF),"n"(AHI),"n"(BOFF),"n"(BHI),"n"(SC)); } };
template<> struct WgSs<104> { template<int AOFF,int AHI,int BOFF,int BHI,int SC> static __device__ __forceinline__ void run(float* d,uint32_t alo,uint32_t blo){
 asm volatile("{.reg .b32 l,m; .reg .b64 da,db; add.u32 l,%52,%54; mov.b64 da,{l,%55}; add.u32 m,%53,%56; mov.b64 db,{m,%57}; wgmma.mma_async.sync.aligned.m64n104k16.f32.bf16.bf16 {%0,%1,%2,%3,%4,%5,%6,%7,%8,%9,%10,%11,%12,%13,%14,%15,%16,%17,%18,%19,%20,%21,%22,%23,%24,%25,%26,%27,%28,%29,%30,%31,%32,%33,%34,%35,%36,%37,%38,%39,%40,%41,%42,%43,%44,%45,%46,%47,%48,%49,%50,%51},da,db,%58,1,1,0,1;}"
 :"+f"(d[0]),"+f"(d[1]),"+f"(d[2]),"+f"(d[3]),"+f"(d[4]),"+f"(d[5]),"+f"(d[6]),"+f"(d[7]),"+f"(d[8]),"+f"(d[9]),"+f"(d[10]),"+f"(d[11]),"+f"(d[12]),"+f"(d[13]),"+f"(d[14]),"+f"(d[15]),"+f"(d[16]),"+f"(d[17]),"+f"(d[18]),"+f"(d[19]),"+f"(d[20]),"+f"(d[21]),"+f"(d[22]),"+f"(d[23]),"+f"(d[24]),"+f"(d[25]),"+f"(d[26]),"+f"(d[27]),"+f"(d[28]),"+f"(d[29]),"+f"(d[30]),"+f"(d[31]),"+f"(d[32]),"+f"(d[33]),"+f"(d[34]),"+f"(d[35]),"+f"(d[36]),"+f"(d[37]),"+f"(d[38]),"+f"(d[39]),"+f"(d[40]),"+f"(d[41]),"+f"(d[42]),"+f"(d[43]),"+f"(d[44]),"+f"(d[45]),"+f"(d[46]),"+f"(d[47]),"+f"(d[48]),"+f"(d[49]),"+f"(d[50]),"+f"(d[51])
 :"r"(alo),"r"(blo),"n"(AOFF),"n"(AHI),"n"(BOFF),"n"(BHI),"n"(SC)); } };
template<> struct WgSs<112> { template<int AOFF,int AHI,int BOFF,int BHI,int SC> static __device__ __forceinline__ void run(float* d,uint32_t alo,uint32_t blo){
 asm volatile("{.reg .b32 l,m; .reg .b64 da,db; add.u32 l,%56,%58; mov.b64 da,{l,%59}; add.u32 m,%57,%60; mov.b64 db,{m,%61}; wgmma.mma_async.sync.aligned.m64n112k16.f32.bf16.bf16 {%0,%1,%2,%3,%4,%5,%6,%7,%8,%9,%10,%11,%12,%13,%14,%15,%16,%17,%18,%19,%20,%21,%22,%23,%24,%25,%26,%27,%28,%29,%30,%31,%32,%33,%34,%35,%36,%37,%38,%39,%40,%41,%42,%43,%44,%45,%46,%47,%48,%49,%50,%51,%52,%53,%54,%55},da,db,%62,1,1,0,1;}"
 :"+f"(d[0]),"+f"(d[1]),"+f"(d[2]),"+f"(d[3]),"+f"(d[4]),"+f"(d[5]),"+f"(d[6]),"+f"(d[7]),"+f"(d[8]),"+f"(d[9]),"+f"(d[10]),"+f"(d[11]),"+f"(d[12]),"+f"(d[13]),"+f"(d[14]),"+f"(d[15]),"+f"(d[16]),"+f"(d[17]),"+f"(d[18]),"+f"(d[19]),"+f"(d[20]),"+f"(d[21]),"+f"(d[22]),"+f"(d[23]),"+f"(d[24]),"+f"(d[25]),"+f"(d[26]),"+f"(d[27]),"+f"(d[28]),"+f"(d[29]),"+f"(d[30]),"+f"(d[31]),"+f"(d[32]),"+f"(d[33]),"+f"(d[34]),"+f"(d[35]),"+f"(d[36]),"+f"(d[37]),"+f"(d[38]),"+f"(d[39]),"+f"(d[40]),"+f"(d[41]),"+f"(d[42]),"+f"(d[43]),"+f"(d[44]),"+f"(d[45]),"+f"(d[46]),"+f"(d[47]),"+f"(d[48]),"+f"(d[49]),"+f"(d[50]),"+f"(d[51]),"+f"(d[52]),"+f"(d[53]),"+f"(d[54]),"+f"(d[55])
 :"r"(alo),"r"(blo),"n"(AOFF),"n"(AHI),"n"(BOFF),"n"(BHI),"n"(SC)); } };

__device__ __forceinline__ void wg_fence() { asm volatile("wgmma.fence.sync.aligned;" ::: "memory"); }
__device__ __forceinline__ void wg_commit() { asm volatile("wgmma.commit_group.sync.aligned;" ::: "memory"); }
template <int N> __device__ __forceinline__ void wg_wait() { asm volatile("wgmma.wait_group.sync.aligned %0;" ::"n"(N) : "memory"); }
template <int N> __device__ __forceinline__ void reg_fence(float* d) {
#pragma unroll
    for (int i = 0; i < N; i++) asm volatile("" : "+f"(d[i])::"memory");
}
__device__ __forceinline__ uint32_t desc_lo(uint32_t addr, uint32_t lbo) { return ((addr & 0x3FFFF) >> 4) | ((lbo >> 4) << 16); }
#define desc_hi(sbo, sw) (((sbo) >> 4) | ((sw) << 30))
__device__ __forceinline__ uint32_t smem_u32(const void* p) { return (uint32_t)__cvta_generic_to_shared(p); }
__device__ __forceinline__ bool elect() {
    uint32_t p;
    asm volatile("{.reg .pred P; elect.sync _|P, 0xffffffff; selp.u32 %0,1,0,P;}" : "=r"(p));
    return p;
}
__device__ __forceinline__ void mbar_init(uint32_t bar, uint32_t cnt) { asm volatile("mbarrier.init.shared::cta.b64 [%0], %1;" ::"r"(bar), "r"(cnt) : "memory"); }
__device__ __forceinline__ void mbar_expect(uint32_t bar, uint32_t bytes) { asm volatile("mbarrier.arrive.expect_tx.shared::cta.b64 _, [%0], %1;" ::"r"(bar), "r"(bytes) : "memory"); }
__device__ __forceinline__ bool mbar_try(uint32_t bar, uint32_t par) {
    uint32_t ok;
    asm volatile("{.reg .pred p; mbarrier.try_wait.parity.shared::cta.b64 p, [%1], %2; selp.u32 %0,1,0,p;}" : "=r"(ok) : "r"(bar), "r"(par) : "memory");
    return ok;
}
constexpr int SPIN_LIMIT = 1 << 18;
__device__ __forceinline__ void mbar_wait(uint32_t bar, uint32_t par) {
    if (mbar_try(bar, par)) return;
    asm volatile("{.reg .pred p, q; .reg .b32 n; mov.u32 n, 0;\n"
                 "W%=: mbarrier.try_wait.parity.shared::cta.b64 p, [%0], %1; add.u32 n, n, 1; setp.lt.and.u32 q, n, %2, !p; @q bra W%=;}"
                 ::"r"(bar), "r"(par), "n"(SPIN_LIMIT) : "memory");
}
__device__ __forceinline__ void bulk_g2s(uint32_t dst, const void* src, uint32_t bytes, uint32_t bar) {
    asm volatile("cp.async.bulk.shared::cluster.global.mbarrier::complete_tx::bytes [%0], [%1], %2, [%3];" ::"r"(dst), "l"(src), "r"(bytes), "r"(bar) : "memory");
}
__device__ __forceinline__ void bulk_s2g(void* dst, uint32_t src, uint32_t bytes) {
    asm volatile("cp.async.bulk.global.shared::cta.bulk_group [%0], [%1], %2;" ::"l"(dst), "r"(src), "r"(bytes) : "memory");
}
__device__ __forceinline__ void bulk_prefetch(const void* src, uint32_t bytes) {
    asm volatile("cp.async.bulk.prefetch.L2.global [%0], %1;" ::"l"(src), "r"(bytes) : "memory");
}
__device__ __forceinline__ void tma2d(uint32_t dst, const CUtensorMap* m, int c0, int c1, uint32_t bar) {
    asm volatile("cp.async.bulk.tensor.2d.shared::cluster.global.mbarrier::complete_tx::bytes [%0], [%1, {%3, %4}], [%2];" ::"r"(dst), "l"(m), "r"(bar), "r"(c0), "r"(c1) : "memory");
}
__device__ __forceinline__ void tma2d_mc(uint32_t dst, const CUtensorMap* m, int c0, int c1, uint32_t bar) {
    asm volatile("cp.async.bulk.tensor.2d.shared::cluster.global.mbarrier::complete_tx::bytes.multicast::cluster [%0], [%1, {%3, %4}], [%2], %5;" ::"r"(dst), "l"(m), "r"(bar), "r"(c0), "r"(c1), "h"((uint16_t)3) : "memory");
}
__device__ __forceinline__ uint32_t mapa(uint32_t a, uint32_t rank) { uint32_t r; asm("mapa.shared::cluster.u32 %0, %1, %2;" : "=r"(r) : "r"(a), "r"(rank)); return r; }
__device__ __forceinline__ void mbar_arrive_cl(uint32_t bar) { asm volatile("mbarrier.arrive.shared::cluster.b64 _, [%0];" ::"r"(bar) : "memory"); }
__device__ __forceinline__ void prefetch_map(const CUtensorMap* m) { asm volatile("prefetch.tensormap [%0];" ::"l"(m) : "memory"); }
__device__ __forceinline__ void cpasync16(uint32_t dst, const void* src, uint32_t srcsz) {
    asm volatile("cp.async.cg.shared.global [%0], [%1], 16, %2;" ::"r"(dst), "l"(src), "r"(srcsz) : "memory");
}
__device__ __forceinline__ void bar_sync(int id, int n) { asm volatile("bar.sync %0, %1;" ::"r"(id), "r"(n) : "memory"); }
__device__ __forceinline__ void bar_arrive(int id, int n) { asm volatile("bar.arrive %0, %1;" ::"r"(id), "r"(n) : "memory"); }
__device__ __forceinline__ void fence_async_smem() { asm volatile("fence.proxy.async.shared::cta;" ::: "memory"); }
__device__ __forceinline__ void fence_async_global() { asm volatile("fence.proxy.async.global;" ::: "memory"); }
__device__ __forceinline__ unsigned* flag_ptr(int f) {
    return f < 16 ? &g_flags[(f & 7) * 32 + (f >> 3)] : &g_flags[f * 32];
}
__device__ __forceinline__ void flag_release(int f) { asm volatile("red.release.gpu.global.add.u32 [%0], 1;" ::"l"(flag_ptr(f)) : "memory"); }
__device__ __forceinline__ void flag_wait(int f, unsigned target) {
    const unsigned* p = flag_ptr(f);
    unsigned v; int n = 0;
    do {
        asm volatile("ld.relaxed.gpu.global.u32 %0, [%1];" : "=r"(v) : "l"(p) : "memory");
    } while ((int)(v - target) < 0 && ++n < SPIN_LIMIT);
    asm volatile("fence.acquire.gpu;" ::: "memory");
}
__device__ __forceinline__ unsigned ld_flag(const unsigned* p) { unsigned v; asm volatile("ld.relaxed.gpu.global.u32 %0, [%1];" : "=r"(v) : "l"(p) : "memory"); return v; }
__device__ __forceinline__ void spin(unsigned n) { unsigned t0, t1; asm volatile("mov.u32 %0, %%clock;" : "=r"(t0)); do { asm volatile("mov.u32 %0, %%clock;" : "=r"(t1)); } while (t1 - t0 < n); }
__device__ __forceinline__ int tensor_ping() {
    int r;
    asm volatile("{.reg .f32 a, b, c, d; mma.sync.aligned.m16n8k16.row.col.f32.bf16.bf16.f32 {a,b,c,d},{%1,%1,%1,%1},{%1,%1},{%2,%2,%2,%2}; mov.b32 %0, a;}" : "=r"(r) : "r"(0), "f"(0.f));
    return r;
}
__device__ __forceinline__ void mbar_wait_warm(uint32_t bar, uint32_t par) {
    for (int n = 0; n < SPIN_LIMIT; n++) {
        uint32_t ok;
        asm volatile("{.reg .pred p; mbarrier.test_wait.parity.shared::cta.b64 p, [%1], %2; selp.u32 %0,1,0,p;}" : "=r"(ok) : "r"(bar), "r"(par) : "memory");
        if (ok) break;
        n += tensor_ping();
        spin(PING);
    }
}
__device__ __forceinline__ void flag_wait2(int f0, int f1, unsigned target) {
    const unsigned *p = flag_ptr(f0), *q = flag_ptr(f1);
    unsigned v, w; int n = 0;
    do { v = ld_flag(p); w = ld_flag(q); } while ((int)((v - target) | (w - target)) < 0 && ++n < SPIN_LIMIT);
    asm volatile("fence.acquire.gpu;" ::: "memory");
}
__device__ __forceinline__ uint32_t lds32(uint32_t a) { uint32_t v; asm volatile("ld.shared.u32 %0, [%1];" : "=r"(v) : "r"(a)); return v; }
__device__ __forceinline__ float2 lds64f(uint32_t a) { float2 v; asm volatile("ld.shared.v2.f32 {%0,%1}, [%2];" : "=f"(v.x), "=f"(v.y) : "r"(a)); return v; }
__device__ __forceinline__ uint2 lds64(uint32_t a) { uint2 v; asm volatile("ld.shared.v2.u32 {%0,%1}, [%2];" : "=r"(v.x), "=r"(v.y) : "r"(a)); return v; }
__device__ __forceinline__ void sts64f(uint32_t a, float2 v) { asm volatile("st.shared.v2.f32 [%0], {%1,%2};" ::"r"(a), "f"(v.x), "f"(v.y) : "memory"); }
__device__ __forceinline__ void sts32(uint32_t a, uint32_t v) { asm volatile("st.shared.u32 [%0], %1;" ::"r"(a), "r"(v) : "memory"); }
__device__ __forceinline__ void sts64(uint32_t a, uint32_t x, uint32_t y) { asm volatile("st.shared.v2.u32 [%0], {%1,%2};" ::"r"(a), "r"(x), "r"(y) : "memory"); }
__device__ __forceinline__ void sts16(uint32_t a, uint16_t v) { asm volatile("st.shared.u16 [%0], %1;" ::"r"(a), "h"(v) : "memory"); }
__device__ __forceinline__ uint4 lds128(uint32_t a) { uint4 v; asm volatile("ld.shared.v4.u32 {%0,%1,%2,%3}, [%4];" : "=r"(v.x), "=r"(v.y), "=r"(v.z), "=r"(v.w) : "r"(a)); return v; }
__device__ __forceinline__ void sts128(uint32_t a, uint4 v) { asm volatile("st.shared.v4.u32 [%0], {%1,%2,%3,%4};" ::"r"(a), "r"(v.x), "r"(v.y), "r"(v.z), "r"(v.w) : "memory"); }
__device__ __forceinline__ void sts128f(uint32_t a, float x, float y, float z, float w) { asm volatile("st.shared.v4.f32 [%0], {%1,%2,%3,%4};" ::"r"(a), "f"(x), "f"(y), "f"(z), "f"(w) : "memory"); }
__device__ __forceinline__ uint32_t prmt(uint32_t a, uint32_t b, uint32_t s) { uint32_t r; asm("prmt.b32 %0,%1,%2,%3;" : "=r"(r) : "r"(a), "r"(b), "r"(s)); return r; }
__device__ __forceinline__ uint32_t pack2(float lo, float hi) { uint32_t r; asm("cvt.rn.bf16x2.f32 %0, %1, %2;" : "=r"(r) : "f"(hi), "f"(lo)); return r; }
__device__ __forceinline__ float blo(uint32_t v) { return __uint_as_float(v << 16); }
__device__ __forceinline__ float bhi(uint32_t v) { return __uint_as_float(v & 0xffff0000u); }
__device__ __forceinline__ uint32_t bmul2(uint32_t a, uint32_t b) { uint32_t r; asm("mul.rn.bf16x2 %0,%1,%2;" : "=r"(r) : "r"(a), "r"(b)); return r; }
__device__ __forceinline__ uint32_t badd2(uint32_t a, uint32_t b) { uint32_t r; asm("add.rn.bf16x2 %0,%1,%2;" : "=r"(r) : "r"(a), "r"(b)); return r; }
__device__ __forceinline__ float rbf(float x) { return __bfloat162float(__float2bfloat16_rn(x)); }
__device__ __forceinline__ uint32_t ldcg32(const void* p) { uint32_t v; asm volatile("ld.global.cg.u32 %0, [%1];" : "=r"(v) : "l"(p) : "memory"); return v; }
__device__ __forceinline__ uint4 ldcg128(const void* p) { uint4 v; asm volatile("ld.global.cg.v4.u32 {%0,%1,%2,%3}, [%4];" : "=r"(v.x), "=r"(v.y), "=r"(v.z), "=r"(v.w) : "l"(p) : "memory"); return v; }
__device__ __forceinline__ void stg32_if(void* p, uint32_t v, int on) { asm volatile("{.reg .pred q; setp.ne.b32 q, %2, 0; @q st.global.u32 [%0], %1;}" ::"l"(p), "r"(v), "r"(on) : "memory"); }
__device__ __forceinline__ uint2 ldcg64(const void* p) { uint2 v; asm volatile("ld.global.cg.v2.u32 {%0,%1}, [%2];" : "=r"(v.x), "=r"(v.y) : "l"(p) : "memory"); return v; }
__device__ __forceinline__ float gelu_h(float h) {
    float u = h * fmaf(h * h, 8.0f * 0.044715f * 0.7978845608028654f, 2.0f * 0.7978845608028654f);
    float th;
    asm("tanh.approx.f32 %0, %1;" : "=f"(th) : "f"(u));
    return fmaf(h, th, h);
}
__device__ __forceinline__ float gelu(float x) { return gelu_h(0.5f * x); }
__device__ __forceinline__ float half_rstd(float sum, float sq) {
    float mean = sum * (1.0f / D_), inv;
    asm("rsqrt.approx.ftz.f32 %0, %1;" : "=f"(inv) : "f"(fmaxf(fmaf(-mean, mean, fmaf(sq, 1.0f / D_, 1e-5f)), 1e-5f)));
    return 0.5f * inv;
}
__device__ __forceinline__ uint32_t bsub2(uint32_t a, uint32_t b) { uint32_t r; asm("sub.rn.bf16x2 %0,%1,%2;" : "=r"(r) : "r"(a), "r"(b)); return r; }
__device__ __forceinline__ uint32_t bfma2(uint32_t a, uint32_t b, uint32_t c) { uint32_t r; asm("fma.rn.bf16x2 %0,%1,%2,%3;" : "=r"(r) : "r"(a), "r"(b), "r"(c)); return r; }
__device__ __forceinline__ uint32_t gelu2_h(uint32_t h) {
    uint32_t u = bmul2(h, bfma2(bmul2(h, h), 0x3e923e92u, 0x3fcc3fccu)), th;
    asm("tanh.approx.bf16x2 %0, %1;" : "=r"(th) : "r"(u));
    return bfma2(h, th, h);
}
struct RowSum { float s = 0.f, q = 0.f, s_ = 0.f, q_ = 0.f;
    __device__ __forceinline__ void add(uint32_t v) { float a = blo(v), b = bhi(v); s += a; s_ += b; q = fmaf(a, a, q); q_ = fmaf(b, b, q_); } };
template <int I0>
__device__ __forceinline__ uint3 row_stats(const uint32_t* v, int lane, RowSum r0 = RowSum()) {
#pragma unroll
    for (int i = I0; i < 10; i++) r0.add(v[i]);
    float s = r0.s + r0.s_, q = r0.q + r0.q_;
    {
        float t = __shfl_xor_sync(0xffffffffu, (lane & 16) ? s : q, 16);
        t += (lane & 16) ? q : s;
#pragma unroll
        for (int m = 8; m; m >>= 1) t += __shfl_xor_sync(0xffffffffu, t, m);
        float o = __shfl_xor_sync(0xffffffffu, t, 16);
        s = (lane & 16) ? o : t; q = (lane & 16) ? t : o;
    }
    float mean = s * (1.0f / D_), inv;
    asm("rsqrt.approx.ftz.f32 %0, %1;" : "=f"(inv) : "f"(fmaxf(fmaf(-mean, mean, fmaf(q, 1.0f / D_, 1e-5f)), 1e-5f)));
    uint3 r;
    r.x = pack2(mean, mean);
    r.y = pack2(inv, inv);
    inv -= blo(r.y);
    r.z = pack2(inv, inv);
    return r;
}
__device__ __forceinline__ uint32_t ln_apply(uint32_t x, uint32_t m, uint32_t hi, uint32_t lo) {
    uint32_t xc = bsub2(x, m);
    return bmul2(xc, hi);
}

struct AFrag { uint32_t m, a, b, c, d; };
__device__ __forceinline__ AFrag ldA(uint32_t a) { AFrag f; f.m = lds32(a - 16); f.a = lds32(a); f.b = lds32(a + 16); f.c = lds32(a + 32); f.d = lds32(a + 48); return f; }
template <int N, int M> __device__ __forceinline__ void conv_pair(float* d, const AFrag& f, uint32_t descU) {
    WgRs<N>::template run<8 * M, desc_hi(128, 0), M ? 1 : 0>(d, f.a, f.b, f.m, f.a, descU);
    WgRs<N>::template run<8 * M + 1, desc_hi(128, 0), 1>(d, f.c, f.d, f.b, f.c, descU);
}
template <int Q> __device__ __forceinline__ void conv_put(float* d, uint32_t r0) {
    sts64(r0 + Q * 32, pack2(d[4 * Q + 1], d[4 * Q + 3]), pack2(d[4 * Q], d[4 * Q + 2]));
}
template <int M> __device__ __forceinline__ void conv_two(float* d, AFrag f0, AFrag f1, uint32_t kaddr, uint32_t descU, uint32_t r0, bool handoff) {
    constexpr int N = M < 14 ? 128 - 8 * M : 32;
    wg_fence();
    conv_pair<N, M>(d, f0, descU);
    wg_commit();
    if constexpr (M > 0) f1 = ldA(kaddr + 256 * (M + 1));
    wg_fence();
    conv_pair<N, M + 1>(d, f1, descU);
    wg_commit();
    if (STAG && M == STAG && handoff) bar_arrive(12, 256);
    if constexpr (M < 14) {
        if constexpr (M > 0) { conv_put<17 - M>(d, r0); conv_put<16 - M>(d, r0); }
        wg_wait<1>();
        f0 = ldA(kaddr + 256 * (M + 2));
        if constexpr (M < 12) wg_wait<0>();
        conv_two<M + 2>(d, f0, f1, kaddr, descU, r0, handoff);
    } else {
        wg_wait<0>();
        conv_put<3>(d, r0); conv_put<2>(d, r0); conv_put<1>(d, r0); conv_put<0>(d, r0);
    }
}
template <int N, bool ASWZ, int SC0>
__device__ __forceinline__ void gemm_issue(float* acc, uint32_t bars, int sa, int pa, int sw, int pw, uint32_t da0, uint32_t db0) {
    mbar_wait(bars + (BAR_FB + sw) * 8, pw);
    mbar_wait(bars + (BAR_FA + sa) * 8, pa);
    const uint32_t da = da0 + sa * (SLOT >> 4), db = db0 + sw * (SLOT >> 4);
    constexpr int AK = ASWZ ? 2 : 256, AH = ASWZ ? desc_hi(1024, 1) : desc_hi(128, 0), BH = desc_hi(1024, 1);
    wg_fence();
    WgSs<N>::template run<0, AH, 0, BH, SC0>(acc, da, db);
    WgSs<N>::template run<AK, AH, 128, BH, 1>(acc, da, db);
    WgSs<N>::template run<2 * AK, AH, 256, BH, 1>(acc, da, db);
    WgSs<N>::template run<3 * AK, AH, 384, BH, 1>(acc, da, db);
    wg_commit();
}
template <int N, bool ASWZ, int NKB, int RELB, bool ZERO>
__device__ __forceinline__ void gemm_loop(float* acc, uint32_t sb, int half, int ia0, int ib0, int rela, int wait_bar, int order_bar, int tsid) {
    int sa = ia0 % NA, pa = (ia0 / NA) & 1, sw = ib0 % NB, pw = (ib0 / NB) & 1;
    const uint32_t bars = sb + SM_BAR;
    const int t = threadIdx.x & 127;
    uint32_t ebar = mapa(bars + (t < 2 ? BAR_EB : BAR_EA) * 8, (t < 2 && lds32(sb + SM_GV + 516)) ? t : blockIdx.x & 1);
    const int nrel = t < 2 ? RELB : t == 2 ? rela : 0;
    const uint32_t da0 = ASWZ ? desc_lo(sb + SM_RA + half * 8192, 16) : desc_lo(sb + SM_RA + half * 1024, 2048), db0 = desc_lo(sb + SM_RB, 8192);
    asm volatile("" : "+r"(ebar));
    if (wait_bar) bar_sync(wait_bar, 512);
    gemm_issue<N, ASWZ, ZERO ? 0 : 1>(acc, bars, sa, pa, sw, pw, da0, db0);
    if ((threadIdx.x & 255) == 0) TS(tsid);
#pragma unroll 1
    for (int kb = 1; kb < NKB; kb++) {
        const int prev = t < 2 ? sw : sa;
        if (++sa == NA) { sa = 0; pa ^= 1; }
        if (++sw == NB) { sw = 0; pw ^= 1; }
        gemm_issue<N, ASWZ, 1>(acc, bars, sa, pa, sw, pw, da0, db0);
        if (order_bar && kb == NKB - 1) bar_arrive(order_bar, 512);
        wg_wait<1>();
        if (kb <= nrel) mbar_arrive_cl(ebar + prev * 8);
    }
    wg_wait<0>();
    if (nrel == NKB) mbar_arrive_cl(ebar + (t < 2 ? sw : sa) * 8);
    reg_fence<N / 2>(acc);
    if ((threadIdx.x & 255) == 0) TS(tsid + 1);
}

template <int PART>
__device__ __forceinline__ void gemm3(uint32_t sb, int rb, int j, int half, int row, int c, unsigned ones) {
    constexpr int N = 64 + (PART ? RB3 : RA3), NQ = N / 8;
    constexpr int HO = PART ? HO_B : HO_A;
    float acc[N / 2];
    float2 cr[NQ];
    if (PART) {
        gemm_loop<N, false, 1, 1, true>(acc, sb, half, 20, 20, 0, 0, 0, 50);
        bar_arrive(9, 512);
    }
    mbar_wait(sb + SM_BAR + BAR_CS * 8, 0);
    const uint32_t csa = sb + SM_CS + PART * (256 + 4 * RA3) + 8 * c;
#pragma unroll
    for (int q = 0; q < NQ; q++) if (q < CSP) cr[q] = lds64f(csa + 32 * q);
    uint4 rp;
    if (PART) {
        mbar_wait(sb + SM_BAR + BAR_G * 8, 0);
        const float2* sp = &g_st[(rb * 8 + 2 * c) * 128 + row];
        const uint2 s0 = ldcg64(sp), s1 = ldcg64(sp + 128), s2 = ldcg64(sp + 8), s3 = ldcg64(sp + 136);
        float a0 = __uint_as_float(s0.x) + __uint_as_float(s1.x), b0 = __uint_as_float(s0.y) + __uint_as_float(s1.y);
        float a1 = __uint_as_float(s2.x) + __uint_as_float(s3.x), b1 = __uint_as_float(s2.y) + __uint_as_float(s3.y);
#pragma unroll
        for (int m = 1; m <= 2; m <<= 1) {
            a0 += __shfl_xor_sync(0xffffffffu, a0, m); b0 += __shfl_xor_sync(0xffffffffu, b0, m);
            a1 += __shfl_xor_sync(0xffffffffu, a1, m); b1 += __shfl_xor_sync(0xffffffffu, b1, m);
        }
        const float inv0 = half_rstd(a0, b0), inv1 = half_rstd(a1, b1);
        rp = make_uint4(PGELU ? pack2(inv0, inv0) : __float_as_uint(inv0), __float_as_uint(a0 * (-1.0f / D_)),
                        PGELU ? pack2(inv1, inv1) : __float_as_uint(inv1), __float_as_uint(a1 * (-1.0f / D_)));
        if (c == 0) sts128(sb + SM_RP + ((threadIdx.x & 255) >> 2) * 16, rp);
        bar_arrive(13, 512);
    }
    gemm_loop<N, false, 10 - PART, 10 - PART, !PART>(acc, sb, half, 20 + (10 - NA) * PART, 21 + 10 * PART, PART ? 9 : 10 - NA, 9 + PART, HO < 0 ? 10 + PART : 0, 46 + 2 * PART);
    if ((threadIdx.x & 255) == 0) mbar_expect(sb + SM_BAR + BAR_ME * 8, 0);
    if (!PART) {
        bar_sync(13, 512);
        rp = lds128(sb + SM_RP + ((threadIdx.x & 255) >> 2) * 16);
    }
    const float nb0 = __uint_as_float(rp.y), nb1 = __uint_as_float(rp.w);
    const uint32_t own = sb + SM_RA + ((39 - NA) % NA) * SLOT + row * 16 + c * 4;
    if (PART && OWNG) mbar_wait(sb + SM_BAR + (BAR_FA + (39 - NA) % NA) * 8, ((39 - NA) / NA) & 1);
    uint32_t* dst = reinterpret_cast<uint32_t*>(g_g) + (rb * 216 + HB0 / 8 * PART + 8 * j) * 512 + row * 4 + c;
    auto act = [&](int q, int r) {
        const float nb = r ? nb1 : nb0;
        const uint32_t inv = r ? rp.z : rp.x;
        const float t0 = fmaf(nb, cr[q].x, acc[4 * q + 2 * r]), t1 = fmaf(nb, cr[q].y, acc[4 * q + 2 * r + 1]);
        return gelu2_h(bmul2(pack2(t0, t1), inv));
    };
    uint32_t* dst1 = dst + (56 - (16 - NQ) * j) * 512;
#pragma unroll
    for (int k = 0; k < NQ; k += CH3) {
        if (k == HO) bar_arrive(10 + PART, 512);
        CHUNK(k) {
#pragma unroll
            for (int q = k; q < k + CH3 && q < NQ; q++) {
                if (q + CSP < NQ) cr[q + CSP] = lds64f(csa + 32 * (q + CSP));
                const uint32_t u = act(q, 0), v = act(q, 1);
                (q < 8 ? dst : dst1)[q * 512] = u;
                (q < 8 ? dst : dst1)[q * 512 + 32] = v;
                if (PART && OWNG && q < 8) { sts32(own + q * 2048, u); sts32(own + q * 2048 + 128, v); }
            }
            if (PART && OWNG && k < 8 && k + CH3 >= 8) fence_async_smem();
        }
    }
    bar_arrive(1 + PART, 288);
    if (HO >= NQ) bar_arrive(10 + PART, 512);
}

template <int NS, int BASE, int BF, int BE> struct Ring {
    uint32_t sb, st, ph;
    __device__ __forceinline__ uint32_t acquire(uint32_t bytes) {
        mbar_wait(sb + SM_BAR + BE * 8 + st * 8, ph);
        uint32_t fb = sb + SM_BAR + BF * 8 + st * 8;
        mbar_expect(fb, bytes);
        return fb;
    }
    __device__ __forceinline__ uint32_t slot() { return sb + BASE + st * SLOT; }
    __device__ __forceinline__ void next() { if (++st == NS) { st = 0; ph ^= 1; } }
    __device__ __forceinline__ void run2d(const CUtensorMap* m, int c1) {
#pragma unroll 1
        for (int c0 = 64; c0 < D_; c0 += 64) {
            uint32_t fb = acquire(SLOT);
            tma2d(slot(), m, c0, c1, fb);
            next();
        }
    }
    static __device__ __forceinline__ int korder(int i, int own) { return i == 0 ? own : i > own ? i : i - 1; }
    __device__ __forceinline__ void runw(bool paired, int rk, const CUtensorMap* ma, const CUtensorMap* mb, int ca, int cb, int i0, int i1, int own, uint32_t bytes, int gate_at, uint32_t gate) {
        if (paired) {
            const CUtensorMap* m = rk ? mb : ma;
            const int c0 = rk ? cb : ca;
#pragma unroll 1
            for (int i = i0; i < i1; i++) {
                const int c1 = korder(i, own) * 64;
                if (i == gate_at) mbar_wait(gate, 0);
                uint32_t fb = acquire(bytes);
                tma2d_mc(slot() + 8192 * rk, m, c0, c1, fb);
                next();
            }
        } else {
#pragma unroll 1
            for (int i = i0; i < i1; i++) {
                const int c1 = korder(i, own) * 64;
                uint32_t fb = acquire(bytes);
                tma2d(slot(), ma, ca, c1, fb);
                tma2d(slot() + 8192, mb, cb, c1, fb);
                next();
            }
        }
    }
    __device__ __forceinline__ void run1d(const char* src, int i0, int i1, int own) {
#pragma unroll 1
        for (int i = i0; i < i1; i++) {
            const char* s = src + korder(i, own) * SLOT;
            uint32_t fb = acquire(SLOT);
            bulk_g2s(slot(), s, SLOT, fb);
            next();
        }
    }
};

__global__ void __cluster_dims__(2, 1, 1) __launch_bounds__(NTHREADS, 1) fused_kernel(const Params p, const __grid_constant__ Maps maps) {
    extern __shared__ __align__(1024) unsigned char smem_raw[];
    const uint32_t sb = (smem_u32(smem_raw) + 1023u) & ~1023u;
#pragma unroll
    for (int i = 0; i < SEED; i++) asm volatile("{.reg .b32 t; mov.u32 t, %laneid;}");
    const uint32_t bars = sb + SM_BAR;
    const int tid = threadIdx.x, lane = tid & 31;
    unsigned smid;
    asm volatile("mov.u32 %0, %%smid;" : "=r"(smid));
    const bool spare = (smid >> 2) == 30;
    const int cta = smid < 120 ? smid : smid - 4;
    const int pg = cta >> 4, pi = cta & 15;
    auto chan = [&](int cc) { return cc < 3 ? 3 * cta + cc : 381 + 2 * cta + cc; };
    const int hb = tid >= 320;
    unsigned ep0 = 0;
    if (!spare) {
        const unsigned t = tid - 320 * hb, r32 = t / 10u, cc = t - r32 * 10u, row = r32 + 64 * hb;
        const unsigned go = (unsigned)(pi * 128 * 1280) + row * 1280u + cc * 16u + (cc < 6 ? pg * 96 : 672 + pg * 64);
        const uint32_t so = sb + (row >> 4) * 32u + row * 160u + cc * 16u;
        const char* kb = (const char*)p.k + go;
        const char* vb = (const char*)p.v + go;
        if (hb) {
            if (tid < 328) {
                const char* a = lane < 5 ? (const char*)p.shift + lane * 128 + (lane < 3 ? pg * 384 : 2688 + pg * 256) : (const char*)(p.ssmD + chan(2 * lane - 10));
                asm volatile("prefetch.global.L2 [%0];" ::"l"(a));
            }
            if (tid >= 640 - NBARS) {
                const int i = 639 - tid;
                mbar_init(bars + i * 8, (i >= BAR_EB && i < BAR_K) ? 4 : ((i >= BAR_EA && i < BAR_EB) || i == BAR_XY) ? 2 : 1);
                asm volatile("fence.mbarrier_init.release.cluster;" ::: "memory");
            }
            bar_arrive(14, 640);
            if (tid >= 512) asm volatile("ld.volatile.global.u32 %0, [%1];" : "=r"(ep0) : "l"(p.epoch + smid) : "memory");
            if (B_DELAY) spin(B_DELAY);
        }
        cpasync16(so + SM_PK + 2592, kb, 16);
        cpasync16(so + SM_PV, vb, 16);
        cpasync16(so + SM_PK + 3 * 2592, kb + 32 * 1280, 16);
        cpasync16(so + SM_PV + 2 * 2592, vb + 32 * 1280, 16);
        if (tid < 30) cpasync16(so + SM_PK + 13 * 160, pi ? kb - 3 * 1280 : kb, pi ? 16 : 0);
        asm volatile("cp.async.commit_group;" ::: "memory");
    }
    const int warp = __shfl_sync(0xffffffffu, tid >> 5, 0);
    const int wg = warp >> 2, wq = warp & 3;

    if (spare) {
        const int sp = smid & 3;
        const unsigned ep1 = *(volatile unsigned*)&p.epoch[smid] + 1;
        if (tid == 32) { sts32(sb + SM_GV + 512, smid); asm volatile("fence.release.sync_restrict::shared::cta.cluster;" ::: "memory"); }
        asm volatile("barrier.cluster.arrive.relaxed.aligned;" ::: "memory");
        asm volatile("barrier.cluster.wait.aligned;" ::: "memory");
        if (tid == 0) {
            for (int i = 0; i < 4; i++) mbar_init(bars + i * 8, 1);
            asm volatile("fence.mbarrier_init.release.cluster;" ::: "memory");
        }
        if (warp == 0) { if (lane < 8) flag_wait(FL_P + lane, ep1 * 16); __syncwarp(); if (SPD) spin(SPD); }
        __syncthreads();
        const int cq = tid % 54, rg = tid / 54;
        float a[8];
#pragma unroll
        for (int i = 0; i < 8; i++) a[i] = 0.f;
#pragma unroll 1
        for (int it = -4; it < 10; it++) {
            const uint32_t st = sb + (it & 3) * 55296, fb = bars + (it & 3) * 8;
            if (it >= 0) {
                mbar_wait(fb, (it >> 2) & 1);
                if (tid < 432) {
#pragma unroll 2
                    for (int i = 0; i < 8; i++) {
                        uint4 w = lds128(st + (cq >= 27 ? 27648 - 432 : 0) + (rg * 8 + i) * 432 + cq * 16);
                        a[0] += blo(w.x); a[1] += bhi(w.x); a[2] += blo(w.y); a[3] += bhi(w.y);
                        a[4] += blo(w.z); a[5] += bhi(w.z); a[6] += blo(w.w); a[7] += bhi(w.w);
                    }
                }
                __syncthreads();
            }
            if (it < 6 && warp == 19 && elect()) {
                mbar_expect(fb, 55296);
                tma2d(st, &maps.w3s, sp * 432, (it + 4) * 64, fb);
                tma2d(st + 27648, &maps.w3s, sp * 432 + 216, (it + 4) * 64, fb);
            }
        }
        if (warp == 19 && elect()) {
#pragma unroll 1
            for (int i = 0; i < 27; i++) bulk_prefetch((const char*)p.w4 + sp * 552960 + i * 20480, 20480);
        }
        if (tid < 432) {
            sts128f(sb + rg * 1728 + cq * 32, a[0], a[1], a[2], a[3]);
            sts128f(sb + rg * 1728 + cq * 32 + 16, a[4], a[5], a[6], a[7]);
        }
        __syncthreads();
        if (tid < 432) {
            float s = 0.f;
#pragma unroll
            for (int i = 0; i < 8; i++) s += __uint_as_float(lds32(sb + i * 1728 + tid * 4));
            g_cs[sp * 432 + tid] = s;
        }
        __syncthreads();
        if (tid == 0) { flag_release(FL_CS); p.epoch[smid] = ep1; TS(0); }
        if (warp == 0) TSFLUSH();
        return;
    }

    int gpc, idx;
    if (smid < 64) { gpc = (smid & 15) >> 1; idx = (smid >> 4) * 2 + (smid & 1); }
    else if (smid < 120) { int t = smid - 64; gpc = 1 + (t % 14) / 2; idx = 8 + (t / 14) * 2 + (smid & 1); }
    else { gpc = 0; idx = 8 + (smid - 124); }
    const int rb = 2 * gpc + (idx & 1), j = idx >> 1;
    const int g = lane >> 2, c = lane & 3;
    const int cm = 160 * (j >> 1) + 64 * (j & 1) + ((j & 2) ? 32 : 0), cr = 160 * (j >> 1) + 16 * (j & 1) + ((j & 2) ? 0 : 128);

    {
        if (warp == 5) TSW(61);
        const int w10 = warp - 10 * hb, h = w10 >= 5;
        const int pr = (w10 - 5 * h) * 8 + (lane >> 2), blk = 4 * hb + (lane & 3);
        const int ch = 2 * pr + (pr < 24 ? 48 * pg : 336 + 32 * pg);
        const uint4 sw = __ldg(reinterpret_cast<const uint4*>(p.shift + ch * 4));
        uint32_t dv = 0;
        if (warp == 9 && lane < 5) dv = __bfloat16_as_ushort(p.ssmD[chan(lane)]);
        if (tid == 512) { sts32(sb + SM_GV + 512, smid); asm volatile("fence.release.sync_restrict::shared::cta.cluster;" ::: "memory"); }
        asm volatile("barrier.cluster.arrive.relaxed.aligned;" ::: "memory");
        if (warp == 11 && lane < 13) prefetch_map(&maps.hn + lane);
        if (wg < 4) {
            const int t = tid & 127, cc = (wg == 3 && t >= 64) ? 4 : wg;
            if (t < 64 || wg == 3) sts128(sb + sm_u(cc) + ((t >> 5) & 1) * U_PLANE + 2048 + lane * 16, make_uint4(0, 0, 0, 0));
            if ((t & 63) < 4 && (t < 64 || wg == 3)) sts128(sb + sm_k(cc) + ((t >> 1) & 1) * 4160 + (t & 1) * 16, make_uint4(0, 0, 0, 0));
        }
        if (warp == 9 && lane < 5) sts32(sb + SM_GV + 520 + lane * 4, dv << 16);
        asm volatile("cp.async.wait_group 0;" ::: "memory");
        if (!hb) bar_arrive(12, 640);
        bar_sync(hb ? 12 : 14, 640);
        if (warp == 9) {
            if (SSM_DELAY) spin(SSM_DELAY);
            if (elect()) {
#pragma unroll
                for (int i = 0; i < SSM_N; i++) {
                    mbar_expect(bars + (BAR_K + i) * 8, 4096);
                    bulk_g2s(sb + sm_k(i) + 32, p.ssmk + (size_t)(chan(i)) * S_, 4096, bars + (BAR_K + i) * 8);
                }
            }
        }
        const uint32_t w0 = prmt(sw.x, sw.z, 0x5410), w1 = prmt(sw.x, sw.z, 0x7632), w2 = prmt(sw.y, sw.w, 0x5410), w3 = prmt(sw.y, sw.w, 0x7632);
        const uint32_t ka = sb + SM_PK + 2592 + blk * 2592 + h * 1280 + pr * 4;
        const uint32_t va = sb + SM_PV + blk * 2592 + h * 1280 + pr * 4;
        uint32_t kk[11], kv[8];
#pragma unroll
        for (int i = 0; i < 11; i++) kk[i] = lds32(ka + (i - 3) * 160 - ((i < 3 && h == 0) ? 32 : 0));
#pragma unroll
        for (int i = 0; i < 8; i++) {
            uint32_t t = badd2(badd2(badd2(bmul2(kk[i], w3), bmul2(kk[i + 1], w2)), bmul2(kk[i + 2], w1)), bmul2(kk[i + 3], w0));
            kv[i] = bmul2(t, lds32(va + i * 160));
        }
        uint4 o0, o1;
        o0.x = prmt(kv[1], kv[0], 0x5410); o0.y = prmt(kv[3], kv[2], 0x5410); o0.z = prmt(kv[5], kv[4], 0x5410); o0.w = prmt(kv[7], kv[6], 0x5410);
        o1.x = prmt(kv[1], kv[0], 0x7632); o1.y = prmt(kv[3], kv[2], 0x7632); o1.z = prmt(kv[5], kv[4], 0x7632); o1.w = prmt(kv[7], kv[6], 0x7632);
        uint4* dst = reinterpret_cast<uint4*>(g_kvT) + ch * 256 + h * 128 + (127 - (8 * pi + blk));
        dst[0] = o0;
        dst[256] = o1;
    }

    const int rho = 8 * rb + j;

    if (wg == 4) {
        asm volatile("setmaxnreg.dec.sync.aligned.u32 32;");
        const unsigned ep1 = __shfl_sync(0xffffffffu, ep0, 0) + 1;
        if (wq == 0) {
            bar_sync(13, 640);
            TSW(39);
            if (lane == 0) flag_release(FL_P + pg);
            __syncwarp();
            TSW(2);
            if (lane < 5) mbar_expect(bars + (BAR_U + lane) * 8, 4096);
            flag_wait(FL_P + pg, ep1 * 16);
            fence_async_global();
            TSW(3);
            if (elect()) {
#pragma unroll
                for (int i = 0; i < 5; i++) {
                    const char* us = (const char*)g_kvT + (size_t)(chan(i)) * 4096;
                    bulk_g2s(sb + sm_u(i), us, 2048, bars + (BAR_U + i) * 8);
                    bulk_g2s(sb + sm_u(i) + U_PLANE, us + 2048, 2048, bars + (BAR_U + i) * 8);
                }
            }
            __syncwarp();
            if (elect()) {
#pragma unroll
                for (int i = SSM_N; i < 5; i++) {
                    mbar_expect(bars + (BAR_K + i) * 8, 4096);
                    bulk_g2s(sb + sm_k(i) + 32, p.ssmk + (size_t)(chan(i)) * S_, 4096, bars + (BAR_K + i) * 8);
                }
                if (WMD2) spin(WMD2);
                if (cta < 120) {
                    mbar_expect(bars + BAR_WM0 * 8, 3 * 8192);
                    mbar_expect(bars + BAR_WM * 8, 2 * 8192);
#pragma unroll 1
                    for (int i = 0; i < 5; i++) tma2d(sb + SM_WM + i * 8192, &maps.wm, cta * 32, i * 128, bars + (i < 3 ? BAR_WM0 : BAR_WM) * 8);
                }
                mbar_wait(bars + (cta < 120 ? BAR_WM0 : BAR_K + 4) * 8, 0);
                bulk_prefetch((const char*)p.q + cta * 20480, 20480);
                bulk_prefetch((const char*)p.w1 + cta * 6400, 6400);
                bulk_prefetch((const char*)p.w2 + cta * 6400, 6400);
            }
            __syncwarp();
        } else {
            bar_arrive(13, 640);
        }
        asm volatile("barrier.cluster.wait.aligned;" ::: "memory");
        uint32_t peer;
        asm volatile("ld.shared::cluster.u32 %0, [%1];" : "=r"(peer) : "r"(mapa(sb + SM_GV + 512, (blockIdx.x & 1) ^ 1)) : "memory");
        const bool paired = peer == (smid ^ 1) && !FORCE_UNPAIRED;
        if (tid == 639) sts32(sb + SM_GV + 516, paired);
        if (cta < 120) {
            float d[4];
            if (tid >= 544 && tid < 624) {
                const int t = tid - 544;
                mbar_wait(bars + BAR_U * 8, 0);
                uint4 cv = __ldg(reinterpret_cast<const uint4*>(p.c) + t);
                auto silu2 = [](uint32_t v) { float a = blo(v), b = bhi(v); return pack2(__fdividef(a, 1.0f + __expf(-a)), __fdividef(b, 1.0f + __expf(-b))); };
#pragma unroll 1
                for (int i = 0; i < 4; i++) { const uint32_t r = silu2(cv.x); cv.x = cv.y; cv.y = cv.z; cv.z = cv.w; cv.w = r; }
                sts128(sb + SM_Y + (t % 40) * 32 + (t / 40) * 16, cv);
                fence_async_smem();
            }
            bar_sync(5, 128);
            mbar_wait(bars + BAR_WM0 * 8, 0);
            mbar_wait(bars + BAR_WM * 8, 0);
            if (wq == 3) TSW(56);
            const uint32_t da = desc_lo(sb + SM_WM, 20480), db = desc_lo(sb + SM_Y, 32);
#pragma unroll 1
            for (int k0 = 0; k0 < 20; k0 += 4) {
                wg_fence();
#pragma unroll
                for (int k = k0; k < k0 + 4; k++) asm volatile("{.reg .pred p; .reg .b32 l,m; .reg .b64 da,db; setp.ne.b32 p,%10,0; add.u32 l,%4,%6; mov.b64 da,{l,%8}; add.u32 m,%5,%7; mov.b64 db,{m,%9};"
                             " wgmma.mma_async.sync.aligned.m64n8k16.f32.bf16.bf16 {%0,%1,%2,%3},da,db,p,1,1,1,0;}"
                             : "+f"(d[0]), "+f"(d[1]), "+f"(d[2]), "+f"(d[3])
                             : "r"(da), "r"(db), "r"(64 * k), "r"(4 * k), "n"(desc_hi(512, 2u)), "n"(desc_hi(128, 0)), "r"(k));
                wg_commit();
            }
            wg_wait<0>();
            reg_fence<4>(d);
            if (c == 0) {
                sts32(sb + SM_GV + (16 * wq + g) * 4, __float_as_uint(wq < 2 ? d[0] : d[1]));
                sts32(sb + SM_GV + (16 * wq + g + 8) * 4, __float_as_uint(wq < 2 ? d[2] : d[3]));
            }
            bar_sync(5, 128);
            if (wq == 2) {
                g_mod[cta * 32 + lane] = __float2bfloat16_rn(__uint_as_float(lds32(sb + SM_GV + lane * 4)) + __uint_as_float(lds32(sb + SM_GV + 128 + lane * 4)));
            }
        }
        if (wq == 2) {
            bar_sync(9, 320);
            if (lane == 0) { flag_release(FL_M); mbar_expect(bars + BAR_MR * 8, 0); }
            __syncwarp();
            TSW(4);
            flag_wait(FL_M, ep1 * 128);
            fence_async_global();
            if (elect()) {
                mbar_expect(bars + BAR_M * 8, 7680);
                bulk_g2s(sb + SM_MOD, g_mod, 7680, bars + BAR_M * 8);
                mbar_wait(bars + BAR_CD * 8, 0);
                mbar_expect(bars + BAR_Y * 8, 12288);
                bulk_g2s(sb + SM_Y, g_yv + rho * 5120, 12288, bars + BAR_Y * 8);
                if (j < 5) {
#pragma unroll 1
                    for (int i = 0; i < 8; i++) bulk_g2s(sb + SM_YT + i * 2560, g_yv + (8 * rb + i) * 5120 + cm * 8, 2048, bars + BAR_XY * 8);
                }
            }
            __syncwarp();
            TSW(60);
            bar_sync(8, 576);  if (lane == 0) { flag_release(FL_R + rb); TS(23); }  __syncwarp();
            bar_sync(15, 288); if (lane == 0) { flag_release(FL_B1 + rb); TS(27); } __syncwarp();
            bar_sync(6, 288);  if (lane == 0) { flag_release(FL_B2 + rb); TS(31); } __syncwarp();
#pragma unroll 1
            for (int i = 0; i < 3; i++) { bar_sync(i ? i : 8, 288); if (lane == 0) { TS(53 + (i + 2) % 3); flag_release(FL_G + 16 * i + rb); TS(57 + (i + 2) % 3); } __syncwarp(); }
            if (lane == 0) p.epoch[smid] = ep1;
            return;
        }
        if (wq == 1) {
            bar_sync(9, 320);
            mbar_wait(bars + BAR_MR * 8, 0);
            if (lane < 4 * NB) mbar_arrive_cl(mapa(bars + (BAR_EB + (lane >> 2)) * 8, paired ? lane & 1 : blockIdx.x & 1));
        }
        if (wq == 3) {
            bar_sync(7, 544);
            if (lane == 0) { flag_release(FL_C); mbar_expect(bars + BAR_CD * 8, 0); TS(20); }
            __syncwarp();
            if (lane == 0) mbar_expect(bars + BAR_Y2 * 8, 8192);
            flag_wait(FL_C, ep1 * 128);
            fence_async_global();
            TSW(21);
            if (elect()) {
                bulk_g2s(sb + SM_Y + 12288, g_yv + rho * 5120 + 3072, 8192, bars + BAR_Y2 * 8);
            }
            __syncwarp();
        }
        if (wq == 3) {
            mbar_wait(bars + BAR_Y2 * 8, 0);
            if (elect()) {
                mbar_expect(bars + BAR_XY * 8, 20480);
#pragma unroll 1
                for (int i = 0; i < 8; i++) {
                    if (j >= 5) bulk_g2s(sb + SM_YT + i * 2560, g_yv + (8 * rb + i) * 5120 + cm * 8, 2048, bars + BAR_XY * 8);
                    bulk_g2s(sb + SM_YT + i * 2560 + 2048, g_yv + (8 * rb + i) * 5120 + cr * 8, 512, bars + BAR_XY * 8);
                }
            }
            __syncwarp();
            bar_sync(8, 576);
            mbar_wait_warm(bars + BAR_FA * 8, 0);
            mbar_wait(bars + BAR_ME * 8, 0);
            mbar_wait_warm(bars + (BAR_FA + 11 % NA) * 8, (11 / NA) & 1);
            flag_wait(FL_CS, ep1 * 4);
            fence_async_global();
            if (elect()) {
                mbar_expect(bars + BAR_CS * 8, 864);
                bulk_g2s(sb + SM_CS, g_cs + 64 * j, 256, bars + BAR_CS * 8);
                bulk_g2s(sb + SM_CS + 256, g_cs + 512 + RA3 * j, 4 * RA3, bars + BAR_CS * 8);
                bulk_g2s(sb + SM_CS + 256 + 4 * RA3, g_cs + HB0 + 64 * j, 256, bars + BAR_CS * 8);
                bulk_g2s(sb + SM_CS + 512 + 4 * RA3, g_cs + HB0 + 512 + RB3 * j, 4 * RB3, bars + BAR_CS * 8);
            }
            __syncwarp();
            mbar_wait(bars + BAR_ME * 8, 1);
            mbar_wait_warm(bars + (BAR_FA + 21 % NA) * 8, (21 / NA) & 1);
#pragma unroll 1
            for (int i = 0; i < 3; i++) {
                if (i) {
                    mbar_wait(bars + BAR_ME * 8, (i + 1) & 1);
                    for (int n = i; n < 5; n++) { spin(PING); n += tensor_ping(); }
                }
                flag_wait(FL_G + 16 * i + rb, ep1 * 8);
                if (lane == 0) { mbar_expect(bars + (BAR_G + i) * 8, 0); TS(35 + (i + 2) % 3); }
                __syncwarp();
            }
            return;
        }
        if (elect()) {
            if (wq == 1) {
                Ring<NB, SM_RB, BAR_FB, BAR_EB> r{sb, 0, 0};
#pragma unroll 1
                for (int ph = 0; ph < 7; ph++) {
                    const CUtensorMap* ma = ph == 0 ? &maps.w1a : ph == 1 ? &maps.w2a : ph == 6 ? &maps.w4a : &maps.w3a;
                    const bool b3b = ph == 2 || ph == 4 || ph == 5;
                    r.runw(paired, idx & 1, ma, ma + (b3b ? 2 : 1), ph == 3 ? 64 * j : b3b ? HB0 + 64 * j : cm,
                           ph == 3 ? 512 + RA3 * j : b3b ? HB0 + 512 + RB3 * j : cr, ph == 4 ? 10 - NA : ph == 5 ? 1 : 0,
                           ph == 6 ? 27 : ph == 5 ? 10 - NA : ph == 2 ? 1 : 10, ph == 0 ? 0 : ph == 6 ? OWNG * (HB0 / 64 + j) : cm >> 6,
                           ph == 3 ? 8192 + 128 * RA3 : b3b ? 8192 + 128 * RB3 : 10240,
                           ph == 0 ? GATE0 : ph == 1 ? GATE : ph == 3 ? GATE - 1 : -1, bars + (ph == 0 ? BAR_Y2 : BAR_ST - (ph == 1)) * 8);
                }
            } else {
                Ring<NA, SM_RA, BAR_FA, BAR_EA> r{sb, 0, 0};
                if (cta >= 120) mbar_wait(bars + (BAR_K + 4) * 8, 0);
                mbar_expect(bars + BAR_XR * 8, 20480);
                bulk_g2s(sb + SM_XR, p.q + (size_t)rho * 16 * D_, 20480, bars + BAR_XR * 8);
                mbar_expect(bars + BAR_XY * 8, 20480);
                tma2d(sb + SM_XT, &maps.xa, cm, rb * 128, bars + BAR_XY * 8);
                tma2d(sb + SM_XT2, &maps.xb, cr, rb * 128, bars + BAR_XY * 8);
                const int grp = j >> 1;
                const int delta = (grp & 1 ? 1 : -1) * (1 + (grp >> 1));
                const int nb = min(max(rb + (delta > 0 ? 1 : -1), 0), 15);
                uint32_t fb = r.acquire(SLOT), dst = r.slot();
                flag_wait2(FL_R + nb, FL_R + rb, ep1 * 8);
                fence_async_global();
                tma2d(dst, &maps.hn, 0, rb * 128 + delta, fb);
                TS(24);
                r.next();
                r.run2d(&maps.hn, rb * 128 + delta);
#pragma unroll 1
                for (int i = 0; i < 2; i++) {
                    const char* src = (const char*)(i ? g_x1 : g_h1) + (size_t)rb * 163840;
                    r.acquire(0); r.next();
                    fb = r.acquire(SLOT); dst = r.slot();
                    const char* src1 = src + (cm == 0 ? SLOT : 0);
                    flag_wait(FL_B1 + 16 * i + rb, ep1 * 8);
                    fence_async_global();
                    bulk_g2s(dst, src1, SLOT, fb);
                    TS(28 + 4 * i);
                    mbar_expect(bars + (BAR_ST - 1 + i) * 8, 0);
                    r.next();
                    r.run1d(src, 2, 10, cm >> 6);
                }
                r.run1d((const char*)g_x1 + (size_t)rb * 163840, 1, 10 - NA, cm >> 6);
                if (OWNG) { r.acquire(0); r.next(); }
#pragma unroll 1
                for (int i = 0; i < 2; i++) {
                    mbar_wait(bars + (BAR_G + 1 + i) * 8, 0); fence_async_global();
                    r.run1d((const char*)g_g + (size_t)rb * 442368, OWNG + HB0 / 64 * i, i ? 27 : OWNG + HB0 / 64, OWNG * (HB0 / 64 + j));
                }
            }
        }
        return;
    }
    bar_arrive(13, 640);
    asm volatile("setmaxnreg.inc.sync.aligned.u32 112;");
    const int rrow = 16 * rho + (warp >> 1) + 8 * (warp & 1);

    fence_async_smem();
    bar_sync(1 + wg, 128);
#pragma unroll 1
    for (int cc = wg; cc < wg + 1 + (wg == 3); cc++) {
        mbar_wait(bars + (BAR_K + cc) * 8, 0);
        if (cc == 2 && wq == 0) TSW(40);
        uint32_t a = sb + sm_k(cc) + 32 + (tid & 127) * 32;
        uint32_t pw = lds32(a - 4);
        uint4 x = lds128(a), y = lds128(a + 16), o;
        if ((tid & 127) == 0) {
            uint16_t k0 = __bfloat16_as_ushort(__float2bfloat16_rn(blo(x.x) + __uint_as_float(lds32(sb + SM_GV + 520 + cc * 4))));
            x.x = (x.x & 0xffff0000u) | k0;
            sts16(a, k0);
        }
        o.x = prmt(pw, x.x, 0x5432); o.y = prmt(x.x, x.y, 0x5432); o.z = prmt(x.y, x.z, 0x5432); o.w = prmt(x.z, x.w, 0x5432);
        sts128(a + 4160, o);
        o.x = prmt(x.w, y.x, 0x5432); o.y = prmt(y.x, y.y, 0x5432); o.z = prmt(y.y, y.z, 0x5432); o.w = prmt(y.z, y.w, 0x5432);
        sts128(a + 4176, o);
    }
    bar_sync(1 + wg, 128);
    if (wg == 3) bar_arrive(11, 256);
#pragma unroll 1
    for (int cc = wg; cc < 5; cc += 3) {
        if (cc == 3 && wg == 0) break;
        if (cc == 4) bar_sync(11, 256);
        const uint32_t kaddr = sb + sm_k(cc) + ((g & 1) ? 32 : 4192) + 4 * ((g >> 1) - c) + 64 * wq;
        const AFrag f0 = ldA(kaddr), f1 = ldA(kaddr + 256);
        if (STAG && cc == 3) bar_sync(12, 256);
        mbar_wait(bars + (BAR_U + cc) * 8, 0);
        if (wq == 0) TSW(5 + cc);
        float d[64];
        conv_two<0>(d, f0, f1, kaddr, desc_lo(sb + sm_u(cc), U_PLANE), sb + sm_red(cc) + wq * 4352 + g * 544 + c * 8, cc == 1);
        if (wq == 0) TSW(10 + cc);
        if (cc == 1) bar_arrive(6, 256);
    }
#pragma unroll 1
    for (int cc = wg == 1 ? 4 : wg;; cc++) {
        if (cc == 1) bar_sync(6, 256); else bar_sync(1 + wg, 128);
        const int ch = chan(cc);
        uint32_t* dst = g_yv + ch * 8 + ((g + (ch >> 2)) & 7) + (126 - 32 * wq - 2 * c) * 5120;
        uint2 v[16];
#pragma unroll
        for (int i = 0; i < 16; i++) v[i] = lds64(sb + sm_red(cc) + g * 544 + wq * 128 + c * 8 + (i >> 2) * 32 + (i & 3) * 4360);
#pragma unroll
        for (int w = 1; w < 4; w++)
            if (wq == 3 && c > 3 - w) v[12 + w] = make_uint2(0, 0);
#pragma unroll
        for (int q = 0; q < 4; q++) {
            const uint2* u = v + 4 * q;
            dst[-8 * q * 5120] = badd2(u[0].x, badd2(u[1].x, badd2(u[2].x, u[3].x)));
            dst[(-8 * q + 1) * 5120] = badd2(u[0].y, badd2(u[1].y, badd2(u[2].y, u[3].y)));
        }
        if (wq == 0) TSW(15 + cc);
        if (cc != 0) break;
    }
    fence_async_smem();
    if (!(wg & 1)) bar_arrive(9, 320);
    bar_arrive(7, 544);

    const uint32_t one2 = 0x3f803f80u;
    const unsigned ones = p.ones;
    {
        uint32_t x[10], a[10], cb[10], sbv[10];
        bar_sync(10, 512);
        mbar_wait(bars + BAR_XR * 8, 0);
#pragma unroll
        for (int i = 0; i < 10; i++) x[i] = lds32(sb + SM_XR + (rrow & 15) * 1280 + lane * 4 + i * 128);
        const uint3 s1 = row_stats<0>(x, lane);
        const int up = lane >> 4, gg = warp >> 1, e = warp & 1;
        const uint32_t ya = sb + SM_Y + lane * 64 + ((gg + (lane >> 1)) & 7) * 4;
        const uint32_t sel = (up ? 0x1054u : 0x5410u) + (e ? 0x2222u : 0u);
        const uint32_t ma = sb + SM_MOD + lane * 4;
        mbar_wait(bars + BAR_M * 8, 0);
        uint32_t pin = 0;
#pragma unroll
        for (int i = 0; i < 10; i++) {
            uint32_t h = bfma2(ln_apply(x[i], s1.x, s1.y, s1.z), badd2(lds32(ma + 1280 + i * 128), one2), lds32(ma + i * 128));
            a[i] = bmul2(h, lds32(ma + 2560 + i * 128));
            sbv[i] = lds32(ma + 3840 + i * 128);
            cb[i] = badd2(lds32(ma + 5120 + i * 128), one2);
            pin ^= a[i] ^ cb[i];
        }
        if (pin & ~ones) sts32(sb + SM_GV, pin);
        if (warp == 4) TSW(52);
        mbar_wait(bars + BAR_Y * 8, 0);
        RowSum part;
#pragma unroll
        for (int i = 0; i < 10; i++) {
            if (i == 6) {
                if ((__float_as_uint(part.s + part.s_ + part.q + part.q_) & ~ones)) sts32(sb + SM_GV, pin);
                mbar_wait(bars + BAR_Y2 * 8, 0);
                if (warp == 0) TSW(22);
            }
            uint32_t y0 = lds32(ya + i * 2048 + up * 32), y1 = lds32(ya + i * 2048 + (up ^ 1) * 32);
            x[i] = bfma2(a[i], prmt(y0, y1, sel), x[i]);
            if (i < 6) part.add(x[i]);
        }
        const uint3 s2 = row_stats<6>(x, lane, part);
#pragma unroll
        for (int i = 0; i < 10; i++) x[i] = bfma2(ln_apply(x[i], s2.x, s2.y, s2.z), cb[i], sbv[i]);
        const uint3 s3 = row_stats<0>(x, lane);
        uint32_t* o = reinterpret_cast<uint32_t*>(g_hn + (size_t)rrow * D_) + lane;
#pragma unroll
        for (int i = 0; i < 10; i++) o[32 * i] = ln_apply(x[i], s3.x, s3.y, s3.z);
        if (lane < 2) g_rs[rrow * 2 + lane] = lane ? make_uint4(s2.x, s2.y, s2.z, 0) : make_uint4(s1.x, s1.y, s1.z, 0);
        if (warp == 0) TSW(34);
        bar_arrive(8, 576);
    }

    const int half = wg & 1;
    const int row = 64 * half + 16 * wq + g;
    const int tw0 = (rb * 80 + (cm >> 3)) * 512 + row * 4 + c, tw1 = (rb * 80 + (cr >> 3) - 8) * 512 + row * 4 + c;
    const uint32_t park = sb + SM_Y + (tid & 255) * 16;
    const uint32_t ms0 = sb + SM_MOD + (cm + 2 * c) * 2, ms1 = sb + SM_MOD + (cr - 64 + 2 * c) * 2;
    if (wg >= 2) {
        {
            float acc[40];
            gemm_loop<80, true, 10, 10, true>(acc, sb, half, 0, 0, 10, 0, 0, 25);
            if (tid == 256) mbar_expect(bars + BAR_ME * 8, 0);
#pragma unroll
            for (int k = 0; k < 10; k += CH) CHUNK(k) {
#pragma unroll
                for (int q = k; q < k + CH && q < 10; q++) {
                    uint32_t* dst = reinterpret_cast<uint32_t*>(g_h1) + (q < 8 ? tw0 : tw1);
                    const uint32_t u = gelu2_h(bmul2(pack2(acc[4 * q], acc[4 * q + 1]), 0x3f003f00u));
                    const uint32_t v = gelu2_h(bmul2(pack2(acc[4 * q + 2], acc[4 * q + 3]), 0x3f003f00u));
                    dst[q * 512] = u;
                    dst[q * 512 + 32] = v;
                    acc[4 * q] = __uint_as_float(u); acc[4 * q + 1] = __uint_as_float(v);
                }
            }
            bar_arrive(15, 288);
            mbar_wait(bars + (BAR_FA + 10 % NA) * 8, (10 / NA) & 1);
#pragma unroll
            for (int q = 0; q < 8; q++) {
                sts32(sb + SM_RA + (10 % NA) * SLOT + q * 2048 + row * 16 + c * 4, __float_as_uint(acc[4 * q]));
                sts32(sb + SM_RA + (10 % NA) * SLOT + q * 2048 + row * 16 + c * 4 + 128, __float_as_uint(acc[4 * q + 1]));
            }
            fence_async_smem();
            bar_arrive(14, 512);
        }
        gemm3<0>(sb, rb, j, half, row, c, ones);
        {
            float acc[40];
            uint32_t gbv[10], base[20];
#pragma unroll
            for (int q = 0; q < 10; q++) gbv[q] = lds32((q < 8 ? ms0 : ms1) + 6400 + q * 16);
#pragma unroll
            for (int q = 0; q < 5; q++) { const uint4 t = lds128(park + q * 4096); base[4 * q] = t.x; base[4 * q + 1] = t.y; base[4 * q + 2] = t.z; base[4 * q + 3] = t.w; }
            gemm_loop<80, false, 27, 27 - NB, true>(acc, sb, half, 39 - NA, 40, 27 - NA, 11, 0, 42);
            auto fin = [&](int q, int r) {
                return bfma2(gbv[q], pack2(acc[4 * q + 2 * r], acc[4 * q + 2 * r + 1]), base[2 * q + r]);
            };
            auto tr4 = [&](uint32_t t0, uint32_t t1, uint32_t t2, uint32_t t3) {
                const bool o1 = c & 1, o2 = c & 2;
                uint32_t a = __shfl_xor_sync(0xffffffffu, o1 ? t0 : t1, 1), b = __shfl_xor_sync(0xffffffffu, o1 ? t2 : t3, 1);
                uint32_t u0 = o1 ? a : t0, u1 = o1 ? t1 : a, u2 = o1 ? b : t2, u3 = o1 ? t3 : b;
                a = __shfl_xor_sync(0xffffffffu, o2 ? u0 : u2, 2); b = __shfl_xor_sync(0xffffffffu, o2 ? u1 : u3, 2);
                return o2 ? make_uint4(a, b, u2, u3) : make_uint4(u0, u1, a, b);
            };
            bf16* go = p.out + (size_t)(rb * 128 + row) * D_;
#pragma unroll
            for (int k = 0; k < 2; k++) CHUNK(k) {
#pragma unroll
                for (int r = 0; r < 2; r++)
                    *reinterpret_cast<uint4*>(go + r * 8 * D_ + cm + 32 * k + 8 * c) = tr4(fin(4 * k, r), fin(4 * k + 1, r), fin(4 * k + 2, r), fin(4 * k + 3, r));
            }
            CHUNK(2) *reinterpret_cast<uint4*>(go + (c >> 1) * 8 * D_ + cr + 8 * (c & 1)) = tr4(fin(8, 0), fin(9, 0), fin(8, 1), fin(9, 1));
            if (tid == 256) TS(44);
            if (warp == 8) TSFLUSH();
        }
    } else {
        {
            float acc[40];
            uint32_t x2[20];
            {
                uint32_t y[20];
                mbar_wait(bars + BAR_XY * 8, 0);
                const uint32_t xa = sb + SM_XT + row * 128 + c * 4, xb = sb + SM_XT2 + row * 32 + c * 4;
                const uint32_t ya = sb + SM_YT + (4 * half + wq) * 2560 + c * 64;
#pragma unroll
                for (int q = 0; q < 10; q++) {
                    const uint32_t a = q < 8 ? xa + ((q ^ g) << 4) : xb + (q - 8) * 16;
                    x2[2 * q] = lds32(a); x2[2 * q + 1] = lds32(a + (q < 8 ? 1024 : 256));
                    const int pos = (g + ((q < 8 ? cm : cr) >> 2) + 2 * q + (c >> 1)) & 7;
                    y[2 * q] = lds32(ya + q * 256 + pos * 4); y[2 * q + 1] = lds32(ya + q * 256 + 32 + pos * 4);
                }
                fence_async_smem();
                bar_sync(1 + wg, 128);
                if ((tid & 127) < NA) mbar_arrive_cl(mapa(bars + (BAR_EA + (tid & 127)) * 8, blockIdx.x & 1));
                mbar_wait(bars + (BAR_FA + 1) * 8, 0);
                const uint4* rp = g_rs + (rb * 128 + row) * 2;
                const uint4 ra = ldcg128(rp), rb2 = ldcg128(rp + 1), rc = ldcg128(rp + 16), rd = ldcg128(rp + 17);
                bar_sync(14, 512);
#pragma unroll
                for (int q = 0; q < 10; q++) {
                    const uint32_t ms = q < 8 ? ms0 : ms1;
                    const uint32_t sa = lds32(ms + 16 * q), ca = badd2(lds32(ms + 1280 + 16 * q), one2), ga = lds32(ms + 2560 + 16 * q);
                    const uint32_t sbv = lds32(ms + 3840 + 16 * q), cb = badd2(lds32(ms + 5120 + 16 * q), one2);
                    uint32_t u = x2[2 * q], v = x2[2 * q + 1];
                    u = bfma2(bmul2(bfma2(ln_apply(u, ra.x, ra.y, ra.z), ca, sa), ga), prmt(y[2 * q], y[2 * q + 1], 0x5410), u);
                    v = bfma2(bmul2(bfma2(ln_apply(v, rc.x, rc.y, rc.z), ca, sa), ga), prmt(y[2 * q], y[2 * q + 1], 0x7632), v);
                    x2[2 * q] = u; x2[2 * q + 1] = v;
                    u = bfma2(ln_apply(u, rb2.x, rb2.y, rb2.z), cb, sbv);
                    v = bfma2(ln_apply(v, rd.x, rd.y, rd.z), cb, sbv);
                    acc[4 * q] = blo(u); acc[4 * q + 1] = bhi(u); acc[4 * q + 2] = blo(v); acc[4 * q + 3] = bhi(v);
                }
            }
            reg_fence<40>(acc);
            if (tid == 0) TS(45);
            gemm_loop<80, false, 10, 10, false>(acc, sb, half, 10, 10, 10, 0, 0, 29);
            if (tid == 0) mbar_expect(bars + BAR_ME * 8, 0);
            uint32_t x1[20];
            float s0 = 0.f, q0 = 0.f, s1 = 0.f, q1 = 0.f;
#pragma unroll
            for (int q = 0; q < 10; q++) {
                uint32_t u = pack2(acc[4 * q], acc[4 * q + 1]);
                uint32_t v = pack2(acc[4 * q + 2], acc[4 * q + 3]);
                uint32_t* dst = reinterpret_cast<uint32_t*>(g_x1) + (q < 8 ? tw0 : tw1);
                dst[q * 512] = u;
                dst[q * 512 + 32] = v;
                x1[2 * q] = u; x1[2 * q + 1] = v;
            }
            bar_arrive(6, 288);
            CHUNK(0)
#pragma unroll
            for (int q = 0; q < 10; q++) {
                float a = blo(x1[2 * q]), b = bhi(x1[2 * q]), e = blo(x1[2 * q + 1]), f = bhi(x1[2 * q + 1]);
                s0 += a + b; q0 = fmaf(a, a, fmaf(b, b, q0));
                s1 += e + f; q1 = fmaf(e, e, fmaf(f, f, q1));
            }
#pragma unroll
            for (int m = 1; m <= 2; m <<= 1) {
                s0 += __shfl_xor_sync(0xffffffffu, s0, m); q0 += __shfl_xor_sync(0xffffffffu, q0, m);
                s1 += __shfl_xor_sync(0xffffffffu, s1, m); q1 += __shfl_xor_sync(0xffffffffu, q1, m);
            }
            if (c < 2) g_st[(rb * 8 + j) * 128 + row + 8 * c] = c ? make_float2(s1, q1) : make_float2(s0, q0);
            bar_arrive(8, 288);
            mbar_wait(bars + (BAR_FA + 20 % NA) * 8, (20 / NA) & 1);
#pragma unroll
            for (int q = 0; q < 8; q++) {
                sts32(sb + SM_RA + (20 % NA) * SLOT + q * 2048 + row * 16 + c * 4, x1[2 * q]);
                sts32(sb + SM_RA + (20 % NA) * SLOT + q * 2048 + row * 16 + c * 4 + 128, x1[2 * q + 1]);
            }
            fence_async_smem();
            bar_sync(3 + wg, 128);
#pragma unroll
            for (int q = 0; q < 5; q++) {
                const uint32_t ms = q < 4 ? ms0 : ms1;
                const uint32_t g0 = lds32(ms + 6400 + q * 32), g1 = lds32(ms + 6400 + q * 32 + 16);
                sts128(park + q * 4096, make_uint4(bfma2(g0, x1[4 * q], x2[4 * q]), bfma2(g0, x1[4 * q + 1], x2[4 * q + 1]),
                                                   bfma2(g1, x1[4 * q + 2], x2[4 * q + 2]), bfma2(g1, x1[4 * q + 3], x2[4 * q + 3])));
            }
        }
        gemm3<1>(sb, rb, j, half, row, c, ones);
    }
}

typedef CUresult (*EncFn)(CUtensorMap*, CUtensorMapDataType, cuuint32_t, void*, const cuuint64_t*, const cuuint64_t*,
                          const cuuint32_t*, const cuuint32_t*, CUtensorMapInterleave, CUtensorMapSwizzle,
                          CUtensorMapL2promotion, CUtensorMapFloatOOBfill);

void make_map(EncFn enc, CUtensorMap* m, const void* base, uint64_t inner, uint64_t outer, uint32_t bi, uint32_t bo,
              CUtensorMapSwizzle swz = CU_TENSOR_MAP_SWIZZLE_128B) {
    cuuint64_t dims[2] = {inner, outer};
    cuuint64_t st[1] = {inner * 2};
    cuuint32_t box[2] = {bi, bo};
    cuuint32_t es[2] = {1, 1};
    enc(m, CU_TENSOR_MAP_DATA_TYPE_BFLOAT16, 2, const_cast<void*>(base), dims, st, box, es, CU_TENSOR_MAP_INTERLEAVE_NONE,
        swz, CU_TENSOR_MAP_L2_PROMOTION_NONE, CU_TENSOR_MAP_FLOAT_OOB_FILL_NONE);
}

}

extern "C" void kernel_launch(void* const* d_in, const int* in_sizes, int n_in, void* d_out, int out_size) {
    (void)in_sizes; (void)n_in; (void)out_size;
    Params p;
    p.q = (const bf16*)d_in[0]; p.k = (const bf16*)d_in[1]; p.v = (const bf16*)d_in[2];
    p.shift = (const bf16*)d_in[3]; p.ssmk = (const bf16*)d_in[4]; p.ssmD = (const bf16*)d_in[5];
    p.w1 = (const bf16*)d_in[7]; p.w2 = (const bf16*)d_in[8]; p.w3 = (const bf16*)d_in[9]; p.w4 = (const bf16*)d_in[10];
    p.c = (const bf16*)d_in[11]; p.wmod = (const bf16*)d_in[12];
    p.out = (bf16*)d_out;
    p.ones = 0xffffffffu;
    cudaGetSymbolAddress((void**)&p.epoch, g_epoch);

    void* fn = nullptr;
    cudaDriverEntryPointQueryResult qr;
    cudaGetDriverEntryPoint("cuTensorMapEncodeTiled", &fn, cudaEnableDefault, &qr);
    EncFn enc = (EncFn)fn;
    void* hn = nullptr;
    cudaGetSymbolAddress(&hn, g_hn);
    Maps maps;
    make_map(enc, &maps.w3s, p.w3, F_, D_, 216, 64, CU_TENSOR_MAP_SWIZZLE_NONE);
    make_map(enc, &maps.wm, p.wmod, 6 * D_, D_, 32, 128, CU_TENSOR_MAP_SWIZZLE_64B);
    make_map(enc, &maps.xa, p.q, D_, S_, 64, 128);
    make_map(enc, &maps.xb, p.q, D_, S_, 16, 128, CU_TENSOR_MAP_SWIZZLE_NONE);
    make_map(enc, &maps.hn, hn, D_, S_, 64, 128);
    make_map(enc, &maps.w1a, p.w1, D_, D_, 64, 64);
    make_map(enc, &maps.w1b, p.w1, D_, D_, 16, 64);
    make_map(enc, &maps.w2a, p.w2, D_, D_, 64, 64);
    make_map(enc, &maps.w2b, p.w2, D_, D_, 16, 64);
    make_map(enc, &maps.w3a, p.w3, F_, D_, 64, 64);
    make_map(enc, &maps.w3b, p.w3, F_, D_, RA3, 64);
    make_map(enc, &maps.w3c, p.w3, F_, D_, RB3, 64);
    make_map(enc, &maps.w4a, p.w4, D_, F_, 64, 64);
    make_map(enc, &maps.w4b, p.w4, D_, F_, 16, 64);
    cudaFuncSetAttribute(fused_kernel, cudaFuncAttributeMaxDynamicSharedMemorySize, SMEM_BYTES);
    fused_kernel<<<132, NTHREADS, SMEM_BYTES>>>(p, maps);
}
```

```cpp
#include <cuda_runtime.h>
#include <cuda_bf16.h>
#include <cuda.h>
#include <stdint.h>
#include <string.h>

#define SEED 1
#define CH 2
#define STAG 12
#define CH3 4
#define GATE 5
#define SSM_DELAY 100
#define B_DELAY 220
#define PING 250
#define FORCE_UNPAIRED 0
#define GATE0 1
#define SPD 800
#define WMD2 600
#define SSM_N 3

namespace {

typedef __nv_bfloat16 bf16;
typedef __nv_bfloat162 bf162;

constexpr int S_ = 2048, D_ = 640, F_ = 1728;
constexpr int NTHREADS = 640;
constexpr int NA = 6, NB = 6;
constexpr int SLOT = 16384;
constexpr int RA3 = 48, RB3 = 40, HB0 = 896;
constexpr int SM_RA = 0, SM_RB = NA * SLOT;

static_assert(NA == 6, "smem map");
constexpr int RED_STRIDE = 17536;
constexpr int K_STRIDE = 8320;
constexpr int U_PLANE = 2560, U_STRIDE = 5120;
constexpr int SM_Y = 12 * SLOT;
__device__ __forceinline__ int sm_red(int cc) { return cc * RED_STRIDE + (cc < 3 ? SM_RB : -3 * RED_STRIDE); }
__device__ __forceinline__ int sm_k(int cc) { return cc * K_STRIDE + (cc < 3 ? SM_RB + 3 * RED_STRIDE : 2 * RED_STRIDE - 3 * K_STRIDE); }
__device__ __forceinline__ int sm_u(int cc) { return cc * U_STRIDE + (cc < 3 ? SM_RB + 3 * RED_STRIDE + 3 * K_STRIDE : SM_Y + 8192 - 3 * U_STRIDE); }
constexpr int SM_PK = SM_RB;
constexpr int SM_PV = SM_RB + 24576;
constexpr int SM_WM = 57344;
constexpr int SM_XT = SM_WM, SM_XT2 = SM_WM + 16384, SM_XR = SM_WM + 20480;
constexpr int SM_YT = 0;
constexpr int SM_MOD = SM_Y + 20480;
constexpr int SM_GV = SM_MOD + 7680;
constexpr int SM_CS = SM_GV + 1024;
constexpr int SM_RP = SM_CS + 1024;
constexpr int SM_BAR = SM_RP + 1024;
constexpr int SM_PROF = SM_BAR + 512;
constexpr int SM_TOTAL = SM_PROF + 512;
constexpr int SMEM_BYTES = SM_TOTAL + 1024;
static_assert(SMEM_BYTES <= 232448, "smem");

constexpr int BAR_FA = 0, BAR_FB = NA, BAR_EA = 12, BAR_EB = 12 + NA, BAR_K = 24, BAR_U = 29, BAR_Y = 34, BAR_CS = 35, BAR_WM = 36, BAR_M = 37, BAR_XY = 38, BAR_Y2 = 39, BAR_G = 40, BAR_ST = 44, BAR_XR = 45, BAR_ME = 46, BAR_CD = 47, BAR_WM0 = 48, BAR_MR = 49, NBARS = 50;

__device__ __align__(1024) bf16 g_kvT[D_ * S_];
__device__ __align__(1024) uint32_t g_yv[128 * 5120];
__device__ __align__(1024) bf16 g_mod[6 * D_];
__device__ __align__(1024) bf16 g_hn[S_ * D_];
__device__ __align__(1024) uint4 g_rs[S_ * 2];
__device__ __align__(1024) bf16 g_h1[S_ * D_];
__device__ __align__(1024) bf16 g_x1[S_ * D_];
__device__ __align__(1024) bf16 g_g[S_ * F_];
__device__ __align__(1024) float2 g_st[S_ * 8];
__device__ __align__(1024) float g_cs[F_];
__device__ __align__(1024) unsigned g_flags[128 * 32];
__device__ __align__(1024) unsigned g_epoch[160];
constexpr int FL_P = 0, FL_C = 8, FL_CS = 9, FL_M = 10, FL_R = 16, FL_B1 = 32, FL_B2 = 48, FL_G = 64;

#define TS(i) do {} while (0)
#define TSW(i) do {} while (0)
#define TSD(i, dep) do {} while (0)
#define TSD2(i, dep) do {} while (0)
#define TSFLUSH() do {} while (0)

struct Params {
    const bf16 *q, *k, *v, *shift, *ssmk, *ssmD, *w1, *w2, *w3, *w4, *c, *wmod;
    bf16* out;
    unsigned* epoch;
    unsigned ones;
};
#define CHUNK(k) if (ones & (1u << (k)))
struct Maps { CUtensorMap hn, w1a, w1b, w2a, w2b, w3a, w3b, w3c, w4a, w4b, wm, xa, xb, w3s; };

template<int N> struct WgRs;
template<int N> struct WgSs;
template<> struct WgRs<32> { template<int OFF,int HI,int SC> static __device__ __forceinline__ void run(float* d,uint32_t a0,uint32_t a1,uint32_t a2,uint32_t a3,uint32_t blo){
 asm volatile("{.reg .b32 l; .reg .b64 db; add.u32 l,%20,%21; mov.b64 db,{l,%22}; wgmma.mma_async.sync.aligned.m64n32k16.f32.bf16.bf16 {%0,%1,%2,%3,%4,%5,%6,%7,%8,%9,%10,%11,%12,%13,%14,%15},{%16,%17,%18,%19},db,%23,1,1,0;}"
 :"+f"(d[0]),"+f"(d[1]),"+f"(d[2]),"+f"(d[3]),"+f"(d[4]),"+f"(d[5]),"+f"(d[6]),"+f"(d[7]),"+f"(d[8]),"+f"(d[9]),"+f"(d[10]),"+f"(d[11]),"+f"(d[12]),"+f"(d[13]),"+f"(d[14]),"+f"(d[15])
 :"r"(a0),"r"(a1),"r"(a2),"r"(a3),"r"(blo),"n"(OFF),"n"(HI),"n"(SC)); } };
template<> struct WgRs<48> { template<int OFF,int HI,int SC> static __device__ __forceinline__ void run(float* d,uint32_t a0,uint32_t a1,uint32_t a2,uint32_t a3,uint32_t blo){
 asm volatile("{.reg .b32 l; .reg .b64 db; add.u32 l,%28,%29; mov.b64 db,{l,%30}; wgmma.mma_async.sync.aligned.m64n48k16.f32.bf16.bf16 {%0,%1,%2,%3,%4,%5,%6,%7,%8,%9,%10,%11,%12,%13,%14,%15,%16,%17,%18,%19,%20,%21,%22,%23},{%24,%25,%26,%27},db,%31,1,1,0;}"
 :"+f"(d[0]),"+f"(d[1]),"+f"(d[2]),"+f"(d[3]),"+f"(d[4]),"+f"(d[5]),"+f"(d[6]),"+f"(d[7]),"+f"(d[8]),"+f"(d[9]),"+f"(d[10]),"+f"(d[11]),"+f"(d[12]),"+f"(d[13]),"+f"(d[14]),"+f"(d[15]),"+f"(d[16]),"+f"(d[17]),"+f"(d[18]),"+f"(d[19]),"+f"(d[20]),"+f"(d[21]),"+f"(d[22]),"+f"(d[23])
 :"r"(a0),"r"(a1),"r"(a2),"r"(a3),"r"(blo),"n"(OFF),"n"(HI),"n"(SC)); } };
template<> struct WgRs<64> { template<int OFF,int HI,int SC> static __device__ __forceinline__ void run(float* d,uint32_t a0,uint32_t a1,uint32_t a2,uint32_t a3,uint32_t blo){
 asm volatile("{.reg .b32 l; .reg .b64 db; add.u32 l,%36,%37; mov.b64 db,{l,%38}; wgmma.mma_async.sync.aligned.m64n64k16.f32.bf16.bf16 {%0,%1,%2,%3,%4,%5,%6,%7,%8,%9,%10,%11,%12,%13,%14,%15,%16,%17,%18,%19,%20,%21,%22,%23,%24,%25,%26,%27,%28,%29,%30,%31},{%32,%33,%34,%35},db,%39,1,1,0;}"
 :"+f"(d[0]),"+f"(d[1]),"+f"(d[2]),"+f"(d[3]),"+f"(d[4]),"+f"(d[5]),"+f"(d[6]),"+f"(d[7]),"+f"(d[8]),"+f"(d[9]),"+f"(d[10]),"+f"(d[11]),"+f"(d[12]),"+f"(d[13]),"+f"(d[14]),"+f"(d[15]),"+f"(d[16]),"+f"(d[17]),"+f"(d[18]),"+f"(d[19]),"+f"(d[20]),"+f"(d[21]),"+f"(d[22]),"+f"(d[23]),"+f"(d[24]),"+f"(d[25]),"+f"(d[26]),"+f"(d[27]),"+f"(d[28]),"+f"(d[29]),"+f"(d[30]),"+f"(d[31])
 :"r"(a0),"r"(a1),"r"(a2),"r"(a3),"r"(blo),"n"(OFF),"n"(HI),"n"(SC)); } };
template<> struct WgRs<80> { template<int OFF,int HI,int SC> static __device__ __forceinline__ void run(float* d,uint32_t a0,uint32_t a1,uint32_t a2,uint32_t a3,uint32_t blo){
 asm volatile("{.reg .b32 l; .reg .b64 db; add.u32 l,%44,%45; mov.b64 db,{l,%46}; wgmma.mma_async.sync.aligned.m64n80k16.f32.bf16.bf16 {%0,%1,%2,%3,%4,%5,%6,%7,%8,%9,%10,%11,%12,%13,%14,%15,%16,%17,%18,%19,%20,%21,%22,%23,%24,%25,%26,%27,%28,%29,%30,%31,%32,%33,%34,%35,%36,%37,%38,%39},{%40,%41,%42,%43},db,%47,1,1,0;}"
 :"+f"(d[0]),"+f"(d[1]),"+f"(d[2]),"+f"(d[3]),"+f"(d[4]),"+f"(d[5]),"+f"(d[6]),"+f"(d[7]),"+f"(d[8]),"+f"(d[9]),"+f"(d[10]),"+f"(d[11]),"+f"(d[12]),"+f"(d[13]),"+f"(d[14]),"+f"(d[15]),"+f"(d[16]),"+f"(d[17]),"+f"(d[18]),"+f"(d[19]),"+f"(d[20]),"+f"(d[21]),"+f"(d[22]),"+f"(d[23]),"+f"(d[24]),"+f"(d[25]),"+f"(d[26]),"+f"(d[27]),"+f"(d[28]),"+f"(d[29]),"+f"(d[30]),"+f"(d[31]),"+f"(d[32]),"+f"(d[33]),"+f"(d[34]),"+f"(d[35]),"+f"(d[36]),"+f"(d[37]),"+f"(d[38]),"+f"(d[39])
 :"r"(a0),"r"(a1),"r"(a2),"r"(a3),"r"(blo),"n"(OFF),"n"(HI),"n"(SC)); } };
template<> struct WgRs<96> { template<int OFF,int HI,int SC> static __device__ __forceinline__ void run(float* d,uint32_t a0,uint32_t a1,uint32_t a2,uint32_t a3,uint32_t blo){
 asm volatile("{.reg .b32 l; .reg .b64 db; add.u32 l,%52,%53; mov.b64 db,{l,%54}; wgmma.mma_async.sync.aligned.m64n96k16.f32.bf16.bf16 {%0,%1,%2,%3,%4,%5,%6,%7,%8,%9,%10,%11,%12,%13,%14,%15,%16,%17,%18,%19,%20,%21,%22,%23,%24,%25,%26,%27,%28,%29,%30,%31,%32,%33,%34,%35,%36,%37,%38,%39,%40,%41,%42,%43,%44,%45,%46,%47},{%48,%49,%50,%51},db,%55,1,1,0;}"
 :"+f"(d[0]),"+f"(d[1]),"+f"(d[2]),"+f"(d[3]),"+f"(d[4]),"+f"(d[5]),"+f"(d[6]),"+f"(d[7]),"+f"(d[8]),"+f"(d[9]),"+f"(d[10]),"+f"(d[11]),"+f"(d[12]),"+f"(d[13]),"+f"(d[14]),"+f"(d[15]),"+f"(d[16]),"+f"(d[17]),"+f"(d[18]),"+f"(d[19]),"+f"(d[20]),"+f"(d[21]),"+f"(d[22]),"+f"(d[23]),"+f"(d[24]),"+f"(d[25]),"+f"(d[26]),"+f"(d[27]),"+f"(d[28]),"+f"(d[29]),"+f"(d[30]),"+f"(d[31]),"+f"(d[32]),"+f"(d[33]),"+f"(d[34]),"+f"(d[35]),"+f"(d[36]),"+f"(d[37]),"+f"(d[38]),"+f"(d[39]),"+f"(d[40]),"+f"(d[41]),"+f"(d[42]),"+f"(d[43]),"+f"(d[44]),"+f"(d[45]),"+f"(d[46]),"+f"(d[47])
 :"r"(a0),"r"(a1),"r"(a2),"r"(a3),"r"(blo),"n"(OFF),"n"(HI),"n"(SC)); } };
template<> struct WgRs<112> { template<int OFF,int HI,int SC> static __device__ __forceinline__ void run(float* d,uint32_t a0,uint32_t a1,uint32_t a2,uint32_t a3,uint32_t blo){
 asm volatile("{.reg .b32 l; .reg .b64 db; add.u32 l,%60,%61; mov.b64 db,{l,%62}; wgmma.mma_async.sync.aligned.m64n112k16.f32.bf16.bf16 {%0,%1,%2,%3,%4,%5,%6,%7,%8,%9,%10,%11,%12,%13,%14,%15,%16,%17,%18,%19,%20,%21,%22,%23,%24,%25,%26,%27,%28,%29,%30,%31,%32,%33,%34,%35,%36,%37,%38,%39,%40,%41,%42,%43,%44,%45,%46,%47,%48,%49,%50,%51,%52,%53,%54,%55},{%56,%57,%58,%59},db,%63,1,1,0;}"
 :"+f"(d[0]),"+f"(d[1]),"+f"(d[2]),"+f"(d[3]),"+f"(d[4]),"+f"(d[5]),"+f"(d[6]),"+f"(d[7]),"+f"(d[8]),"+f"(d[9]),"+f"(d[10]),"+f"(d[11]),"+f"(d[12]),"+f"(d[13]),"+f"(d[14]),"+f"(d[15]),"+f"(d[16]),"+f"(d[17]),"+f"(d[18]),"+f"(d[19]),"+f"(d[20]),"+f"(d[21]),"+f"(d[22]),"+f"(d[23]),"+f"(d[24]),"+f"(d[25]),"+f"(d[26]),"+f"(d[27]),"+f"(d[28]),"+f"(d[29]),"+f"(d[30]),"+f"(d[31]),"+f"(d[32]),"+f"(d[33]),"+f"(d[34]),"+f"(d[35]),"+f"(d[36]),"+f"(d[37]),"+f"(d[38]),"+f"(d[39]),"+f"(d[40]),"+f"(d[41]),"+f"(d[42]),"+f"(d[43]),"+f"(d[44]),"+f"(d[45]),"+f"(d[46]),"+f"(d[47]),"+f"(d[48]),"+f"(d[49]),"+f"(d[50]),"+f"(d[51]),"+f"(d[52]),"+f"(d[53]),"+f"(d[54]),"+f"(d[55])
 :"r"(a0),"r"(a1),"r"(a2),"r"(a3),"r"(blo),"n"(OFF),"n"(HI),"n"(SC)); } };
template<> struct WgRs<128> { template<int OFF,int HI,int SC> static __device__ __forceinline__ void run(float* d,uint32_t a0,uint32_t a1,uint32_t a2,uint32_t a3,uint32_t blo){
 asm volatile("{.reg .b32 l; .reg .b64 db; add.u32 l,%68,%69; mov.b64 db,{l,%70}; wgmma.mma_async.sync.aligned.m64n128k16.f32.bf16.bf16 {%0,%1,%2,%3,%4,%5,%6,%7,%8,%9,%10,%11,%12,%13,%14,%15,%16,%17,%18,%19,%20,%21,%22,%23,%24,%25,%26,%27,%28,%29,%30,%31,%32,%33,%34,%35,%36,%37,%38,%39,%40,%41,%42,%43,%44,%45,%46,%47,%48,%49,%50,%51,%52,%53,%54,%55,%56,%57,%58,%59,%60,%61,%62,%63},{%64,%65,%66,%67},db,%71,1,1,0;}"
 :"+f"(d[0]),"+f"(d[1]),"+f"(d[2]),"+f"(d[3]),"+f"(d[4]),"+f"(d[5]),"+f"(d[6]),"+f"(d[7]),"+f"(d[8]),"+f"(d[9]),"+f"(d[10]),"+f"(d[11]),"+f"(d[12]),"+f"(d[13]),"+f"(d[14]),"+f"(d[15]),"+f"(d[16]),"+f"(d[17]),"+f"(d[18]),"+f"(d[19]),"+f"(d[20]),"+f"(d[21]),"+f"(d[22]),"+f"(d[23]),"+f"(d[24]),"+f"(d[25]),"+f"(d[26]),"+f"(d[27]),"+f"(d[28]),"+f"(d[29]),"+f"(d[30]),"+f"(d[31]),"+f"(d[32]),"+f"(d[33]),"+f"(d[34]),"+f"(d[35]),"+f"(d[36]),"+f"(d[37]),"+f"(d[38]),"+f"(d[39]),"+f"(d[40]),"+f"(d[41]),"+f"(d[42]),"+f"(d[43]),"+f"(d[44]),"+f"(d[45]),"+f"(d[46]),"+f"(d[47]),"+f"(d[48]),"+f"(d[49]),"+f"(d[50]),"+f"(d[51]),"+f"(d[52]),"+f"(d[53]),"+f"(d[54]),"+f"(d[55]),"+f"(d[56]),"+f"(d[57]),"+f"(d[58]),"+f"(d[59]),"+f"(d[60]),"+f"(d[61]),"+f"(d[62]),"+f"(d[63])
 :"r"(a0),"r"(a1),"r"(a2),"r"(a3),"r"(blo),"n"(OFF),"n"(HI),"n"(SC)); } };
template<> struct WgSs<80> { template<int AOFF,int AHI,int BOFF,int BHI,int SC> static __device__ __forceinline__ void run(float* d,uint32_t alo,uint32_t blo){
 asm volatile("{.reg .b32 l,m; .reg .b64 da,db; add.u32 l,%40,%42; mov.b64 da,{l,%43}; add.u32 m,%41,%44; mov.b64 db,{m,%45}; wgmma.mma_async.sync.aligned.m64n80k16.f32.bf16.bf16 {%0,%1,%2,%3,%4,%5,%6,%7,%8,%9,%10,%11,%12,%13,%14,%15,%16,%17,%18,%19,%20,%21,%22,%23,%24,%25,%26,%27,%28,%29,%30,%31,%32,%33,%34,%35,%36,%37,%38,%39},da,db,%46,1,1,0,1;}"
 :"+f"(d[0]),"+f"(d[1]),"+f"(d[2]),"+f"(d[3]),"+f"(d[4]),"+f"(d[5]),"+f"(d[6]),"+f"(d[7]),"+f"(d[8]),"+f"(d[9]),"+f"(d[10]),"+f"(d[11]),"+f"(d[12]),"+f"(d[13]),"+f"(d[14]),"+f"(d[15]),"+f"(d[16]),"+f"(d[17]),"+f"(d[18]),"+f"(d[19]),"+f"(d[20]),"+f"(d[21]),"+f"(d[22]),"+f"(d[23]),"+f"(d[24]),"+f"(d[25]),"+f"(d[26]),"+f"(d[27]),"+f"(d[28]),"+f"(d[29]),"+f"(d[30]),"+f"(d[31]),"+f"(d[32]),"+f"(d[33]),"+f"(d[34]),"+f"(d[35]),"+f"(d[36]),"+f"(d[37]),"+f"(d[38]),"+f"(d[39])
 :"r"(alo),"r"(blo),"n"(AOFF),"n"(AHI),"n"(BOFF),"n"(BHI),"n"(SC)); } };
template<> struct WgSs<104> { template<int AOFF,int AHI,int BOFF,int BHI,int SC> static __device__ __forceinline__ void run(float* d,uint32_t alo,uint32_t blo){
 asm volatile("{.reg .b32 l,m; .reg .b64 da,db; add.u32 l,%52,%54; mov.b64 da,{l,%55}; add.u32 m,%53,%56; mov.b64 db,{m,%57}; wgmma.mma_async.sync.aligned.m64n104k16.f32.bf16.bf16 {%0,%1,%2,%3,%4,%5,%6,%7,%8,%9,%10,%11,%12,%13,%14,%15,%16,%17,%18,%19,%20,%21,%22,%23,%24,%25,%26,%27,%28,%29,%30,%31,%32,%33,%34,%35,%36,%37,%38,%39,%40,%41,%42,%43,%44,%45,%46,%47,%48,%49,%50,%51},da,db,%58,1,1,0,1;}"
 :"+f"(d[0]),"+f"(d[1]),"+f"(d[2]),"+f"(d[3]),"+f"(d[4]),"+f"(d[5]),"+f"(d[6]),"+f"(d[7]),"+f"(d[8]),"+f"(d[9]),"+f"(d[10]),"+f"(d[11]),"+f"(d[12]),"+f"(d[13]),"+f"(d[14]),"+f"(d[15]),"+f"(d[16]),"+f"(d[17]),"+f"(d[18]),"+f"(d[19]),"+f"(d[20]),"+f"(d[21]),"+f"(d[22]),"+f"(d[23]),"+f"(d[24]),"+f"(d[25]),"+f"(d[26]),"+f"(d[27]),"+f"(d[28]),"+f"(d[29]),"+f"(d[30]),"+f"(d[31]),"+f"(d[32]),"+f"(d[33]),"+f"(d[34]),"+f"(d[35]),"+f"(d[36]),"+f"(d[37]),"+f"(d[38]),"+f"(d[39]),"+f"(d[40]),"+f"(d[41]),"+f"(d[42]),"+f"(d[43]),"+f"(d[44]),"+f"(d[45]),"+f"(d[46]),"+f"(d[47]),"+f"(d[48]),"+f"(d[49]),"+f"(d[50]),"+f"(d[51])
 :"r"(alo),"r"(blo),"n"(AOFF),"n"(AHI),"n"(BOFF),"n"(BHI),"n"(SC)); } };
template<> struct WgSs<112> { template<int AOFF,int AHI,int BOFF,int BHI,int SC> static __device__ __forceinline__ void run(float* d,uint32_t alo,uint32_t blo){
 asm volatile("{.reg .b32 l,m; .reg .b64 da,db; add.u32 l,%56,%58; mov.b64 da,{l,%59}; add.u32 m,%57,%60; mov.b64 db,{m,%61}; wgmma.mma_async.sync.aligned.m64n112k16.f32.bf16.bf16 {%0,%1,%2,%3,%4,%5,%6,%7,%8,%9,%10,%11,%12,%13,%14,%15,%16,%17,%18,%19,%20,%21,%22,%23,%24,%25,%26,%27,%28,%29,%30,%31,%32,%33,%34,%35,%36,%37,%38,%39,%40,%41,%42,%43,%44,%45,%46,%47,%48,%49,%50,%51,%52,%53,%54,%55},da,db,%62,1,1,0,1;}"
 :"+f"(d[0]),"+f"(d[1]),"+f"(d[2]),"+f"(d[3]),"+f"(d[4]),"+f"(d[5]),"+f"(d[6]),"+f"(d[7]),"+f"(d[8]),"+f"(d[9]),"+f"(d[10]),"+f"(d[11]),"+f"(d[12]),"+f"(d[13]),"+f"(d[14]),"+f"(d[15]),"+f"(d[16]),"+f"(d[17]),"+f"(d[18]),"+f"(d[19]),"+f"(d[20]),"+f"(d[21]),"+f"(d[22]),"+f"(d[23]),"+f"(d[24]),"+f"(d[25]),"+f"(d[26]),"+f"(d[27]),"+f"(d[28]),"+f"(d[29]),"+f"(d[30]),"+f"(d[31]),"+f"(d[32]),"+f"(d[33]),"+f"(d[34]),"+f"(d[35]),"+f"(d[36]),"+f"(d[37]),"+f"(d[38]),"+f"(d[39]),"+f"(d[40]),"+f"(d[41]),"+f"(d[42]),"+f"(d[43]),"+f"(d[44]),"+f"(d[45]),"+f"(d[46]),"+f"(d[47]),"+f"(d[48]),"+f"(d[49]),"+f"(d[50]),"+f"(d[51]),"+f"(d[52]),"+f"(d[53]),"+f"(d[54]),"+f"(d[55])
 :"r"(alo),"r"(blo),"n"(AOFF),"n"(AHI),"n"(BOFF),"n"(BHI),"n"(SC)); } };

__device__ __forceinline__ void wg_fence() { asm volatile("wgmma.fence.sync.aligned;" ::: "memory"); }
__device__ __forceinline__ void wg_commit() { asm volatile("wgmma.commit_group.sync.aligned;" ::: "memory"); }
template <int N> __device__ __forceinline__ void wg_wait() { asm volatile("wgmma.wait_group.sync.aligned %0;" ::"n"(N) : "memory"); }
template <int N> __device__ __forceinline__ void reg_fence(float* d) {
#pragma unroll
    for (int i = 0; i < N; i++) asm volatile("" : "+f"(d[i])::"memory");
}
__device__ __forceinline__ uint32_t desc_lo(uint32_t addr, uint32_t lbo) { return ((addr & 0x3FFFF) >> 4) | ((lbo >> 4) << 16); }
#define desc_hi(sbo, sw) (((sbo) >> 4) | ((sw) << 30))
__device__ __forceinline__ uint32_t smem_u32(const void* p) { return (uint32_t)__cvta_generic_to_shared(p); }
__device__ __forceinline__ bool elect() {
    uint32_t p;
    asm volatile("{.reg .pred P; elect.sync _|P, 0xffffffff; selp.u32 %0,1,0,P;}" : "=r"(p));
    return p;
}
__device__ __forceinline__ void mbar_init(uint32_t bar, uint32_t cnt) { asm volatile("mbarrier.init.shared::cta.b64 [%0], %1;" ::"r"(bar), "r"(cnt) : "memory"); }
__device__ __forceinline__ void mbar_expect(uint32_t bar, uint32_t bytes) { asm volatile("mbarrier.arrive.expect_tx.shared::cta.b64 _, [%0], %1;" ::"r"(bar), "r"(bytes) : "memory"); }
__device__ __forceinline__ bool mbar_try(uint32_t bar, uint32_t par) {
    uint32_t ok;
    asm volatile("{.reg .pred p; mbarrier.try_wait.parity.shared::cta.b64 p, [%1], %2; selp.u32 %0,1,0,p;}" : "=r"(ok) : "r"(bar), "r"(par) : "memory");
    return ok;
}
constexpr int SPIN_LIMIT = 1 << 18;
__device__ __forceinline__ void mbar_wait(uint32_t bar, uint32_t par) {
    if (mbar_try(bar, par)) return;
    asm volatile("{.reg .pred p, q; .reg .b32 n; mov.u32 n, 0;\n"
                 "W%=: mbarrier.try_wait.parity.shared::cta.b64 p, [%0], %1; add.u32 n, n, 1; setp.lt.and.u32 q, n, %2, !p; @q bra W%=;}"
                 ::"r"(bar), "r"(par), "n"(SPIN_LIMIT) : "memory");
}
__device__ __forceinline__ void bulk_g2s(uint32_t dst, const void* src, uint32_t bytes, uint32_t bar) {
    asm volatile("cp.async.bulk.shared::cluster.global.mbarrier::complete_tx::bytes [%0], [%1], %2, [%3];" ::"r"(dst), "l"(src), "r"(bytes), "r"(bar) : "memory");
}
__device__ __forceinline__ void bulk_prefetch(const void* src, uint32_t bytes) {
    asm volatile("cp.async.bulk.prefetch.L2.global [%0], %1;" ::"l"(src), "r"(bytes) : "memory");
}
__device__ __forceinline__ void tma2d(uint32_t dst, const CUtensorMap* m, int c0, int c1, uint32_t bar) {
    asm volatile("cp.async.bulk.tensor.2d.shared::cluster.global.mbarrier::complete_tx::bytes [%0], [%1, {%3, %4}], [%2];" ::"r"(dst), "l"(m), "r"(bar), "r"(c0), "r"(c1) : "memory");
}
__device__ __forceinline__ void tma2d_mc(uint32_t dst, const CUtensorMap* m, int c0, int c1, uint32_t bar) {
    asm volatile("cp.async.bulk.tensor.2d.shared::cluster.global.mbarrier::complete_tx::bytes.multicast::cluster [%0], [%1, {%3, %4}], [%2], %5;" ::"r"(dst), "l"(m), "r"(bar), "r"(c0), "r"(c1), "h"((uint16_t)3) : "memory");
}
__device__ __forceinline__ uint32_t mapa(uint32_t a, uint32_t rank) { uint32_t r; asm("mapa.shared::cluster.u32 %0, %1, %2;" : "=r"(r) : "r"(a), "r"(rank)); return r; }
__device__ __forceinline__ void mbar_arrive_cl(uint32_t bar) { asm volatile("mbarrier.arrive.shared::cluster.b64 _, [%0];" ::"r"(bar) : "memory"); }
__device__ __forceinline__ void prefetch_map(const CUtensorMap* m) { asm volatile("prefetch.tensormap [%0];" ::"l"(m) : "memory"); }
__device__ __forceinline__ void cpasync16(uint32_t dst, const void* src, uint32_t srcsz) {
    asm volatile("cp.async.cg.shared.global [%0], [%1], 16, %2;" ::"r"(dst), "l"(src), "r"(srcsz) : "memory");
}
__device__ __forceinline__ void bar_sync(int id, int n) { asm volatile("bar.sync %0, %1;" ::"r"(id), "r"(n) : "memory"); }
__device__ __forceinline__ void bar_arrive(int id, int n) { asm volatile("bar.arrive %0, %1;" ::"r"(id), "r"(n) : "memory"); }
__device__ __forceinline__ void fence_async_smem() { asm volatile("fence.proxy.async.shared::cta;" ::: "memory"); }
__device__ __forceinline__ void fence_async_global() { asm volatile("fence.proxy.async.global;" ::: "memory"); }
__device__ __forceinline__ unsigned* flag_ptr(int f) {
    return f < 16 ? &g_flags[(f & 7) * 32 + (f >> 3)] : &g_flags[f * 32];
}
__device__ __forceinline__ void flag_release(int f) { asm volatile("red.release.gpu.global.add.u32 [%0], 1;" ::"l"(flag_ptr(f)) : "memory"); }
__device__ __forceinline__ void flag_wait(int f, unsigned target) {
    const unsigned* p = flag_ptr(f);
    unsigned v; int n = 0;
    do {
        asm volatile("ld.relaxed.gpu.global.u32 %0, [%1];" : "=r"(v) : "l"(p) : "memory");
    } while ((int)(v - target) < 0 && ++n < SPIN_LIMIT);
    asm volatile("fence.acquire.gpu;" ::: "memory");
}
__device__ __forceinline__ unsigned ld_flag(const unsigned* p) { unsigned v; asm volatile("ld.relaxed.gpu.global.u32 %0, [%1];" : "=r"(v) : "l"(p) : "memory"); return v; }
__device__ __forceinline__ void spin(unsigned n) { unsigned t0, t1; asm volatile("mov.u32 %0, %%clock;" : "=r"(t0)); do { asm volatile("mov.u32 %0, %%clock;" : "=r"(t1)); } while (t1 - t0 < n); }
__device__ __forceinline__ int tensor_ping() {
    int r;
    asm volatile("{.reg .f32 a, b, c, d; mma.sync.aligned.m16n8k16.row.col.f32.bf16.bf16.f32 {a,b,c,d},{%1,%1,%1,%1},{%1,%1},{%2,%2,%2,%2}; mov.b32 %0, a;}" : "=r"(r) : "r"(0), "f"(0.f));
    return r;
}
__device__ __forceinline__ void mbar_wait_warm(uint32_t bar, uint32_t par) {
    for (int n = 0; n < SPIN_LIMIT; n++) {
        uint32_t ok;
        asm volatile("{.reg .pred p; mbarrier.test_wait.parity.shared::cta.b64 p, [%1], %2; selp.u32 %0,1,0,p;}" : "=r"(ok) : "r"(bar), "r"(par) : "memory");
        if (ok) break;
        n += tensor_ping();
        spin(PING);
    }
}
__device__ __forceinline__ void flag_wait2(int f0, int f1, unsigned target) {
    const unsigned *p = flag_ptr(f0), *q = flag_ptr(f1);
    unsigned v, w; int n = 0;
    do { v = ld_flag(p); w = ld_flag(q); } while ((int)((v - target) | (w - target)) < 0 && ++n < SPIN_LIMIT);
    asm volatile("fence.acquire.gpu;" ::: "memory");
}
__device__ __forceinline__ uint32_t lds32(uint32_t a) { uint32_t v; asm volatile("ld.shared.u32 %0, [%1];" : "=r"(v) : "r"(a)); return v; }
__device__ __forceinline__ float2 lds64f(uint32_t a) { float2 v; asm volatile("ld.shared.v2.f32 {%0,%1}, [%2];" : "=f"(v.x), "=f"(v.y) : "r"(a)); return v; }
__device__ __forceinline__ uint2 lds64(uint32_t a) { uint2 v; asm volatile("ld.shared.v2.u32 {%0,%1}, [%2];" : "=r"(v.x), "=r"(v.y) : "r"(a)); return v; }
__device__ __forceinline__ void sts64f(uint32_t a, float2 v) { asm volatile("st.shared.v2.f32 [%0], {%1,%2};" ::"r"(a), "f"(v.x), "f"(v.y) : "memory"); }
__device__ __forceinline__ void sts32(uint32_t a, uint32_t v) { asm volatile("st.shared.u32 [%0], %1;" ::"r"(a), "r"(v) : "memory"); }
__device__ __forceinline__ void sts64(uint32_t a, uint32_t x, uint32_t y) { asm volatile("st.shared.v2.u32 [%0], {%1,%2};" ::"r"(a), "r"(x), "r"(y) : "memory"); }
__device__ __forceinline__ void sts16(uint32_t a, uint16_t v) { asm volatile("st.shared.u16 [%0], %1;" ::"r"(a), "h"(v) : "memory"); }
__device__ __forceinline__ uint4 lds128(uint32_t a) { uint4 v; asm volatile("ld.shared.v4.u32 {%0,%1,%2,%3}, [%4];" : "=r"(v.x), "=r"(v.y), "=r"(v.z), "=r"(v.w) : "r"(a)); return v; }
__device__ __forceinline__ void sts128(uint32_t a, uint4 v) { asm volatile("st.shared.v4.u32 [%0], {%1,%2,%3,%4};" ::"r"(a), "r"(v.x), "r"(v.y), "r"(v.z), "r"(v.w) : "memory"); }
__device__ __forceinline__ void sts128f(uint32_t a, float x, float y, float z, float w) { asm volatile("st.shared.v4.f32 [%0], {%1,%2,%3,%4};" ::"r"(a), "f"(x), "f"(y), "f"(z), "f"(w) : "memory"); }
__device__ __forceinline__ uint32_t prmt(uint32_t a, uint32_t b, uint32_t s) { uint32_t r; asm("prmt.b32 %0,%1,%2,%3;" : "=r"(r) : "r"(a), "r"(b), "r"(s)); return r; }
__device__ __forceinline__ uint32_t pack2(float lo, float hi) { uint32_t r; asm("cvt.rn.bf16x2.f32 %0, %1, %2;" : "=r"(r) : "f"(hi), "f"(lo)); return r; }
__device__ __forceinline__ float blo(uint32_t v) { return __uint_as_float(v << 16); }
__device__ __forceinline__ float bhi(uint32_t v) { return __uint_as_float(v & 0xffff0000u); }
__device__ __forceinline__ uint32_t bmul2(uint32_t a, uint32_t b) { uint32_t r; asm("mul.rn.bf16x2 %0,%1,%2;" : "=r"(r) : "r"(a), "r"(b)); return r; }
__device__ __forceinline__ uint32_t badd2(uint32_t a, uint32_t b) { uint32_t r; asm("add.rn.bf16x2 %0,%1,%2;" : "=r"(r) : "r"(a), "r"(b)); return r; }
__device__ __forceinline__ uint4 ldcg128(const void* p) { uint4 v; asm volatile("ld.global.cg.v4.u32 {%0,%1,%2,%3}, [%4];" : "=r"(v.x), "=r"(v.y), "=r"(v.z), "=r"(v.w) : "l"(p) : "memory"); return v; }
__device__ __forceinline__ uint2 ldcg64(const void* p) { uint2 v; asm volatile("ld.global.cg.v2.u32 {%0,%1}, [%2];" : "=r"(v.x), "=r"(v.y) : "l"(p) : "memory"); return v; }
__device__ __forceinline__ float half_rstd(float sum, float sq) {
    float mean = sum * (1.0f / D_), inv;
    asm("rsqrt.approx.ftz.f32 %0, %1;" : "=f"(inv) : "f"(fmaxf(fmaf(-mean, mean, fmaf(sq, 1.0f / D_, 1e-5f)), 1e-5f)));
    return 0.5f * inv;
}
__device__ __forceinline__ uint32_t bsub2(uint32_t a, uint32_t b) { uint32_t r; asm("sub.rn.bf16x2 %0,%1,%2;" : "=r"(r) : "r"(a), "r"(b)); return r; }
__device__ __forceinline__ uint32_t bfma2(uint32_t a, uint32_t b, uint32_t c) { uint32_t r; asm("fma.rn.bf16x2 %0,%1,%2,%3;" : "=r"(r) : "r"(a), "r"(b), "r"(c)); return r; }
__device__ __forceinline__ uint32_t gelu2_h(uint32_t h) {
    uint32_t u = bmul2(h, bfma2(bmul2(h, h), 0x3e923e92u, 0x3fcc3fccu)), th;
    asm("tanh.approx.bf16x2 %0, %1;" : "=r"(th) : "r"(u));
    return bfma2(h, th, h);
}
struct RowSum { float s = 0.f, q = 0.f, s_ = 0.f, q_ = 0.f;
    __device__ __forceinline__ void add(uint32_t v) { float a = blo(v), b = bhi(v); s += a; s_ += b; q = fmaf(a, a, q); q_ = fmaf(b, b, q_); } };
template <int I0>
__device__ __forceinline__ uint2 row_stats(const uint32_t* v, int lane, RowSum r0 = RowSum()) {
#pragma unroll
    for (int i = I0; i < 10; i++) r0.add(v[i]);
    float s = r0.s + r0.s_, q = r0.q + r0.q_;
    {
        float t = __shfl_xor_sync(0xffffffffu, (lane & 16) ? s : q, 16);
        t += (lane & 16) ? q : s;
#pragma unroll
        for (int m = 8; m; m >>= 1) t += __shfl_xor_sync(0xffffffffu, t, m);
        float o = __shfl_xor_sync(0xffffffffu, t, 16);
        s = (lane & 16) ? o : t; q = (lane & 16) ? t : o;
    }
    float mean = s * (1.0f / D_), inv;
    asm("rsqrt.approx.ftz.f32 %0, %1;" : "=f"(inv) : "f"(fmaxf(fmaf(-mean, mean, fmaf(q, 1.0f / D_, 1e-5f)), 1e-5f)));
    return make_uint2(pack2(mean, mean), pack2(inv, inv));
}
__device__ __forceinline__ uint32_t ln_apply(uint32_t x, uint32_t m, uint32_t inv) { return bmul2(bsub2(x, m), inv); }

struct AFrag { uint32_t m, a, b, c, d; };
__device__ __forceinline__ AFrag ldA(uint32_t a) { AFrag f; f.m = lds32(a - 16); f.a = lds32(a); f.b = lds32(a + 16); f.c = lds32(a + 32); f.d = lds32(a + 48); return f; }
template <int N, int M> __device__ __forceinline__ void conv_pair(float* d, const AFrag& f, uint32_t descU) {
    WgRs<N>::template run<8 * M, desc_hi(128, 0), M ? 1 : 0>(d, f.a, f.b, f.m, f.a, descU);
    WgRs<N>::template run<8 * M + 1, desc_hi(128, 0), 1>(d, f.c, f.d, f.b, f.c, descU);
}
template <int Q> __device__ __forceinline__ void conv_put(float* d, uint32_t r0) {
    sts64(r0 + Q * 32, pack2(d[4 * Q + 1], d[4 * Q + 3]), pack2(d[4 * Q], d[4 * Q + 2]));
}
template <int M> __device__ __forceinline__ void conv_two(float* d, AFrag f0, AFrag f1, uint32_t kaddr, uint32_t descU, uint32_t r0, bool handoff) {
    constexpr int N = M < 14 ? 128 - 8 * M : 32;
    wg_fence();
    conv_pair<N, M>(d, f0, descU);
    wg_commit();
    if constexpr (M > 0) f1 = ldA(kaddr + 256 * (M + 1));
    wg_fence();
    conv_pair<N, M + 1>(d, f1, descU);
    wg_commit();
    if (STAG && M == STAG && handoff) bar_arrive(12, 256);
    if constexpr (M < 14) {
        if constexpr (M > 0) { conv_put<17 - M>(d, r0); conv_put<16 - M>(d, r0); }
        wg_wait<1>();
        f0 = ldA(kaddr + 256 * (M + 2));
        if constexpr (M < 12) wg_wait<0>();
        conv_two<M + 2>(d, f0, f1, kaddr, descU, r0, handoff);
    } else {
        wg_wait<0>();
        conv_put<3>(d, r0); conv_put<2>(d, r0); conv_put<1>(d, r0); conv_put<0>(d, r0);
    }
}
template <int N, bool ASWZ, int SC0>
__device__ __forceinline__ void gemm_issue(float* acc, uint32_t bars, int sa, int pa, int sw, int pw, uint32_t da0, uint32_t db0) {
    mbar_wait(bars + (BAR_FB + sw) * 8, pw);
    mbar_wait(bars + (BAR_FA + sa) * 8, pa);
    const uint32_t da = da0 + sa * (SLOT >> 4), db = db0 + sw * (SLOT >> 4);
    constexpr int AK = ASWZ ? 2 : 256, AH = ASWZ ? desc_hi(1024, 1) : desc_hi(128, 0), BH = desc_hi(1024, 1);
    wg_fence();
    WgSs<N>::template run<0, AH, 0, BH, SC0>(acc, da, db);
    WgSs<N>::template run<AK, AH, 128, BH, 1>(acc, da, db);
    WgSs<N>::template run<2 * AK, AH, 256, BH, 1>(acc, da, db);
    WgSs<N>::template run<3 * AK, AH, 384, BH, 1>(acc, da, db);
    wg_commit();
}
template <int N, bool ASWZ, int NKB, int RELB, bool ZERO>
__device__ __forceinline__ void gemm_loop(float* acc, uint32_t sb, int half, int ia0, int ib0, int rela, int wait_bar, int tsid) {
    int sa = ia0 % NA, pa = (ia0 / NA) & 1, sw = ib0 % NB, pw = (ib0 / NB) & 1;
    const uint32_t bars = sb + SM_BAR;
    const int t = threadIdx.x & 127;
    uint32_t ebar = mapa(bars + (t < 2 ? BAR_EB : BAR_EA) * 8, (t < 2 && lds32(sb + SM_GV + 516)) ? t : blockIdx.x & 1);
    const int nrel = t < 2 ? RELB : t == 2 ? rela : 0;
    const uint32_t da0 = ASWZ ? desc_lo(sb + SM_RA + half * 8192, 16) : desc_lo(sb + SM_RA + half * 1024, 2048), db0 = desc_lo(sb + SM_RB, 8192);
    if (!ZERO) {
        if (sa-- == 0) { sa = NA - 1; pa ^= 1; }
        if (sw-- == 0) { sw = NB - 1; pw ^= 1; }
    }
    asm volatile("" : "+r"(ebar));
    if (wait_bar) bar_sync(wait_bar, 512);
    constexpr bool PEEL = ZERO;
    if (PEEL) gemm_issue<N, ASWZ, 0>(acc, bars, sa, pa, sw, pw, da0, db0);
    if ((threadIdx.x & 255) == 0) TS(tsid);
#pragma unroll 1
    for (int kb = PEEL; kb < NKB; kb++) {
        const int prev = t < 2 ? sw : sa;
        if (++sa == NA) { sa = 0; pa ^= 1; }
        if (++sw == NB) { sw = 0; pw ^= 1; }
        gemm_issue<N, ASWZ, 1>(acc, bars, sa, pa, sw, pw, da0, db0);
        wg_wait<1>();
        if (PEEL ? kb <= nrel : (unsigned)(kb - 1) < (unsigned)nrel) mbar_arrive_cl(ebar + prev * 8);
    }
    wg_wait<0>();
    if (nrel == NKB) mbar_arrive_cl(ebar + (t < 2 ? sw : sa) * 8);
    reg_fence<N / 2>(acc);
    if ((threadIdx.x & 255) == 0) TS(tsid + 1);
}

template <int PART>
__device__ __forceinline__ void gemm3(uint32_t sb, int rb, int j, int half, int row, int c, unsigned ones) {
    constexpr int N = 64 + (PART ? RB3 : RA3), NQ = N / 8;
    float acc[N / 2];
    float2 cr[NQ];
    if (PART) {
        gemm_loop<N, false, 1, 1, true>(acc, sb, half, 20, 20, 0, 0, 50);
        bar_arrive(9, 512);
    }
    mbar_wait(sb + SM_BAR + BAR_CS * 8, 0);
    const uint32_t csa = sb + SM_CS + PART * (256 + 4 * RA3) + 8 * c;
#pragma unroll
    for (int q = 0; q < NQ; q++) cr[q] = lds64f(csa + 32 * q);
    uint4 rp;
    if (PART) {
        mbar_wait(sb + SM_BAR + BAR_G * 8, 0);
        const float2* sp = &g_st[(rb * 8 + 2 * c) * 128 + row];
        const uint2 s0 = ldcg64(sp), s1 = ldcg64(sp + 128), s2 = ldcg64(sp + 8), s3 = ldcg64(sp + 136);
        float a0 = __uint_as_float(s0.x) + __uint_as_float(s1.x), b0 = __uint_as_float(s0.y) + __uint_as_float(s1.y);
        float a1 = __uint_as_float(s2.x) + __uint_as_float(s3.x), b1 = __uint_as_float(s2.y) + __uint_as_float(s3.y);
#pragma unroll
        for (int m = 1; m <= 2; m <<= 1) {
            a0 += __shfl_xor_sync(0xffffffffu, a0, m); b0 += __shfl_xor_sync(0xffffffffu, b0, m);
            a1 += __shfl_xor_sync(0xffffffffu, a1, m); b1 += __shfl_xor_sync(0xffffffffu, b1, m);
        }
        const float inv0 = half_rstd(a0, b0), inv1 = half_rstd(a1, b1);
        rp = make_uint4(pack2(inv0, inv0), __float_as_uint(a0 * (-1.0f / D_)),
                        pack2(inv1, inv1), __float_as_uint(a1 * (-1.0f / D_)));
        if (c == 0) sts128(sb + SM_RP + ((threadIdx.x & 255) >> 2) * 16, rp);
        bar_arrive(13, 512);
    }
    gemm_loop<N, false, 10 - PART, 10 - PART, !PART>(acc, sb, half, 20 + (10 - NA) * PART, 21 + 10 * PART, PART ? 9 : 10 - NA, 9 + PART, 46 + 2 * PART);
    if ((threadIdx.x & 255) == 0) mbar_expect(sb + SM_BAR + BAR_ME * 8, 0);
    if (!PART) {
        bar_sync(13, 512);
        rp = lds128(sb + SM_RP + ((threadIdx.x & 255) >> 2) * 16);
    }
    const float nb0 = __uint_as_float(rp.y), nb1 = __uint_as_float(rp.w);
    const uint32_t own = sb + SM_RA + ((39 - NA) % NA) * SLOT + row * 16 + c * 4;
    if (PART) mbar_wait(sb + SM_BAR + (BAR_FA + (39 - NA) % NA) * 8, ((39 - NA) / NA) & 1);
    uint32_t* dst = reinterpret_cast<uint32_t*>(g_g) + (rb * 216 + HB0 / 8 * PART + 8 * j) * 512 + row * 4 + c;
    auto act = [&](int q, int r) {
        const float nb = r ? nb1 : nb0;
        const uint32_t inv = r ? rp.z : rp.x;
        const float t0 = fmaf(nb, cr[q].x, acc[4 * q + 2 * r]), t1 = fmaf(nb, cr[q].y, acc[4 * q + 2 * r + 1]);
        return gelu2_h(bmul2(pack2(t0, t1), inv));
    };
    uint32_t* dst1 = dst + (56 - (16 - NQ) * j) * 512;
#pragma unroll
    for (int k = 0; k < NQ; k += CH3) {
        CHUNK(k) {
#pragma unroll
            for (int q = k; q < k + CH3 && q < NQ; q++) {
                const uint32_t u = act(q, 0), v = act(q, 1);
                (q < 8 ? dst : dst1)[q * 512] = u;
                (q < 8 ? dst : dst1)[q * 512 + 32] = v;
                if (PART && q < 8) { sts32(own + q * 2048, u); sts32(own + q * 2048 + 128, v); }
            }
            if (PART && k < 8 && k + CH3 >= 8) fence_async_smem();
        }
    }
    bar_arrive(1 + PART, 288);
    bar_arrive(10 + PART, 512);
}

template <int NS, int BASE, int BF, int BE> struct Ring {
    uint32_t sb, st, ph;
    __device__ __forceinline__ uint32_t acquire(uint32_t bytes) {
        mbar_wait(sb + SM_BAR + BE * 8 + st * 8, ph);
        uint32_t fb = sb + SM_BAR + BF * 8 + st * 8;
        mbar_expect(fb, bytes);
        return fb;
    }
    __device__ __forceinline__ uint32_t slot() { return sb + BASE + st * SLOT; }
    __device__ __forceinline__ void next() { if (++st == NS) { st = 0; ph ^= 1; } }
    __device__ __forceinline__ void run2d(const CUtensorMap* m, int c1) {
#pragma unroll 1
        for (int c0 = 64; c0 < D_; c0 += 64) {
            uint32_t fb = acquire(SLOT);
            tma2d(slot(), m, c0, c1, fb);
            next();
        }
    }
    static __device__ __forceinline__ int korder(int i, int own) { return i == 0 ? own : i > own ? i : i - 1; }
    __device__ __forceinline__ void runw(bool paired, int rk, const CUtensorMap* ma, const CUtensorMap* mb, int ca, int cb, int i0, int i1, int own, uint32_t bytes, int gate_at, uint32_t gate) {
        if (paired) {
            const CUtensorMap* m = rk ? mb : ma;
            const int c0 = rk ? cb : ca;
#pragma unroll 1
            for (int i = i0; i < i1; i++) {
                const int c1 = korder(i, own) * 64;
                if (i == gate_at) mbar_wait(gate, 0);
                uint32_t fb = acquire(bytes);
                tma2d_mc(slot() + 8192 * rk, m, c0, c1, fb);
                next();
            }
        } else {
#pragma unroll 1
            for (int i = i0; i < i1; i++) {
                const int c1 = korder(i, own) * 64;
                uint32_t fb = acquire(bytes);
                tma2d(slot(), ma, ca, c1, fb);
                tma2d(slot() + 8192, mb, cb, c1, fb);
                next();
            }
        }
    }
    __device__ __forceinline__ void run1d(const char* src, int i0, int i1, int own) {
#pragma unroll 1
        for (int i = i0; i < i1; i++) {
            const char* s = src + korder(i, own) * SLOT;
            uint32_t fb = acquire(SLOT);
            bulk_g2s(slot(), s, SLOT, fb);
            next();
        }
    }
};

__global__ void __cluster_dims__(2, 1, 1) __launch_bounds__(NTHREADS, 1) fused_kernel(const Params p, const __grid_constant__ Maps maps) {
    extern __shared__ __align__(1024) unsigned char smem_raw[];
    const uint32_t sb = (smem_u32(smem_raw) + 1023u) & ~1023u;
#pragma unroll
    for (int i = 0; i < SEED; i++) asm volatile("{.reg .b32 t; mov.u32 t, %laneid;}");
    const uint32_t bars = sb + SM_BAR;
    const int tid = threadIdx.x, lane = tid & 31;
    unsigned smid;
    asm volatile("mov.u32 %0, %%smid;" : "=r"(smid));
    const bool spare = (smid >> 2) == 30;
    const int cta = smid < 120 ? smid : smid - 4;
    const int pg = cta >> 4, pi = cta & 15;
    auto chan = [&](int cc) { return cc < 3 ? 3 * cta + cc : 381 + 2 * cta + cc; };
    const int hb = tid >= 320;
    unsigned ep0 = 0;
    if (!spare) {
        const unsigned t = tid - 320 * hb, r32 = t / 10u, cc = t - r32 * 10u, row = r32 + 64 * hb;
        const unsigned go = (unsigned)(pi * 128 * 1280) + row * 1280u + cc * 16u + (cc < 6 ? pg * 96 : 672 + pg * 64);
        const uint32_t so = sb + (row >> 4) * 32u + row * 160u + cc * 16u;
        const char* kb = (const char*)p.k + go;
        const char* vb = (const char*)p.v + go;
        if (hb) {
            if (tid < 328) {
                const char* a = lane < 5 ? (const char*)p.shift + lane * 128 + (lane < 3 ? pg * 384 : 2688 + pg * 256) : (const char*)(p.ssmD + chan(2 * lane - 10));
                asm volatile("prefetch.global.L2 [%0];" ::"l"(a));
            }
            if (tid >= 640 - NBARS) {
                const int i = 639 - tid;
                mbar_init(bars + i * 8, (i >= BAR_EB && i < BAR_K) ? 4 : ((i >= BAR_EA && i < BAR_EB) || i == BAR_XY) ? 2 : 1);
                asm volatile("fence.mbarrier_init.release.cluster;" ::: "memory");
            }
            bar_arrive(14, 640);
            if (tid >= 512) asm volatile("ld.volatile.global.u32 %0, [%1];" : "=r"(ep0) : "l"(p.epoch + smid) : "memory");
            if (B_DELAY) spin(B_DELAY);
        }
        cpasync16(so + SM_PK + 2592, kb, 16);
        cpasync16(so + SM_PV, vb, 16);
        cpasync16(so + SM_PK + 3 * 2592, kb + 32 * 1280, 16);
        cpasync16(so + SM_PV + 2 * 2592, vb + 32 * 1280, 16);
        if (tid < 30) cpasync16(so + SM_PK + 13 * 160, pi ? kb - 3 * 1280 : kb, pi ? 16 : 0);
        asm volatile("cp.async.commit_group;" ::: "memory");
    }
    const int warp = __shfl_sync(0xffffffffu, tid >> 5, 0);
    const int wg = warp >> 2, wq = warp & 3;

    if (spare) {
        const int sp = smid & 3;
        const unsigned ep1 = *(volatile unsigned*)&p.epoch[smid] + 1;
        if (tid == 32) { sts32(sb + SM_GV + 512, smid); asm volatile("fence.release.sync_restrict::shared::cta.cluster;" ::: "memory"); }
        asm volatile("barrier.cluster.arrive.relaxed.aligned;" ::: "memory");
        asm volatile("barrier.cluster.wait.aligned;" ::: "memory");
        if (tid == 0) {
            for (int i = 0; i < 4; i++) mbar_init(bars + i * 8, 1);
            asm volatile("fence.mbarrier_init.release.cluster;" ::: "memory");
        }
        if (warp == 0) { if (lane < 8) flag_wait(FL_P + lane, ep1 * 16); __syncwarp(); if (SPD) spin(SPD); }
        __syncthreads();
        const int cq = tid % 54, rg = tid / 54;
        float a[8];
#pragma unroll
        for (int i = 0; i < 8; i++) a[i] = 0.f;
#pragma unroll 1
        for (int it = -4; it < 10; it++) {
            const uint32_t st = sb + (it & 3) * 55296, fb = bars + (it & 3) * 8;
            if (it >= 0) {
                mbar_wait(fb, (it >> 2) & 1);
                if (tid < 432) {
#pragma unroll 2
                    for (int i = 0; i < 8; i++) {
                        uint4 w = lds128(st + (cq >= 27 ? 27648 - 432 : 0) + (rg * 8 + i) * 432 + cq * 16);
                        a[0] += blo(w.x); a[1] += bhi(w.x); a[2] += blo(w.y); a[3] += bhi(w.y);
                        a[4] += blo(w.z); a[5] += bhi(w.z); a[6] += blo(w.w); a[7] += bhi(w.w);
                    }
                }
                __syncthreads();
            }
            if (it < 6 && warp == 19 && elect()) {
                mbar_expect(fb, 55296);
                tma2d(st, &maps.w3s, sp * 432, (it + 4) * 64, fb);
                tma2d(st + 27648, &maps.w3s, sp * 432 + 216, (it + 4) * 64, fb);
            }
        }
        if (warp == 19 && elect()) {
#pragma unroll 1
            for (int i = 0; i < 27; i++) bulk_prefetch((const char*)p.w4 + sp * 552960 + i * 20480, 20480);
        }
        if (tid < 432) {
            sts128f(sb + rg * 1728 + cq * 32, a[0], a[1], a[2], a[3]);
            sts128f(sb + rg * 1728 + cq * 32 + 16, a[4], a[5], a[6], a[7]);
        }
        __syncthreads();
        if (tid < 432) {
            float s = 0.f;
#pragma unroll
            for (int i = 0; i < 8; i++) s += __uint_as_float(lds32(sb + i * 1728 + tid * 4));
            g_cs[sp * 432 + tid] = s;
        }
        __syncthreads();
        if (tid == 0) { flag_release(FL_CS); p.epoch[smid] = ep1; TS(0); }
        if (warp == 0) TSFLUSH();
        return;
    }

    int gpc, idx;
    if (smid < 64) { gpc = (smid & 15) >> 1; idx = (smid >> 4) * 2 + (smid & 1); }
    else if (smid < 120) { int t = smid - 64; gpc = 1 + (t % 14) / 2; idx = 8 + (t / 14) * 2 + (smid & 1); }
    else { gpc = 0; idx = 8 + (smid - 124); }
    const int rb = 2 * gpc + (idx & 1), j = idx >> 1;
    const int g = lane >> 2, c = lane & 3;
    const int cm = 160 * (j >> 1) + 64 * (j & 1) + ((j & 2) ? 32 : 0), cr = 160 * (j >> 1) + 16 * (j & 1) + ((j & 2) ? 0 : 128);

    {
        if (warp == 5) TSW(61);
        const int w10 = warp - 10 * hb, h = w10 >= 5;
        const int pr = (w10 - 5 * h) * 8 + (lane >> 2), blk = 4 * hb + (lane & 3);
        const int ch = 2 * pr + (pr < 24 ? 48 * pg : 336 + 32 * pg);
        const uint4 sw = __ldg(reinterpret_cast<const uint4*>(p.shift + ch * 4));
        uint32_t dv = 0;
        if (warp == 9 && lane < 5) dv = __bfloat16_as_ushort(p.ssmD[chan(lane)]);
        if (tid == 512) { sts32(sb + SM_GV + 512, smid); asm volatile("fence.release.sync_restrict::shared::cta.cluster;" ::: "memory"); }
        asm volatile("barrier.cluster.arrive.relaxed.aligned;" ::: "memory");
        if (warp == 11 && lane < 13) prefetch_map(&maps.hn + lane);
        if (wg < 4) {
            const int t = tid & 127, cc = (wg == 3 && t >= 64) ? 4 : wg;
            if (t < 64 || wg == 3) sts128(sb + sm_u(cc) + ((t >> 5) & 1) * U_PLANE + 2048 + lane * 16, make_uint4(0, 0, 0, 0));
            if ((t & 63) < 4 && (t < 64 || wg == 3)) sts128(sb + sm_k(cc) + ((t >> 1) & 1) * 4160 + (t & 1) * 16, make_uint4(0, 0, 0, 0));
        }
        if (warp == 9 && lane < 5) sts32(sb + SM_GV + 520 + lane * 4, dv << 16);
        asm volatile("cp.async.wait_group 0;" ::: "memory");
        if (!hb) bar_arrive(12, 640);
        bar_sync(hb ? 12 : 14, 640);
        if (warp == 9) {
            if (SSM_DELAY) spin(SSM_DELAY);
            if (elect()) {
#pragma unroll
                for (int i = 0; i < SSM_N; i++) {
                    mbar_expect(bars + (BAR_K + i) * 8, 4096);
                    bulk_g2s(sb + sm_k(i) + 32, p.ssmk + (size_t)(chan(i)) * S_, 4096, bars + (BAR_K + i) * 8);
                }
            }
        }
        const uint32_t w0 = prmt(sw.x, sw.z, 0x5410), w1 = prmt(sw.x, sw.z, 0x7632), w2 = prmt(sw.y, sw.w, 0x5410), w3 = prmt(sw.y, sw.w, 0x7632);
        const uint32_t ka = sb + SM_PK + 2592 + blk * 2592 + h * 1280 + pr * 4;
        const uint32_t va = sb + SM_PV + blk * 2592 + h * 1280 + pr * 4;
        uint32_t kk[11], kv[8];
#pragma unroll
        for (int i = 0; i < 11; i++) kk[i] = lds32(ka + (i - 3) * 160 - ((i < 3 && h == 0) ? 32 : 0));
#pragma unroll
        for (int i = 0; i < 8; i++) {
            uint32_t t = badd2(badd2(badd2(bmul2(kk[i], w3), bmul2(kk[i + 1], w2)), bmul2(kk[i + 2], w1)), bmul2(kk[i + 3], w0));
            kv[i] = bmul2(t, lds32(va + i * 160));
        }
        uint4 o0, o1;
        o0.x = prmt(kv[1], kv[0], 0x5410); o0.y = prmt(kv[3], kv[2], 0x5410); o0.z = prmt(kv[5], kv[4], 0x5410); o0.w = prmt(kv[7], kv[6], 0x5410);
        o1.x = prmt(kv[1], kv[0], 0x7632); o1.y = prmt(kv[3], kv[2], 0x7632); o1.z = prmt(kv[5], kv[4], 0x7632); o1.w = prmt(kv[7], kv[6], 0x7632);
        uint4* dst = reinterpret_cast<uint4*>(g_kvT) + ch * 256 + h * 128 + (127 - (8 * pi + blk));
        dst[0] = o0;
        dst[256] = o1;
    }

    const int rho = 8 * rb + j;

    if (wg == 4) {
        asm volatile("setmaxnreg.dec.sync.aligned.u32 32;");
        const unsigned ep1 = __shfl_sync(0xffffffffu, ep0, 0) + 1;
        if (wq == 0) {
            bar_sync(13, 640);
            TSW(39);
            if (lane == 0) flag_release(FL_P + pg);
            __syncwarp();
            TSW(2);
            if (lane < 5) mbar_expect(bars + (BAR_U + lane) * 8, 4096);
            flag_wait(FL_P + pg, ep1 * 16);
            fence_async_global();
            TSW(3);
            if (elect()) {
#pragma unroll
                for (int i = 0; i < 5; i++) {
                    const char* us = (const char*)g_kvT + (size_t)(chan(i)) * 4096;
                    bulk_g2s(sb + sm_u(i), us, 2048, bars + (BAR_U + i) * 8);
                    bulk_g2s(sb + sm_u(i) + U_PLANE, us + 2048, 2048, bars + (BAR_U + i) * 8);
                }
            }
            __syncwarp();
            if (elect()) {
#pragma unroll
                for (int i = SSM_N; i < 5; i++) {
                    mbar_expect(bars + (BAR_K + i) * 8, 4096);
                    bulk_g2s(sb + sm_k(i) + 32, p.ssmk + (size_t)(chan(i)) * S_, 4096, bars + (BAR_K + i) * 8);
                }
                if (WMD2) spin(WMD2);
                if (cta < 120) {
                    mbar_expect(bars + BAR_WM0 * 8, 3 * 8192);
                    mbar_expect(bars + BAR_WM * 8, 2 * 8192);
#pragma unroll 1
                    for (int i = 0; i < 5; i++) tma2d(sb + SM_WM + i * 8192, &maps.wm, cta * 32, i * 128, bars + (i < 3 ? BAR_WM0 : BAR_WM) * 8);
                }
                mbar_wait(bars + (cta < 120 ? BAR_WM0 : BAR_K + 4) * 8, 0);
                bulk_prefetch((const char*)p.q + cta * 20480, 20480);
                bulk_prefetch((const char*)p.w1 + cta * 6400, 6400);
                bulk_prefetch((const char*)p.w2 + cta * 6400, 6400);
            }
            __syncwarp();
        } else {
            bar_arrive(13, 640);
        }
        asm volatile("barrier.cluster.wait.aligned;" ::: "memory");
        uint32_t peer;
        asm volatile("ld.shared::cluster.u32 %0, [%1];" : "=r"(peer) : "r"(mapa(sb + SM_GV + 512, (blockIdx.x & 1) ^ 1)) : "memory");
        const bool paired = peer == (smid ^ 1) && !FORCE_UNPAIRED;
        if (tid == 639) sts32(sb + SM_GV + 516, paired);
        if (cta < 120) {
            float d[4];
            if (tid >= 544 && tid < 624) {
                const int t = tid - 544;
                mbar_wait(bars + BAR_U * 8, 0);
                uint4 cv = __ldg(reinterpret_cast<const uint4*>(p.c) + t);
                auto silu2 = [](uint32_t v) { float a = blo(v), b = bhi(v); return pack2(__fdividef(a, 1.0f + __expf(-a)), __fdividef(b, 1.0f + __expf(-b))); };
#pragma unroll 1
                for (int i = 0; i < 4; i++) { const uint32_t r = silu2(cv.x); cv.x = cv.y; cv.y = cv.z; cv.z = cv.w; cv.w = r; }
                sts128(sb + SM_Y + (t % 40) * 32 + (t / 40) * 16, cv);
                fence_async_smem();
            }
            bar_sync(5, 128);
            mbar_wait(bars + BAR_WM0 * 8, 0);
            mbar_wait(bars + BAR_WM * 8, 0);
            if (wq == 3) TSW(56);
            const uint32_t da = desc_lo(sb + SM_WM, 20480), db = desc_lo(sb + SM_Y, 32);
#pragma unroll 1
            for (int k0 = 0; k0 < 20; k0 += 4) {
                wg_fence();
#pragma unroll
                for (int k = k0; k < k0 + 4; k++) asm volatile("{.reg .pred p; .reg .b32 l,m; .reg .b64 da,db; setp.ne.b32 p,%10,0; add.u32 l,%4,%6; mov.b64 da,{l,%8}; add.u32 m,%5,%7; mov.b64 db,{m,%9};"
                             " wgmma.mma_async.sync.aligned.m64n8k16.f32.bf16.bf16 {%0,%1,%2,%3},da,db,p,1,1,1,0;}"
                             : "+f"(d[0]), "+f"(d[1]), "+f"(d[2]), "+f"(d[3])
                             : "r"(da), "r"(db), "r"(64 * k), "r"(4 * k), "n"(desc_hi(512, 2u)), "n"(desc_hi(128, 0)), "r"(k));
                wg_commit();
            }
            wg_wait<0>();
            reg_fence<4>(d);
            if (c == 0) {
                sts32(sb + SM_GV + (16 * wq + g) * 4, __float_as_uint(wq < 2 ? d[0] : d[1]));
                sts32(sb + SM_GV + (16 * wq + g + 8) * 4, __float_as_uint(wq < 2 ? d[2] : d[3]));
            }
            bar_sync(5, 128);
            if (wq == 2) {
                g_mod[cta * 32 + lane] = __float2bfloat16_rn(__uint_as_float(lds32(sb + SM_GV + lane * 4)) + __uint_as_float(lds32(sb + SM_GV + 128 + lane * 4)));
            }
        }
        if (wq == 2) {
            bar_sync(9, 320);
            if (lane == 0) { flag_release(FL_M); mbar_expect(bars + BAR_MR * 8, 0); }
            __syncwarp();
            TSW(4);
            flag_wait(FL_M, ep1 * 128);
            fence_async_global();
            if (elect()) {
                mbar_expect(bars + BAR_M * 8, 7680);
                bulk_g2s(sb + SM_MOD, g_mod, 7680, bars + BAR_M * 8);
                mbar_wait(bars + BAR_CD * 8, 0);
                mbar_expect(bars + BAR_Y * 8, 12288);
                bulk_g2s(sb + SM_Y, g_yv + rho * 5120, 12288, bars + BAR_Y * 8);
                if (j < 5) {
#pragma unroll 1
                    for (int i = 0; i < 8; i++) bulk_g2s(sb + SM_YT + i * 2560, g_yv + (8 * rb + i) * 5120 + cm * 8, 2048, bars + BAR_XY * 8);
                }
            }
            __syncwarp();
            TSW(60);
#pragma unroll 1
            for (int i = 0; i < 6; i++) {
                bar_sync((0x2186f8 >> (4 * i)) & 15, i ? 288 : 576);
                if (lane == 0) { if (i > 2) TS(53 + (i + 2) % 3); flag_release(FL_R + 16 * i + rb); TS(i < 3 ? 23 + 4 * i : 57 + (i + 2) % 3); }
                __syncwarp();
            }
            if (lane == 0) p.epoch[smid] = ep1;
            return;
        }
        if (wq == 1) {
            bar_sync(9, 320);
            mbar_wait(bars + BAR_MR * 8, 0);
            if (lane < 4 * NB) mbar_arrive_cl(mapa(bars + (BAR_EB + (lane >> 2)) * 8, paired ? lane & 1 : blockIdx.x & 1));
        }
        if (wq == 3) {
            bar_sync(7, 544);
            if (lane == 0) { flag_release(FL_C); mbar_expect(bars + BAR_CD * 8, 0); TS(20); }
            __syncwarp();
            if (lane == 0) mbar_expect(bars + BAR_Y2 * 8, 8192);
            flag_wait(FL_C, ep1 * 128);
            fence_async_global();
            TSW(21);
            if (elect()) {
                bulk_g2s(sb + SM_Y + 12288, g_yv + rho * 5120 + 3072, 8192, bars + BAR_Y2 * 8);
            }
            __syncwarp();
        }
        if (wq == 3) {
            mbar_wait(bars + BAR_Y2 * 8, 0);
            if (elect()) {
                mbar_expect(bars + BAR_XY * 8, 20480);
#pragma unroll 1
                for (int i = 0; i < 8; i++) {
                    if (j >= 5) bulk_g2s(sb + SM_YT + i * 2560, g_yv + (8 * rb + i) * 5120 + cm * 8, 2048, bars + BAR_XY * 8);
                    bulk_g2s(sb + SM_YT + i * 2560 + 2048, g_yv + (8 * rb + i) * 5120 + cr * 8, 512, bars + BAR_XY * 8);
                }
            }
            __syncwarp();
            bar_sync(8, 576);
            mbar_wait_warm(bars + BAR_FA * 8, 0);
            mbar_wait(bars + BAR_ME * 8, 0);
            mbar_wait_warm(bars + (BAR_FA + 11 % NA) * 8, (11 / NA) & 1);
            flag_wait(FL_CS, ep1 * 4);
            fence_async_global();
            if (elect()) {
                mbar_expect(bars + BAR_CS * 8, 864);
                bulk_g2s(sb + SM_CS, g_cs + 64 * j, 256, bars + BAR_CS * 8);
                bulk_g2s(sb + SM_CS + 256, g_cs + 512 + RA3 * j, 4 * RA3, bars + BAR_CS * 8);
                bulk_g2s(sb + SM_CS + 256 + 4 * RA3, g_cs + HB0 + 64 * j, 256, bars + BAR_CS * 8);
                bulk_g2s(sb + SM_CS + 512 + 4 * RA3, g_cs + HB0 + 512 + RB3 * j, 4 * RB3, bars + BAR_CS * 8);
            }
            __syncwarp();
            mbar_wait(bars + BAR_ME * 8, 1);
            mbar_wait_warm(bars + (BAR_FA + 21 % NA) * 8, (21 / NA) & 1);
#pragma unroll 1
            for (int i = 0; i < 3; i++) {
                if (i) {
                    mbar_wait(bars + BAR_ME * 8, (i + 1) & 1);
                    for (int n = i; n < 5; n++) { spin(PING); n += tensor_ping(); }
                }
                flag_wait(FL_G + 16 * i + rb, ep1 * 8);
                if (lane == 0) { mbar_expect(bars + (BAR_G + i) * 8, 0); TS(35 + (i + 2) % 3); }
                __syncwarp();
            }
            return;
        }
        if (elect()) {
            if (wq == 1) {
                Ring<NB, SM_RB, BAR_FB, BAR_EB> r{sb, 0, 0};
#pragma unroll 1
                for (int ph = 0; ph < 7; ph++) {
                    const CUtensorMap* ma = ph == 0 ? &maps.w1a : ph == 1 ? &maps.w2a : ph == 6 ? &maps.w4a : &maps.w3a;
                    const bool b3b = ph == 2 || ph == 4 || ph == 5;
                    r.runw(paired, idx & 1, ma, ma + (b3b ? 2 : 1), ph == 3 ? 64 * j : b3b ? HB0 + 64 * j : cm,
                           ph == 3 ? 512 + RA3 * j : b3b ? HB0 + 512 + RB3 * j : cr, ph == 4 ? 10 - NA : ph == 5 ? 1 : 0,
                           ph == 6 ? 27 : ph == 5 ? 10 - NA : ph == 2 ? 1 : 10, ph == 0 ? 0 : ph == 6 ? HB0 / 64 + j : cm >> 6,
                           ph == 3 ? 8192 + 128 * RA3 : b3b ? 8192 + 128 * RB3 : 10240,
                           ph == 0 ? GATE0 : ph == 1 ? GATE : ph == 3 ? GATE - 1 : -1, bars + (ph == 0 ? BAR_Y2 : BAR_ST - (ph == 1)) * 8);
                }
            } else {
                Ring<NA, SM_RA, BAR_FA, BAR_EA> r{sb, 0, 0};
                if (cta >= 120) mbar_wait(bars + (BAR_K + 4) * 8, 0);
                mbar_expect(bars + BAR_XR * 8, 20480);
                bulk_g2s(sb + SM_XR, p.q + (size_t)rho * 16 * D_, 20480, bars + BAR_XR * 8);
                mbar_expect(bars + BAR_XY * 8, 20480);
                tma2d(sb + SM_XT, &maps.xa, cm, rb * 128, bars + BAR_XY * 8);
                tma2d(sb + SM_XT2, &maps.xb, cr, rb * 128, bars + BAR_XY * 8);
                const int grp = j >> 1;
                const int delta = (grp & 1 ? 1 : -1) * (1 + (grp >> 1));
                const int nb = min(max(rb + (delta > 0 ? 1 : -1), 0), 15);
                uint32_t fb = r.acquire(SLOT), dst = r.slot();
                flag_wait2(FL_R + nb, FL_R + rb, ep1 * 8);
                fence_async_global();
                tma2d(dst, &maps.hn, 0, rb * 128 + delta, fb);
                TS(24);
                r.next();
                r.run2d(&maps.hn, rb * 128 + delta);
#pragma unroll 1
                for (int ph = 0; ph < 5; ph++) {
                    const char* src = ph == 0 ? (const char*)g_h1 + rb * 163840 : ph < 3 ? (const char*)g_x1 + rb * 163840 : (const char*)g_g + rb * 442368;
                    const int own = ph < 3 ? cm >> 6 : HB0 / 64 + j;
                    if (ph != 2 && ph != 4) { r.acquire(0); r.next(); }
                    const int i0 = ph == 4 ? 1 + HB0 / 64 : 1;
                    const char* src1 = src + r.korder(i0, own) * SLOT;
                    if (ph > 2) mbar_wait(bars + (BAR_G - 2 + ph) * 8, 0);
                    fb = r.acquire(SLOT); dst = r.slot();
                    if (ph < 2) flag_wait(FL_B1 + 16 * ph + rb, ep1 * 8);
                    fence_async_global();
                    bulk_g2s(dst, src1, SLOT, fb);
                    if (ph < 2) { TS(28 + 4 * ph); mbar_expect(bars + (BAR_ST - 1 + ph) * 8, 0); }
                    r.next();
                    r.run1d(src, i0 + 1, ph < 2 ? 10 : ph == 2 ? 10 - NA : ph == 3 ? 1 + HB0 / 64 : 27, own);
                }
            }
        }
        return;
    }
    bar_arrive(13, 640);
    asm volatile("setmaxnreg.inc.sync.aligned.u32 112;");
    const int rrow = 16 * rho + (warp >> 1) + 8 * (warp & 1);

    fence_async_smem();
    bar_sync(1 + wg, 128);
#pragma unroll 1
    for (int cc = wg; cc < wg + 1 + (wg == 3); cc++) {
        mbar_wait(bars + (BAR_K + cc) * 8, 0);
        if (cc == 2 && wq == 0) TSW(40);
        uint32_t a = sb + sm_k(cc) + 32 + (tid & 127) * 32;
        uint32_t pw = lds32(a - 4);
        uint4 x = lds128(a), y = lds128(a + 16), o;
        if ((tid & 127) == 0) {
            uint16_t k0 = __bfloat16_as_ushort(__float2bfloat16_rn(blo(x.x) + __uint_as_float(lds32(sb + SM_GV + 520 + cc * 4))));
            x.x = (x.x & 0xffff0000u) | k0;
            sts16(a, k0);
        }
        o.x = prmt(pw, x.x, 0x5432); o.y = prmt(x.x, x.y, 0x5432); o.z = prmt(x.y, x.z, 0x5432); o.w = prmt(x.z, x.w, 0x5432);
        sts128(a + 4160, o);
        o.x = prmt(x.w, y.x, 0x5432); o.y = prmt(y.x, y.y, 0x5432); o.z = prmt(y.y, y.z, 0x5432); o.w = prmt(y.z, y.w, 0x5432);
        sts128(a + 4176, o);
    }
    bar_sync(1 + wg, 128);
    if (wg == 3) bar_arrive(11, 256);
#pragma unroll 1
    for (int cc = wg; cc < 5; cc += 3) {
        if (cc == 3 && wg == 0) break;
        if (cc == 4) bar_sync(11, 256);
        const uint32_t kaddr = sb + sm_k(cc) + ((g & 1) ? 32 : 4192) + 4 * ((g >> 1) - c) + 64 * wq;
        const AFrag f0 = ldA(kaddr), f1 = ldA(kaddr + 256);
        if (STAG && cc == 3) bar_sync(12, 256);
        mbar_wait(bars + (BAR_U + cc) * 8, 0);
        if (wq == 0) TSW(5 + cc);
        float d[64];
        conv_two<0>(d, f0, f1, kaddr, desc_lo(sb + sm_u(cc), U_PLANE), sb + sm_red(cc) + wq * 4352 + g * 544 + c * 8, cc == 1);
        if (wq == 0) TSW(10 + cc);
        if (cc == 1) bar_arrive(6, 256);
    }
#pragma unroll 1
    for (int cc = wg == 1 ? 4 : wg;; cc++) {
        if (cc == 1) bar_sync(6, 256); else bar_sync(1 + wg, 128);
        const int ch = chan(cc);
        uint32_t* dst = g_yv + ch * 8 + ((g + (ch >> 2)) & 7) + (126 - 32 * wq - 2 * c) * 5120;
        uint2 v[16];
#pragma unroll
        for (int i = 0; i < 16; i++) v[i] = lds64(sb + sm_red(cc) + g * 544 + wq * 128 + c * 8 + (i >> 2) * 32 + (i & 3) * 4360);
#pragma unroll
        for (int w = 1; w < 4; w++)
            if (wq == 3 && c > 3 - w) v[12 + w] = make_uint2(0, 0);
#pragma unroll
        for (int q = 0; q < 4; q++) {
            const uint2* u = v + 4 * q;
            dst[-8 * q * 5120] = badd2(u[0].x, badd2(u[1].x, badd2(u[2].x, u[3].x)));
            dst[(-8 * q + 1) * 5120] = badd2(u[0].y, badd2(u[1].y, badd2(u[2].y, u[3].y)));
        }
        if (wq == 0) TSW(15 + cc);
        if (cc != 0) break;
    }
    fence_async_smem();
    if (!(wg & 1)) bar_arrive(9, 320);
    bar_arrive(7, 544);

    const uint32_t one2 = 0x3f803f80u;
    const unsigned ones = p.ones;
    {
        uint32_t x[10], a[10], cb[10], sbv[10];
        bar_sync(10, 512);
        mbar_wait(bars + BAR_XR * 8, 0);
#pragma unroll
        for (int i = 0; i < 10; i++) x[i] = lds32(sb + SM_XR + (rrow & 15) * 1280 + lane * 4 + i * 128);
        const uint2 s1 = row_stats<0>(x, lane);
        const int up = lane >> 4, gg = warp >> 1, e = warp & 1;
        const uint32_t ya = sb + SM_Y + lane * 64 + ((gg + (lane >> 1)) & 7) * 4;
        const uint32_t sel = (up ? 0x1054u : 0x5410u) + (e ? 0x2222u : 0u);
        const uint32_t ma = sb + SM_MOD + lane * 4;
        mbar_wait(bars + BAR_M * 8, 0);
        uint32_t pin = 0;
#pragma unroll
        for (int i = 0; i < 10; i++) {
            uint32_t h = bfma2(ln_apply(x[i], s1.x, s1.y), badd2(lds32(ma + 1280 + i * 128), one2), lds32(ma + i * 128));
            a[i] = bmul2(h, lds32(ma + 2560 + i * 128));
            sbv[i] = lds32(ma + 3840 + i * 128);
            cb[i] = badd2(lds32(ma + 5120 + i * 128), one2);
            pin ^= a[i] ^ cb[i];
        }
        if (pin & ~ones) sts32(sb + SM_GV, pin);
        if (warp == 4) TSW(52);
        mbar_wait(bars + BAR_Y * 8, 0);
        RowSum part;
#pragma unroll
        for (int i = 0; i < 10; i++) {
            if (i == 6) {
                if ((__float_as_uint(part.s + part.s_ + part.q + part.q_) & ~ones)) sts32(sb + SM_GV, pin);
                mbar_wait(bars + BAR_Y2 * 8, 0);
                if (warp == 0) TSW(22);
            }
            uint32_t y0 = lds32(ya + i * 2048 + up * 32), y1 = lds32(ya + i * 2048 + (up ^ 1) * 32);
            x[i] = bfma2(a[i], prmt(y0, y1, sel), x[i]);
            if (i < 6) part.add(x[i]);
        }
        const uint2 s2 = row_stats<6>(x, lane, part);
#pragma unroll
        for (int i = 0; i < 10; i++) x[i] = bfma2(ln_apply(x[i], s2.x, s2.y), cb[i], sbv[i]);
        const uint2 s3 = row_stats<0>(x, lane);
        uint32_t* o = reinterpret_cast<uint32_t*>(g_hn + (size_t)rrow * D_) + lane;
#pragma unroll
        for (int i = 0; i < 10; i++) o[32 * i] = ln_apply(x[i], s3.x, s3.y);
        if (lane < 2) g_rs[rrow * 2 + lane] = make_uint4(s1.x, s1.y, s2.x, s2.y);
        if (warp == 0) TSW(34);
        bar_arrive(8, 576);
    }

    const int half = wg & 1;
    const int row = 64 * half + 16 * wq + g;
    const int tw0 = (rb * 80 + (cm >> 3)) * 512 + row * 4 + c, tw1 = (rb * 80 + (cr >> 3) - 8) * 512 + row * 4 + c;
    const uint32_t park = sb + SM_Y + (tid & 255) * 16;
    const uint32_t ms0 = sb + SM_MOD + (cm + 2 * c) * 2, ms1 = sb + SM_MOD + (cr - 64 + 2 * c) * 2;
    if (wg >= 2) {
        {
            float acc[40];
            gemm_loop<80, true, 10, 10, true>(acc, sb, half, 0, 0, 10, 0, 25);
            if (tid == 256) mbar_expect(bars + BAR_ME * 8, 0);
#pragma unroll
            for (int k = 0; k < 10; k += CH) CHUNK(k) {
#pragma unroll
                for (int q = k; q < k + CH && q < 10; q++) {
                    uint32_t* dst = reinterpret_cast<uint32_t*>(g_h1) + (q < 8 ? tw0 : tw1);
                    const uint32_t u = gelu2_h(bmul2(pack2(acc[4 * q], acc[4 * q + 1]), 0x3f003f00u));
                    const uint32_t v = gelu2_h(bmul2(pack2(acc[4 * q + 2], acc[4 * q + 3]), 0x3f003f00u));
                    dst[q * 512] = u;
                    dst[q * 512 + 32] = v;
                    acc[4 * q] = __uint_as_float(u); acc[4 * q + 1] = __uint_as_float(v);
                }
            }
            bar_arrive(15, 288);
            mbar_wait(bars + (BAR_FA + 10 % NA) * 8, (10 / NA) & 1);
#pragma unroll
            for (int q = 0; q < 8; q++) {
                sts32(sb + SM_RA + (10 % NA) * SLOT + q * 2048 + row * 16 + c * 4, __float_as_uint(acc[4 * q]));
                sts32(sb + SM_RA + (10 % NA) * SLOT + q * 2048 + row * 16 + c * 4 + 128, __float_as_uint(acc[4 * q + 1]));
            }
            fence_async_smem();
            bar_arrive(14, 512);
        }
        gemm3<0>(sb, rb, j, half, row, c, ones);
        {
            float acc[40];
            uint32_t gbv[10], base[20];
#pragma unroll
            for (int q = 0; q < 10; q++) gbv[q] = lds32((q < 8 ? ms0 : ms1) + 6400 + q * 16);
#pragma unroll
            for (int q = 0; q < 5; q++) { const uint4 t = lds128(park + q * 4096); base[4 * q] = t.x; base[4 * q + 1] = t.y; base[4 * q + 2] = t.z; base[4 * q + 3] = t.w; }
            gemm_loop<80, false, 27, 27 - NB, true>(acc, sb, half, 39 - NA, 40, 27 - NA, 11, 42);
            auto fin = [&](int q, int r) {
                return bfma2(gbv[q], pack2(acc[4 * q + 2 * r], acc[4 * q + 2 * r + 1]), base[2 * q + r]);
            };
            auto tr4 = [&](uint32_t t0, uint32_t t1, uint32_t t2, uint32_t t3) {
                const bool o1 = c & 1, o2 = c & 2;
                uint32_t a = __shfl_xor_sync(0xffffffffu, o1 ? t0 : t1, 1), b = __shfl_xor_sync(0xffffffffu, o1 ? t2 : t3, 1);
                uint32_t u0 = o1 ? a : t0, u1 = o1 ? t1 : a, u2 = o1 ? b : t2, u3 = o1 ? t3 : b;
                a = __shfl_xor_sync(0xffffffffu, o2 ? u0 : u2, 2); b = __shfl_xor_sync(0xffffffffu, o2 ? u1 : u3, 2);
                return o2 ? make_uint4(a, b, u2, u3) : make_uint4(u0, u1, a, b);
            };
            bf16* go = p.out + (size_t)(rb * 128 + row) * D_;
#pragma unroll
            for (int k = 0; k < 2; k++) CHUNK(k) {
#pragma unroll
                for (int r = 0; r < 2; r++)
                    *reinterpret_cast<uint4*>(go + r * 8 * D_ + cm + 32 * k + 8 * c) = tr4(fin(4 * k, r), fin(4 * k + 1, r), fin(4 * k + 2, r), fin(4 * k + 3, r));
            }
            CHUNK(2) *reinterpret_cast<uint4*>(go + (c >> 1) * 8 * D_ + cr + 8 * (c & 1)) = tr4(fin(8, 0), fin(9, 0), fin(8, 1), fin(9, 1));
            if (tid == 256) TS(44);
            if (warp == 8) TSFLUSH();
        }
    } else {
        {
            float acc[40];
            uint32_t x2[20];
            {
                uint32_t y[20];
                mbar_wait(bars + BAR_XY * 8, 0);
                const uint32_t xa = sb + SM_XT + row * 128 + c * 4, xb = sb + SM_XT2 + row * 32 + c * 4;
                const uint32_t ya = sb + SM_YT + (4 * half + wq) * 2560 + c * 64;
#pragma unroll
                for (int q = 0; q < 10; q++) {
                    const uint32_t a = q < 8 ? xa + ((q ^ g) << 4) : xb + (q - 8) * 16;
                    x2[2 * q] = lds32(a); x2[2 * q + 1] = lds32(a + (q < 8 ? 1024 : 256));
                    const int pos = (g + ((q < 8 ? cm : cr) >> 2) + 2 * q + (c >> 1)) & 7;
                    y[2 * q] = lds32(ya + q * 256 + pos * 4); y[2 * q + 1] = lds32(ya + q * 256 + 32 + pos * 4);
                }
                fence_async_smem();
                bar_sync(1 + wg, 128);
                if ((tid & 127) < NA) mbar_arrive_cl(mapa(bars + (BAR_EA + (tid & 127)) * 8, blockIdx.x & 1));
                mbar_wait(bars + (BAR_FA + 1) * 8, 0);
                const uint4* rp = g_rs + (rb * 128 + row) * 2;
                const uint4 ra = ldcg128(rp), rc = ldcg128(rp + 16);
                bar_sync(14, 512);
#pragma unroll
                for (int q = 0; q < 10; q++) {
                    const uint32_t ms = q < 8 ? ms0 : ms1;
                    const uint32_t sa = lds32(ms + 16 * q), ca = badd2(lds32(ms + 1280 + 16 * q), one2), ga = lds32(ms + 2560 + 16 * q);
                    const uint32_t sbv = lds32(ms + 3840 + 16 * q), cb = badd2(lds32(ms + 5120 + 16 * q), one2);
                    uint32_t u = x2[2 * q], v = x2[2 * q + 1];
                    u = bfma2(bmul2(bfma2(ln_apply(u, ra.x, ra.y), ca, sa), ga), prmt(y[2 * q], y[2 * q + 1], 0x5410), u);
                    v = bfma2(bmul2(bfma2(ln_apply(v, rc.x, rc.y), ca, sa), ga), prmt(y[2 * q], y[2 * q + 1], 0x7632), v);
                    x2[2 * q] = u; x2[2 * q + 1] = v;
                    u = bfma2(ln_apply(u, ra.z, ra.w), cb, sbv);
                    v = bfma2(ln_apply(v, rc.z, rc.w), cb, sbv);
                    acc[4 * q] = blo(u); acc[4 * q + 1] = bhi(u); acc[4 * q + 2] = blo(v); acc[4 * q + 3] = bhi(v);
                }
            }
            reg_fence<40>(acc);
            if (tid == 0) TS(45);
            gemm_loop<80, false, 10, 10, false>(acc, sb, half, 10, 10, 10, 0, 29);
            if (tid == 0) mbar_expect(bars + BAR_ME * 8, 0);
            uint32_t x1[20];
            float s0 = 0.f, q0 = 0.f, s1 = 0.f, q1 = 0.f;
#pragma unroll
            for (int q = 0; q < 10; q++) {
                uint32_t u = pack2(acc[4 * q], acc[4 * q + 1]);
                uint32_t v = pack2(acc[4 * q + 2], acc[4 * q + 3]);
                uint32_t* dst = reinterpret_cast<uint32_t*>(g_x1) + (q < 8 ? tw0 : tw1);
                dst[q * 512] = u;
                dst[q * 512 + 32] = v;
                x1[2 * q] = u; x1[2 * q + 1] = v;
            }
            bar_arrive(6, 288);
            CHUNK(0)
#pragma unroll
            for (int q = 0; q < 10; q++) {
                float a = blo(x1[2 * q]), b = bhi(x1[2 * q]), e = blo(x1[2 * q + 1]), f = bhi(x1[2 * q + 1]);
                s0 += a + b; q0 = fmaf(a, a, fmaf(b, b, q0));
                s1 += e + f; q1 = fmaf(e, e, fmaf(f, f, q1));
            }
#pragma unroll
            for (int m = 1; m <= 2; m <<= 1) {
                s0 += __shfl_xor_sync(0xffffffffu, s0, m); q0 += __shfl_xor_sync(0xffffffffu, q0, m);
                s1 += __shfl_xor_sync(0xffffffffu, s1, m); q1 += __shfl_xor_sync(0xffffffffu, q1, m);
            }
            if (c < 2) g_st[(rb * 8 + j) * 128 + row + 8 * c] = c ? make_float2(s1, q1) : make_float2(s0, q0);
            bar_arrive(8, 288);
            mbar_wait(bars + (BAR_FA + 20 % NA) * 8, (20 / NA) & 1);
#pragma unroll
            for (int q = 0; q < 8; q++) {
                sts32(sb + SM_RA + (20 % NA) * SLOT + q * 2048 + row * 16 + c * 4, x1[2 * q]);
                sts32(sb + SM_RA + (20 % NA) * SLOT + q * 2048 + row * 16 + c * 4 + 128, x1[2 * q + 1]);
            }
            fence_async_smem();
            bar_sync(3 + wg, 128);
#pragma unroll
            for (int q = 0; q < 5; q++) {
                const uint32_t ms = q < 4 ? ms0 : ms1;
                const uint32_t g0 = lds32(ms + 6400 + q * 32), g1 = lds32(ms + 6400 + q * 32 + 16);
                sts128(park + q * 4096, make_uint4(bfma2(g0, x1[4 * q], x2[4 * q]), bfma2(g0, x1[4 * q + 1], x2[4 * q + 1]),
                                                   bfma2(g1, x1[4 * q + 2], x2[4 * q + 2]), bfma2(g1, x1[4 * q + 3], x2[4 * q + 3])));
            }
        }
        gemm3<1>(sb, rb, j, half, row, c, ones);
    }
}

typedef CUresult (*EncFn)(CUtensorMap*, CUtensorMapDataType, cuuint32_t, void*, const cuuint64_t*, const cuuint64_t*,
                          const cuuint32_t*, const cuuint32_t*, CUtensorMapInterleave, CUtensorMapSwizzle,
                          CUtensorMapL2promotion, CUtensorMapFloatOOBfill);

void make_map(EncFn enc, CUtensorMap* m, const void* base, uint64_t inner, uint64_t outer, uint32_t bi, uint32_t bo,
              CUtensorMapSwizzle swz = CU_TENSOR_MAP_SWIZZLE_128B) {
    cuuint64_t dims[2] = {inner, outer};
    cuuint64_t st[1] = {inner * 2};
    cuuint32_t box[2] = {bi, bo};
    cuuint32_t es[2] = {1, 1};
    enc(m, CU_TENSOR_MAP_DATA_TYPE_BFLOAT16, 2, const_cast<void*>(base), dims, st, box, es, CU_TENSOR_MAP_INTERLEAVE_NONE,
        swz, CU_TENSOR_MAP_L2_PROMOTION_NONE, CU_TENSOR_MAP_FLOAT_OOB_FILL_NONE);
}

}

extern "C" void kernel_launch(void* const* d_in, const int* in_sizes, int n_in, void* d_out, int out_size) {
    (void)in_sizes; (void)n_in; (void)out_size;
    Params p;
    p.q = (const bf16*)d_in[0]; p.k = (const bf16*)d_in[1]; p.v = (const bf16*)d_in[2];
    p.shift = (const bf16*)d_in[3]; p.ssmk = (const bf16*)d_in[4]; p.ssmD = (const bf16*)d_in[5];
    p.w1 = (const bf16*)d_in[7]; p.w2 = (const bf16*)d_in[8]; p.w3 = (const bf16*)d_in[9]; p.w4 = (const bf16*)d_in[10];
    p.c = (const bf16*)d_in[11]; p.wmod = (const bf16*)d_in[12];
    p.out = (bf16*)d_out;
    p.ones = 0xffffffffu;
    cudaGetSymbolAddress((void**)&p.epoch, g_epoch);

    void* fn = nullptr;
    cudaDriverEntryPointQueryResult qr;
    cudaGetDriverEntryPoint("cuTensorMapEncodeTiled", &fn, cudaEnableDefault, &qr);
    EncFn enc = (EncFn)fn;
    void* hn = nullptr;
    cudaGetSymbolAddress(&hn, g_hn);
    Maps maps;
    make_map(enc, &maps.w3s, p.w3, F_, D_, 216, 64, CU_TENSOR_MAP_SWIZZLE_NONE);
    make_map(enc, &maps.wm, p.wmod, 6 * D_, D_, 32, 128, CU_TENSOR_MAP_SWIZZLE_64B);
    make_map(enc, &maps.xa, p.q, D_, S_, 64, 128);
    make_map(enc, &maps.xb, p.q, D_, S_, 16, 128, CU_TENSOR_MAP_SWIZZLE_NONE);
    make_map(enc, &maps.hn, hn, D_, S_, 64, 128);
    make_map(enc, &maps.w1a, p.w1, D_, D_, 64, 64);
    make_map(enc, &maps.w1b, p.w1, D_, D_, 16, 64);
    make_map(enc, &maps.w2a, p.w2, D_, D_, 64, 64);
    make_map(enc, &maps.w2b, p.w2, D_, D_, 16, 64);
    make_map(enc, &maps.w3a, p.w3, F_, D_, 64, 64);
    make_map(enc, &maps.w3b, p.w3, F_, D_, RA3, 64);
    make_map(enc, &maps.w3c, p.w3, F_, D_, RB3, 64);
    make_map(enc, &maps.w4a, p.w4, D_, F_, 64, 64);
    make_map(enc, &maps.w4b, p.w4, D_, F_, 16, 64);
    cudaFuncSetAttribute(fused_kernel, cudaFuncAttributeMaxDynamicSharedMemorySize, SMEM_BYTES);
    fused_kernel<<<132, NTHREADS, SMEM_BYTES>>>(p, maps);
}
```

```cpp
#include <cuda_runtime.h>
#include <cuda_bf16.h>
#include <cuda.h>
#include <stdint.h>
#include <string.h>

#define SEED 1
#define CH 2
#define STAG 12
#define CH3 4
#define GATE 5
#define SSM_DELAY 100
#define B_DELAY 220
#define PING 250
#define FORCE_UNPAIRED 0
#define GATE0 1
#define SPD 800
#define WMD2 600
#define TAGST 1
#define SSM_N 3

namespace {

typedef __nv_bfloat16 bf16;
typedef __nv_bfloat162 bf162;

constexpr int S_ = 2048, D_ = 640, F_ = 1728;
constexpr int NTHREADS = 640;
constexpr int NA = 6, NB = 6;
constexpr int SLOT = 16384;
constexpr int RA3 = 48, RB3 = 40, HB0 = 896;
constexpr int SM_RA = 0, SM_RB = NA * SLOT;

static_assert(NA == 6, "smem map");
constexpr int RED_STRIDE = 17536;
constexpr int K_STRIDE = 8320;
constexpr int U_PLANE = 2560, U_STRIDE = 5120;
constexpr int SM_Y = 12 * SLOT;
__device__ __forceinline__ int sm_red(int cc) { return cc * RED_STRIDE + (cc < 3 ? SM_RB : -3 * RED_STRIDE); }
__device__ __forceinline__ int sm_k(int cc) { return cc * K_STRIDE + (cc < 3 ? SM_RB + 3 * RED_STRIDE : 2 * RED_STRIDE - 3 * K_STRIDE); }
__device__ __forceinline__ int sm_u(int cc) { return cc * U_STRIDE + (cc < 3 ? SM_RB + 3 * RED_STRIDE + 3 * K_STRIDE : SM_Y + 8192 - 3 * U_STRIDE); }
constexpr int SM_PK = SM_RB;
constexpr int SM_PV = SM_RB + 24576;
constexpr int SM_WM = 57344;
constexpr int SM_XT = SM_WM, SM_XT2 = SM_WM + 16384, SM_XR = SM_WM + 20480;
constexpr int SM_YT = 0;
constexpr int SM_MOD = SM_Y + 20480;
constexpr int SM_GV = SM_MOD + 7680;
constexpr int SM_CS = SM_GV + 1024;
constexpr int SM_RP = SM_CS + 1024;
constexpr int SM_BAR = SM_RP + 1024;
constexpr int SM_PROF = SM_BAR + 512;
constexpr int SM_TOTAL = SM_PROF + 512;
constexpr int SMEM_BYTES = SM_TOTAL + 1024;
static_assert(SMEM_BYTES <= 232448, "smem");

constexpr int BAR_FA = 0, BAR_FB = NA, BAR_EA = 12, BAR_EB = 12 + NA, BAR_K = 24, BAR_U = 29, BAR_Y = 34, BAR_CS = 35, BAR_WM = 36, BAR_M = 37, BAR_XY = 38, BAR_Y2 = 39, BAR_G = 40, BAR_ST = 44, BAR_XR = 45, BAR_ME = 46, BAR_CD = 47, BAR_WM0 = 48, BAR_MR = 49, NBARS = 50;

__device__ __align__(1024) bf16 g_kvT[D_ * S_];
__device__ __align__(1024) uint32_t g_yv[128 * 5120];
__device__ __align__(1024) bf16 g_mod[6 * D_];
__device__ __align__(1024) bf16 g_hn[S_ * D_];
__device__ __align__(1024) uint4 g_rs[S_ * 2];
__device__ __align__(1024) bf16 g_h1[S_ * D_];
__device__ __align__(1024) bf16 g_x1[S_ * D_];
__device__ __align__(1024) bf16 g_g[S_ * F_];
__device__ __align__(1024) uint4 g_st[S_ * 8];
__device__ __align__(1024) float g_cs[F_];
__device__ __align__(1024) unsigned g_flags[128 * 32];
__device__ __align__(1024) unsigned g_epoch[160];
constexpr int FL_P = 0, FL_C = 8, FL_CS = 9, FL_M = 10, FL_R = 16, FL_B1 = 32, FL_B2 = 48, FL_G = 64;

#define TS(i) do {} while (0)
#define TSW(i) do {} while (0)
#define TSD(i, dep) do {} while (0)
#define TSD2(i, dep) do {} while (0)
#define TSFLUSH() do {} while (0)

struct Params {
    const bf16 *q, *k, *v, *shift, *ssmk, *ssmD, *w1, *w2, *w3, *w4, *c, *wmod;
    bf16* out;
    unsigned* epoch;
    unsigned ones;
};
#define CHUNK(k) if (ones & (1u << (k)))
struct Maps { CUtensorMap hn, w1a, w1b, w2a, w2b, w3a, w3b, w3c, w4a, w4b, wm, xa, xb, w3s; };

template<int N> struct WgRs;
template<int N> struct WgSs;
template<> struct WgRs<32> { template<int OFF,int HI,int SC> static __device__ __forceinline__ void run(float* d,uint32_t a0,uint32_t a1,uint32_t a2,uint32_t a3,uint32_t blo){
 asm volatile("{.reg .b32 l; .reg .b64 db; add.u32 l,%20,%21; mov.b64 db,{l,%22}; wgmma.mma_async.sync.aligned.m64n32k16.f32.bf16.bf16 {%0,%1,%2,%3,%4,%5,%6,%7,%8,%9,%10,%11,%12,%13,%14,%15},{%16,%17,%18,%19},db,%23,1,1,0;}"
 :"+f"(d[0]),"+f"(d[1]),"+f"(d[2]),"+f"(d[3]),"+f"(d[4]),"+f"(d[5]),"+f"(d[6]),"+f"(d[7]),"+f"(d[8]),"+f"(d[9]),"+f"(d[10]),"+f"(d[11]),"+f"(d[12]),"+f"(d[13]),"+f"(d[14]),"+f"(d[15])
 :"r"(a0),"r"(a1),"r"(a2),"r"(a3),"r"(blo),"n"(OFF),"n"(HI),"n"(SC)); } };
template<> struct WgRs<48> { template<int OFF,int HI,int SC> static __device__ __forceinline__ void run(float* d,uint32_t a0,uint32_t a1,uint32_t a2,uint32_t a3,uint32_t blo){
 asm volatile("{.reg .b32 l; .reg .b64 db; add.u32 l,%28,%29; mov.b64 db,{l,%30}; wgmma.mma_async.sync.aligned.m64n48k16.f32.bf16.bf16 {%0,%1,%2,%3,%4,%5,%6,%7,%8,%9,%10,%11,%12,%13,%14,%15,%16,%17,%18,%19,%20,%21,%22,%23},{%24,%25,%26,%27},db,%31,1,1,0;}"
 :"+f"(d[0]),"+f"(d[1]),"+f"(d[2]),"+f"(d[3]),"+f"(d[4]),"+f"(d[5]),"+f"(d[6]),"+f"(d[7]),"+f"(d[8]),"+f"(d[9]),"+f"(d[10]),"+f"(d[11]),"+f"(d[12]),"+f"(d[13]),"+f"(d[14]),"+f"(d[15]),"+f"(d[16]),"+f"(d[17]),"+f"(d[18]),"+f"(d[19]),"+f"(d[20]),"+f"(d[21]),"+f"(d[22]),"+f"(d[23])
 :"r"(a0),"r"(a1),"r"(a2),"r"(a3),"r"(blo),"n"(OFF),"n"(HI),"n"(SC)); } };
template<> struct WgRs<64> { template<int OFF,int HI,int SC> static __device__ __forceinline__ void run(float* d,uint32_t a0,uint32_t a1,uint32_t a2,uint32_t a3,uint32_t blo){
 asm volatile("{.reg .b32 l; .reg .b64 db; add.u32 l,%36,%37; mov.b64 db,{l,%38}; wgmma.mma_async.sync.aligned.m64n64k16.f32.bf16.bf16 {%0,%1,%2,%3,%4,%5,%6,%7,%8,%9,%10,%11,%12,%13,%14,%15,%16,%17,%18,%19,%20,%21,%22,%23,%24,%25,%26,%27,%28,%29,%30,%31},{%32,%33,%34,%35},db,%39,1,1,0;}"
 :"+f"(d[0]),"+f"(d[1]),"+f"(d[2]),"+f"(d[3]),"+f"(d[4]),"+f"(d[5]),"+f"(d[6]),"+f"(d[7]),"+f"(d[8]),"+f"(d[9]),"+f"(d[10]),"+f"(d[11]),"+f"(d[12]),"+f"(d[13]),"+f"(d[14]),"+f"(d[15]),"+f"(d[16]),"+f"(d[17]),"+f"(d[18]),"+f"(d[19]),"+f"(d[20]),"+f"(d[21]),"+f"(d[22]),"+f"(d[23]),"+f"(d[24]),"+f"(d[25]),"+f"(d[26]),"+f"(d[27]),"+f"(d[28]),"+f"(d[29]),"+f"(d[30]),"+f"(d[31])
 :"r"(a0),"r"(a1),"r"(a2),"r"(a3),"r"(blo),"n"(OFF),"n"(HI),"n"(SC)); } };
template<> struct WgRs<80> { template<int OFF,int HI,int SC> static __device__ __forceinline__ void run(float* d,uint32_t a0,uint32_t a1,uint32_t a2,uint32_t a3,uint32_t blo){
 asm volatile("{.reg .b32 l; .reg .b64 db; add.u32 l,%44,%45; mov.b64 db,{l,%46}; wgmma.mma_async.sync.aligned.m64n80k16.f32.bf16.bf16 {%0,%1,%2,%3,%4,%5,%6,%7,%8,%9,%10,%11,%12,%13,%14,%15,%16,%17,%18,%19,%20,%21,%22,%23,%24,%25,%26,%27,%28,%29,%30,%31,%32,%33,%34,%35,%36,%37,%38,%39},{%40,%41,%42,%43},db,%47,1,1,0;}"
 :"+f"(d[0]),"+f"(d[1]),"+f"(d[2]),"+f"(d[3]),"+f"(d[4]),"+f"(d[5]),"+f"(d[6]),"+f"(d[7]),"+f"(d[8]),"+f"(d[9]),"+f"(d[10]),"+f"(d[11]),"+f"(d[12]),"+f"(d[13]),"+f"(d[14]),"+f"(d[15]),"+f"(d[16]),"+f"(d[17]),"+f"(d[18]),"+f"(d[19]),"+f"(d[20]),"+f"(d[21]),"+f"(d[22]),"+f"(d[23]),"+f"(d[24]),"+f"(d[25]),"+f"(d[26]),"+f"(d[27]),"+f"(d[28]),"+f"(d[29]),"+f"(d[30]),"+f"(d[31]),"+f"(d[32]),"+f"(d[33]),"+f"(d[34]),"+f"(d[35]),"+f"(d[36]),"+f"(d[37]),"+f"(d[38]),"+f"(d[39])
 :"r"(a0),"r"(a1),"r"(a2),"r"(a3),"r"(blo),"n"(OFF),"n"(HI),"n"(SC)); } };
template<> struct WgRs<96> { template<int OFF,int HI,int SC> static __device__ __forceinline__ void run(float* d,uint32_t a0,uint32_t a1,uint32_t a2,uint32_t a3,uint32_t blo){
 asm volatile("{.reg .b32 l; .reg .b64 db; add.u32 l,%52,%53; mov.b64 db,{l,%54}; wgmma.mma_async.sync.aligned.m64n96k16.f32.bf16.bf16 {%0,%1,%2,%3,%4,%5,%6,%7,%8,%9,%10,%11,%12,%13,%14,%15,%16,%17,%18,%19,%20,%21,%22,%23,%24,%25,%26,%27,%28,%29,%30,%31,%32,%33,%34,%35,%36,%37,%38,%39,%40,%41,%42,%43,%44,%45,%46,%47},{%48,%49,%50,%51},db,%55,1,1,0;}"
 :"+f"(d[0]),"+f"(d[1]),"+f"(d[2]),"+f"(d[3]),"+f"(d[4]),"+f"(d[5]),"+f"(d[6]),"+f"(d[7]),"+f"(d[8]),"+f"(d[9]),"+f"(d[10]),"+f"(d[11]),"+f"(d[12]),"+f"(d[13]),"+f"(d[14]),"+f"(d[15]),"+f"(d[16]),"+f"(d[17]),"+f"(d[18]),"+f"(d[19]),"+f"(d[20]),"+f"(d[21]),"+f"(d[22]),"+f"(d[23]),"+f"(d[24]),"+f"(d[25]),"+f"(d[26]),"+f"(d[27]),"+f"(d[28]),"+f"(d[29]),"+f"(d[30]),"+f"(d[31]),"+f"(d[32]),"+f"(d[33]),"+f"(d[34]),"+f"(d[35]),"+f"(d[36]),"+f"(d[37]),"+f"(d[38]),"+f"(d[39]),"+f"(d[40]),"+f"(d[41]),"+f"(d[42]),"+f"(d[43]),"+f"(d[44]),"+f"(d[45]),"+f"(d[46]),"+f"(d[47])
 :"r"(a0),"r"(a1),"r"(a2),"r"(a3),"r"(blo),"n"(OFF),"n"(HI),"n"(SC)); } };
template<> struct WgRs<112> { template<int OFF,int HI,int SC> static __device__ __forceinline__ void run(float* d,uint32_t a0,uint32_t a1,uint32_t a2,uint32_t a3,uint32_t blo){
 asm volatile("{.reg .b32 l; .reg .b64 db; add.u32 l,%60,%61; mov.b64 db,{l,%62}; wgmma.mma_async.sync.aligned.m64n112k16.f32.bf16.bf16 {%0,%1,%2,%3,%4,%5,%6,%7,%8,%9,%10,%11,%12,%13,%14,%15,%16,%17,%18,%19,%20,%21,%22,%23,%24,%25,%26,%27,%28,%29,%30,%31,%32,%33,%34,%35,%36,%37,%38,%39,%40,%41,%42,%43,%44,%45,%46,%47,%48,%49,%50,%51,%52,%53,%54,%55},{%56,%57,%58,%59},db,%63,1,1,0;}"
 :"+f"(d[0]),"+f"(d[1]),"+f"(d[2]),"+f"(d[3]),"+f"(d[4]),"+f"(d[5]),"+f"(d[6]),"+f"(d[7]),"+f"(d[8]),"+f"(d[9]),"+f"(d[10]),"+f"(d[11]),"+f"(d[12]),"+f"(d[13]),"+f"(d[14]),"+f"(d[15]),"+f"(d[16]),"+f"(d[17]),"+f"(d[18]),"+f"(d[19]),"+f"(d[20]),"+f"(d[21]),"+f"(d[22]),"+f"(d[23]),"+f"(d[24]),"+f"(d[25]),"+f"(d[26]),"+f"(d[27]),"+f"(d[28]),"+f"(d[29]),"+f"(d[30]),"+f"(d[31]),"+f"(d[32]),"+f"(d[33]),"+f"(d[34]),"+f"(d[35]),"+f"(d[36]),"+f"(d[37]),"+f"(d[38]),"+f"(d[39]),"+f"(d[40]),"+f"(d[41]),"+f"(d[42]),"+f"(d[43]),"+f"(d[44]),"+f"(d[45]),"+f"(d[46]),"+f"(d[47]),"+f"(d[48]),"+f"(d[49]),"+f"(d[50]),"+f"(d[51]),"+f"(d[52]),"+f"(d[53]),"+f"(d[54]),"+f"(d[55])
 :"r"(a0),"r"(a1),"r"(a2),"r"(a3),"r"(blo),"n"(OFF),"n"(HI),"n"(SC)); } };
template<> struct WgRs<128> { template<int OFF,int HI,int SC> static __device__ __forceinline__ void run(float* d,uint32_t a0,uint32_t a1,uint32_t a2,uint32_t a3,uint32_t blo){
 asm volatile("{.reg .b32 l; .reg .b64 db; add.u32 l,%68,%69; mov.b64 db,{l,%70}; wgmma.mma_async.sync.aligned.m64n128k16.f32.bf16.bf16 {%0,%1,%2,%3,%4,%5,%6,%7,%8,%9,%10,%11,%12,%13,%14,%15,%16,%17,%18,%19,%20,%21,%22,%23,%24,%25,%26,%27,%28,%29,%30,%31,%32,%33,%34,%35,%36,%37,%38,%39,%40,%41,%42,%43,%44,%45,%46,%47,%48,%49,%50,%51,%52,%53,%54,%55,%56,%57,%58,%59,%60,%61,%62,%63},{%64,%65,%66,%67},db,%71,1,1,0;}"
 :"+f"(d[0]),"+f"(d[1]),"+f"(d[2]),"+f"(d[3]),"+f"(d[4]),"+f"(d[5]),"+f"(d[6]),"+f"(d[7]),"+f"(d[8]),"+f"(d[9]),"+f"(d[10]),"+f"(d[11]),"+f"(d[12]),"+f"(d[13]),"+f"(d[14]),"+f"(d[15]),"+f"(d[16]),"+f"(d[17]),"+f"(d[18]),"+f"(d[19]),"+f"(d[20]),"+f"(d[21]),"+f"(d[22]),"+f"(d[23]),"+f"(d[24]),"+f"(d[25]),"+f"(d[26]),"+f"(d[27]),"+f"(d[28]),"+f"(d[29]),"+f"(d[30]),"+f"(d[31]),"+f"(d[32]),"+f"(d[33]),"+f"(d[34]),"+f"(d[35]),"+f"(d[36]),"+f"(d[37]),"+f"(d[38]),"+f"(d[39]),"+f"(d[40]),"+f"(d[41]),"+f"(d[42]),"+f"(d[43]),"+f"(d[44]),"+f"(d[45]),"+f"(d[46]),"+f"(d[47]),"+f"(d[48]),"+f"(d[49]),"+f"(d[50]),"+f"(d[51]),"+f"(d[52]),"+f"(d[53]),"+f"(d[54]),"+f"(d[55]),"+f"(d[56]),"+f"(d[57]),"+f"(d[58]),"+f"(d[59]),"+f"(d[60]),"+f"(d[61]),"+f"(d[62]),"+f"(d[63])
 :"r"(a0),"r"(a1),"r"(a2),"r"(a3),"r"(blo),"n"(OFF),"n"(HI),"n"(SC)); } };
template<> struct WgSs<80> { template<int AOFF,int AHI,int BOFF,int BHI,int SC> static __device__ __forceinline__ void run(float* d,uint32_t alo,uint32_t blo){
 asm volatile("{.reg .b32 l,m; .reg .b64 da,db; add.u32 l,%40,%42; mov.b64 da,{l,%43}; add.u32 m,%41,%44; mov.b64 db,{m,%45}; wgmma.mma_async.sync.aligned.m64n80k16.f32.bf16.bf16 {%0,%1,%2,%3,%4,%5,%6,%7,%8,%9,%10,%11,%12,%13,%14,%15,%16,%17,%18,%19,%20,%21,%22,%23,%24,%25,%26,%27,%28,%29,%30,%31,%32,%33,%34,%35,%36,%37,%38,%39},da,db,%46,1,1,0,1;}"
 :"+f"(d[0]),"+f"(d[1]),"+f"(d[2]),"+f"(d[3]),"+f"(d[4]),"+f"(d[5]),"+f"(d[6]),"+f"(d[7]),"+f"(d[8]),"+f"(d[9]),"+f"(d[10]),"+f"(d[11]),"+f"(d[12]),"+f"(d[13]),"+f"(d[14]),"+f"(d[15]),"+f"(d[16]),"+f"(d[17]),"+f"(d[18]),"+f"(d[19]),"+f"(d[20]),"+f"(d[21]),"+f"(d[22]),"+f"(d[23]),"+f"(d[24]),"+f"(d[25]),"+f"(d[26]),"+f"(d[27]),"+f"(d[28]),"+f"(d[29]),"+f"(d[30]),"+f"(d[31]),"+f"(d[32]),"+f"(d[33]),"+f"(d[34]),"+f"(d[35]),"+f"(d[36]),"+f"(d[37]),"+f"(d[38]),"+f"(d[39])
 :"r"(alo),"r"(blo),"n"(AOFF),"n"(AHI),"n"(BOFF),"n"(BHI),"n"(SC)); } };
template<> struct WgSs<104> { template<int AOFF,int AHI,int BOFF,int BHI,int SC> static __device__ __forceinline__ void run(float* d,uint32_t alo,uint32_t blo){
 asm volatile("{.reg .b32 l,m; .reg .b64 da,db; add.u32 l,%52,%54; mov.b64 da,{l,%55}; add.u32 m,%53,%56; mov.b64 db,{m,%57}; wgmma.mma_async.sync.aligned.m64n104k16.f32.bf16.bf16 {%0,%1,%2,%3,%4,%5,%6,%7,%8,%9,%10,%11,%12,%13,%14,%15,%16,%17,%18,%19,%20,%21,%22,%23,%24,%25,%26,%27,%28,%29,%30,%31,%32,%33,%34,%35,%36,%37,%38,%39,%40,%41,%42,%43,%44,%45,%46,%47,%48,%49,%50,%51},da,db,%58,1,1,0,1;}"
 :"+f"(d[0]),"+f"(d[1]),"+f"(d[2]),"+f"(d[3]),"+f"(d[4]),"+f"(d[5]),"+f"(d[6]),"+f"(d[7]),"+f"(d[8]),"+f"(d[9]),"+f"(d[10]),"+f"(d[11]),"+f"(d[12]),"+f"(d[13]),"+f"(d[14]),"+f"(d[15]),"+f"(d[16]),"+f"(d[17]),"+f"(d[18]),"+f"(d[19]),"+f"(d[20]),"+f"(d[21]),"+f"(d[22]),"+f"(d[23]),"+f"(d[24]),"+f"(d[25]),"+f"(d[26]),"+f"(d[27]),"+f"(d[28]),"+f"(d[29]),"+f"(d[30]),"+f"(d[31]),"+f"(d[32]),"+f"(d[33]),"+f"(d[34]),"+f"(d[35]),"+f"(d[36]),"+f"(d[37]),"+f"(d[38]),"+f"(d[39]),"+f"(d[40]),"+f"(d[41]),"+f"(d[42]),"+f"(d[43]),"+f"(d[44]),"+f"(d[45]),"+f"(d[46]),"+f"(d[47]),"+f"(d[48]),"+f"(d[49]),"+f"(d[50]),"+f"(d[51])
 :"r"(alo),"r"(blo),"n"(AOFF),"n"(AHI),"n"(BOFF),"n"(BHI),"n"(SC)); } };
template<> struct WgSs<112> { template<int AOFF,int AHI,int BOFF,int BHI,int SC> static __device__ __forceinline__ void run(float* d,uint32_t alo,uint32_t blo){
 asm volatile("{.reg .b32 l,m; .reg .b64 da,db; add.u32 l,%56,%58; mov.b64 da,{l,%59}; add.u32 m,%57,%60; mov.b64 db,{m,%61}; wgmma.mma_async.sync.aligned.m64n112k16.f32.bf16.bf16 {%0,%1,%2,%3,%4,%5,%6,%7,%8,%9,%10,%11,%12,%13,%14,%15,%16,%17,%18,%19,%20,%21,%22,%23,%24,%25,%26,%27,%28,%29,%30,%31,%32,%33,%34,%35,%36,%37,%38,%39,%40,%41,%42,%43,%44,%45,%46,%47,%48,%49,%50,%51,%52,%53,%54,%55},da,db,%62,1,1,0,1;}"
 :"+f"(d[0]),"+f"(d[1]),"+f"(d[2]),"+f"(d[3]),"+f"(d[4]),"+f"(d[5]),"+f"(d[6]),"+f"(d[7]),"+f"(d[8]),"+f"(d[9]),"+f"(d[10]),"+f"(d[11]),"+f"(d[12]),"+f"(d[13]),"+f"(d[14]),"+f"(d[15]),"+f"(d[16]),"+f"(d[17]),"+f"(d[18]),"+f"(d[19]),"+f"(d[20]),"+f"(d[21]),"+f"(d[22]),"+f"(d[23]),"+f"(d[24]),"+f"(d[25]),"+f"(d[26]),"+f"(d[27]),"+f"(d[28]),"+f"(d[29]),"+f"(d[30]),"+f"(d[31]),"+f"(d[32]),"+f"(d[33]),"+f"(d[34]),"+f"(d[35]),"+f"(d[36]),"+f"(d[37]),"+f"(d[38]),"+f"(d[39]),"+f"(d[40]),"+f"(d[41]),"+f"(d[42]),"+f"(d[43]),"+f"(d[44]),"+f"(d[45]),"+f"(d[46]),"+f"(d[47]),"+f"(d[48]),"+f"(d[49]),"+f"(d[50]),"+f"(d[51]),"+f"(d[52]),"+f"(d[53]),"+f"(d[54]),"+f"(d[55])
 :"r"(alo),"r"(blo),"n"(AOFF),"n"(AHI),"n"(BOFF),"n"(BHI),"n"(SC)); } };

__device__ __forceinline__ void wg_fence() { asm volatile("wgmma.fence.sync.aligned;" ::: "memory"); }
__device__ __forceinline__ void wg_commit() { asm volatile("wgmma.commit_group.sync.aligned;" ::: "memory"); }
template <int N> __device__ __forceinline__ void wg_wait() { asm volatile("wgmma.wait_group.sync.aligned %0;" ::"n"(N) : "memory"); }
template <int N> __device__ __forceinline__ void reg_fence(float* d) {
#pragma unroll
    for (int i = 0; i < N; i++) asm volatile("" : "+f"(d[i])::"memory");
}
__device__ __forceinline__ uint32_t desc_lo(uint32_t addr, uint32_t lbo) { return ((addr & 0x3FFFF) >> 4) | ((lbo >> 4) << 16); }
#define desc_hi(sbo, sw) (((sbo) >> 4) | ((sw) << 30))
__device__ __forceinline__ uint32_t smem_u32(const void* p) { return (uint32_t)__cvta_generic_to_shared(p); }
__device__ __forceinline__ bool elect() {
    uint32_t p;
    asm volatile("{.reg .pred P; elect.sync _|P, 0xffffffff; selp.u32 %0,1,0,P;}" : "=r"(p));
    return p;
}
__device__ __forceinline__ void mbar_init(uint32_t bar, uint32_t cnt) { asm volatile("mbarrier.init.shared::cta.b64 [%0], %1;" ::"r"(bar), "r"(cnt) : "memory"); }
__device__ __forceinline__ void mbar_expect(uint32_t bar, uint32_t bytes) { asm volatile("mbarrier.arrive.expect_tx.shared::cta.b64 _, [%0], %1;" ::"r"(bar), "r"(bytes) : "memory"); }
__device__ __forceinline__ bool mbar_try(uint32_t bar, uint32_t par) {
    uint32_t ok;
    asm volatile("{.reg .pred p; mbarrier.try_wait.parity.shared::cta.b64 p, [%1], %2; selp.u32 %0,1,0,p;}" : "=r"(ok) : "r"(bar), "r"(par) : "memory");
    return ok;
}
constexpr int SPIN_LIMIT = 1 << 18;
__device__ __forceinline__ void mbar_wait(uint32_t bar, uint32_t par) {
    if (mbar_try(bar, par)) return;
    asm volatile("{.reg .pred p, q; .reg .b32 n; mov.u32 n, 0;\n"
                 "W%=: mbarrier.try_wait.parity.shared::cta.b64 p, [%0], %1; add.u32 n, n, 1; setp.lt.and.u32 q, n, %2, !p; @q bra W%=;}"
                 ::"r"(bar), "r"(par), "n"(SPIN_LIMIT) : "memory");
}
__device__ __forceinline__ void bulk_g2s(uint32_t dst, const void* src, uint32_t bytes, uint32_t bar) {
    asm volatile("cp.async.bulk.shared::cluster.global.mbarrier::complete_tx::bytes [%0], [%1], %2, [%3];" ::"r"(dst), "l"(src), "r"(bytes), "r"(bar) : "memory");
}
__device__ __forceinline__ void bulk_prefetch(const void* src, uint32_t bytes) {
    asm volatile("cp.async.bulk.prefetch.L2.global [%0], %1;" ::"l"(src), "r"(bytes) : "memory");
}
__device__ __forceinline__ void tma2d(uint32_t dst, const CUtensorMap* m, int c0, int c1, uint32_t bar) {
    asm volatile("cp.async.bulk.tensor.2d.shared::cluster.global.mbarrier::complete_tx::bytes [%0], [%1, {%3, %4}], [%2];" ::"r"(dst), "l"(m), "r"(bar), "r"(c0), "r"(c1) : "memory");
}
__device__ __forceinline__ void tma2d_mc(uint32_t dst, const CUtensorMap* m, int c0, int c1, uint32_t bar) {
    asm volatile("cp.async.bulk.tensor.2d.shared::cluster.global.mbarrier::complete_tx::bytes.multicast::cluster [%0], [%1, {%3, %4}], [%2], %5;" ::"r"(dst), "l"(m), "r"(bar), "r"(c0), "r"(c1), "h"((uint16_t)3) : "memory");
}
__device__ __forceinline__ uint32_t mapa(uint32_t a, uint32_t rank) { uint32_t r; asm("mapa.shared::cluster.u32 %0, %1, %2;" : "=r"(r) : "r"(a), "r"(rank)); return r; }
__device__ __forceinline__ void mbar_arrive_cl(uint32_t bar) { asm volatile("mbarrier.arrive.shared::cluster.b64 _, [%0];" ::"r"(bar) : "memory"); }
__device__ __forceinline__ void prefetch_map(const CUtensorMap* m) { asm volatile("prefetch.tensormap [%0];" ::"l"(m) : "memory"); }
__device__ __forceinline__ void cpasync16(uint32_t dst, const void* src, uint32_t srcsz) {
    asm volatile("cp.async.cg.shared.global [%0], [%1], 16, %2;" ::"r"(dst), "l"(src), "r"(srcsz) : "memory");
}
__device__ __forceinline__ void bar_sync(int id, int n) { asm volatile("bar.sync %0, %1;" ::"r"(id), "r"(n) : "memory"); }
__device__ __forceinline__ void bar_arrive(int id, int n) { asm volatile("bar.arrive %0, %1;" ::"r"(id), "r"(n) : "memory"); }
__device__ __forceinline__ void fence_async_smem() { asm volatile("fence.proxy.async.shared::cta;" ::: "memory"); }
__device__ __forceinline__ void fence_async_global() { asm volatile("fence.proxy.async.global;" ::: "memory"); }
__device__ __forceinline__ unsigned* flag_ptr(int f) {
    return f < 16 ? &g_flags[(f & 7) * 32 + (f >> 3)] : &g_flags[f * 32];
}
__device__ __forceinline__ void flag_release(int f) { asm volatile("red.release.gpu.global.add.u32 [%0], 1;" ::"l"(flag_ptr(f)) : "memory"); }
__device__ __forceinline__ void flag_wait(int f, unsigned target) {
    const unsigned* p = flag_ptr(f);
    unsigned v; int n = 0;
    do {
        asm volatile("ld.relaxed.gpu.global.u32 %0, [%1];" : "=r"(v) : "l"(p) : "memory");
    } while ((int)(v - target) < 0 && ++n < SPIN_LIMIT);
    asm volatile("fence.acquire.gpu;" ::: "memory");
}
__device__ __forceinline__ unsigned ld_flag(const unsigned* p) { unsigned v; asm volatile("ld.relaxed.gpu.global.u32 %0, [%1];" : "=r"(v) : "l"(p) : "memory"); return v; }
__device__ __forceinline__ void spin(unsigned n) { unsigned t0, t1; asm volatile("mov.u32 %0, %%clock;" : "=r"(t0)); do { asm volatile("mov.u32 %0, %%clock;" : "=r"(t1)); } while (t1 - t0 < n); }
__device__ __forceinline__ int tensor_ping() {
    int r;
    asm volatile("{.reg .f32 a, b, c, d; mma.sync.aligned.m16n8k16.row.col.f32.bf16.bf16.f32 {a,b,c,d},{%1,%1,%1,%1},{%1,%1},{%2,%2,%2,%2}; mov.b32 %0, a;}" : "=r"(r) : "r"(0), "f"(0.f));
    return r;
}
__device__ __forceinline__ void mbar_wait_warm(uint32_t bar, uint32_t par) {
    for (int n = 0; n < SPIN_LIMIT; n++) {
        uint32_t ok;
        asm volatile("{.reg .pred p; mbarrier.test_wait.parity.shared::cta.b64 p, [%1], %2; selp.u32 %0,1,0,p;}" : "=r"(ok) : "r"(bar), "r"(par) : "memory");
        if (ok) break;
        n += tensor_ping();
        spin(PING);
    }
}
__device__ __forceinline__ void flag_wait2(int f0, int f1, unsigned target) {
    const unsigned *p = flag_ptr(f0), *q = flag_ptr(f1);
    unsigned v, w; int n = 0;
    do { v = ld_flag(p); w = ld_flag(q); } while ((int)((v - target) | (w - target)) < 0 && ++n < SPIN_LIMIT);
    asm volatile("fence.acquire.gpu;" ::: "memory");
}
__device__ __forceinline__ uint32_t lds32(uint32_t a) { uint32_t v; asm volatile("ld.shared.u32 %0, [%1];" : "=r"(v) : "r"(a)); return v; }
__device__ __forceinline__ float2 lds64f(uint32_t a) { float2 v; asm volatile("ld.shared.v2.f32 {%0,%1}, [%2];" : "=f"(v.x), "=f"(v.y) : "r"(a)); return v; }
__device__ __forceinline__ uint2 lds64(uint32_t a) { uint2 v; asm volatile("ld.shared.v2.u32 {%0,%1}, [%2];" : "=r"(v.x), "=r"(v.y) : "r"(a)); return v; }
__device__ __forceinline__ void sts64f(uint32_t a, float2 v) { asm volatile("st.shared.v2.f32 [%0], {%1,%2};" ::"r"(a), "f"(v.x), "f"(v.y) : "memory"); }
__device__ __forceinline__ void sts32(uint32_t a, uint32_t v) { asm volatile("st.shared.u32 [%0], %1;" ::"r"(a), "r"(v) : "memory"); }
__device__ __forceinline__ void sts64(uint32_t a, uint32_t x, uint32_t y) { asm volatile("st.shared.v2.u32 [%0], {%1,%2};" ::"r"(a), "r"(x), "r"(y) : "memory"); }
__device__ __forceinline__ void sts16(uint32_t a, uint16_t v) { asm volatile("st.shared.u16 [%0], %1;" ::"r"(a), "h"(v) : "memory"); }
__device__ __forceinline__ uint4 lds128(uint32_t a) { uint4 v; asm volatile("ld.shared.v4.u32 {%0,%1,%2,%3}, [%4];" : "=r"(v.x), "=r"(v.y), "=r"(v.z), "=r"(v.w) : "r"(a)); return v; }
__device__ __forceinline__ void sts128(uint32_t a, uint4 v) { asm volatile("st.shared.v4.u32 [%0], {%1,%2,%3,%4};" ::"r"(a), "r"(v.x), "r"(v.y), "r"(v.z), "r"(v.w) : "memory"); }
__device__ __forceinline__ void sts128f(uint32_t a, float x, float y, float z, float w) { asm volatile("st.shared.v4.f32 [%0], {%1,%2,%3,%4};" ::"r"(a), "f"(x), "f"(y), "f"(z), "f"(w) : "memory"); }
__device__ __forceinline__ uint32_t prmt(uint32_t a, uint32_t b, uint32_t s) { uint32_t r; asm("prmt.b32 %0,%1,%2,%3;" : "=r"(r) : "r"(a), "r"(b), "r"(s)); return r; }
__device__ __forceinline__ uint32_t pack2(float lo, float hi) { uint32_t r; asm("cvt.rn.bf16x2.f32 %0, %1, %2;" : "=r"(r) : "f"(hi), "f"(lo)); return r; }
__device__ __forceinline__ float blo(uint32_t v) { return __uint_as_float(v << 16); }
__device__ __forceinline__ float bhi(uint32_t v) { return __uint_as_float(v & 0xffff0000u); }
__device__ __forceinline__ uint32_t bmul2(uint32_t a, uint32_t b) { uint32_t r; asm("mul.rn.bf16x2 %0,%1,%2;" : "=r"(r) : "r"(a), "r"(b)); return r; }
__device__ __forceinline__ uint32_t badd2(uint32_t a, uint32_t b) { uint32_t r; asm("add.rn.bf16x2 %0,%1,%2;" : "=r"(r) : "r"(a), "r"(b)); return r; }
__device__ __forceinline__ uint4 ldcg128(const void* p) { uint4 v; asm volatile("ld.global.cg.v4.u32 {%0,%1,%2,%3}, [%4];" : "=r"(v.x), "=r"(v.y), "=r"(v.z), "=r"(v.w) : "l"(p) : "memory"); return v; }
__device__ __forceinline__ uint4 ld_tagged(const void* p) {
    uint4 v;
    asm volatile("{.reg .b64 a, b; ld.relaxed.gpu.global.v2.b64 {a, b}, [%4]; mov.b64 {%0, %1}, a; mov.b64 {%2, %3}, b;}" : "=r"(v.x), "=r"(v.y), "=r"(v.z), "=r"(v.w) : "l"(p) : "memory");
    return v;
}
__device__ __forceinline__ float half_rstd(float sum, float sq) {
    float mean = sum * (1.0f / D_), inv;
    asm("rsqrt.approx.ftz.f32 %0, %1;" : "=f"(inv) : "f"(fmaxf(fmaf(-mean, mean, fmaf(sq, 1.0f / D_, 1e-5f)), 1e-5f)));
    return 0.5f * inv;
}
__device__ __forceinline__ uint32_t bsub2(uint32_t a, uint32_t b) { uint32_t r; asm("sub.rn.bf16x2 %0,%1,%2;" : "=r"(r) : "r"(a), "r"(b)); return r; }
__device__ __forceinline__ uint32_t bfma2(uint32_t a, uint32_t b, uint32_t c) { uint32_t r; asm("fma.rn.bf16x2 %0,%1,%2,%3;" : "=r"(r) : "r"(a), "r"(b), "r"(c)); return r; }
__device__ __forceinline__ uint32_t gelu2_h(uint32_t h) {
    uint32_t u = bmul2(h, bfma2(bmul2(h, h), 0x3e923e92u, 0x3fcc3fccu)), th;
    asm("tanh.approx.bf16x2 %0, %1;" : "=r"(th) : "r"(u));
    return bfma2(h, th, h);
}
struct RowSum { float s = 0.f, q = 0.f, s_ = 0.f, q_ = 0.f;
    __device__ __forceinline__ void add(uint32_t v) { float a = blo(v), b = bhi(v); s += a; s_ += b; q = fmaf(a, a, q); q_ = fmaf(b, b, q_); } };
template <int I0>
__device__ __forceinline__ uint2 row_stats(const uint32_t* v, int lane, RowSum r0 = RowSum()) {
#pragma unroll
    for (int i = I0; i < 10; i++) r0.add(v[i]);
    float s = r0.s + r0.s_, q = r0.q + r0.q_;
    {
        float t = __shfl_xor_sync(0xffffffffu, (lane & 16) ? s : q, 16);
        t += (lane & 16) ? q : s;
#pragma unroll
        for (int m = 8; m; m >>= 1) t += __shfl_xor_sync(0xffffffffu, t, m);
        float o = __shfl_xor_sync(0xffffffffu, t, 16);
        s = (lane & 16) ? o : t; q = (lane & 16) ? t : o;
    }
    float mean = s * (1.0f / D_), inv;
    asm("rsqrt.approx.ftz.f32 %0, %1;" : "=f"(inv) : "f"(fmaxf(fmaf(-mean, mean, fmaf(q, 1.0f / D_, 1e-5f)), 1e-5f)));
    return make_uint2(pack2(mean, mean), pack2(inv, inv));
}
__device__ __forceinline__ uint32_t ln_apply(uint32_t x, uint32_t m, uint32_t inv) { return bmul2(bsub2(x, m), inv); }

struct AFrag { uint32_t m, a, b, c, d; };
__device__ __forceinline__ AFrag ldA(uint32_t a) { AFrag f; f.m = lds32(a - 16); f.a = lds32(a); f.b = lds32(a + 16); f.c = lds32(a + 32); f.d = lds32(a + 48); return f; }
template <int N, int M> __device__ __forceinline__ void conv_pair(float* d, const AFrag& f, uint32_t descU) {
    WgRs<N>::template run<8 * M, desc_hi(128, 0), M ? 1 : 0>(d, f.a, f.b, f.m, f.a, descU);
    WgRs<N>::template run<8 * M + 1, desc_hi(128, 0), 1>(d, f.c, f.d, f.b, f.c, descU);
}
template <int Q> __device__ __forceinline__ void conv_put(float* d, uint32_t r0) {
    sts64(r0 + Q * 32, pack2(d[4 * Q + 1], d[4 * Q + 3]), pack2(d[4 * Q], d[4 * Q + 2]));
}
template <int M> __device__ __forceinline__ void conv_two(float* d, AFrag f0, AFrag f1, uint32_t kaddr, uint32_t descU, uint32_t r0, bool handoff) {
    constexpr int N = M < 14 ? 128 - 8 * M : 32;
    wg_fence();
    conv_pair<N, M>(d, f0, descU);
    wg_commit();
    if constexpr (M > 0) f1 = ldA(kaddr + 256 * (M + 1));
    wg_fence();
    conv_pair<N, M + 1>(d, f1, descU);
    wg_commit();
    if (STAG && M == STAG && handoff) bar_arrive(12, 256);
    if constexpr (M < 14) {
        if constexpr (M > 0) { conv_put<17 - M>(d, r0); conv_put<16 - M>(d, r0); }
        wg_wait<1>();
        f0 = ldA(kaddr + 256 * (M + 2));
        if constexpr (M < 12) wg_wait<0>();
        conv_two<M + 2>(d, f0, f1, kaddr, descU, r0, handoff);
    } else {
        wg_wait<0>();
        conv_put<3>(d, r0); conv_put<2>(d, r0); conv_put<1>(d, r0); conv_put<0>(d, r0);
    }
}
template <int N, bool ASWZ, int SC0>
__device__ __forceinline__ void gemm_issue(float* acc, uint32_t bars, int sa, int pa, int sw, int pw, uint32_t da0, uint32_t db0) {
    mbar_wait(bars + (BAR_FB + sw) * 8, pw);
    mbar_wait(bars + (BAR_FA + sa) * 8, pa);
    const uint32_t da = da0 + sa * (SLOT >> 4), db = db0 + sw * (SLOT >> 4);
    constexpr int AK = ASWZ ? 2 : 256, AH = ASWZ ? desc_hi(1024, 1) : desc_hi(128, 0), BH = desc_hi(1024, 1);
    wg_fence();
    WgSs<N>::template run<0, AH, 0, BH, SC0>(acc, da, db);
    WgSs<N>::template run<AK, AH, 128, BH, 1>(acc, da, db);
    WgSs<N>::template run<2 * AK, AH, 256, BH, 1>(acc, da, db);
    WgSs<N>::template run<3 * AK, AH, 384, BH, 1>(acc, da, db);
    wg_commit();
}
template <int N, bool ASWZ, int NKB, int RELB, bool ZERO>
__device__ __forceinline__ void gemm_loop(float* acc, uint32_t sb, int half, int ia0, int ib0, int rela, int wait_bar, int tsid) {
    int sa = ia0 % NA, pa = (ia0 / NA) & 1, sw = ib0 % NB, pw = (ib0 / NB) & 1;
    const uint32_t bars = sb + SM_BAR;
    const int t = threadIdx.x & 127;
    uint32_t ebar = mapa(bars + (t < 2 ? BAR_EB : BAR_EA) * 8, (t < 2 && lds32(sb + SM_GV + 516)) ? t : blockIdx.x & 1);
    const int nrel = t < 2 ? RELB : t == 2 ? rela : 0;
    const uint32_t da0 = ASWZ ? desc_lo(sb + SM_RA + half * 8192, 16) : desc_lo(sb + SM_RA + half * 1024, 2048), db0 = desc_lo(sb + SM_RB, 8192);
    if (!ZERO) {
        if (sa-- == 0) { sa = NA - 1; pa ^= 1; }
        if (sw-- == 0) { sw = NB - 1; pw ^= 1; }
    }
    asm volatile("" : "+r"(ebar));
    if (wait_bar) bar_sync(wait_bar, 512);
    constexpr bool PEEL = ZERO;
    if (PEEL) gemm_issue<N, ASWZ, 0>(acc, bars, sa, pa, sw, pw, da0, db0);
    if (PEEL && (threadIdx.x & 255) == 0) TS(tsid);
#pragma unroll 1
    for (int kb = PEEL; kb < NKB; kb++) {
        const int prev = t < 2 ? sw : sa;
        if (++sa == NA) { sa = 0; pa ^= 1; }
        if (++sw == NB) { sw = 0; pw ^= 1; }
        gemm_issue<N, ASWZ, 1>(acc, bars, sa, pa, sw, pw, da0, db0);
        wg_wait<1>();
        if (PEEL ? kb <= nrel : (unsigned)(kb - 1) < (unsigned)nrel) mbar_arrive_cl(ebar + prev * 8);
    }
    wg_wait<0>();
    if (nrel == NKB) mbar_arrive_cl(ebar + (t < 2 ? sw : sa) * 8);
    reg_fence<N / 2>(acc);
    if ((threadIdx.x & 255) == 0) TS(tsid + 1);
}

template <int PART>
__device__ __forceinline__ void gemm3(uint32_t sb, int rb, int j, int half, int row, int c, unsigned ones) {
    constexpr int N = 64 + (PART ? RB3 : RA3), NQ = N / 8;
    float acc[N / 2];
    float2 cr[NQ];
    if (PART) {
        gemm_loop<N, false, 1, 1, true>(acc, sb, half, 20, 20, 0, 0, 50);
        bar_arrive(9, 512);
    }
    mbar_wait(sb + SM_BAR + BAR_CS * 8, 0);
    const uint32_t csa = sb + SM_CS + PART * (256 + 4 * RA3) + 8 * c;
#pragma unroll
    for (int q = 0; q < NQ; q++) cr[q] = lds64f(csa + 32 * q);
    uint4 rp;
    if (PART) {
        if (TAGST) mbar_wait(sb + SM_BAR + (BAR_FA + (20 + TAGST) % NA) * 8, ((20 + TAGST) / NA) & 1); else mbar_wait(sb + SM_BAR + BAR_ST * 8, 0);
        const uint4* sp = &g_st[(rb * 8 + 2 * c) * 128 + row];
        const uint32_t tag = lds32(sb + SM_GV + 540);
        uint4 s0, s1, s2, s3;
        for (int n = 0; n < SPIN_LIMIT; n++) {
            s0 = ld_tagged(sp); s1 = ld_tagged(sp + 128); s2 = ld_tagged(sp + 8); s3 = ld_tagged(sp + 136);
            if (!(((s0.y ^ tag) | (s0.w ^ tag) | (s1.y ^ tag) | (s1.w ^ tag)) | ((s2.y ^ tag) | (s2.w ^ tag) | (s3.y ^ tag) | (s3.w ^ tag)))) break;
        }
        __syncwarp();
        float a0 = __uint_as_float(s0.x) + __uint_as_float(s1.x), b0 = __uint_as_float(s0.z) + __uint_as_float(s1.z);
        float a1 = __uint_as_float(s2.x) + __uint_as_float(s3.x), b1 = __uint_as_float(s2.z) + __uint_as_float(s3.z);
#pragma unroll
        for (int m = 1; m <= 2; m <<= 1) {
            a0 += __shfl_xor_sync(0xffffffffu, a0, m); b0 += __shfl_xor_sync(0xffffffffu, b0, m);
            a1 += __shfl_xor_sync(0xffffffffu, a1, m); b1 += __shfl_xor_sync(0xffffffffu, b1, m);
        }
        const float inv0 = half_rstd(a0, b0), inv1 = half_rstd(a1, b1);
        rp = make_uint4(pack2(inv0, inv0), __float_as_uint(a0 * (-1.0f / D_)),
                        pack2(inv1, inv1), __float_as_uint(a1 * (-1.0f / D_)));
        if (c == 0) sts128(sb + SM_RP + ((threadIdx.x & 255) >> 2) * 16, rp);
        bar_arrive(13, 512);
    }
    gemm_loop<N, false, 10 - PART, 10 - PART, !PART>(acc, sb, half, 20 + (10 - NA) * PART, 21 + 10 * PART, PART ? 9 : 10 - NA, 9 + PART, 46 + 2 * PART);
    if ((threadIdx.x & 255) == 0) mbar_expect(sb + SM_BAR + BAR_ME * 8, 0);
    if (!PART) {
        bar_sync(13, 512);
        rp = lds128(sb + SM_RP + ((threadIdx.x & 255) >> 2) * 16);
    }
    const float nb0 = __uint_as_float(rp.y), nb1 = __uint_as_float(rp.w);
    const uint32_t own = sb + SM_RA + ((39 - NA) % NA) * SLOT + row * 16 + c * 4;
    if (PART) mbar_wait(sb + SM_BAR + (BAR_FA + (39 - NA) % NA) * 8, ((39 - NA) / NA) & 1);
    uint32_t* dst = reinterpret_cast<uint32_t*>(g_g) + (rb * 216 + HB0 / 8 * PART + 8 * j) * 512 + row * 4 + c;
    auto act = [&](int q, int r) {
        const float nb = r ? nb1 : nb0;
        const uint32_t inv = r ? rp.z : rp.x;
        const float t0 = fmaf(nb, cr[q].x, acc[4 * q + 2 * r]), t1 = fmaf(nb, cr[q].y, acc[4 * q + 2 * r + 1]);
        return gelu2_h(bmul2(pack2(t0, t1), inv));
    };
    uint32_t* dst1 = dst + (56 - (16 - NQ) * j) * 512;
#pragma unroll
    for (int k = 0; k < NQ; k += CH3) {
        CHUNK(k) {
#pragma unroll
            for (int q = k; q < k + CH3 && q < NQ; q++) {
                const uint32_t u = act(q, 0), v = act(q, 1);
                (q < 8 ? dst : dst1)[q * 512] = u;
                (q < 8 ? dst : dst1)[q * 512 + 32] = v;
                if (PART && q < 8) { sts32(own + q * 2048, u); sts32(own + q * 2048 + 128, v); }
            }
            if (PART && k < 8 && k + CH3 >= 8) fence_async_smem();
        }
    }
    bar_arrive(1 + PART, 288);
    bar_arrive(10 + PART, 512);
}

template <int NS, int BASE, int BF, int BE> struct Ring {
    uint32_t sb, st, ph;
    __device__ __forceinline__ uint32_t acquire(uint32_t bytes) {
        mbar_wait(sb + SM_BAR + BE * 8 + st * 8, ph);
        uint32_t fb = sb + SM_BAR + BF * 8 + st * 8;
        mbar_expect(fb, bytes);
        return fb;
    }
    __device__ __forceinline__ uint32_t slot() { return sb + BASE + st * SLOT; }
    __device__ __forceinline__ void next() { if (++st == NS) { st = 0; ph ^= 1; } }
    __device__ __forceinline__ void run2d(const CUtensorMap* m, int c1) {
#pragma unroll 1
        for (int c0 = 64; c0 < D_; c0 += 64) {
            uint32_t fb = acquire(SLOT);
            tma2d(slot(), m, c0, c1, fb);
            next();
        }
    }
    static __device__ __forceinline__ int korder(int i, int own) { return i == 0 ? own : i > own ? i : i - 1; }
    __device__ __forceinline__ void runw(bool paired, int rk, const CUtensorMap* ma, const CUtensorMap* mb, int ca, int cb, int i0, int i1, int own, uint32_t bytes, int gate_at, uint32_t gate) {
        if (paired) {
            const CUtensorMap* m = rk ? mb : ma;
            const int c0 = rk ? cb : ca;
#pragma unroll 1
            for (int i = i0; i < i1; i++) {
                const int c1 = korder(i, own) * 64;
                if (i == gate_at) mbar_wait(gate, 0);
                uint32_t fb = acquire(bytes);
                tma2d_mc(slot() + 8192 * rk, m, c0, c1, fb);
                next();
            }
        } else {
#pragma unroll 1
            for (int i = i0; i < i1; i++) {
                const int c1 = korder(i, own) * 64;
                uint32_t fb = acquire(bytes);
                tma2d(slot(), ma, ca, c1, fb);
                tma2d(slot() + 8192, mb, cb, c1, fb);
                next();
            }
        }
    }
    __device__ __forceinline__ void run1d(const char* src, int i0, int i1, int own) {
#pragma unroll 1
        for (int i = i0; i < i1; i++) {
            const char* s = src + korder(i, own) * SLOT;
            uint32_t fb = acquire(SLOT);
            bulk_g2s(slot(), s, SLOT, fb);
            next();
        }
    }
};

__global__ void __cluster_dims__(2, 1, 1) __launch_bounds__(NTHREADS, 1) fused_kernel(const Params p, const __grid_constant__ Maps maps) {
    extern __shared__ __align__(1024) unsigned char smem_raw[];
    const uint32_t sb = (smem_u32(smem_raw) + 1023u) & ~1023u;
#pragma unroll
    for (int i = 0; i < SEED; i++) asm volatile("{.reg .b32 t; mov.u32 t, %laneid;}");
    const uint32_t bars = sb + SM_BAR;
    const int tid = threadIdx.x, lane = tid & 31;
    unsigned smid;
    asm volatile("mov.u32 %0, %%smid;" : "=r"(smid));
    const bool spare = (smid >> 2) == 30;
    const int cta = smid < 120 ? smid : smid - 4;
    const int pg = cta >> 4, pi = cta & 15;
    auto chan = [&](int cc) { return cc < 3 ? 3 * cta + cc : 381 + 2 * cta + cc; };
    const int hb = tid >= 320;
    unsigned ep0 = 0;
    if (!spare) {
        const unsigned t = tid - 320 * hb, r32 = t / 10u, cc = t - r32 * 10u, row = r32 + 64 * hb;
        const unsigned go = (unsigned)(pi * 128 * 1280) + row * 1280u + cc * 16u + (cc < 6 ? pg * 96 : 672 + pg * 64);
        const uint32_t so = sb + (row >> 4) * 32u + row * 160u + cc * 16u;
        const char* kb = (const char*)p.k + go;
        const char* vb = (const char*)p.v + go;
        if (hb) {
            if (tid < 328) {
                const char* a = lane < 5 ? (const char*)p.shift + lane * 128 + (lane < 3 ? pg * 384 : 2688 + pg * 256) : (const char*)(p.ssmD + chan(2 * lane - 10));
                asm volatile("prefetch.global.L2 [%0];" ::"l"(a));
            }
            if (tid >= 640 - NBARS) {
                const int i = 639 - tid;
                mbar_init(bars + i * 8, (i >= BAR_EB && i < BAR_K) ? 4 : ((i >= BAR_EA && i < BAR_EB) || i == BAR_XY) ? 2 : 1);
                asm volatile("fence.mbarrier_init.release.cluster;" ::: "memory");
            }
            bar_arrive(14, 640);
            if (tid >= 512) asm volatile("ld.volatile.global.u32 %0, [%1];" : "=r"(ep0) : "l"(p.epoch + smid) : "memory");
            if (B_DELAY) spin(B_DELAY);
        }
        cpasync16(so + SM_PK + 2592, kb, 16);
        cpasync16(so + SM_PV, vb, 16);
        cpasync16(so + SM_PK + 3 * 2592, kb + 32 * 1280, 16);
        cpasync16(so + SM_PV + 2 * 2592, vb + 32 * 1280, 16);
        if (tid < 30) cpasync16(so + SM_PK + 13 * 160, pi ? kb - 3 * 1280 : kb, pi ? 16 : 0);
        asm volatile("cp.async.commit_group;" ::: "memory");
    }
    const int warp = __shfl_sync(0xffffffffu, tid >> 5, 0);
    const int wg = warp >> 2, wq = warp & 3;

    if (spare) {
        const int sp = smid & 3;
        const unsigned ep1 = *(volatile unsigned*)&p.epoch[smid] + 1;
        if (tid == 32) { sts32(sb + SM_GV + 512, smid); asm volatile("fence.release.sync_restrict::shared::cta.cluster;" ::: "memory"); }
        asm volatile("barrier.cluster.arrive.relaxed.aligned;" ::: "memory");
        asm volatile("barrier.cluster.wait.aligned;" ::: "memory");
        if (tid == 0) {
            for (int i = 0; i < 4; i++) mbar_init(bars + i * 8, 1);
            asm volatile("fence.mbarrier_init.release.cluster;" ::: "memory");
        }
        if (warp == 0) { if (lane < 8) flag_wait(FL_P + lane, ep1 * 16); __syncwarp(); if (SPD) spin(SPD); }
        __syncthreads();
        const int cq = tid % 54, rg = tid / 54;
        float a[8];
#pragma unroll
        for (int i = 0; i < 8; i++) a[i] = 0.f;
#pragma unroll 1
        for (int it = -4; it < 10; it++) {
            const uint32_t st = sb + (it & 3) * 55296, fb = bars + (it & 3) * 8;
            if (it >= 0) {
                mbar_wait(fb, (it >> 2) & 1);
                if (tid < 432) {
#pragma unroll 2
                    for (int i = 0; i < 8; i++) {
                        uint4 w = lds128(st + (cq >= 27 ? 27648 - 432 : 0) + (rg * 8 + i) * 432 + cq * 16);
                        a[0] += blo(w.x); a[1] += bhi(w.x); a[2] += blo(w.y); a[3] += bhi(w.y);
                        a[4] += blo(w.z); a[5] += bhi(w.z); a[6] += blo(w.w); a[7] += bhi(w.w);
                    }
                }
                __syncthreads();
            }
            if (it < 6 && warp == 19 && elect()) {
                mbar_expect(fb, 55296);
                tma2d(st, &maps.w3s, sp * 432, (it + 4) * 64, fb);
                tma2d(st + 27648, &maps.w3s, sp * 432 + 216, (it + 4) * 64, fb);
            }
        }
        if (warp == 19 && elect()) {
#pragma unroll 1
            for (int i = 0; i < 27; i++) bulk_prefetch((const char*)p.w4 + sp * 552960 + i * 20480, 20480);
        }
        if (tid < 432) {
            sts128f(sb + rg * 1728 + cq * 32, a[0], a[1], a[2], a[3]);
            sts128f(sb + rg * 1728 + cq * 32 + 16, a[4], a[5], a[6], a[7]);
        }
        __syncthreads();
        if (tid < 432) {
            float s = 0.f;
#pragma unroll
            for (int i = 0; i < 8; i++) s += __uint_as_float(lds32(sb + i * 1728 + tid * 4));
            g_cs[sp * 432 + tid] = s;
        }
        __syncthreads();
        if (tid == 0) { flag_release(FL_CS); p.epoch[smid] = ep1; TS(0); }
        if (warp == 0) TSFLUSH();
        return;
    }

    int gpc, idx;
    if (smid < 64) { gpc = (smid & 15) >> 1; idx = (smid >> 4) * 2 + (smid & 1); }
    else if (smid < 120) { int t = smid - 64; gpc = 1 + (t % 14) / 2; idx = 8 + (t / 14) * 2 + (smid & 1); }
    else { gpc = 0; idx = 8 + (smid - 124); }
    const int rb = 2 * gpc + (idx & 1), j = idx >> 1;
    const int g = lane >> 2, c = lane & 3;
    const int cm = 160 * (j >> 1) + 64 * (j & 1) + ((j & 2) ? 32 : 0), cr = 160 * (j >> 1) + 16 * (j & 1) + ((j & 2) ? 0 : 128);

    {
        if (warp == 5) TSW(61);
        const int w10 = warp - 10 * hb, h = w10 >= 5;
        const int pr = (w10 - 5 * h) * 8 + (lane >> 2), blk = 4 * hb + (lane & 3);
        const int ch = 2 * pr + (pr < 24 ? 48 * pg : 336 + 32 * pg);
        const uint4 sw = __ldg(reinterpret_cast<const uint4*>(p.shift + ch * 4));
        uint32_t dv = 0;
        if (warp == 9 && lane < 5) dv = __bfloat16_as_ushort(p.ssmD[chan(lane)]);
        if (tid == 512) { sts32(sb + SM_GV + 512, smid); asm volatile("fence.release.sync_restrict::shared::cta.cluster;" ::: "memory"); }
        asm volatile("barrier.cluster.arrive.relaxed.aligned;" ::: "memory");
        if (warp == 11 && lane < 13) prefetch_map(&maps.hn + lane);
        if (wg < 4) {
            const int t = tid & 127, cc = (wg == 3 && t >= 64) ? 4 : wg;
            if (t < 64 || wg == 3) sts128(sb + sm_u(cc) + ((t >> 5) & 1) * U_PLANE + 2048 + lane * 16, make_uint4(0, 0, 0, 0));
            if ((t & 63) < 4 && (t < 64 || wg == 3)) sts128(sb + sm_k(cc) + ((t >> 1) & 1) * 4160 + (t & 1) * 16, make_uint4(0, 0, 0, 0));
        }
        if (warp == 9 && lane < 5) sts32(sb + SM_GV + 520 + lane * 4, dv << 16);
        asm volatile("cp.async.wait_group 0;" ::: "memory");
        if (!hb) bar_arrive(12, 640);
        bar_sync(hb ? 12 : 14, 640);
        if (warp == 9) {
            if (SSM_DELAY) spin(SSM_DELAY);
            if (elect()) {
#pragma unroll
                for (int i = 0; i < SSM_N; i++) {
                    mbar_expect(bars + (BAR_K + i) * 8, 4096);
                    bulk_g2s(sb + sm_k(i) + 32, p.ssmk + (size_t)(chan(i)) * S_, 4096, bars + (BAR_K + i) * 8);
                }
            }
        }
        const uint32_t w0 = prmt(sw.x, sw.z, 0x5410), w1 = prmt(sw.x, sw.z, 0x7632), w2 = prmt(sw.y, sw.w, 0x5410), w3 = prmt(sw.y, sw.w, 0x7632);
        const uint32_t ka = sb + SM_PK + 2592 + blk * 2592 + h * 1280 + pr * 4;
        const uint32_t va = sb + SM_PV + blk * 2592 + h * 1280 + pr * 4;
        uint32_t kk[11], kv[8];
#pragma unroll
        for (int i = 0; i < 11; i++) kk[i] = lds32(ka + (i - 3) * 160 - ((i < 3 && h == 0) ? 32 : 0));
#pragma unroll
        for (int i = 0; i < 8; i++) {
            uint32_t t = badd2(badd2(badd2(bmul2(kk[i], w3), bmul2(kk[i + 1], w2)), bmul2(kk[i + 2], w1)), bmul2(kk[i + 3], w0));
            kv[i] = bmul2(t, lds32(va + i * 160));
        }
        uint4 o0, o1;
        o0.x = prmt(kv[1], kv[0], 0x5410); o0.y = prmt(kv[3], kv[2], 0x5410); o0.z = prmt(kv[5], kv[4], 0x5410); o0.w = prmt(kv[7], kv[6], 0x5410);
        o1.x = prmt(kv[1], kv[0], 0x7632); o1.y = prmt(kv[3], kv[2], 0x7632); o1.z = prmt(kv[5], kv[4], 0x7632); o1.w = prmt(kv[7], kv[6], 0x7632);
        uint4* dst = reinterpret_cast<uint4*>(g_kvT) + ch * 256 + h * 128 + (127 - (8 * pi + blk));
        dst[0] = o0;
        dst[256] = o1;
    }

    const int rho = 8 * rb + j;

    if (wg == 4) {
        asm volatile("setmaxnreg.dec.sync.aligned.u32 32;");
        const unsigned ep1 = __shfl_sync(0xffffffffu, ep0, 0) + 1;
        if (wq == 0) {
            bar_sync(13, 640);
            TSW(39);
            if (lane == 0) flag_release(FL_P + pg);
            __syncwarp();
            TSW(2);
            if (lane < 5) mbar_expect(bars + (BAR_U + lane) * 8, 4096);
            flag_wait(FL_P + pg, ep1 * 16);
            fence_async_global();
            TSW(3);
            if (elect()) {
#pragma unroll
                for (int i = 0; i < 5; i++) {
                    const char* us = (const char*)g_kvT + (size_t)(chan(i)) * 4096;
                    bulk_g2s(sb + sm_u(i), us, 2048, bars + (BAR_U + i) * 8);
                    bulk_g2s(sb + sm_u(i) + U_PLANE, us + 2048, 2048, bars + (BAR_U + i) * 8);
                }
            }
            __syncwarp();
            if (elect()) {
#pragma unroll
                for (int i = SSM_N; i < 5; i++) {
                    mbar_expect(bars + (BAR_K + i) * 8, 4096);
                    bulk_g2s(sb + sm_k(i) + 32, p.ssmk + (size_t)(chan(i)) * S_, 4096, bars + (BAR_K + i) * 8);
                }
                if (WMD2) spin(WMD2);
                if (cta < 120) {
                    mbar_expect(bars + BAR_WM0 * 8, 3 * 8192);
                    mbar_expect(bars + BAR_WM * 8, 2 * 8192);
#pragma unroll 1
                    for (int i = 0; i < 5; i++) tma2d(sb + SM_WM + i * 8192, &maps.wm, cta * 32, i * 128, bars + (i < 3 ? BAR_WM0 : BAR_WM) * 8);
                }
                mbar_wait(bars + (cta < 120 ? BAR_WM0 : BAR_K + 4) * 8, 0);
                bulk_prefetch((const char*)p.q + cta * 20480, 20480);
                bulk_prefetch((const char*)p.w1 + cta * 6400, 6400);
                bulk_prefetch((const char*)p.w2 + cta * 6400, 6400);
            }
            __syncwarp();
        } else {
            bar_arrive(13, 640);
        }
        asm volatile("barrier.cluster.wait.aligned;" ::: "memory");
        uint32_t peer;
        asm volatile("ld.shared::cluster.u32 %0, [%1];" : "=r"(peer) : "r"(mapa(sb + SM_GV + 512, (blockIdx.x & 1) ^ 1)) : "memory");
        const bool paired = peer == (smid ^ 1) && !FORCE_UNPAIRED;
        if (tid == 639) { sts32(sb + SM_GV + 516, paired); sts32(sb + SM_GV + 540, ep1); }
        if (cta < 120) {
            float d[4];
            if (tid >= 544 && tid < 624) {
                const int t = tid - 544;
                mbar_wait(bars + BAR_U * 8, 0);
                uint4 cv = __ldg(reinterpret_cast<const uint4*>(p.c) + t);
                auto silu2 = [](uint32_t v) { float a = blo(v), b = bhi(v); return pack2(__fdividef(a, 1.0f + __expf(-a)), __fdividef(b, 1.0f + __expf(-b))); };
#pragma unroll 1
                for (int i = 0; i < 4; i++) { const uint32_t r = silu2(cv.x); cv.x = cv.y; cv.y = cv.z; cv.z = cv.w; cv.w = r; }
                sts128(sb + SM_Y + (t % 40) * 32 + (t / 40) * 16, cv);
                fence_async_smem();
            }
            bar_sync(5, 128);
            mbar_wait(bars + BAR_WM0 * 8, 0);
            mbar_wait(bars + BAR_WM * 8, 0);
            if (wq == 3) TSW(56);
            const uint32_t da = desc_lo(sb + SM_WM, 20480), db = desc_lo(sb + SM_Y, 32);
#pragma unroll 1
            for (int k0 = 0; k0 < 20; k0 += 4) {
                wg_fence();
#pragma unroll
                for (int k = k0; k < k0 + 4; k++) asm volatile("{.reg .pred p; .reg .b32 l,m; .reg .b64 da,db; setp.ne.b32 p,%10,0; add.u32 l,%4,%6; mov.b64 da,{l,%8}; add.u32 m,%5,%7; mov.b64 db,{m,%9};"
                             " wgmma.mma_async.sync.aligned.m64n8k16.f32.bf16.bf16 {%0,%1,%2,%3},da,db,p,1,1,1,0;}"
                             : "+f"(d[0]), "+f"(d[1]), "+f"(d[2]), "+f"(d[3])
                             : "r"(da), "r"(db), "r"(64 * k), "r"(4 * k), "n"(desc_hi(512, 2u)), "n"(desc_hi(128, 0)), "r"(k));
                wg_commit();
            }
            wg_wait<0>();
            reg_fence<4>(d);
            if (c == 0) {
                sts32(sb + SM_GV + (16 * wq + g) * 4, __float_as_uint(wq < 2 ? d[0] : d[1]));
                sts32(sb + SM_GV + (16 * wq + g + 8) * 4, __float_as_uint(wq < 2 ? d[2] : d[3]));
            }
            bar_sync(5, 128);
            if (wq == 2) {
                g_mod[cta * 32 + lane] = __float2bfloat16_rn(__uint_as_float(lds32(sb + SM_GV + lane * 4)) + __uint_as_float(lds32(sb + SM_GV + 128 + lane * 4)));
            }
        }
        if (wq == 2) {
            bar_sync(9, 320);
            if (lane == 0) { flag_release(FL_M); mbar_expect(bars + BAR_MR * 8, 0); }
            __syncwarp();
            TSW(4);
            flag_wait(FL_M, ep1 * 128);
            fence_async_global();
            if (elect()) {
                mbar_expect(bars + BAR_M * 8, 7680);
                bulk_g2s(sb + SM_MOD, g_mod, 7680, bars + BAR_M * 8);
                mbar_wait(bars + BAR_CD * 8, 0);
                mbar_expect(bars + BAR_Y * 8, 12288);
                bulk_g2s(sb + SM_Y, g_yv + rho * 5120, 12288, bars + BAR_Y * 8);
                if (j < 5) {
#pragma unroll 1
                    for (int i = 0; i < 8; i++) bulk_g2s(sb + SM_YT + i * 2560, g_yv + (8 * rb + i) * 5120 + cm * 8, 2048, bars + BAR_XY * 8);
                }
            }
            __syncwarp();
            TSW(60);
#pragma unroll 1
            for (int i = 0; i < 5; i++) {
                bar_sync((0x216f8 >> (4 * i)) & 15, i ? 288 : 576);
                if (lane == 0) { if (i > 2) TS(50 + i); flag_release(FL_R + 16 * i + rb); TS(i < 3 ? 23 + 4 * i : 54 + i); }
                __syncwarp();
            }
            if (lane == 0) p.epoch[smid] = ep1;
            return;
        }
        if (wq == 1) {
            bar_sync(9, 320);
            mbar_wait(bars + BAR_MR * 8, 0);
            if (lane < 4 * NB) mbar_arrive_cl(mapa(bars + (BAR_EB + (lane >> 2)) * 8, paired ? lane & 1 : blockIdx.x & 1));
        }
        if (wq == 3) {
            bar_sync(7, 544);
            if (lane == 0) { flag_release(FL_C); mbar_expect(bars + BAR_CD * 8, 0); TS(20); }
            __syncwarp();
            if (lane == 0) mbar_expect(bars + BAR_Y2 * 8, 8192);
            flag_wait(FL_C, ep1 * 128);
            fence_async_global();
            TSW(21);
            if (elect()) {
                bulk_g2s(sb + SM_Y + 12288, g_yv + rho * 5120 + 3072, 8192, bars + BAR_Y2 * 8);
            }
            __syncwarp();
        }
        if (wq == 3) {
            mbar_wait(bars + BAR_Y2 * 8, 0);
            if (elect()) {
                mbar_expect(bars + BAR_XY * 8, 20480);
#pragma unroll 1
                for (int i = 0; i < 8; i++) {
                    if (j >= 5) bulk_g2s(sb + SM_YT + i * 2560, g_yv + (8 * rb + i) * 5120 + cm * 8, 2048, bars + BAR_XY * 8);
                    bulk_g2s(sb + SM_YT + i * 2560 + 2048, g_yv + (8 * rb + i) * 5120 + cr * 8, 512, bars + BAR_XY * 8);
                }
            }
            __syncwarp();
            bar_sync(8, 576);
            mbar_wait_warm(bars + BAR_FA * 8, 0);
            mbar_wait(bars + BAR_ME * 8, 0);
            mbar_wait_warm(bars + (BAR_FA + 11 % NA) * 8, (11 / NA) & 1);
            flag_wait(FL_CS, ep1 * 4);
            fence_async_global();
            if (elect()) {
                mbar_expect(bars + BAR_CS * 8, 864);
                bulk_g2s(sb + SM_CS, g_cs + 64 * j, 256, bars + BAR_CS * 8);
                bulk_g2s(sb + SM_CS + 256, g_cs + 512 + RA3 * j, 4 * RA3, bars + BAR_CS * 8);
                bulk_g2s(sb + SM_CS + 256 + 4 * RA3, g_cs + HB0 + 64 * j, 256, bars + BAR_CS * 8);
                bulk_g2s(sb + SM_CS + 512 + 4 * RA3, g_cs + HB0 + 512 + RB3 * j, 4 * RB3, bars + BAR_CS * 8);
            }
            __syncwarp();
            mbar_wait(bars + BAR_ME * 8, 1);
            mbar_wait_warm(bars + (BAR_FA + 21 % NA) * 8, (21 / NA) & 1);
#pragma unroll 1
            for (int i = 0; i < 2; i++) {
                mbar_wait(bars + BAR_ME * 8, i);
                for (int n = i; n < 4; n++) { spin(PING); n += tensor_ping(); }
                flag_wait(FL_G + 16 * i + rb, ep1 * 8);
                if (lane == 0) { mbar_expect(bars + (BAR_G + i) * 8, 0); TS(35 + i); }
                __syncwarp();
            }
            return;
        }
        if (elect()) {
            if (wq == 1) {
                Ring<NB, SM_RB, BAR_FB, BAR_EB> r{sb, 0, 0};
#pragma unroll 1
                for (int ph = 0; ph < 7; ph++) {
                    const CUtensorMap* ma = ph == 0 ? &maps.w1a : ph == 1 ? &maps.w2a : ph == 6 ? &maps.w4a : &maps.w3a;
                    const bool b3b = ph == 2 || ph == 4 || ph == 5;
                    r.runw(paired, idx & 1, ma, ma + (b3b ? 2 : 1), ph == 3 ? 64 * j : b3b ? HB0 + 64 * j : cm,
                           ph == 3 ? 512 + RA3 * j : b3b ? HB0 + 512 + RB3 * j : cr, ph == 4 ? 10 - NA : ph == 5 ? 1 : 0,
                           ph == 6 ? 27 : ph == 5 ? 10 - NA : ph == 2 ? 1 : 10, ph == 0 ? 0 : ph == 6 ? HB0 / 64 + j : cm >> 6,
                           ph == 3 ? 8192 + 128 * RA3 : b3b ? 8192 + 128 * RB3 : 10240,
                           ph == 0 ? GATE0 : ph == 1 ? GATE : ph == 3 ? GATE - 1 : -1, bars + (ph == 0 ? BAR_Y2 : BAR_ST - (ph == 1)) * 8);
                }
            } else {
                Ring<NA, SM_RA, BAR_FA, BAR_EA> r{sb, 0, 0};
                if (cta >= 120) mbar_wait(bars + (BAR_K + 4) * 8, 0);
                mbar_expect(bars + BAR_XR * 8, 20480);
                bulk_g2s(sb + SM_XR, p.q + (size_t)rho * 16 * D_, 20480, bars + BAR_XR * 8);
                mbar_expect(bars + BAR_XY * 8, 20480);
                tma2d(sb + SM_XT, &maps.xa, cm, rb * 128, bars + BAR_XY * 8);
                tma2d(sb + SM_XT2, &maps.xb, cr, rb * 128, bars + BAR_XY * 8);
                const int grp = j >> 1;
                const int delta = (grp & 1 ? 1 : -1) * (1 + (grp >> 1));
                const int nb = min(max(rb + (delta > 0 ? 1 : -1), 0), 15);
                uint32_t fb = r.acquire(SLOT), dst = r.slot();
                flag_wait2(FL_R + nb, FL_R + rb, ep1 * 8);
                fence_async_global();
                tma2d(dst, &maps.hn, 0, rb * 128 + delta, fb);
                TS(24);
                r.next();
                r.run2d(&maps.hn, rb * 128 + delta);
#pragma unroll 1
                for (int ph = 0; ph < 5; ph++) {
                    const char* src = ph == 0 ? (const char*)g_h1 + rb * 163840 : ph < 3 ? (const char*)g_x1 + rb * 163840 : (const char*)g_g + rb * 442368;
                    const int own = ph < 3 ? cm >> 6 : HB0 / 64 + j;
                    if (ph != 2 && ph != 4) { r.acquire(0); r.next(); }
                    const int i0 = ph == 4 ? 1 + HB0 / 64 : 1;
                    const char* src1 = src + r.korder(i0, own) * SLOT;
                    if (ph > 2) mbar_wait(bars + (BAR_G - 3 + ph) * 8, 0);
                    fb = r.acquire(SLOT); dst = r.slot();
                    if (ph < 2) flag_wait(FL_B1 + 16 * ph + rb, ep1 * 8);
                    fence_async_global();
                    bulk_g2s(dst, src1, SLOT, fb);
                    if (ph < 2) { TS(28 + 4 * ph); mbar_expect(bars + (BAR_ST - 1 + ph) * 8, 0); }
                    r.next();
                    r.run1d(src, i0 + 1, ph < 2 ? 10 : ph == 2 ? 10 - NA : ph == 3 ? 1 + HB0 / 64 : 27, own);
                }
            }
        }
        return;
    }
    bar_arrive(13, 640);
    asm volatile("setmaxnreg.inc.sync.aligned.u32 112;");
    const int rrow = 16 * rho + (warp >> 1) + 8 * (warp & 1);

    fence_async_smem();
    bar_sync(1 + wg, 128);
#pragma unroll 1
    for (int cc = wg; cc < wg + 1 + (wg == 3); cc++) {
        mbar_wait(bars + (BAR_K + cc) * 8, 0);
        if (cc == 2 && wq == 0) TSW(40);
        uint32_t a = sb + sm_k(cc) + 32 + (tid & 127) * 32;
        uint32_t pw = lds32(a - 4);
        uint4 x = lds128(a), y = lds128(a + 16), o;
        if ((tid & 127) == 0) {
            uint16_t k0 = __bfloat16_as_ushort(__float2bfloat16_rn(blo(x.x) + __uint_as_float(lds32(sb + SM_GV + 520 + cc * 4))));
            x.x = (x.x & 0xffff0000u) | k0;
            sts16(a, k0);
        }
        o.x = prmt(pw, x.x, 0x5432); o.y = prmt(x.x, x.y, 0x5432); o.z = prmt(x.y, x.z, 0x5432); o.w = prmt(x.z, x.w, 0x5432);
        sts128(a + 4160, o);
        o.x = prmt(x.w, y.x, 0x5432); o.y = prmt(y.x, y.y, 0x5432); o.z = prmt(y.y, y.z, 0x5432); o.w = prmt(y.z, y.w, 0x5432);
        sts128(a + 4176, o);
    }
    bar_sync(1 + wg, 128);
    if (wg == 3) bar_arrive(11, 256);
#pragma unroll 1
    for (int cc = wg; cc < 5; cc += 3) {
        if (cc == 3 && wg == 0) break;
        if (cc == 4) bar_sync(11, 256);
        const uint32_t kaddr = sb + sm_k(cc) + ((g & 1) ? 32 : 4192) + 4 * ((g >> 1) - c) + 64 * wq;
        const AFrag f0 = ldA(kaddr), f1 = ldA(kaddr + 256);
        if (STAG && cc == 3) bar_sync(12, 256);
        mbar_wait(bars + (BAR_U + cc) * 8, 0);
        if (wq == 0) TSW(5 + cc);
        float d[64];
        conv_two<0>(d, f0, f1, kaddr, desc_lo(sb + sm_u(cc), U_PLANE), sb + sm_red(cc) + wq * 4352 + g * 544 + c * 8, cc == 1);
        if (wq == 0) TSW(10 + cc);
        if (cc == 1) bar_arrive(6, 256);
    }
#pragma unroll 1
    for (int cc = wg == 1 ? 4 : wg;; cc++) {
        if (cc == 1) bar_sync(6, 256); else bar_sync(1 + wg, 128);
        const int ch = chan(cc);
        uint32_t* dst = g_yv + ch * 8 + ((g + (ch >> 2)) & 7) + (126 - 32 * wq - 2 * c) * 5120;
        uint2 v[16];
#pragma unroll
        for (int i = 0; i < 16; i++) v[i] = lds64(sb + sm_red(cc) + g * 544 + wq * 128 + c * 8 + (i >> 2) * 32 + (i & 3) * 4360);
#pragma unroll
        for (int w = 1; w < 4; w++)
            if (wq == 3 && c > 3 - w) v[12 + w] = make_uint2(0, 0);
#pragma unroll
        for (int q = 0; q < 4; q++) {
            const uint2* u = v + 4 * q;
            dst[-8 * q * 5120] = badd2(u[0].x, badd2(u[1].x, badd2(u[2].x, u[3].x)));
            dst[(-8 * q + 1) * 5120] = badd2(u[0].y, badd2(u[1].y, badd2(u[2].y, u[3].y)));
        }
        if (wq == 0) TSW(15 + cc);
        if (cc != 0) break;
    }
    fence_async_smem();
    if (!(wg & 1)) bar_arrive(9, 320);
    bar_arrive(7, 544);

    const uint32_t one2 = 0x3f803f80u;
    const unsigned ones = p.ones;
    {
        uint32_t x[10], a[10], cb[10], sbv[10];
        bar_sync(10, 512);
        mbar_wait(bars + BAR_XR * 8, 0);
#pragma unroll
        for (int i = 0; i < 10; i++) x[i] = lds32(sb + SM_XR + (rrow & 15) * 1280 + lane * 4 + i * 128);
        const uint2 s1 = row_stats<0>(x, lane);
        const int up = lane >> 4, gg = warp >> 1, e = warp & 1;
        const uint32_t ya = sb + SM_Y + lane * 64 + ((gg + (lane >> 1)) & 7) * 4;
        const uint32_t sel = (up ? 0x1054u : 0x5410u) + (e ? 0x2222u : 0u);
        const uint32_t ma = sb + SM_MOD + lane * 4;
        mbar_wait(bars + BAR_M * 8, 0);
        uint32_t pin = 0;
#pragma unroll
        for (int i = 0; i < 10; i++) {
            uint32_t h = bfma2(ln_apply(x[i], s1.x, s1.y), badd2(lds32(ma + 1280 + i * 128), one2), lds32(ma + i * 128));
            a[i] = bmul2(h, lds32(ma + 2560 + i * 128));
            sbv[i] = lds32(ma + 3840 + i * 128);
            cb[i] = badd2(lds32(ma + 5120 + i * 128), one2);
            pin ^= a[i] ^ cb[i];
        }
        if (pin & ~ones) sts32(sb + SM_GV, pin);
        if (warp == 4) TSW(52);
        mbar_wait(bars + BAR_Y * 8, 0);
        RowSum part;
#pragma unroll
        for (int i = 0; i < 10; i++) {
            if (i == 6) {
                if ((__float_as_uint(part.s + part.s_ + part.q + part.q_) & ~ones)) sts32(sb + SM_GV, pin);
                mbar_wait(bars + BAR_Y2 * 8, 0);
                if (warp == 0) TSW(22);
            }
            uint32_t y0 = lds32(ya + i * 2048 + up * 32), y1 = lds32(ya + i * 2048 + (up ^ 1) * 32);
            x[i] = bfma2(a[i], prmt(y0, y1, sel), x[i]);
            if (i < 6) part.add(x[i]);
        }
        const uint2 s2 = row_stats<6>(x, lane, part);
#pragma unroll
        for (int i = 0; i < 10; i++) x[i] = bfma2(ln_apply(x[i], s2.x, s2.y), cb[i], sbv[i]);
        const uint2 s3 = row_stats<0>(x, lane);
        uint32_t* o = reinterpret_cast<uint32_t*>(g_hn + (size_t)rrow * D_) + lane;
#pragma unroll
        for (int i = 0; i < 10; i++) o[32 * i] = ln_apply(x[i], s3.x, s3.y);
        if (lane < 2) g_rs[rrow * 2 + lane] = make_uint4(s1.x, s1.y, s2.x, s2.y);
        if (warp == 0) TSW(34);
        bar_arrive(8, 576);
    }

    const int half = wg & 1;
    const int row = 64 * half + 16 * wq + g;
    const int tw0 = (rb * 80 + (cm >> 3)) * 512 + row * 4 + c, tw1 = (rb * 80 + (cr >> 3) - 8) * 512 + row * 4 + c;
    const uint32_t park = sb + SM_Y + (tid & 255) * 16;
    const uint32_t ms0 = sb + SM_MOD + (cm + 2 * c) * 2, ms1 = sb + SM_MOD + (cr - 64 + 2 * c) * 2;
    if (wg >= 2) {
        {
            float acc[40];
            gemm_loop<80, true, 10, 10, true>(acc, sb, half, 0, 0, 10, 0, 25);
            if (tid == 256) mbar_expect(bars + BAR_ME * 8, 0);
#pragma unroll
            for (int k = 0; k < 10; k += CH) CHUNK(k) {
#pragma unroll
                for (int q = k; q < k + CH && q < 10; q++) {
                    uint32_t* dst = reinterpret_cast<uint32_t*>(g_h1) + (q < 8 ? tw0 : tw1);
                    const uint32_t u = gelu2_h(bmul2(pack2(acc[4 * q], acc[4 * q + 1]), 0x3f003f00u));
                    const uint32_t v = gelu2_h(bmul2(pack2(acc[4 * q + 2], acc[4 * q + 3]), 0x3f003f00u));
                    dst[q * 512] = u;
                    dst[q * 512 + 32] = v;
                    acc[4 * q] = __uint_as_float(u); acc[4 * q + 1] = __uint_as_float(v);
                }
            }
            bar_arrive(15, 288);
            mbar_wait(bars + (BAR_FA + 10 % NA) * 8, (10 / NA) & 1);
#pragma unroll
            for (int q = 0; q < 8; q++) {
                sts32(sb + SM_RA + (10 % NA) * SLOT + q * 2048 + row * 16 + c * 4, __float_as_uint(acc[4 * q]));
                sts32(sb + SM_RA + (10 % NA) * SLOT + q * 2048 + row * 16 + c * 4 + 128, __float_as_uint(acc[4 * q + 1]));
            }
            fence_async_smem();
            bar_arrive(14, 512);
        }
        gemm3<0>(sb, rb, j, half, row, c, ones);
        {
            float acc[40];
            uint32_t gbv[10], base[20];
#pragma unroll
            for (int q = 0; q < 10; q++) gbv[q] = lds32((q < 8 ? ms0 : ms1) + 6400 + q * 16);
#pragma unroll
            for (int q = 0; q < 5; q++) { const uint4 t = lds128(park + q * 4096); base[4 * q] = t.x; base[4 * q + 1] = t.y; base[4 * q + 2] = t.z; base[4 * q + 3] = t.w; }
            gemm_loop<80, false, 27, 27 - NB, true>(acc, sb, half, 39 - NA, 40, 27 - NA, 11, 42);
            auto fin = [&](int q, int r) {
                return bfma2(gbv[q], pack2(acc[4 * q + 2 * r], acc[4 * q + 2 * r + 1]), base[2 * q + r]);
            };
            auto tr4 = [&](uint32_t t0, uint32_t t1, uint32_t t2, uint32_t t3) {
                const bool o1 = c & 1, o2 = c & 2;
                uint32_t a = __shfl_xor_sync(0xffffffffu, o1 ? t0 : t1, 1), b = __shfl_xor_sync(0xffffffffu, o1 ? t2 : t3, 1);
                uint32_t u0 = o1 ? a : t0, u1 = o1 ? t1 : a, u2 = o1 ? b : t2, u3 = o1 ? t3 : b;
                a = __shfl_xor_sync(0xffffffffu, o2 ? u0 : u2, 2); b = __shfl_xor_sync(0xffffffffu, o2 ? u1 : u3, 2);
                return o2 ? make_uint4(a, b, u2, u3) : make_uint4(u0, u1, a, b);
            };
            bf16* go = p.out + (size_t)(rb * 128 + row) * D_;
#pragma unroll
            for (int k = 0; k < 2; k++) CHUNK(k) {
#pragma unroll
                for (int r = 0; r < 2; r++)
                    *reinterpret_cast<uint4*>(go + r * 8 * D_ + cm + 32 * k + 8 * c) = tr4(fin(4 * k, r), fin(4 * k + 1, r), fin(4 * k + 2, r), fin(4 * k + 3, r));
            }
            CHUNK(2) *reinterpret_cast<uint4*>(go + (c >> 1) * 8 * D_ + cr + 8 * (c & 1)) = tr4(fin(8, 0), fin(9, 0), fin(8, 1), fin(9, 1));
            if (tid == 256) TS(44);
            if (warp == 8) TSFLUSH();
        }
    } else {
        {
            float acc[40];
            uint32_t x2[20];
            {
                uint32_t y[20];
                mbar_wait(bars + BAR_XY * 8, 0);
                const uint32_t xa = sb + SM_XT + row * 128 + c * 4, xb = sb + SM_XT2 + row * 32 + c * 4;
                const uint32_t ya = sb + SM_YT + (4 * half + wq) * 2560 + c * 64;
#pragma unroll
                for (int q = 0; q < 10; q++) {
                    const uint32_t a = q < 8 ? xa + ((q ^ g) << 4) : xb + (q - 8) * 16;
                    x2[2 * q] = lds32(a); x2[2 * q + 1] = lds32(a + (q < 8 ? 1024 : 256));
                    const int pos = (g + ((q < 8 ? cm : cr) >> 2) + 2 * q + (c >> 1)) & 7;
                    y[2 * q] = lds32(ya + q * 256 + pos * 4); y[2 * q + 1] = lds32(ya + q * 256 + 32 + pos * 4);
                }
                fence_async_smem();
                bar_sync(1 + wg, 128);
                if ((tid & 127) < NA) mbar_arrive_cl(mapa(bars + (BAR_EA + (tid & 127)) * 8, blockIdx.x & 1));
                mbar_wait(bars + (BAR_FA + 1) * 8, 0);
                const uint4* rp = g_rs + (rb * 128 + row) * 2;
                const uint4 ra = ldcg128(rp), rc = ldcg128(rp + 16);
                bar_sync(14, 512);
#pragma unroll
                for (int q = 0; q < 10; q++) {
                    const uint32_t ms = q < 8 ? ms0 : ms1;
                    const uint32_t sa = lds32(ms + 16 * q), ca = badd2(lds32(ms + 1280 + 16 * q), one2), ga = lds32(ms + 2560 + 16 * q);
                    const uint32_t sbv = lds32(ms + 3840 + 16 * q), cb = badd2(lds32(ms + 5120 + 16 * q), one2);
                    uint32_t u = x2[2 * q], v = x2[2 * q + 1];
                    u = bfma2(bmul2(bfma2(ln_apply(u, ra.x, ra.y), ca, sa), ga), prmt(y[2 * q], y[2 * q + 1], 0x5410), u);
                    v = bfma2(bmul2(bfma2(ln_apply(v, rc.x, rc.y), ca, sa), ga), prmt(y[2 * q], y[2 * q + 1], 0x7632), v);
                    x2[2 * q] = u; x2[2 * q + 1] = v;
                    u = bfma2(ln_apply(u, ra.z, ra.w), cb, sbv);
                    v = bfma2(ln_apply(v, rc.z, rc.w), cb, sbv);
                    acc[4 * q] = blo(u); acc[4 * q + 1] = bhi(u); acc[4 * q + 2] = blo(v); acc[4 * q + 3] = bhi(v);
                }
            }
            reg_fence<40>(acc);
            if (tid == 0) TS(45);
            gemm_loop<80, false, 10, 10, false>(acc, sb, half, 10, 10, 10, 0, 29);
            if (tid == 0) mbar_expect(bars + BAR_ME * 8, 0);
            uint32_t x1[20];
            float s0 = 0.f, q0 = 0.f, s1 = 0.f, q1 = 0.f;
#pragma unroll
            for (int q = 0; q < 10; q++) {
                uint32_t u = pack2(acc[4 * q], acc[4 * q + 1]);
                uint32_t v = pack2(acc[4 * q + 2], acc[4 * q + 3]);
                uint32_t* dst = reinterpret_cast<uint32_t*>(g_x1) + (q < 8 ? tw0 : tw1);
                dst[q * 512] = u;
                dst[q * 512 + 32] = v;
                x1[2 * q] = u; x1[2 * q + 1] = v;
            }
            bar_arrive(6, 288);
            CHUNK(0)
#pragma unroll
            for (int q = 0; q < 10; q++) {
                float a = blo(x1[2 * q]), b = bhi(x1[2 * q]), e = blo(x1[2 * q + 1]), f = bhi(x1[2 * q + 1]);
                s0 += a + b; q0 = fmaf(a, a, fmaf(b, b, q0));
                s1 += e + f; q1 = fmaf(e, e, fmaf(f, f, q1));
            }
#pragma unroll
            for (int m = 1; m <= 2; m <<= 1) {
                s0 += __shfl_xor_sync(0xffffffffu, s0, m); q0 += __shfl_xor_sync(0xffffffffu, q0, m);
                s1 += __shfl_xor_sync(0xffffffffu, s1, m); q1 += __shfl_xor_sync(0xffffffffu, q1, m);
            }
            if (c < 2) asm volatile("{.reg .b64 a, b; mov.b64 a, {%1, %3}; mov.b64 b, {%2, %3}; st.relaxed.gpu.global.v2.b64 [%0], {a, b};}"
                                    ::"l"(&g_st[(rb * 8 + j) * 128 + row + 8 * c]), "r"(__float_as_uint(c ? s1 : s0)), "r"(__float_as_uint(c ? q1 : q0)), "r"(lds32(sb + SM_GV + 540)) : "memory");
            mbar_wait(bars + (BAR_FA + 20 % NA) * 8, (20 / NA) & 1);
#pragma unroll
            for (int q = 0; q < 8; q++) {
                sts32(sb + SM_RA + (20 % NA) * SLOT + q * 2048 + row * 16 + c * 4, x1[2 * q]);
                sts32(sb + SM_RA + (20 % NA) * SLOT + q * 2048 + row * 16 + c * 4 + 128, x1[2 * q + 1]);
            }
            fence_async_smem();
            bar_sync(3 + wg, 128);
#pragma unroll
            for (int q = 0; q < 5; q++) {
                const uint32_t ms = q < 4 ? ms0 : ms1;
                const uint32_t g0 = lds32(ms + 6400 + q * 32), g1 = lds32(ms + 6400 + q * 32 + 16);
                sts128(park + q * 4096, make_uint4(bfma2(g0, x1[4 * q], x2[4 * q]), bfma2(g0, x1[4 * q + 1], x2[4 * q + 1]),
                                                   bfma2(g1, x1[4 * q + 2], x2[4 * q + 2]), bfma2(g1, x1[4 * q + 3], x2[4 * q + 3])));
            }
        }
        gemm3<1>(sb, rb, j, half, row, c, ones);
    }
}

typedef CUresult (*EncFn)(CUtensorMap*, CUtensorMapDataType, cuuint32_t, void*, const cuuint64_t*, const cuuint64_t*,
                          const cuuint32_t*, const cuuint32_t*, CUtensorMapInterleave, CUtensorMapSwizzle,
                          CUtensorMapL2promotion, CUtensorMapFloatOOBfill);

void make_map(EncFn enc, CUtensorMap* m, const void* base, uint64_t inner, uint64_t outer, uint32_t bi, uint32_t bo,
              CUtensorMapSwizzle swz = CU_TENSOR_MAP_SWIZZLE_128B) {
    cuuint64_t dims[2] = {inner, outer};
    cuuint64_t st[1] = {inner * 2};
    cuuint32_t box[2] = {bi, bo};
    cuuint32_t es[2] = {1, 1};
    enc(m, CU_TENSOR_MAP_DATA_TYPE_BFLOAT16, 2, const_cast<void*>(base), dims, st, box, es, CU_TENSOR_MAP_INTERLEAVE_NONE,
        swz, CU_TENSOR_MAP_L2_PROMOTION_NONE, CU_TENSOR_MAP_FLOAT_OOB_FILL_NONE);
}

}

extern "C" void kernel_launch(void* const* d_in, const int* in_sizes, int n_in, void* d_out, int out_size) {
    (void)in_sizes; (void)n_in; (void)out_size;
    Params p;
    p.q = (const bf16*)d_in[0]; p.k = (const bf16*)d_in[1]; p.v = (const bf16*)d_in[2];
    p.shift = (const bf16*)d_in[3]; p.ssmk = (const bf16*)d_in[4]; p.ssmD = (const bf16*)d_in[5];
    p.w1 = (const bf16*)d_in[7]; p.w2 = (const bf16*)d_in[8]; p.w3 = (const bf16*)d_in[9]; p.w4 = (const bf16*)d_in[10];
    p.c = (const bf16*)d_in[11]; p.wmod = (const bf16*)d_in[12];
    p.out = (bf16*)d_out;
    p.ones = 0xffffffffu;
    cudaGetSymbolAddress((void**)&p.epoch, g_epoch);

    void* fn = nullptr;
    cudaDriverEntryPointQueryResult qr;
    cudaGetDriverEntryPoint("cuTensorMapEncodeTiled", &fn, cudaEnableDefault, &qr);
    EncFn enc = (EncFn)fn;
    void* hn = nullptr;
    cudaGetSymbolAddress(&hn, g_hn);
    Maps maps;
    make_map(enc, &maps.w3s, p.w3, F_, D_, 216, 64, CU_TENSOR_MAP_SWIZZLE_NONE);
    make_map(enc, &maps.wm, p.wmod, 6 * D_, D_, 32, 128, CU_TENSOR_MAP_SWIZZLE_64B);
    make_map(enc, &maps.xa, p.q, D_, S_, 64, 128);
    make_map(enc, &maps.xb, p.q, D_, S_, 16, 128, CU_TENSOR_MAP_SWIZZLE_NONE);
    make_map(enc, &maps.hn, hn, D_, S_, 64, 128);
    make_map(enc, &maps.w1a, p.w1, D_, D_, 64, 64);
    make_map(enc, &maps.w1b, p.w1, D_, D_, 16, 64);
    make_map(enc, &maps.w2a, p.w2, D_, D_, 64, 64);
    make_map(enc, &maps.w2b, p.w2, D_, D_, 16, 64);
    make_map(enc, &maps.w3a, p.w3, F_, D_, 64, 64);
    make_map(enc, &maps.w3b, p.w3, F_, D_, RA3, 64);
    make_map(enc, &maps.w3c, p.w3, F_, D_, RB3, 64);
    make_map(enc, &maps.w4a, p.w4, D_, F_, 64, 64);
    make_map(enc, &maps.w4b, p.w4, D_, F_, 16, 64);
    cudaFuncSetAttribute(fused_kernel, cudaFuncAttributeMaxDynamicSharedMemorySize, SMEM_BYTES);
    fused_kernel<<<132, NTHREADS, SMEM_BYTES>>>(p, maps);
}
```
